```python
import torch

def _softmax(x, axis=-1):
    return torch.softmax(x, dim=axis)
def _gelu(x):
    return torch.nn.functional.gelu(x, approximate="tanh")
def _silu(x):
    return torch.nn.functional.silu(x)
def _sigmoid(x):
    return torch.sigmoid(x)
def _layernorm(x, axis=-1, eps=1e-5):
    m = x.mean(dim=axis, keepdim=True)
    v = x.var(dim=axis, keepdim=True, unbiased=False)
    return (x - m) / torch.sqrt(v + eps)
def _scatter_add(tgt, idx, src, axis=0):
    return tgt.clone().index_add_(axis, idx, src)
def _segment_sum(src, seg, n):
    out = torch.zeros((n,) + src.shape[1:], dtype=src.dtype)
    return out.index_add_(0, seg, src)
def _pad(x, pw):
    flat = tuple(v for pair in reversed(pw) for v in pair)
    return torch.nn.functional.pad(x, flat)

kernel_name = 'gated_mix__ssm_conv_h3__ssm_conv_s4d__prompt'

def setup_inputs():

    _w = (lambda a: (lambda t: t.to(torch.bfloat16) if t.is_floating_point() else t)(torch.as_tensor(a)))
    def _A_setup():
        B, S, D = 1, 2048, 576
        ks = 4
        return {
            "q": _w((lambda *s: torch.randn(*s, dtype=torch.bfloat16) * 0.05)(B, S, D)),
            "k": _w((lambda *s: torch.randn(*s, dtype=torch.bfloat16) * 0.8)(B, S, D)),
            "v": _w((lambda *s: torch.randn(*s, dtype=torch.bfloat16) * 0.8)(B, S, D)),
            "shift_k": _w((lambda *s: torch.randn(*s, dtype=torch.bfloat16) * 0.8)(D, ks) * 0.5),
            "ssm_k": _w((lambda *s: torch.randn(*s, dtype=torch.bfloat16) * 0.8)(D, S) * (1.0 / S ** 0.5)),
            "ssm_D": _w((lambda *s: torch.randn(*s, dtype=torch.bfloat16) * 0.8)(D)),
        }
    _A_in = _A_setup()

    def _B_setup():
        Bsz, L, D, N = 1, 2048, 576, 128
        return {
            "u": _w((lambda *s: torch.randn(*s, dtype=torch.bfloat16) * 0.05)(Bsz, L, D)),
            "log_A_real": _w((lambda *s: torch.randn(*s, dtype=torch.bfloat16) * 3.2)(D, N) * 0.5),
            "A_imag": _w((lambda *s: torch.randn(*s, dtype=torch.bfloat16) * 0.2)(D, N) * 3.14),
            "C_real": _w((lambda *s: torch.randn(*s, dtype=torch.bfloat16) * 3.2)(D, N) / N ** 0.5),
            "C_imag": _w((lambda *s: torch.randn(*s, dtype=torch.bfloat16) * 3.2)(D, N) / N ** 0.5),
            "log_dt": _w((lambda *s: torch.randn(*s, dtype=torch.bfloat16) * 0.2)(D) * 0.5 - 4.0),
            "D_skip": _w((lambda *s: torch.randn(*s, dtype=torch.bfloat16) * 0.4)(D)),
        }
    _B_in = _B_setup()

    return {
        "A_q": _A_in["q"],
        "A_k": _A_in["k"],
        "A_v": _A_in["v"],
        "A_shift_k": _A_in["shift_k"],
        "A_ssm_k": _A_in["ssm_k"],
        "A_ssm_D": _A_in["ssm_D"],
        "B_u": _B_in["u"],
        "B_log_A_real": _B_in["log_A_real"],
        "B_A_imag": _B_in["A_imag"],
        "B_C_real": _B_in["C_real"],
        "B_C_imag": _B_in["C_imag"],
        "B_log_dt": _B_in["log_dt"],
        "B_D_skip": _B_in["D_skip"],
        "gate_w": _w((lambda *s: torch.randn(*s, dtype=torch.bfloat16) * 0.05)(576) * 16.0),
    }

def reference(A_q, A_k, A_v, A_shift_k, A_ssm_k, A_ssm_D, B_u, B_log_A_real, B_A_imag, B_C_real, B_C_imag, B_log_dt, B_D_skip, gate_w):
    def _A_ref(q, k, v, shift_k, ssm_k, ssm_D):
        B, S, D = q.shape
        ks = shift_k.shape[-1]
        k_pad = _pad(k, ((0, 0), (ks - 1, 0), (0, 0)))
        k_shift = torch.zeros_like(k)
        for t in range(ks):
            k_shift = k_shift + k_pad[:, t:t + S, :] * shift_k[:, ks - 1 - t][None, None, :]
        kv = k_shift * v
        L = 2 * S
        kv_pad = _pad(kv, ((0, 0), (0, S), (0, 0)))
        kf_pad = _pad(ssm_k, ((0, 0), (0, S)))
        kv_f = (lambda x, axes=(-2,-1): torch.fft.rfft2(x.float(), dim=axes))(kv_pad[:, None, :, :], axes=(1, 2))
        kf_f = (lambda x, axes=(-2,-1): torch.fft.rfft2(x.float(), dim=axes))(kf_pad[:, None, :], axes=(1, 2))
        kf_f = (lambda x, *d: x.permute(*d))(kf_f, 1, 2, 0)
        y_f = kv_f * kf_f[None, :, :, :]
        y = (lambda x, s, axes=(-2,-1): torch.fft.irfft2(x, s=s, dim=axes).to(torch.bfloat16))(y_f, (1, L), axes=(1, 2))[:, 0, :S, :]
        y = y + kv * ssm_D[None, None, :]
        return q * y

    def _B_ref(u, log_A_real, A_imag, C_real, C_imag, log_dt, D_skip):
        L = u.shape[1]
        dt = torch.exp(log_dt)
        A = -torch.exp(log_A_real) + 1j * A_imag
        C = (C_real + 1j * C_imag) * dt[:, None]
        pos = (lambda x, dt: x.to(dt))(torch.arange(L), log_dt.dtype)
        P = torch.exp((A * dt[:, None])[:, :, None] * pos[None, None, :])
        K = 2.0 * torch.einsum("dn,dnl->dl", C, P).real
        L2 = 2 * L
        u_t = (lambda x, *d: x.permute(*d))(u, 0, 2, 1)
        Kf = (lambda x, *a, **k: torch.fft.rfft(x.float(), *a, **k))(K, L2)
        Uf = (lambda x, *a, **k: torch.fft.rfft(x.float(), *a, **k))(u_t, L2)
        y = (lambda x, *a, **k: torch.fft.irfft(x, *a, **k).to(torch.bfloat16))(Uf * Kf[None, :, :], L2)[:, :, :L]
        y = (lambda x, *d: x.permute(*d))(y, 0, 2, 1)
        return y + u * D_skip[None, None, :]

    x = A_q
    g = _sigmoid((x * gate_w).sum(-1, keepdims=True))
    a = _A_ref(x, A_k, A_v, A_shift_k, A_ssm_k, A_ssm_D)
    b = _B_ref(x, B_log_A_real, B_A_imag, B_C_real, B_C_imag, B_log_dt, B_D_skip)
    return g * a + (1 - g) * b
```

```cpp
#include <cuda_runtime.h>
#include <cuda_bf16.h>
#include <cuda.h>
#include <stdint.h>

#define TIMELINE 0

namespace {

constexpr int SEQ = 2048, DCH = 576, NMODE = 128;
constexpr int CS = 8, CPC = 40, NCL = 15, NTHREADS = 384;

constexpr int UPITCH = 4368, UPAD = 272;
constexpr int HPITCH = 4160;
constexpr int PBSZ = 16896;
constexpr int YPITCH = 528;
constexpr int KTAB = 28672;
constexpr int OFF_TQ = 0;
constexpr int OFF_TK = 20480;
constexpr int OFF_YA = OFF_TK;
constexpr int OFF_TV = 43520;
constexpr int OFF_UX = 64000;
constexpr int OFF_RAWA = OFF_UX + 5 * UPITCH + 16;
constexpr int OFF_PB = OFF_RAWA + 5 * HPITCH;
constexpr int OFF_YB = OFF_PB + 2 * PBSZ;
constexpr int OFF_UKV = OFF_YB + 40 * YPITCH;
constexpr int OFF_HB = OFF_UKV + 5 * UPITCH + 16;
constexpr int OFF_KC = OFF_HB + 10 * HPITCH;
constexpr int OFF_SW = OFF_KC + 3 * 1408;
constexpr int OFF_GW = OFF_SW + 320;
constexpr int OFF_MB = OFF_GW + 80;
constexpr int SMEM_BYTES = OFF_MB + 32 * 8;
static_assert(((OFF_RAWA - OFF_HB) & 63) == 32, "bank offset between raw/shift copies");
static_assert(OFF_PB + 3 * KTAB <= OFF_HB + 4 * HPITCH, "ktab alias zone");
static_assert(SMEM_BYTES <= 232448, "smem");
static_assert((OFF_RAWA & 15) == 0 && (OFF_PB & 15) == 0 && (OFF_HB & 15) == 0 && (OFF_MB & 7) == 0 && (OFF_KC & 15) == 0, "align");

enum { MB_XQ = 0, MB_KV = 2, MB_HA = 4, MB_HRDY = 5, MB_UX = 6, MB_UKV = 11, MB_YB = 16, MB_YA = 21, MB_COUNT = 26 };
enum { NB_TOK0 = 1, NB_TOK1 = 2, NB_WG0 = 3, NB_R1 = 6, NB_R2 = 7, NB_HBFREE = 8 };

struct Params {
  CUtensorMap tq, tk, tv, to;
  const __nv_bfloat16 *q, *shift_k, *ssm_k, *ssm_D, *logA, *Aim, *Cre, *Cim, *logdt, *Dskip, *gate_w;
};

__device__ float g_part[NCL * SEQ];
__device__ unsigned g_cnt[CS * 32];
#define TL(i) do {} while (0)

__device__ __forceinline__ uint32_t lds32(uint32_t a) { uint32_t v; asm volatile("ld.shared.u32 %0, [%1];" : "=r"(v) : "r"(a) : "memory"); return v; }
__device__ __forceinline__ uint32_t lds16(uint32_t a) { uint32_t v; asm volatile("ld.shared.u16 %0, [%1];" : "=r"(v) : "r"(a) : "memory"); return v; }
__device__ __forceinline__ uint2 lds64(uint32_t a) { uint2 v; asm volatile("ld.shared.v2.u32 {%0,%1}, [%2];" : "=r"(v.x), "=r"(v.y) : "r"(a) : "memory"); return v; }
__device__ __forceinline__ uint4 lds128(uint32_t a) { uint4 v; asm volatile("ld.shared.v4.u32 {%0,%1,%2,%3}, [%4];" : "=r"(v.x), "=r"(v.y), "=r"(v.z), "=r"(v.w) : "r"(a) : "memory"); return v; }
__device__ __forceinline__ void sts16(uint32_t a, uint32_t v) { asm volatile("st.shared.u16 [%0], %1;" :: "r"(a), "r"(v) : "memory"); }
__device__ __forceinline__ void sts32(uint32_t a, uint32_t v) { asm volatile("st.shared.u32 [%0], %1;" :: "r"(a), "r"(v) : "memory"); }
__device__ __forceinline__ void sts64(uint32_t a, uint32_t x, uint32_t y) { asm volatile("st.shared.v2.u32 [%0], {%1,%2};" :: "r"(a), "r"(x), "r"(y) : "memory"); }
__device__ __forceinline__ void sts128(uint32_t a, uint32_t x, uint32_t y, uint32_t z, uint32_t w) { asm volatile("st.shared.v4.u32 [%0], {%1,%2,%3,%4};" :: "r"(a), "r"(x), "r"(y), "r"(z), "r"(w) : "memory"); }
__device__ __forceinline__ void ldsm4t(uint32_t (&r)[4], uint32_t a) { asm volatile("ldmatrix.sync.aligned.m8n8.x4.trans.shared.b16 {%0,%1,%2,%3}, [%4];" : "=r"(r[0]), "=r"(r[1]), "=r"(r[2]), "=r"(r[3]) : "r"(a) : "memory"); }
__device__ __forceinline__ void ldsm2t(uint32_t& r0, uint32_t& r1, uint32_t a) { asm volatile("ldmatrix.sync.aligned.m8n8.x2.trans.shared.b16 {%0,%1}, [%2];" : "=r"(r0), "=r"(r1) : "r"(a) : "memory"); }
__device__ __forceinline__ void ldsm4(uint32_t (&r)[4], uint32_t a) { asm volatile("ldmatrix.sync.aligned.m8n8.x4.shared.b16 {%0,%1,%2,%3}, [%4];" : "=r"(r[0]), "=r"(r[1]), "=r"(r[2]), "=r"(r[3]) : "r"(a) : "memory"); }
__device__ __forceinline__ void stsm4(uint32_t a, const uint32_t (&r)[4]) { asm volatile("stmatrix.sync.aligned.m8n8.x4.shared.b16 [%0], {%1,%2,%3,%4};" :: "r"(a), "r"(r[0]), "r"(r[1]), "r"(r[2]), "r"(r[3]) : "memory"); }
__device__ __forceinline__ uint32_t pack(float lo, float hi) { uint32_t r; asm("cvt.rn.bf16x2.f32 %0, %1, %2;" : "=r"(r) : "f"(hi), "f"(lo)); return r; }
__device__ __forceinline__ float blo(uint32_t v) { return __uint_as_float(v << 16); }
__device__ __forceinline__ float bhi(uint32_t v) { return __uint_as_float(v & 0xffff0000u); }
__device__ __forceinline__ float bf16r(float x) { return blo(pack(x, 0.f)); }
__device__ __forceinline__ uint32_t hmul2(uint32_t a, uint32_t b) { uint32_t r; asm("mul.rn.bf16x2 %0, %1, %2;" : "=r"(r) : "r"(a), "r"(b)); return r; }
__device__ __forceinline__ uint32_t hadd2(uint32_t a, uint32_t b) { uint32_t r; asm("add.rn.bf16x2 %0, %1, %2;" : "=r"(r) : "r"(a), "r"(b)); return r; }
__device__ __forceinline__ uint32_t prmt(uint32_t a, uint32_t b, uint32_t s) { return __byte_perm(a, b, s); }
__device__ __forceinline__ float ldbf(const __nv_bfloat16* p) { return blo((uint32_t)__ldg((const unsigned short*)p)); }
__device__ __forceinline__ uint32_t sum4(uint32_t a, uint32_t b, uint32_t c, uint32_t d) {
  return pack((blo(a) + blo(b)) + (blo(c) + blo(d)), (bhi(a) + bhi(b)) + (bhi(c) + bhi(d)));
}
__device__ __forceinline__ void mma16816(float (&c)[4], const uint32_t (&a)[4], uint32_t b0, uint32_t b1) {
  asm volatile("mma.sync.aligned.m16n8k16.row.col.f32.bf16.bf16.f32 {%0,%1,%2,%3}, {%4,%5,%6,%7}, {%8,%9}, {%0,%1,%2,%3};"
               : "+f"(c[0]), "+f"(c[1]), "+f"(c[2]), "+f"(c[3]) : "r"(a[0]), "r"(a[1]), "r"(a[2]), "r"(a[3]), "r"(b0), "r"(b1));
}
__device__ __forceinline__ void bar_sync(int id, int n) { asm volatile("bar.sync %0, %1;" :: "r"(id), "r"(n) : "memory"); }
__device__ __forceinline__ void bar_arrive(int id, int n) { asm volatile("bar.arrive %0, %1;" :: "r"(id), "r"(n) : "memory"); }
__device__ __forceinline__ void cluster_arrive() { asm volatile("barrier.cluster.arrive.relaxed.aligned;" ::: "memory"); }
__device__ __forceinline__ void cluster_wait() { asm volatile("barrier.cluster.wait.aligned;" ::: "memory"); }
__device__ __forceinline__ void fence_async() { asm volatile("fence.proxy.async.shared::cta;" ::: "memory"); }
__device__ __forceinline__ uint32_t mapa(uint32_t a, uint32_t rank) { uint32_t r; asm("mapa.shared::cluster.u32 %0, %1, %2;" : "=r"(r) : "r"(a), "r"(rank)); return r; }
__device__ __forceinline__ void st_async4(uint32_t a, uint32_t x, uint32_t y, uint32_t z, uint32_t w, uint32_t mbar) {
  asm volatile("st.async.weak.shared::cluster.mbarrier::complete_tx::bytes.v4.b32 [%0], {%1,%2,%3,%4}, [%5];"
               :: "r"(a), "r"(x), "r"(y), "r"(z), "r"(w), "r"(mbar) : "memory");
}
__device__ __forceinline__ void mbar_init(uint32_t m, uint32_t cnt) { asm volatile("mbarrier.init.shared::cta.b64 [%0], %1;" :: "r"(m), "r"(cnt) : "memory"); }
__device__ __forceinline__ void mbar_expect(uint32_t m, uint32_t bytes) { asm volatile("mbarrier.arrive.expect_tx.shared::cta.b64 _, [%0], %1;" :: "r"(m), "r"(bytes) : "memory"); }
__device__ __forceinline__ void mbar_arrive(uint32_t m) { asm volatile("mbarrier.arrive.shared::cta.b64 _, [%0];" :: "r"(m) : "memory"); }
__device__ __forceinline__ void mbar_wait(uint32_t m) {
  uint32_t done;
  int it = 0;
  do {
    asm volatile("{.reg .pred p; mbarrier.try_wait.parity.shared::cta.b64 p, [%1], 0; selp.u32 %0, 1, 0, p;}" : "=r"(done) : "r"(m) : "memory");
    if (++it > (1 << 22)) __trap();
  } while (!done);
}
__device__ __forceinline__ void tma_load4(uint32_t dst, const CUtensorMap* tm, int c0, int c3, uint32_t mbar) {
  asm volatile("cp.async.bulk.tensor.4d.shared::cluster.global.mbarrier::complete_tx::bytes [%0], [%1, {%3, %4, %4, %5}], [%2];"
               :: "r"(dst), "l"(tm), "r"(mbar), "r"(c0), "r"(0), "r"(c3) : "memory");
}
__device__ __forceinline__ void tma_store4(const CUtensorMap* tm, int c0, int c3, uint32_t src) {
  asm volatile("cp.async.bulk.tensor.4d.global.shared::cta.bulk_group [%0, {%2, %3, %3, %4}], [%1];"
               :: "l"(tm), "r"(src), "r"(c0), "r"(0), "r"(c3) : "memory");
}
__device__ __forceinline__ void bulk_load(uint32_t dst, const void* src, uint32_t bytes, uint32_t mbar) {
  asm volatile("cp.async.bulk.shared::cluster.global.mbarrier::complete_tx::bytes [%0], [%1], %2, [%3];"
               :: "r"(dst), "l"(src), "r"(bytes), "r"(mbar) : "memory");
}
__device__ __forceinline__ void wg_fence() { asm volatile("wgmma.fence.sync.aligned;" ::: "memory"); }
__device__ __forceinline__ void wg_commit() { asm volatile("wgmma.commit_group.sync.aligned;" ::: "memory"); }
template <int N> __device__ __forceinline__ void wg_wait() { asm volatile("wgmma.wait_group.sync.aligned %0;" :: "n"(N) : "memory"); }
#define WG_REGS "{%0,%1,%2,%3,%4,%5,%6,%7,%8,%9,%10,%11,%12,%13,%14,%15}, {%16,%17,%18,%19}, %20, "
__device__ __forceinline__ void wgmma32_acc(float* d, const uint32_t* a, uint64_t db) {
  asm volatile("wgmma.mma_async.sync.aligned.m64n32k16.f32.bf16.bf16 " WG_REGS "1, 1, 1, 0;"
               : "+f"(d[0]), "+f"(d[1]), "+f"(d[2]), "+f"(d[3]), "+f"(d[4]), "+f"(d[5]), "+f"(d[6]), "+f"(d[7]),
                 "+f"(d[8]), "+f"(d[9]), "+f"(d[10]), "+f"(d[11]), "+f"(d[12]), "+f"(d[13]), "+f"(d[14]), "+f"(d[15])
               : "r"(a[0]), "r"(a[1]), "r"(a[2]), "r"(a[3]), "l"(db));
}
__device__ __forceinline__ void wgmma32_set(float* d, const uint32_t* a, uint64_t db) {
  asm volatile("wgmma.mma_async.sync.aligned.m64n32k16.f32.bf16.bf16 " WG_REGS "0, 1, 1, 0;"
               : "=f"(d[0]), "=f"(d[1]), "=f"(d[2]), "=f"(d[3]), "=f"(d[4]), "=f"(d[5]), "=f"(d[6]), "=f"(d[7]),
                 "=f"(d[8]), "=f"(d[9]), "=f"(d[10]), "=f"(d[11]), "=f"(d[12]), "=f"(d[13]), "=f"(d[14]), "=f"(d[15])
               : "r"(a[0]), "r"(a[1]), "r"(a[2]), "r"(a[3]), "l"(db));
}

struct cf { float x, y; };
__device__ __forceinline__ cf cmul(cf a, cf b) { cf r; r.x = fmaf(a.x, b.x, -a.y * b.y); r.y = fmaf(a.x, b.y, a.y * b.x); return r; }
__device__ __forceinline__ cf cexp_p(float lr2, float lt, float p) {
  float m = exp2f(lr2 * p);
  float t = lt * p;
  t = (t - rintf(t)) * 6.283185307179586f;
  cf r; r.x = m * __cosf(t); r.y = m * __sinf(t); return r;
}
__device__ __forceinline__ void store8(uint32_t a, const cf (&v)[8]) {
  sts128(a, pack(v[0].x, v[1].x), pack(v[2].x, v[3].x), pack(v[4].x, v[5].x), pack(v[6].x, v[7].x));
  sts128(a + KTAB / 2, pack(v[0].y, v[1].y), pack(v[2].y, v[3].y), pack(v[4].y, v[5].y), pack(v[6].y, v[7].y));
}
__device__ __forceinline__ float sigmoidf_(float s) { return 1.f / (1.f + __expf(-s)); }

__global__ void __cluster_dims__(CS, 1, 1) __launch_bounds__(NTHREADS, 1) fused_kernel(const __grid_constant__ Params p) {
  extern __shared__ __align__(1024) uint8_t smem[];
  const uint32_t sb = (uint32_t)__cvta_generic_to_shared(smem);
  const uint32_t mb = sb + OFF_MB;
  const int wg = __shfl_sync(0xffffffffu, threadIdx.x >> 7, 0);
  const int tid = threadIdx.x & 127, w = __shfl_sync(0xffffffffu, tid >> 5, 0), lane = tid & 31, g = lane >> 2, t = lane & 3;
  const int cl = blockIdx.x >> 3, rank = blockIdx.x & 7;
  const int ch0 = cl * CPC;
  const int nu = min(5, (DCH - ch0) >> 3);

  if (threadIdx.x == 256) {
    for (int i = 0; i < MB_COUNT; i++) mbar_init(mb + 8 * i, i == MB_HRDY ? 4 : 1);
    asm volatile("fence.mbarrier_init.release.cluster;" ::: "memory");
    fence_async();
    mbar_expect(mb + 8 * (MB_XQ + 0), 10240);
    tma_load4(sb + OFF_TQ, &p.tq, ch0, 8 * rank, mb + 8 * (MB_XQ + 0));
    mbar_expect(mb + 8 * (MB_XQ + 1), 10240);
    tma_load4(sb + OFF_TQ + 10240, &p.tq, ch0, 8 * rank + 4, mb + 8 * (MB_XQ + 1));
    mbar_expect(mb + 8 * (MB_KV + 0), 2 * 7680 + 10240);
    tma_load4(sb + OFF_TK, &p.tk, ch0, 8 * rank - 1, mb + 8 * (MB_KV + 0));
    tma_load4(sb + OFF_TK + 7680, &p.tk, ch0, 8 * rank + 2, mb + 8 * (MB_KV + 0));
    tma_load4(sb + OFF_TV, &p.tv, ch0, 8 * rank, mb + 8 * (MB_KV + 0));
    mbar_expect(mb + 8 * (MB_KV + 1), 7680 + 10240);
    tma_load4(sb + OFF_TK + 2 * 7680, &p.tk, ch0, 8 * rank + 5, mb + 8 * (MB_KV + 1));
    tma_load4(sb + OFF_TV + 10240, &p.tv, ch0, 8 * rank + 4, mb + 8 * (MB_KV + 1));
    mbar_expect(mb + 8 * MB_HA, nu * 4096);
    for (int u = 0; u < nu; u++)
      bulk_load(sb + OFF_RAWA + u * HPITCH + 16, p.ssm_k + (size_t)(ch0 + 8 * u + rank) * SEQ, 4096, mb + 8 * MB_HA);
    for (int i = MB_UX; i < MB_COUNT; i++) mbar_expect(mb + 8 * i, 4096);
  }
  const int uk0 = wg, uk1 = (wg == 2) ? 9 : 4 - wg;
  float pla[2], pai[2], pcr[2], pci[2], pdt[2], pds[2];
#pragma unroll
  for (int r = 0; r < 2; r++) {
    const int u = r ? uk1 : uk0;
    const int ch = (u < nu) ? ch0 + 8 * u + rank : 0;
    pla[r] = ldbf(p.logA + ch * NMODE + tid);
    pai[r] = ldbf(p.Aim + ch * NMODE + tid);
    pcr[r] = ldbf(p.Cre + ch * NMODE + tid);
    pci[r] = ldbf(p.Cim + ch * NMODE + tid);
    pdt[r] = ldbf(p.logdt + ch);
    pds[r] = ldbf(p.Dskip + ch);
  }
  if (wg == 2) {
    if (tid < 40) {
      const bool ok = ch0 + tid < DCH;
      uint2 sw = make_uint2(0, 0);
      uint32_t gw = 0;
      if (ok) { sw = __ldg((const uint2*)(p.shift_k + (size_t)(ch0 + tid) * 4)); gw = __ldg((const unsigned short*)(p.gate_w + ch0 + tid)); }
      sts64(sb + OFF_SW + 8 * tid, sw.x, sw.y);
      sts16(sb + OFF_GW + 2 * tid, gw);
    }
  } else if (wg == 1) {
    if (tid < 85) sts128(sb + OFF_UX + (tid / 17) * UPITCH + (tid % 17) * 16, 0, 0, 0, 0);
    else if (tid < 90) sts128(sb + OFF_RAWA + (tid - 85) * HPITCH, 0, 0, 0, 0);
  }
  __syncwarp();
  cluster_arrive();
  TL(0);

  const uint32_t tab = sb + OFF_PB + wg * KTAB;
  const uint32_t kc = sb + OFF_KC + wg * 1408;
#pragma unroll 1
  for (int r = 0; r < 2; r++) {
    const int u = r ? uk1 : uk0;
    const bool act = u < nu;
    if (act) {
      const float la = r ? pla[1] : pla[0], ai = r ? pai[1] : pai[0], cr = r ? pcr[1] : pcr[0], ci = r ? pci[1] : pci[0];
      const float dt = bf16r(expf(r ? pdt[1] : pdt[0]));
      const float lr2 = (-bf16r(expf(la)) * dt) * 1.4426950408889634f;
      const float lt = (ai * dt) * 0.15915494309189535f;
      const uint32_t row = tab + tid * 112;
      {
        const cf w1 = cexp_p(lr2, lt, 8.f);
        cf v[8];
        v[0].x = 1.f; v[0].y = 0.f; v[1] = w1; v[2] = cmul(w1, w1); v[3] = cmul(v[2], w1);
        const cf w4 = cmul(v[2], v[2]);
        v[4] = w4; v[5] = cmul(v[1], w4); v[6] = cmul(v[2], w4); v[7] = cmul(v[3], w4);
        const cf w8 = cmul(w4, w4);
        store8(row, v);
#pragma unroll
        for (int c = 1; c < 4; c++) {
#pragma unroll
          for (int i = 0; i < 8; i++) v[i] = (c == 1 && i == 0) ? w8 : cmul(v[i], w8);
          store8(row + 16 * c, v);
        }
      }
      {
        cf z1 = cexp_p(lr2, lt, 1.f), Z = cexp_p(lr2, lt, 256.f);
        z1.y = -z1.y; Z.y = -Z.y;
        const cf z2 = cmul(z1, z1);
        cf h[8], v[8];
        h[0].x = 2.f * cr * dt; h[0].y = -2.f * ci * dt;
        h[1] = cmul(h[0], z1);
#pragma unroll
        for (int i = 2; i < 8; i++) h[i] = cmul(h[i - 2], z2);
        store8(row + 64, h);
        v[0] = cmul(h[0], Z); v[1] = cmul(h[2], Z); v[2] = cmul(h[4], Z); v[3] = cmul(h[6], Z);
        v[4] = cmul(v[0], Z); v[5] = cmul(v[2], Z); v[6] = cmul(v[4], Z); v[7] = cmul(v[5], Z);
        store8(row + 80, v);
        const cf Z2 = cmul(Z, Z);
        h[0] = cmul(v[4], Z2); h[1] = cmul(v[6], Z2); h[2] = cmul(h[0], Z2); h[3] = cmul(h[1], Z2); h[4] = cmul(h[2], Z2);
        h[5].x = h[5].y = h[6].x = h[6].y = h[7].x = h[7].y = 0.f;
        store8(row + 96, h);
      }
      bar_sync(NB_WG0 + wg, 128);
      float c0[4] = {0, 0, 0, 0}, c1[4] = {0, 0, 0, 0}, c2[4] = {0, 0, 0, 0}, c3[4] = {0, 0, 0, 0};
      const int mt = w & 1, hi = w >> 1, mi = lane >> 3;
      const uint32_t aa = tab + (mi >> 1) * (KTAB / 2) + (lane & 7) * 112 + (2 * mt + (mi & 1)) * 16;
      const uint32_t ba = tab + (mi & 1) * (KTAB / 2) + (lane & 7) * 112 + (4 + (hi ? 2 : (mi >> 1))) * 16;
#pragma unroll 4
      for (int ks = 0; ks < 16; ks += 2) {
        uint32_t a0[4], b0[4], a1[4], b1[4];
        ldsm4t(a0, aa + ks * 896); ldsm4t(b0, ba + ks * 896);
        ldsm4t(a1, aa + ks * 896 + 896); ldsm4t(b1, ba + ks * 896 + 896);
        mma16816(c0, a0, b0[0], b0[1]); mma16816(c1, a0, b0[2], b0[3]);
        mma16816(c2, a1, b1[0], b1[1]); mma16816(c3, a1, b1[2], b1[3]);
      }
#pragma unroll
      for (int i = 0; i < 4; i++) { c0[i] += c2[i]; c1[i] += c3[i]; }
      if (tid == 0) c0[0] += r ? pds[1] : pds[0];
#pragma unroll
      for (int hh = 0; hh < 2; hh++) {
        const int a = 16 * mt + g + 8 * hh;
        const uint32_t p0 = pack(c0[2 * hh], c0[2 * hh + 1]), p1 = pack(c1[2 * hh], c1[2 * hh + 1]);
        if (!hi) {
          sts32(kc + 4 * (4 * a + t), p0);
          sts32(kc + 4 * (t < 2 ? 128 + 2 * a + t : 128 + 32 * t + a), p1);
        } else if (t < 3) {
          sts16(kc + 2 * (512 + 64 * t + a), p0);
          sts16(kc + 2 * (544 + 64 * t + a), p0 >> 16);
        }
      }
    }
    if (r == 0) {
      bar_sync(NB_WG0 + wg, 128);
    } else {
      bar_sync(NB_R1, 384);
      if (tid < 32) sts128(sb + OFF_PB + wg * PBSZ + tid * 528, 0, 0, 0, 0);
      else if (wg == 1 && tid >= 32 && tid < 32 + 85) sts128(sb + OFF_UKV + ((tid - 32) / 17) * UPITCH + ((tid - 32) % 17) * 16, 0, 0, 0, 0);
    }
    if (act) {
      const uint32_t hs = sb + OFF_HB + (4 - u) * 2 * HPITCH;
#pragma unroll
      for (int cc = 0; cc < 2; cc++) {
        const int c = tid + 128 * cc;
        uint32_t v[9];
#pragma unroll
        for (int i = 0; i < 9; i++) {
          const int l = 8 * c + i;
          const uint32_t id = (cc == 0 && c < 16) ? (uint32_t)l : (pack((float)l, 0.f) - 0x4280u);
          v[i] = lds16(kc + 2 * id);
        }
        sts128(hs + HPITCH + 16 + 16 * c, prmt(v[0], v[1], 0x5410), prmt(v[2], v[3], 0x5410), prmt(v[4], v[5], 0x5410), prmt(v[6], v[7], 0x5410));
        sts128(hs + 16 + 16 * c, prmt(v[1], v[2], 0x5410), prmt(v[3], v[4], 0x5410), prmt(v[5], v[6], 0x5410), prmt(v[7], v[8], 0x5410));
        if (c == 0) { sts128(hs + HPITCH, 0, 0, 0, 0); sts128(hs, 0, 0, 0, v[0] << 16); }
      }
    }
    TL(1 + r);
    if (wg == 2) break;
  }

  if (wg < 2) {
    fence_async();
    bar_sync(NB_R2, 256);
    cluster_wait();
    cluster_arrive();
    asm volatile("setmaxnreg.inc.sync.aligned.u32 216;");
    const uint32_t haoff = 4 * (8 * w + ((g + 1) >> 1) + t);
    const uint32_t pw = sb + OFF_PB + wg * PBSZ + 4 * ((w * 8 + g) * 132 + t + w);
    const uint32_t pr = sb + OFF_PB + wg * PBSZ + w * 528 + lane * 16;
    const uint32_t rbase = mapa(sb, g);
    if (wg == 1) bar_arrive(NB_TOK0, 256);
    bool hb_done = false;
#pragma unroll 1
    for (int i = wg; i < 2 * nu; i += 2) {
      const bool isA = i >= nu;
      const int u = isA ? i - nu : i;
      uint32_t ha;
      if (isA) {
        mbar_wait(mb + 8 * MB_HRDY);
        ha = (g & 1) ? sb + OFF_RAWA + u * HPITCH : sb + OFF_HB + (9 - u) * HPITCH;
      } else {
        ha = sb + OFF_HB + (8 - 2 * u + (g & 1)) * HPITCH;
      }
      ha += haoff;
      uint32_t a[12][4];
#pragma unroll
      for (int m = 0; m < 12; m++) {
        a[m][0] = lds32(ha + 256 * m + 16); a[m][1] = lds32(ha + 256 * m + 144);
        a[m][2] = lds32(ha + 256 * m);      a[m][3] = lds32(ha + 256 * m + 128);
      }
      mbar_wait(mb + 8 * ((isA ? MB_UKV : MB_UX) + u));
      fence_async();
      const uint32_t ub = sb + (isA ? OFF_UKV : OFF_UX) + u * UPITCH;
      const uint64_t db = (uint64_t)((ub & 0x3FFFF) >> 4) | (1ull << 16) | (8ull << 32);
      float acc[128];
      bar_sync(NB_TOK0 + wg, 256);
      TL(3 + (i >> 1));
      wg_fence();
#pragma unroll
      for (int m = 0; m < 12; m++) {
#pragma unroll
        for (int j = 0; j < 8; j++) {
          if (m < 2 * (j + 1)) {
            if (m == 0) wgmma32_set(acc + 16 * j, a[m], db + (uint64_t)(16 + 32 * j - 16 * m));
            else wgmma32_acc(acc + 16 * j, a[m], db + (uint64_t)(16 + 32 * j - 16 * m));
          }
        }
        if (m == 3) wg_commit();
      }
      wg_commit();
      wg_wait<1>();
#pragma unroll
      for (int m = 12; m < 16; m++) {
        a[m - 12][0] = lds32(ha + 256 * m + 16); a[m - 12][1] = lds32(ha + 256 * m + 144);
        a[m - 12][2] = lds32(ha + 256 * m);      a[m - 12][3] = lds32(ha + 256 * m + 128);
      }
      wg_fence();
#pragma unroll
      for (int m = 12; m < 16; m++) {
#pragma unroll
        for (int j = 6; j < 8; j++)
          if (m < 2 * (j + 1)) wgmma32_acc(acc + 16 * j, a[m - 12], db + (uint64_t)(16 + 32 * j - 16 * m));
      }
      wg_commit();
      if (!hb_done && (i + 2 >= nu || i + 2 > 2)) { bar_arrive(NB_HBFREE, 384); hb_done = true; }
      wg_wait<1>();
      if (i + 1 < 2 * nu) bar_arrive(NB_TOK1 - wg, 256);
      wg_wait<0>();
#pragma unroll
      for (int j = 0; j < 32; j++) {
        float v0 = acc[4 * j], v1 = acc[4 * j + 1];
        if (j > 0) { v0 += acc[4 * j - 2]; v1 += acc[4 * j - 1]; }
        sts32(pw + 16 * j, pack(v0, v1));
      }
      if (i == wg) cluster_wait();
      if (isA) { for (int k = 0; k < nu; k++) mbar_wait(mb + 8 * (MB_UKV + k)); }
      bar_sync(NB_WG0 + wg, 128);
      const uint32_t yd = rbase + (isA ? OFF_YA : OFF_YB) + (8 * u + rank) * YPITCH + (4 * w + t) * 16;
      const uint32_t ym = rbase + OFF_MB + 8 * ((isA ? MB_YA : MB_YB) + u);
#pragma unroll
      for (int hh = 0; hh < 2; hh++) {
        const uint4 p0 = lds128(pr + hh * 2112), p1 = lds128(pr + hh * 2112 + 4224), p2 = lds128(pr + hh * 2112 + 8448), p3 = lds128(pr + hh * 2112 + 12672);
        st_async4(yd + hh * 256, sum4(p0.x, p1.x, p2.x, p3.x), sum4(p0.y, p1.y, p2.y, p3.y), sum4(p0.z, p1.z, p2.z, p3.z), sum4(p0.w, p1.w, p2.w, p3.w), ym);
      }
      bar_sync(NB_WG0 + wg, 128);
      TL(8 + (i >> 1));
    }
  } else {
    bar_arrive(NB_R1, 384);
    asm volatile("setmaxnreg.dec.sync.aligned.u32 72;");
    cluster_wait();
    cluster_arrive();
    const uint32_t rbase = mapa(sb, g);
    const int mi = lane >> 3, tp = (lane & 7) >> 1, jj = lane & 1;
    const uint32_t toff = (4 * (7 - 2 * mi - jj) + tp) * 80;
#pragma unroll 1
    for (int hf = 0; hf < 2; hf++) {
      mbar_wait(mb + 8 * (MB_XQ + hf));
      const int ah = 4 * hf + w;
#pragma unroll 1
      for (int u = 0; u < nu; u++) {
        uint32_t r[4];
        ldsm4t(r, sb + OFF_TQ + ah * 2560 + toff + 16 * u);
        st_async4(rbase + OFF_UX + u * UPITCH + UPAD + 16 * (32 * rank + 4 * ah + t), r[0], r[1], r[2], r[3], rbase + OFF_MB + 8 * (MB_UX + u));
      }
    }
    TL(2);
    {
      float s0 = 0.f, s1 = 0.f;
#pragma unroll
      for (int j = 0; j < 5; j++) {
        const uint4 gw = lds128(sb + OFF_GW + 16 * j);
        const uint4 x0 = lds128(sb + OFF_TQ + tid * 80 + 16 * j), x1 = lds128(sb + OFF_TQ + (tid + 128) * 80 + 16 * j);
        uint32_t m0 = hmul2(x0.x, gw.x), m1 = hmul2(x0.y, gw.y), m2 = hmul2(x0.z, gw.z), m3 = hmul2(x0.w, gw.w);
        s0 += ((blo(m0) + bhi(m0)) + (blo(m1) + bhi(m1))) + ((blo(m2) + bhi(m2)) + (blo(m3) + bhi(m3)));
        m0 = hmul2(x1.x, gw.x); m1 = hmul2(x1.y, gw.y); m2 = hmul2(x1.z, gw.z); m3 = hmul2(x1.w, gw.w);
        s1 += ((blo(m0) + bhi(m0)) + (blo(m1) + bhi(m1))) + ((blo(m2) + bhi(m2)) + (blo(m3) + bhi(m3)));
      }
      __stcg(&g_part[cl * SEQ + rank * 256 + tid], s0);
      __stcg(&g_part[cl * SEQ + rank * 256 + 128 + tid], s1);
    }
    bar_sync(NB_WG0 + 2, 128);
    unsigned g_target = 0;
    if (tid == 96) {
      __threadfence();
      const unsigned old = atomicAdd(&g_cnt[rank * 32], cl == 0 ? 16 - (NCL - 1) : 1);
      g_target = (old & ~15u) + 16;
    }
    TL(3);
    cluster_wait();
    const uint32_t hoff = (4 * (7 - 2 * (mi & 1) - jj) + ((tp + 3) & 3)) * 80 + (tp ? 2560 : 0);
#pragma unroll 1
    for (int hf = 0; hf < 2; hf++) {
      mbar_wait(mb + 8 * (MB_KV + hf));
      TL(4 + hf);
      const int ah = 4 * hf + w;
#pragma unroll 1
      for (int u = 0; u < nu; u++) {
        uint32_t K[4], K4, K5, V[4], o[4];
        ldsm4t(K, sb + OFF_TK + (ah + 1) * 2560 + toff + 16 * u);
        ldsm2t(K4, K5, sb + OFF_TK + ah * 2560 + hoff + 16 * u);
        ldsm4t(V, sb + OFF_TV + ah * 2560 + toff + 16 * u);
        const uint2 sw = lds64(sb + OFF_SW + 8 * (8 * u + g));
        const uint32_t w0 = prmt(sw.x, 0, 0x1010), w1 = prmt(sw.x, 0, 0x3232), w2 = prmt(sw.y, 0, 0x1010), w3 = prmt(sw.y, 0, 0x3232);
        const uint32_t E[6] = {K[0], K[1], K[2], K[3], K4, K5};
        uint32_t O[5];
#pragma unroll
        for (int i = 0; i < 5; i++) O[i] = prmt(E[i], E[i + 1], 0x5432);
#pragma unroll
        for (int i = 0; i < 4; i++) {
          uint32_t s = hmul2(O[i + 1], w3);
          s = hadd2(s, hmul2(E[i + 1], w2));
          s = hadd2(s, hmul2(O[i], w1));
          s = hadd2(s, hmul2(E[i], w0));
          o[i] = hmul2(s, V[i]);
        }
        st_async4(rbase + OFF_UKV + u * UPITCH + UPAD + 16 * (32 * rank + 4 * ah + t), o[0], o[1], o[2], o[3], rbase + OFF_MB + 8 * (MB_UKV + u));
      }
    }
    TL(6);
    float dval = 0.f;
    if (tid < nu) dval = ldbf(p.ssm_D + ch0 + 8 * tid + rank);
    mbar_wait(mb + 8 * MB_HA);
    bar_sync(NB_HBFREE, 384);
#pragma unroll 1
    for (int k = 0; k < 2 * nu; k++) {
      const int u = k >> 1, c = tid + 128 * (k & 1);
      const uint32_t ra = sb + OFF_RAWA + u * HPITCH + 16 + 16 * c;
      const uint4 x = lds128(ra);
      const uint32_t n = lds32(ra + 16);
      sts128(sb + OFF_HB + (9 - u) * HPITCH + 16 + 16 * c, prmt(x.x, x.y, 0x5432), prmt(x.y, x.z, 0x5432), prmt(x.z, x.w, 0x5432), prmt(x.w, n, 0x5432));
    }
    if (tid < nu) {
      const uint32_t ra = sb + OFF_RAWA + tid * HPITCH + 16;
      const uint32_t h0 = pack(blo(lds16(ra)) + dval, 0.f);
      sts16(ra, h0);
      sts128(sb + OFF_HB + (9 - tid) * HPITCH, 0, 0, 0, h0 << 16);
    }
    __syncwarp();
    if (lane == 0) mbar_arrive(mb + 8 * MB_HRDY);
    TL(7);
    uint32_t okflag = 1;
    if (tid == 96) {
      unsigned v;
      int it = 0;
      do {
        asm volatile("ld.acquire.gpu.global.u32 %0, [%1];" : "=r"(v) : "l"(&g_cnt[rank * 32]) : "memory");
      } while ((int)(v - g_target) < 0 && ++it < 20000);
      okflag = (int)(v - g_target) >= 0;
    }
    asm volatile("{.reg .pred p, q; setp.ne.u32 p, %1, 0; bar.red.and.pred q, %2, 128, p; selp.u32 %0, 1, 0, q;}" : "=r"(okflag) : "r"(okflag), "r"(NB_WG0 + 2) : "memory");
#pragma unroll 1
    for (int hf = 0; hf < 2; hf++) {
      const int slot = tid + 128 * hf;
      float s = 0.f;
      if (okflag) {
        float v[NCL];
#pragma unroll
        for (int c = 0; c < NCL; c++) v[c] = __ldcg(&g_part[c * SEQ + rank * 256 + slot]);
#pragma unroll
        for (int c = 0; c < NCL; c++) s += v[c];
      } else {
        const int row = rank * 256 + (slot & ~31) + 8 * (slot & 3) + ((slot >> 2) & 7);
        const uint32_t* xr = (const uint32_t*)(p.q + (size_t)row * DCH);
        const uint32_t* gr = (const uint32_t*)p.gate_w;
#pragma unroll 1
        for (int c = 0; c < DCH / 2; c++) { const uint32_t m = hmul2(__ldg(xr + c), __ldg(gr + c)); s += blo(m) + bhi(m); }
      }
      const float gv = bf16r(sigmoidf_(bf16r(s)));
      sts64(sb + OFF_KC + 8 * slot, pack(gv, gv), pack(1.f - gv, 1.f - gv));
    }
    bar_sync(NB_WG0 + 2, 128);
    TL(8);
    const int r8 = lane & 7;
#pragma unroll 1
    for (int u = 0; u < nu; u++) {
      mbar_wait(mb + 8 * (MB_YB + u));
      mbar_wait(mb + 8 * (MB_YA + u));
#pragma unroll
      for (int hh = 0; hh < 2; hh++) {
        const int gs = w + 4 * hh;
        uint32_t ya[4], yb[4], qv[4], o[4];
        const uint32_t yo = (8 * u + r8) * YPITCH + (4 * gs + mi) * 16;
        ldsm4t(ya, sb + OFF_YA + yo);
        ldsm4t(yb, sb + OFF_YB + yo);
        const uint32_t qa = sb + OFF_TQ + (64 * mi + 32 * (r8 >> 2) + 4 * gs + (r8 & 3)) * 80 + 16 * u;
        ldsm4(qv, qa);
#pragma unroll
        for (int i = 0; i < 4; i++) {
          const uint2 gg = lds64(sb + OFF_KC + 8 * (64 * i + 32 * (g >> 2) + 4 * gs + (g & 3)));
          o[i] = hadd2(hmul2(gg.x, hmul2(qv[i], ya[i])), hmul2(gg.y, yb[i]));
        }
        stsm4(qa, o);
      }
      TL(9 + u);
    }
    fence_async();
    bar_sync(NB_WG0 + 2, 128);
    if (tid == 0) {
      tma_store4(&p.to, ch0, 8 * rank, sb + OFF_TQ);
      tma_store4(&p.to, ch0, 8 * rank + 4, sb + OFF_TQ + 10240);
      asm volatile("cp.async.bulk.commit_group;" ::: "memory");
      asm volatile("cp.async.bulk.wait_group.read 0;" ::: "memory");
    }
    TL(14);
  }
}

typedef CUresult (*EncodeFn)(CUtensorMap*, CUtensorMapDataType, cuuint32_t, void*, const cuuint64_t*, const cuuint64_t*,
                             const cuuint32_t*, const cuuint32_t*, CUtensorMapInterleave, CUtensorMapSwizzle,
                             CUtensorMapL2promotion, CUtensorMapFloatOOBfill);

void make_map(EncodeFn fn, CUtensorMap* tm, const void* ptr, int nhi) {
  cuuint64_t dims[4] = {DCH, 4, 8, SEQ / 32};
  cuuint64_t strides[3] = {8 * DCH * 2, DCH * 2, 32 * DCH * 2};
  cuuint32_t box[4] = {CPC, 4, 8, (cuuint32_t)nhi};
  cuuint32_t es[4] = {1, 1, 1, 1};
  fn(tm, CU_TENSOR_MAP_DATA_TYPE_BFLOAT16, 4, const_cast<void*>(ptr), dims, strides, box, es, CU_TENSOR_MAP_INTERLEAVE_NONE,
     CU_TENSOR_MAP_SWIZZLE_NONE, CU_TENSOR_MAP_L2_PROMOTION_L2_128B, CU_TENSOR_MAP_FLOAT_OOB_FILL_NONE);
}

}

extern "C" void kernel_launch(void* const* d_in, const int* in_sizes, int n_in, void* d_out, int out_size) {
  (void)in_sizes; (void)n_in; (void)out_size;
  static EncodeFn fn = nullptr;
  if (!fn) {
    cudaDriverEntryPointQueryResult qr;
    cudaGetDriverEntryPoint("cuTensorMapEncodeTiled", (void**)&fn, cudaEnableDefault, &qr);
    cudaFuncSetAttribute(fused_kernel, cudaFuncAttributeMaxDynamicSharedMemorySize, SMEM_BYTES);
  }
  Params p;
  make_map(fn, &p.tq, d_in[0], 4);
  make_map(fn, &p.tk, d_in[1], 3);
  make_map(fn, &p.tv, d_in[2], 4);
  make_map(fn, &p.to, d_out, 4);
  p.q = (const __nv_bfloat16*)d_in[0];
  p.shift_k = (const __nv_bfloat16*)d_in[3];
  p.ssm_k = (const __nv_bfloat16*)d_in[4];
  p.ssm_D = (const __nv_bfloat16*)d_in[5];
  p.logA = (const __nv_bfloat16*)d_in[7];
  p.Aim = (const __nv_bfloat16*)d_in[8];
  p.Cre = (const __nv_bfloat16*)d_in[9];
  p.Cim = (const __nv_bfloat16*)d_in[10];
  p.logdt = (const __nv_bfloat16*)d_in[11];
  p.Dskip = (const __nv_bfloat16*)d_in[12];
  p.gate_w = (const __nv_bfloat16*)d_in[13];
  fused_kernel<<<NCL * CS, NTHREADS, SMEM_BYTES, cudaStreamPerThread>>>(p);
}
```

```cpp
#include <cuda_runtime.h>
#include <cuda_bf16.h>
#include <cuda.h>
#include <stdint.h>

#define TIMELINE 0

namespace {

constexpr int SEQ = 2048, DCH = 576, NMODE = 128;
constexpr int CS = 8, CPC = 40, NCL = 15, NTHREADS = 384;

constexpr int UPITCH = 4368, UPAD = 272;
constexpr int HPITCH = 4160;
constexpr int PBSZ = 16896;
constexpr int YPITCH = 528;
constexpr int KTAB = 28672;
constexpr int OFF_TQ = 0;
constexpr int OFF_TK = 20480;
constexpr int OFF_YA = OFF_TK;
constexpr int OFF_TV = 43520;
constexpr int OFF_UX = 64000;
constexpr int OFF_RAWA = OFF_UX + 5 * UPITCH + 48 + 48;
constexpr int OFF_PB = OFF_RAWA - 48 + 5 * HPITCH + 16;
constexpr int OFF_YB = OFF_PB + 2 * PBSZ;
constexpr int OFF_UKV = OFF_YB + 40 * YPITCH;
constexpr int OFF_HB = OFF_UKV + 5 * UPITCH + 48;
constexpr int OFF_KC = OFF_HB + 10 * HPITCH;
constexpr int OFF_SW = OFF_KC + 3 * 1408;
constexpr int OFF_GW = OFF_SW + 320;
constexpr int OFF_MB = OFF_GW + 80;
constexpr int OFF_TL = OFF_MB + 32 * 8;
constexpr int SMEM_BYTES = OFF_TL + (TIMELINE ? 1536 : 0);
static_assert(((OFF_RAWA - OFF_HB) & 63) == 32, "bank offset between raw/shift copies");
static_assert(OFF_PB + 3 * KTAB <= OFF_HB + 4 * HPITCH, "ktab alias zone");
static_assert(SMEM_BYTES <= 232448, "smem");
static_assert(((OFF_RAWA - 48) & 127) == 0, "tma dst");
static_assert((OFF_RAWA & 15) == 0 && (OFF_PB & 15) == 0 && (OFF_HB & 15) == 0 && (OFF_MB & 7) == 0 && (OFF_KC & 15) == 0, "align");

enum { MB_UX = 0, MB_UKV = 5, MB_Y = 10, MB_HRDY = 15, MB_XQ = 16, MB_KV = 18, MB_HA = 20, MB_COUNT = 21 };
enum { NB_TOK0 = 1, NB_TOK1 = 2, NB_WG0 = 3, NB_R1 = 6, NB_R2 = 7, NB_HBFREE = 8 };

struct Params {
  CUtensorMap tq, tk, tv, to, th;
  const __nv_bfloat16 *q, *shift_k, *ssm_k, *ssm_D, *logA, *Aim, *Cre, *Cim, *logdt, *Dskip, *gate_w;
};

__device__ float g_part[NCL * SEQ];
__device__ unsigned g_cnt[CS * 32];
#define TL(i) do {} while (0)
#define TL_INIT() do {} while (0)
#define TL_DUMP() do {} while (0)

__device__ __forceinline__ uint32_t lds32(uint32_t a) { uint32_t v; asm volatile("ld.shared.u32 %0, [%1];" : "=r"(v) : "r"(a) : "memory"); return v; }
__device__ __forceinline__ uint32_t lds16(uint32_t a) { uint32_t v; asm volatile("ld.shared.u16 %0, [%1];" : "=r"(v) : "r"(a) : "memory"); return v; }
__device__ __forceinline__ uint2 lds64(uint32_t a) { uint2 v; asm volatile("ld.shared.v2.u32 {%0,%1}, [%2];" : "=r"(v.x), "=r"(v.y) : "r"(a) : "memory"); return v; }
__device__ __forceinline__ uint4 lds128(uint32_t a) { uint4 v; asm volatile("ld.shared.v4.u32 {%0,%1,%2,%3}, [%4];" : "=r"(v.x), "=r"(v.y), "=r"(v.z), "=r"(v.w) : "r"(a) : "memory"); return v; }
__device__ __forceinline__ void sts16(uint32_t a, uint32_t v) { asm volatile("st.shared.u16 [%0], %1;" :: "r"(a), "r"(v) : "memory"); }
__device__ __forceinline__ void sts32(uint32_t a, uint32_t v) { asm volatile("st.shared.u32 [%0], %1;" :: "r"(a), "r"(v) : "memory"); }
__device__ __forceinline__ void sts64(uint32_t a, uint32_t x, uint32_t y) { asm volatile("st.shared.v2.u32 [%0], {%1,%2};" :: "r"(a), "r"(x), "r"(y) : "memory"); }
__device__ __forceinline__ void sts128(uint32_t a, uint32_t x, uint32_t y, uint32_t z, uint32_t w) { asm volatile("st.shared.v4.u32 [%0], {%1,%2,%3,%4};" :: "r"(a), "r"(x), "r"(y), "r"(z), "r"(w) : "memory"); }
__device__ __forceinline__ void ldsm4t(uint32_t (&r)[4], uint32_t a) { asm volatile("ldmatrix.sync.aligned.m8n8.x4.trans.shared.b16 {%0,%1,%2,%3}, [%4];" : "=r"(r[0]), "=r"(r[1]), "=r"(r[2]), "=r"(r[3]) : "r"(a) : "memory"); }
__device__ __forceinline__ void ldsm2t(uint32_t& r0, uint32_t& r1, uint32_t a) { asm volatile("ldmatrix.sync.aligned.m8n8.x2.trans.shared.b16 {%0,%1}, [%2];" : "=r"(r0), "=r"(r1) : "r"(a) : "memory"); }
__device__ __forceinline__ void ldsm4(uint32_t (&r)[4], uint32_t a) { asm volatile("ldmatrix.sync.aligned.m8n8.x4.shared.b16 {%0,%1,%2,%3}, [%4];" : "=r"(r[0]), "=r"(r[1]), "=r"(r[2]), "=r"(r[3]) : "r"(a) : "memory"); }
__device__ __forceinline__ void stsm4(uint32_t a, const uint32_t (&r)[4]) { asm volatile("stmatrix.sync.aligned.m8n8.x4.shared.b16 [%0], {%1,%2,%3,%4};" :: "r"(a), "r"(r[0]), "r"(r[1]), "r"(r[2]), "r"(r[3]) : "memory"); }
__device__ __forceinline__ uint32_t pack(float lo, float hi) { uint32_t r; asm("cvt.rn.bf16x2.f32 %0, %1, %2;" : "=r"(r) : "f"(hi), "f"(lo)); return r; }
__device__ __forceinline__ float blo(uint32_t v) { return __uint_as_float(v << 16); }
__device__ __forceinline__ float bhi(uint32_t v) { return __uint_as_float(v & 0xffff0000u); }
__device__ __forceinline__ float bf16r(float x) { return blo(pack(x, 0.f)); }
__device__ __forceinline__ uint32_t hmul2(uint32_t a, uint32_t b) { uint32_t r; asm("mul.rn.bf16x2 %0, %1, %2;" : "=r"(r) : "r"(a), "r"(b)); return r; }
__device__ __forceinline__ uint32_t hadd2(uint32_t a, uint32_t b) { uint32_t r; asm("add.rn.bf16x2 %0, %1, %2;" : "=r"(r) : "r"(a), "r"(b)); return r; }
__device__ __forceinline__ uint32_t prmt(uint32_t a, uint32_t b, uint32_t s) { return __byte_perm(a, b, s); }
__device__ __forceinline__ float ldbf(const __nv_bfloat16* p) { return blo((uint32_t)__ldg((const unsigned short*)p)); }
__device__ __forceinline__ uint32_t sum4(uint32_t a, uint32_t b, uint32_t c, uint32_t d) {
  return pack((blo(a) + blo(b)) + (blo(c) + blo(d)), (bhi(a) + bhi(b)) + (bhi(c) + bhi(d)));
}
__device__ __forceinline__ void mma16816(float (&c)[4], const uint32_t (&a)[4], uint32_t b0, uint32_t b1) {
  asm volatile("mma.sync.aligned.m16n8k16.row.col.f32.bf16.bf16.f32 {%0,%1,%2,%3}, {%4,%5,%6,%7}, {%8,%9}, {%0,%1,%2,%3};"
               : "+f"(c[0]), "+f"(c[1]), "+f"(c[2]), "+f"(c[3]) : "r"(a[0]), "r"(a[1]), "r"(a[2]), "r"(a[3]), "r"(b0), "r"(b1));
}
__device__ __forceinline__ void bar_sync(int id, int n) { asm volatile("bar.sync %0, %1;" :: "r"(id), "r"(n) : "memory"); }
__device__ __forceinline__ void bar_arrive(int id, int n) { asm volatile("bar.arrive %0, %1;" :: "r"(id), "r"(n) : "memory"); }
__device__ __forceinline__ void cluster_arrive() { asm volatile("barrier.cluster.arrive.relaxed.aligned;" ::: "memory"); }
__device__ __forceinline__ void cluster_wait() { asm volatile("barrier.cluster.wait.aligned;" ::: "memory"); }
__device__ __forceinline__ void fence_async() { asm volatile("fence.proxy.async.shared::cta;" ::: "memory"); }
__device__ __forceinline__ uint32_t mapa(uint32_t a, uint32_t rank) { uint32_t r; asm("mapa.shared::cluster.u32 %0, %1, %2;" : "=r"(r) : "r"(a), "r"(rank)); return r; }
__device__ __forceinline__ void st_async4(uint32_t a, uint32_t x, uint32_t y, uint32_t z, uint32_t w, uint32_t mbar) {
  asm volatile("st.async.weak.shared::cluster.mbarrier::complete_tx::bytes.v4.b32 [%0], {%1,%2,%3,%4}, [%5];"
               :: "r"(a), "r"(x), "r"(y), "r"(z), "r"(w), "r"(mbar) : "memory");
}
__device__ __forceinline__ void mbar_init(uint32_t m, uint32_t cnt) { asm volatile("mbarrier.init.shared::cta.b64 [%0], %1;" :: "r"(m), "r"(cnt) : "memory"); }
__device__ __forceinline__ void mbar_expect(uint32_t m, uint32_t bytes) { asm volatile("mbarrier.arrive.expect_tx.shared::cta.b64 _, [%0], %1;" :: "r"(m), "r"(bytes) : "memory"); }
__device__ __forceinline__ void mbar_arrive(uint32_t m) { asm volatile("mbarrier.arrive.shared::cta.b64 _, [%0];" :: "r"(m) : "memory"); }
__device__ __forceinline__ void mbar_wait(uint32_t m) {
  uint32_t done;
  int it = 0;
  do {
    asm volatile("{.reg .pred p; mbarrier.try_wait.parity.shared::cta.b64 p, [%1], 0; selp.u32 %0, 1, 0, p;}" : "=r"(done) : "r"(m) : "memory");
    if (++it > (1 << 22)) __trap();
  } while (!done);
}
__device__ __forceinline__ void tma_load4(uint32_t dst, const CUtensorMap* tm, int c0, int c3, uint32_t mbar) {
  asm volatile("cp.async.bulk.tensor.4d.shared::cluster.global.mbarrier::complete_tx::bytes [%0], [%1, {%3, %4, %4, %5}], [%2];"
               :: "r"(dst), "l"(tm), "r"(mbar), "r"(c0), "r"(0), "r"(c3) : "memory");
}
__device__ __forceinline__ void tma_store4(const CUtensorMap* tm, int c0, int c3, uint32_t src) {
  asm volatile("cp.async.bulk.tensor.4d.global.shared::cta.bulk_group [%0, {%2, %3, %3, %4}], [%1];"
               :: "l"(tm), "r"(src), "r"(c0), "r"(0), "r"(c3) : "memory");
}
__device__ __forceinline__ void bulk_load(uint32_t dst, const void* src, uint32_t bytes, uint32_t mbar) {
  asm volatile("cp.async.bulk.shared::cluster.global.mbarrier::complete_tx::bytes [%0], [%1], %2, [%3];"
               :: "r"(dst), "l"(src), "r"(bytes), "r"(mbar) : "memory");
}
__device__ __forceinline__ void wg_fence() { asm volatile("wgmma.fence.sync.aligned;" ::: "memory"); }
__device__ __forceinline__ void wg_commit() { asm volatile("wgmma.commit_group.sync.aligned;" ::: "memory"); }
template <int N> __device__ __forceinline__ void wg_wait() { asm volatile("wgmma.wait_group.sync.aligned %0;" :: "n"(N) : "memory"); }
#define WG_REGS "{%0,%1,%2,%3,%4,%5,%6,%7,%8,%9,%10,%11,%12,%13,%14,%15}, {%16,%17,%18,%19}, %20, "
__device__ __forceinline__ void wgmma32_acc(float* d, const uint32_t* a, uint64_t db) {
  asm volatile("wgmma.mma_async.sync.aligned.m64n32k16.f32.bf16.bf16 " WG_REGS "1, 1, 1, 0;"
               : "+f"(d[0]), "+f"(d[1]), "+f"(d[2]), "+f"(d[3]), "+f"(d[4]), "+f"(d[5]), "+f"(d[6]), "+f"(d[7]),
                 "+f"(d[8]), "+f"(d[9]), "+f"(d[10]), "+f"(d[11]), "+f"(d[12]), "+f"(d[13]), "+f"(d[14]), "+f"(d[15])
               : "r"(a[0]), "r"(a[1]), "r"(a[2]), "r"(a[3]), "l"(db));
}
__device__ __forceinline__ void wgmma32_set(float* d, const uint32_t* a, uint64_t db) {
  asm volatile("wgmma.mma_async.sync.aligned.m64n32k16.f32.bf16.bf16 " WG_REGS "0, 1, 1, 0;"
               : "=f"(d[0]), "=f"(d[1]), "=f"(d[2]), "=f"(d[3]), "=f"(d[4]), "=f"(d[5]), "=f"(d[6]), "=f"(d[7]),
                 "=f"(d[8]), "=f"(d[9]), "=f"(d[10]), "=f"(d[11]), "=f"(d[12]), "=f"(d[13]), "=f"(d[14]), "=f"(d[15])
               : "r"(a[0]), "r"(a[1]), "r"(a[2]), "r"(a[3]), "l"(db));
}

struct cf { float x, y; };
__device__ __forceinline__ cf cmul(cf a, cf b) { cf r; r.x = fmaf(a.x, b.x, -a.y * b.y); r.y = fmaf(a.x, b.y, a.y * b.x); return r; }
__device__ __forceinline__ cf cexp_p(float lr2, float lt, float p) {
  float m = exp2f(lr2 * p);
  float t = lt * p;
  t = (t - rintf(t)) * 6.283185307179586f;
  cf r; r.x = m * __cosf(t); r.y = m * __sinf(t); return r;
}
__device__ __forceinline__ void store8(uint32_t a, const cf (&v)[8]) {
  sts128(a, pack(v[0].x, v[1].x), pack(v[2].x, v[3].x), pack(v[4].x, v[5].x), pack(v[6].x, v[7].x));
  sts128(a + KTAB / 2, pack(v[0].y, v[1].y), pack(v[2].y, v[3].y), pack(v[4].y, v[5].y), pack(v[6].y, v[7].y));
}
__device__ __forceinline__ float sigmoidf_(float s) { return 1.f / (1.f + __expf(-s)); }

__global__ void __cluster_dims__(CS, 1, 1) __launch_bounds__(NTHREADS, 1) fused_kernel(const __grid_constant__ Params p) {
  extern __shared__ __align__(1024) uint8_t smem[];
  TL_INIT();
  TL(31);
  const uint32_t sb = (uint32_t)__cvta_generic_to_shared(smem);
  const uint32_t mb = sb + OFF_MB;
  const int wg = __shfl_sync(0xffffffffu, threadIdx.x >> 7, 0);
  const int tid = threadIdx.x & 127, w = __shfl_sync(0xffffffffu, tid >> 5, 0), lane = tid & 31, g = lane >> 2, t = lane & 3;
  const int cl = blockIdx.x >> 3, rank = blockIdx.x & 7;
  const int ch0 = cl * CPC;
  const int nu = min(5, (DCH - ch0) >> 3);

  if (lane == 0) {
    if (wg == 2) {
      if (w == 0) {
        mbar_init(mb + 8 * MB_XQ, 1);
        mbar_init(mb + 8 * (MB_XQ + 1), 1);
        fence_async();
        mbar_expect(mb + 8 * MB_XQ, 10240);
        tma_load4(sb + OFF_TQ, &p.tq, ch0, 8 * rank, mb + 8 * MB_XQ);
        mbar_expect(mb + 8 * (MB_XQ + 1), 10240);
        tma_load4(sb + OFF_TQ + 10240, &p.tq, ch0, 8 * rank + 4, mb + 8 * (MB_XQ + 1));
        TL(20);
      } else if (w == 1) {
        mbar_init(mb + 8 * MB_KV, 1);
        mbar_init(mb + 8 * (MB_KV + 1), 1);
        mbar_init(mb + 8 * MB_HA, 1);
        fence_async();
        mbar_expect(mb + 8 * MB_KV, 23040);
        mbar_expect(mb + 8 * (MB_KV + 1), 20480);
        mbar_expect(mb + 8 * MB_HA, 5 * HPITCH);
        tma_load4(sb + OFF_TK, &p.tk, ch0, 8 * rank - 1, mb + 8 * MB_KV);
        tma_load4(sb + OFF_TV, &p.tv, ch0, 8 * rank, mb + 8 * (MB_KV + 1));
        asm volatile("cp.async.bulk.tensor.4d.shared::cluster.global.mbarrier::complete_tx::bytes [%0], [%1, {%3, %4, %5, %6}], [%2];"
                     :: "r"(sb + OFF_RAWA - 48), "l"(&p.th), "r"(mb + 8 * MB_HA), "r"(0), "r"(-1), "r"(5 * cl), "r"(rank) : "memory");
        TL(20);
      }
    }
  }
  const int uk0 = wg, uk1 = (wg == 2) ? 9 : 4 - wg;
  float pla[2], pai[2], pcr[2], pci[2], pdt[2], pds[2];
#pragma unroll
  for (int r = 0; r < 2; r++) {
    const int u = r ? uk1 : uk0;
    const int ch = (u < nu) ? ch0 + 8 * u + rank : 0;
    pla[r] = ldbf(p.logA + ch * NMODE + tid);
    pai[r] = ldbf(p.Aim + ch * NMODE + tid);
    pcr[r] = ldbf(p.Cre + ch * NMODE + tid);
    pci[r] = ldbf(p.Cim + ch * NMODE + tid);
    pdt[r] = ldbf(p.logdt + ch);
    pds[r] = ldbf(p.Dskip + ch);
  }
  uint2 swv = make_uint2(0, 0);
  uint32_t gwv = 0;
  if (wg == 2) {
    if (tid < 40 && ch0 + tid < DCH) { swv = __ldg((const uint2*)(p.shift_k + (size_t)(ch0 + tid) * 4)); gwv = __ldg((const unsigned short*)(p.gate_w + ch0 + tid)); }
  } else {
    if (lane == 0) {
      const int b = 2 * (4 * wg + w);
      mbar_init(mb + 8 * b, 1);
      mbar_init(mb + 8 * b + 8, b + 1 == MB_HRDY ? 4 : 1);
      asm volatile("fence.mbarrier_init.release.cluster;" ::: "memory");
      mbar_expect(mb + 8 * b, b >= MB_Y ? 8192 : 4096);
      if (b + 1 != MB_HRDY) mbar_expect(mb + 8 * b + 8, b + 1 >= MB_Y ? 8192 : 4096);
    }
    if (wg == 1 && tid < 85) sts128(sb + OFF_UX + (tid / 17) * UPITCH + (tid % 17) * 16, 0, 0, 0, 0);
  }
  __syncwarp();
  cluster_arrive();
  TL(0);

  const uint32_t tab = sb + OFF_PB + wg * KTAB;
  const uint32_t kc = sb + OFF_KC + wg * 1408;
#pragma unroll 1
  for (int r = 0; r < 2; r++) {
    const int u = r ? uk1 : uk0;
    const bool act = u < nu;
    if (act) {
      const float la = r ? pla[1] : pla[0], ai = r ? pai[1] : pai[0], cr = r ? pcr[1] : pcr[0], ci = r ? pci[1] : pci[0];
      const float dt = bf16r(expf(r ? pdt[1] : pdt[0]));
      const float lr2 = (-bf16r(expf(la)) * dt) * 1.4426950408889634f;
      const float lt = (ai * dt) * 0.15915494309189535f;
      const uint32_t row = tab + tid * 16;
      if (lr2 != 123.f) TL(16 + 4 * r + 6);
      {
        const cf w1 = cexp_p(lr2, lt, 8.f);
        cf v[8];
        v[0].x = 1.f; v[0].y = 0.f; v[1] = w1; v[2] = cmul(w1, w1); v[3] = cmul(v[2], w1);
        const cf w4 = cmul(v[2], v[2]);
        v[4] = w4; v[5] = cmul(v[1], w4); v[6] = cmul(v[2], w4); v[7] = cmul(v[3], w4);
        const cf w8 = cmul(w4, w4);
        store8(row, v);
#pragma unroll
        for (int c = 1; c < 4; c++) {
#pragma unroll
          for (int i = 0; i < 8; i++) v[i] = (c == 1 && i == 0) ? w8 : cmul(v[i], w8);
          store8(row + 2048 * c, v);
        }
      }
      {
        cf z1 = cexp_p(lr2, lt, 1.f), Z = cexp_p(lr2, lt, 256.f);
        z1.y = -z1.y; Z.y = -Z.y;
        const cf z2 = cmul(z1, z1);
        cf h[8], v[8];
        h[0].x = 2.f * cr * dt; h[0].y = -2.f * ci * dt;
        h[1] = cmul(h[0], z1);
#pragma unroll
        for (int i = 2; i < 8; i++) h[i] = cmul(h[i - 2], z2);
        store8(row + 4 * 2048, h);
        v[0] = cmul(h[0], Z); v[1] = cmul(h[2], Z); v[2] = cmul(h[4], Z); v[3] = cmul(h[6], Z);
        v[4] = cmul(v[0], Z); v[5] = cmul(v[2], Z); v[6] = cmul(v[4], Z); v[7] = cmul(v[5], Z);
        store8(row + 5 * 2048, v);
        const cf Z2 = cmul(Z, Z);
        h[0] = cmul(v[4], Z2); h[1] = cmul(v[6], Z2); h[2] = cmul(h[0], Z2); h[3] = cmul(h[1], Z2); h[4] = cmul(h[2], Z2);
        h[5].x = h[5].y = h[6].x = h[6].y = h[7].x = h[7].y = 0.f;
        store8(row + 6 * 2048, h);
      }
      TL(16 + 4 * r + 7);
      fence_async();
      bar_sync(NB_WG0 + wg, 128);
      float c[12];
      const uint64_t da = (uint64_t)((tab & 0x3FFFF) >> 4) | ((uint64_t)(KTAB / 32) << 16) | (128ull << 32);
      wg_fence();
#pragma unroll
      for (int ks = 0; ks < 16; ks++) {
        asm volatile("{.reg .pred p; setp.ne.u32 p, %14, 0; wgmma.mma_async.sync.aligned.m64n24k16.f32.bf16.bf16 {%0,%1,%2,%3,%4,%5,%6,%7,%8,%9,%10,%11}, %12, %13, p, 1, 1, 1, 1;}"
                     : "+f"(c[0]), "+f"(c[1]), "+f"(c[2]), "+f"(c[3]), "+f"(c[4]), "+f"(c[5]), "+f"(c[6]), "+f"(c[7]), "+f"(c[8]), "+f"(c[9]), "+f"(c[10]), "+f"(c[11])
                     : "l"(da + (uint64_t)(8 * ks)), "l"(da + (uint64_t)(8 * ks + 512)), "r"(ks));
      }
      wg_commit();
      wg_wait<0>();
      if (tid == 0) c[0] += r ? pds[1] : pds[0];
      if (w < 2) {
#pragma unroll
        for (int hh = 0; hh < 2; hh++) {
          const int a = 16 * w + g + 8 * hh;
          sts32(kc + 4 * (4 * a + t), pack(c[2 * hh], c[2 * hh + 1]));
          sts32(kc + 4 * (t < 2 ? 128 + 2 * a + t : 128 + 32 * t + a), pack(c[4 + 2 * hh], c[5 + 2 * hh]));
          if (t < 3) {
            const uint32_t p0 = pack(c[8 + 2 * hh], c[9 + 2 * hh]);
            sts16(kc + 2 * (512 + 64 * t + a), p0);
            sts16(kc + 2 * (544 + 64 * t + a), p0 >> 16);
          }
        }
      }
    }
    TL(16 + 4 * r + 8);
    if (r == 0) {
      bar_sync(NB_WG0 + wg, 128);
    } else {
      bar_sync(NB_R1, 384);
      if (tid < 32) sts128(sb + OFF_PB + wg * PBSZ + tid * 528, 0, 0, 0, 0);
      else if (wg == 1 && tid >= 32 && tid < 32 + 85) sts128(sb + OFF_UKV + ((tid - 32) / 17) * UPITCH + ((tid - 32) % 17) * 16, 0, 0, 0, 0);
    }
    if (act) {
      const uint32_t hs = sb + OFF_HB + (4 - u) * 2 * HPITCH;
#pragma unroll
      for (int cc = 0; cc < 2; cc++) {
        const int c = tid + 128 * cc;
        uint32_t v[9];
#pragma unroll
        for (int i = 0; i < 9; i++) {
          const int l = 8 * c + i;
          const uint32_t id = (cc == 0 && c < 16) ? (uint32_t)l : (pack((float)l, 0.f) - 0x4280u);
          v[i] = lds16(kc + 2 * id);
        }
        sts128(hs + HPITCH + 16 + 16 * c, prmt(v[0], v[1], 0x5410), prmt(v[2], v[3], 0x5410), prmt(v[4], v[5], 0x5410), prmt(v[6], v[7], 0x5410));
        sts128(hs + 16 + 16 * c, prmt(v[1], v[2], 0x5410), prmt(v[3], v[4], 0x5410), prmt(v[5], v[6], 0x5410), prmt(v[7], v[8], 0x5410));
        if (c == 0) { sts128(hs + HPITCH, 0, 0, 0, 0); sts128(hs, 0, 0, 0, v[0] << 16); }
      }
    }
    TL(1 + r);
    if (wg == 2) break;
  }

  if (wg < 2) {
    fence_async();
    bar_sync(NB_R2, 256);
    cluster_wait();
    cluster_arrive();
    asm volatile("setmaxnreg.inc.sync.aligned.u32 216;");
    const uint32_t haoff = 4 * (8 * w + ((g + 1) >> 1) + t);
    const uint32_t pw = sb + OFF_PB + wg * PBSZ + 4 * ((w * 8 + g) * 132 + t + w);
    const uint32_t pr = sb + OFF_PB + wg * PBSZ + w * 528 + lane * 16;
    const uint32_t rbase = mapa(sb, g);
    if (wg == 1) bar_arrive(NB_TOK0, 256);
    bool hb_done = false;
#pragma unroll 1
    for (int i = wg; i < 2 * nu; i += 2) {
      const bool isA = i >= nu;
      const int u = isA ? i - nu : i;
      uint32_t ha;
      if (isA) {
        mbar_wait(mb + 8 * MB_HRDY);
        ha = (g & 1) ? sb + OFF_RAWA + u * HPITCH : sb + OFF_HB + (9 - u) * HPITCH;
      } else {
        ha = sb + OFF_HB + (8 - 2 * u + (g & 1)) * HPITCH;
      }
      ha += haoff;
      uint32_t a[12][4];
#pragma unroll
      for (int m = 0; m < 12; m++) {
        a[m][0] = lds32(ha + 256 * m + 16); a[m][1] = lds32(ha + 256 * m + 144);
        a[m][2] = lds32(ha + 256 * m);      a[m][3] = lds32(ha + 256 * m + 128);
      }
      mbar_wait(mb + 8 * ((isA ? MB_UKV : MB_UX) + u));
      fence_async();
      const uint32_t ub = sb + (isA ? OFF_UKV : OFF_UX) + u * UPITCH;
      const uint64_t db = (uint64_t)((ub & 0x3FFFF) >> 4) | (1ull << 16) | (8ull << 32);
      float acc[128];
      bar_sync(NB_TOK0 + wg, 256);
      TL(3 + (i >> 1));
      wg_fence();
#pragma unroll
      for (int m = 0; m < 12; m++) {
#pragma unroll
        for (int j = 0; j < 8; j++) {
          if (m < 2 * (j + 1)) {
            if (m == 0) wgmma32_set(acc + 16 * j, a[m], db + (uint64_t)(16 + 32 * j - 16 * m));
            else wgmma32_acc(acc + 16 * j, a[m], db + (uint64_t)(16 + 32 * j - 16 * m));
          }
        }
        if (m == 3) wg_commit();
      }
      wg_commit();
      wg_wait<1>();
#pragma unroll
      for (int m = 12; m < 16; m++) {
        a[m - 12][0] = lds32(ha + 256 * m + 16); a[m - 12][1] = lds32(ha + 256 * m + 144);
        a[m - 12][2] = lds32(ha + 256 * m);      a[m - 12][3] = lds32(ha + 256 * m + 128);
      }
      wg_fence();
#pragma unroll
      for (int m = 12; m < 16; m++) {
#pragma unroll
        for (int j = 6; j < 8; j++)
          if (m < 2 * (j + 1)) wgmma32_acc(acc + 16 * j, a[m - 12], db + (uint64_t)(16 + 32 * j - 16 * m));
      }
      wg_commit();
      if (!hb_done && (i + 2 >= nu || i + 2 > 2)) { bar_arrive(NB_HBFREE, 384); hb_done = true; }
      wg_wait<1>();
      if (i + 1 < 2 * nu) bar_arrive(NB_TOK1 - wg, 256);
      wg_wait<0>();
#pragma unroll
      for (int j = 0; j < 32; j++) {
        float v0 = acc[4 * j], v1 = acc[4 * j + 1];
        if (j > 0) { v0 += acc[4 * j - 2]; v1 += acc[4 * j - 1]; }
        sts32(pw + 16 * j, pack(v0, v1));
      }
      if (i == wg) cluster_wait();
      if (isA) { for (int k = 0; k < nu; k++) mbar_wait(mb + 8 * (MB_UKV + k)); }
      bar_sync(NB_WG0 + wg, 128);
      const uint32_t yd = rbase + (isA ? OFF_YA : OFF_YB) + (8 * u + rank) * YPITCH + (4 * w + t) * 16;
      const uint32_t ym = rbase + OFF_MB + 8 * (MB_Y + u);
#pragma unroll
      for (int hh = 0; hh < 2; hh++) {
        const uint4 p0 = lds128(pr + hh * 2112), p1 = lds128(pr + hh * 2112 + 4224), p2 = lds128(pr + hh * 2112 + 8448), p3 = lds128(pr + hh * 2112 + 12672);
        st_async4(yd + hh * 256, sum4(p0.x, p1.x, p2.x, p3.x), sum4(p0.y, p1.y, p2.y, p3.y), sum4(p0.z, p1.z, p2.z, p3.z), sum4(p0.w, p1.w, p2.w, p3.w), ym);
      }
      bar_sync(NB_WG0 + wg, 128);
      TL(8 + (i >> 1));
    }
    TL_DUMP();
  } else {
    bar_arrive(NB_R1, 384);
    if (tid < 40) { sts64(sb + OFF_SW + 8 * tid, swv.x, swv.y); sts16(sb + OFF_GW + 2 * tid, gwv); }
    asm volatile("setmaxnreg.dec.sync.aligned.u32 72;");
    cluster_wait();
    cluster_arrive();
    const uint32_t rbase = mapa(sb, g);
    const int mi = lane >> 3, tp = (lane & 7) >> 1, jj = lane & 1;
    const uint32_t toff = (4 * (7 - 2 * mi - jj) + tp) * 80;
#pragma unroll 1
    for (int hf = 0; hf < 2; hf++) {
      mbar_wait(mb + 8 * (MB_XQ + hf));
      const int ah = 4 * hf + w;
#pragma unroll 1
      for (int u = 0; u < nu; u++) {
        uint32_t r[4];
        ldsm4t(r, sb + OFF_TQ + ah * 2560 + toff + 16 * u);
        st_async4(rbase + OFF_UX + u * UPITCH + UPAD + 16 * (32 * rank + 4 * ah + t), r[0], r[1], r[2], r[3], rbase + OFF_MB + 8 * (MB_UX + u));
      }
    }
    TL(2);
    bar_sync(NB_WG0 + 2, 128);
    {
      float s0 = 0.f, s1 = 0.f;
#pragma unroll
      for (int j = 0; j < 5; j++) {
        const uint4 gw = lds128(sb + OFF_GW + 16 * j);
        const uint4 x0 = lds128(sb + OFF_TQ + tid * 80 + 16 * j), x1 = lds128(sb + OFF_TQ + (tid + 128) * 80 + 16 * j);
        uint32_t m0 = hmul2(x0.x, gw.x), m1 = hmul2(x0.y, gw.y), m2 = hmul2(x0.z, gw.z), m3 = hmul2(x0.w, gw.w);
        s0 += ((blo(m0) + bhi(m0)) + (blo(m1) + bhi(m1))) + ((blo(m2) + bhi(m2)) + (blo(m3) + bhi(m3)));
        m0 = hmul2(x1.x, gw.x); m1 = hmul2(x1.y, gw.y); m2 = hmul2(x1.z, gw.z); m3 = hmul2(x1.w, gw.w);
        s1 += ((blo(m0) + bhi(m0)) + (blo(m1) + bhi(m1))) + ((blo(m2) + bhi(m2)) + (blo(m3) + bhi(m3)));
      }
      __stcg(&g_part[cl * SEQ + rank * 256 + tid], s0);
      __stcg(&g_part[cl * SEQ + rank * 256 + 128 + tid], s1);
    }
    bar_sync(NB_WG0 + 2, 128);
    unsigned g_target = 0;
    if (tid == 96) {
      __threadfence();
      const unsigned old = atomicAdd(&g_cnt[rank * 32], cl == 0 ? 16 - (NCL - 1) : 1);
      g_target = (old & ~15u) + 16;
    }
    TL(3);
    cluster_wait();
    const uint32_t hoff = (4 * (7 - 2 * (mi & 1) - jj) + ((tp + 3) & 3)) * 80 + (tp ? 2560 : 0);
#pragma unroll 1
    for (int hf = 0; hf < 2; hf++) {
      if (hf == 0) { mbar_wait(mb + 8 * MB_KV); TL(4); mbar_wait(mb + 8 * (MB_KV + 1)); TL(5); }
      const int ah = 4 * hf + w;
#pragma unroll 1
      for (int u = 0; u < nu; u++) {
        uint32_t K[4], K4, K5, V[4], o[4];
        ldsm4t(K, sb + OFF_TK + (ah + 1) * 2560 + toff + 16 * u);
        ldsm2t(K4, K5, sb + OFF_TK + ah * 2560 + hoff + 16 * u);
        ldsm4t(V, sb + OFF_TV + ah * 2560 + toff + 16 * u);
        const uint2 sw = lds64(sb + OFF_SW + 8 * (8 * u + g));
        const uint32_t w0 = prmt(sw.x, 0, 0x1010), w1 = prmt(sw.x, 0, 0x3232), w2 = prmt(sw.y, 0, 0x1010), w3 = prmt(sw.y, 0, 0x3232);
        const uint32_t E[6] = {K[0], K[1], K[2], K[3], K4, K5};
        uint32_t O[5];
#pragma unroll
        for (int i = 0; i < 5; i++) O[i] = prmt(E[i], E[i + 1], 0x5432);
#pragma unroll
        for (int i = 0; i < 4; i++) {
          uint32_t s = hmul2(O[i + 1], w3);
          s = hadd2(s, hmul2(E[i + 1], w2));
          s = hadd2(s, hmul2(O[i], w1));
          s = hadd2(s, hmul2(E[i], w0));
          o[i] = hmul2(s, V[i]);
        }
        st_async4(rbase + OFF_UKV + u * UPITCH + UPAD + 16 * (32 * rank + 4 * ah + t), o[0], o[1], o[2], o[3], rbase + OFF_MB + 8 * (MB_UKV + u));
      }
    }
    TL(6);
    float dval = 0.f;
    if (tid < nu) dval = ldbf(p.ssm_D + ch0 + 8 * tid + rank);
    mbar_wait(mb + 8 * MB_HA);
    bar_sync(NB_HBFREE, 384);
#pragma unroll 1
    for (int k = 0; k < 2 * nu; k++) {
      const int u = k >> 1, c = tid + 128 * (k & 1);
      const uint32_t ra = sb + OFF_RAWA + u * HPITCH + 16 + 16 * c;
      const uint4 x = lds128(ra);
      const uint32_t n = lds32(ra + 16);
      sts128(sb + OFF_HB + (9 - u) * HPITCH + 16 + 16 * c, prmt(x.x, x.y, 0x5432), prmt(x.y, x.z, 0x5432), prmt(x.z, x.w, 0x5432), prmt(x.w, n, 0x5432));
    }
    if (tid < nu) {
      const uint32_t ra = sb + OFF_RAWA + tid * HPITCH + 16;
      const uint32_t h0 = pack(blo(lds16(ra)) + dval, 0.f);
      sts16(ra, h0);
      sts128(sb + OFF_HB + (9 - tid) * HPITCH, 0, 0, 0, h0 << 16);
    }
    __syncwarp();
    if (lane == 0) mbar_arrive(mb + 8 * MB_HRDY);
    TL(7);
    uint32_t okflag = 1;
    if (tid == 96) {
      unsigned v;
      int it = 0;
      do {
        asm volatile("ld.acquire.gpu.global.u32 %0, [%1];" : "=r"(v) : "l"(&g_cnt[rank * 32]) : "memory");
      } while ((int)(v - g_target) < 0 && ++it < 20000);
      okflag = (int)(v - g_target) >= 0;
    }
    asm volatile("{.reg .pred p, q; setp.ne.u32 p, %1, 0; bar.red.and.pred q, %2, 128, p; selp.u32 %0, 1, 0, q;}" : "=r"(okflag) : "r"(okflag), "r"(NB_WG0 + 2) : "memory");
#pragma unroll 1
    for (int hf = 0; hf < 2; hf++) {
      const int slot = tid + 128 * hf;
      float s = 0.f;
      if (okflag) {
        float v[NCL];
#pragma unroll
        for (int c = 0; c < NCL; c++) v[c] = __ldcg(&g_part[c * SEQ + rank * 256 + slot]);
#pragma unroll
        for (int c = 0; c < NCL; c++) s += v[c];
      } else {
        const int row = rank * 256 + (slot & ~31) + 8 * (slot & 3) + ((slot >> 2) & 7);
        const uint32_t* xr = (const uint32_t*)(p.q + (size_t)row * DCH);
        const uint32_t* gr = (const uint32_t*)p.gate_w;
#pragma unroll 1
        for (int c = 0; c < DCH / 2; c++) { const uint32_t m = hmul2(__ldg(xr + c), __ldg(gr + c)); s += blo(m) + bhi(m); }
      }
      const float gv = bf16r(sigmoidf_(bf16r(s)));
      sts64(sb + OFF_KC + 8 * slot, pack(gv, gv), pack(1.f - gv, 1.f - gv));
    }
    bar_sync(NB_WG0 + 2, 128);
    TL(8);
    const int r8 = lane & 7;
#pragma unroll 1
    for (int u = 0; u < nu; u++) {
      mbar_wait(mb + 8 * (MB_Y + u));
#pragma unroll
      for (int hh = 0; hh < 2; hh++) {
        const int gs = w + 4 * hh;
        uint32_t ya[4], yb[4], qv[4], o[4];
        const uint32_t yo = (8 * u + r8) * YPITCH + (4 * gs + mi) * 16;
        ldsm4t(ya, sb + OFF_YA + yo);
        ldsm4t(yb, sb + OFF_YB + yo);
        const uint32_t qa = sb + OFF_TQ + (64 * mi + 32 * (r8 >> 2) + 4 * gs + (r8 & 3)) * 80 + 16 * u;
        ldsm4(qv, qa);
#pragma unroll
        for (int i = 0; i < 4; i++) {
          const uint2 gg = lds64(sb + OFF_KC + 8 * (64 * i + 32 * (g >> 2) + 4 * gs + (g & 3)));
          o[i] = hadd2(hmul2(gg.x, hmul2(qv[i], ya[i])), hmul2(gg.y, yb[i]));
        }
        stsm4(qa, o);
      }
      TL(9 + u);
    }
    fence_async();
    bar_sync(NB_WG0 + 2, 128);
    if (tid == 0) {
      tma_store4(&p.to, ch0, 8 * rank, sb + OFF_TQ);
      tma_store4(&p.to, ch0, 8 * rank + 4, sb + OFF_TQ + 10240);
      asm volatile("cp.async.bulk.commit_group;" ::: "memory");
      asm volatile("cp.async.bulk.wait_group.read 0;" ::: "memory");
    }
    TL(14);
    TL_DUMP();
  }
}

typedef CUresult (*EncodeFn)(CUtensorMap*, CUtensorMapDataType, cuuint32_t, void*, const cuuint64_t*, const cuuint64_t*,
                             const cuuint32_t*, const cuuint32_t*, CUtensorMapInterleave, CUtensorMapSwizzle,
                             CUtensorMapL2promotion, CUtensorMapFloatOOBfill);

void make_map(EncodeFn fn, CUtensorMap* tm, const void* ptr, int nhi) {
  cuuint64_t dims[4] = {DCH, 4, 8, SEQ / 32};
  cuuint64_t strides[3] = {8 * DCH * 2, DCH * 2, 32 * DCH * 2};
  cuuint32_t box[4] = {CPC, 4, 8, (cuuint32_t)nhi};
  cuuint32_t es[4] = {1, 1, 1, 1};
  fn(tm, CU_TENSOR_MAP_DATA_TYPE_BFLOAT16, 4, const_cast<void*>(ptr), dims, strides, box, es, CU_TENSOR_MAP_INTERLEAVE_NONE,
     CU_TENSOR_MAP_SWIZZLE_NONE, CU_TENSOR_MAP_L2_PROMOTION_L2_128B, CU_TENSOR_MAP_FLOAT_OOB_FILL_NONE);
}

}

extern "C" void kernel_launch(void* const* d_in, const int* in_sizes, int n_in, void* d_out, int out_size) {
  (void)in_sizes; (void)n_in; (void)out_size;
  static EncodeFn fn = nullptr;
  if (!fn) {
    cudaDriverEntryPointQueryResult qr;
    cudaGetDriverEntryPoint("cuTensorMapEncodeTiled", (void**)&fn, cudaEnableDefault, &qr);
    cudaFuncSetAttribute(fused_kernel, cudaFuncAttributeMaxDynamicSharedMemorySize, SMEM_BYTES);
  }
  Params p;
  make_map(fn, &p.tq, d_in[0], 4);
  make_map(fn, &p.tk, d_in[1], 9);
  make_map(fn, &p.tv, d_in[2], 8);
  {
    cuuint64_t dims[4] = {32, SEQ / 32, DCH / 8, 8};
    cuuint64_t strides[3] = {64, 8 * SEQ * 2, SEQ * 2};
    cuuint32_t box[4] = {32, 65, 5, 1};
    cuuint32_t es[4] = {1, 1, 1, 1};
    fn(&p.th, CU_TENSOR_MAP_DATA_TYPE_BFLOAT16, 4, d_in[4], dims, strides, box, es, CU_TENSOR_MAP_INTERLEAVE_NONE,
       CU_TENSOR_MAP_SWIZZLE_NONE, CU_TENSOR_MAP_L2_PROMOTION_L2_128B, CU_TENSOR_MAP_FLOAT_OOB_FILL_NONE);
  }
  make_map(fn, &p.to, d_out, 4);
  p.q = (const __nv_bfloat16*)d_in[0];
  p.shift_k = (const __nv_bfloat16*)d_in[3];
  p.ssm_k = (const __nv_bfloat16*)d_in[4];
  p.ssm_D = (const __nv_bfloat16*)d_in[5];
  p.logA = (const __nv_bfloat16*)d_in[7];
  p.Aim = (const __nv_bfloat16*)d_in[8];
  p.Cre = (const __nv_bfloat16*)d_in[9];
  p.Cim = (const __nv_bfloat16*)d_in[10];
  p.logdt = (const __nv_bfloat16*)d_in[11];
  p.Dskip = (const __nv_bfloat16*)d_in[12];
  p.gate_w = (const __nv_bfloat16*)d_in[13];
  fused_kernel<<<NCL * CS, NTHREADS, SMEM_BYTES, cudaStreamPerThread>>>(p);
}
```

```cpp
#include <cuda_runtime.h>
#include <cuda_bf16.h>
#include <cuda.h>
#include <stdint.h>

#define TIMELINE 0

namespace {

constexpr int SEQ = 2048, DCH = 576, NMODE = 128;
constexpr int CS = 8, CPC = 40, NCL = 15, NTHREADS = 384;

constexpr int UPITCH = 4368, UPAD = 272;
constexpr int HPITCH = 4160;
constexpr int PBSZ = 16896;
constexpr int YPITCH = 528;
constexpr int KTAB = 28672;
constexpr int OFF_TQ = 0;
constexpr int OFF_TK = 20480;
constexpr int OFF_YA = OFF_TK;
constexpr int OFF_TV = 43520;
constexpr int OFF_UX = 64000;
constexpr int OFF_RAWA = OFF_UX + 5 * UPITCH + 48 + 48;
constexpr int OFF_HB = OFF_RAWA + 5 * HPITCH - 32;
constexpr int OFF_PB = OFF_HB + 6 * HPITCH;
constexpr int OFF_HB3 = OFF_PB + 2 * PBSZ;
constexpr int OFF_YB = OFF_HB3 + 2 * HPITCH;
constexpr int OFF_HB4 = OFF_YB + 40 * YPITCH;
constexpr int OFF_UKV = OFF_HB4 + 2 * HPITCH;
constexpr int OFF_KC = OFF_UKV + 5 * UPITCH;
constexpr int OFF_SW = OFF_KC + 3 * 1408;
constexpr int OFF_GW = OFF_SW + 320;
constexpr int OFF_MB = OFF_GW + 80;
constexpr int OFF_TL = OFF_MB + 32 * 8;
constexpr int SMEM_BYTES = OFF_TL + (TIMELINE ? 1536 : 0);
static_assert(((OFF_RAWA - OFF_HB) & 63) == 32, "bank offset between raw/shift copies");
static_assert(KTAB + 2048 <= 2 * PBSZ && KTAB <= OFF_HB4 - OFF_HB3 && KTAB <= OFF_KC - OFF_HB4, "ktab alias zones");
static_assert(SMEM_BYTES <= 232448, "smem");
static_assert(((OFF_RAWA - 48) & 127) == 0, "tma dst");
static_assert((OFF_RAWA & 15) == 0 && (OFF_PB & 15) == 0 && (OFF_HB & 15) == 0 && (OFF_MB & 7) == 0 && (OFF_KC & 15) == 0, "align");

enum { MB_UX = 0, MB_UKV = 5, MB_Y = 10, MB_HRDY = 15, MB_XQ = 16, MB_KV = 18, MB_HA = 19, MB_COUNT = 20 };
enum { NB_WG0 = 1, NB_HB2 = 4, NB_HB4 = 5, NB_HBFREE = 6, NB_PB1 = 7 };

struct Params {
  CUtensorMap tq, tk, tv, to, th;
  const __nv_bfloat16 *q, *shift_k, *ssm_k, *ssm_D, *logA, *Aim, *Cre, *Cim, *logdt, *Dskip, *gate_w;
};

__device__ float g_part[NCL * SEQ];
__device__ unsigned g_cnt[CS * 32];
#define TL(i) do {} while (0)
#define TL_INIT() do {} while (0)
#define TL_DUMP() do {} while (0)

__device__ __forceinline__ uint32_t lds32(uint32_t a) { uint32_t v; asm volatile("ld.shared.u32 %0, [%1];" : "=r"(v) : "r"(a) : "memory"); return v; }
__device__ __forceinline__ uint32_t lds16(uint32_t a) { uint32_t v; asm volatile("ld.shared.u16 %0, [%1];" : "=r"(v) : "r"(a) : "memory"); return v; }
__device__ __forceinline__ uint2 lds64(uint32_t a) { uint2 v; asm volatile("ld.shared.v2.u32 {%0,%1}, [%2];" : "=r"(v.x), "=r"(v.y) : "r"(a) : "memory"); return v; }
__device__ __forceinline__ uint4 lds128(uint32_t a) { uint4 v; asm volatile("ld.shared.v4.u32 {%0,%1,%2,%3}, [%4];" : "=r"(v.x), "=r"(v.y), "=r"(v.z), "=r"(v.w) : "r"(a) : "memory"); return v; }
__device__ __forceinline__ void sts16(uint32_t a, uint32_t v) { asm volatile("st.shared.u16 [%0], %1;" :: "r"(a), "r"(v) : "memory"); }
__device__ __forceinline__ void sts32(uint32_t a, uint32_t v) { asm volatile("st.shared.u32 [%0], %1;" :: "r"(a), "r"(v) : "memory"); }
__device__ __forceinline__ void sts64(uint32_t a, uint32_t x, uint32_t y) { asm volatile("st.shared.v2.u32 [%0], {%1,%2};" :: "r"(a), "r"(x), "r"(y) : "memory"); }
__device__ __forceinline__ void sts128(uint32_t a, uint32_t x, uint32_t y, uint32_t z, uint32_t w) { asm volatile("st.shared.v4.u32 [%0], {%1,%2,%3,%4};" :: "r"(a), "r"(x), "r"(y), "r"(z), "r"(w) : "memory"); }
__device__ __forceinline__ void ldsm4t(uint32_t (&r)[4], uint32_t a) { asm volatile("ldmatrix.sync.aligned.m8n8.x4.trans.shared.b16 {%0,%1,%2,%3}, [%4];" : "=r"(r[0]), "=r"(r[1]), "=r"(r[2]), "=r"(r[3]) : "r"(a) : "memory"); }
__device__ __forceinline__ void ldsm2t(uint32_t& r0, uint32_t& r1, uint32_t a) { asm volatile("ldmatrix.sync.aligned.m8n8.x2.trans.shared.b16 {%0,%1}, [%2];" : "=r"(r0), "=r"(r1) : "r"(a) : "memory"); }
__device__ __forceinline__ void ldsm4(uint32_t (&r)[4], uint32_t a) { asm volatile("ldmatrix.sync.aligned.m8n8.x4.shared.b16 {%0,%1,%2,%3}, [%4];" : "=r"(r[0]), "=r"(r[1]), "=r"(r[2]), "=r"(r[3]) : "r"(a) : "memory"); }
__device__ __forceinline__ void stsm4(uint32_t a, const uint32_t (&r)[4]) { asm volatile("stmatrix.sync.aligned.m8n8.x4.shared.b16 [%0], {%1,%2,%3,%4};" :: "r"(a), "r"(r[0]), "r"(r[1]), "r"(r[2]), "r"(r[3]) : "memory"); }
__device__ __forceinline__ uint32_t pack(float lo, float hi) { uint32_t r; asm("cvt.rn.bf16x2.f32 %0, %1, %2;" : "=r"(r) : "f"(hi), "f"(lo)); return r; }
__device__ __forceinline__ float blo(uint32_t v) { return __uint_as_float(v << 16); }
__device__ __forceinline__ float bhi(uint32_t v) { return __uint_as_float(v & 0xffff0000u); }
__device__ __forceinline__ float bf16r(float x) { return blo(pack(x, 0.f)); }
__device__ __forceinline__ uint32_t hmul2(uint32_t a, uint32_t b) { uint32_t r; asm("mul.rn.bf16x2 %0, %1, %2;" : "=r"(r) : "r"(a), "r"(b)); return r; }
__device__ __forceinline__ uint32_t hadd2(uint32_t a, uint32_t b) { uint32_t r; asm("add.rn.bf16x2 %0, %1, %2;" : "=r"(r) : "r"(a), "r"(b)); return r; }
__device__ __forceinline__ uint32_t prmt(uint32_t a, uint32_t b, uint32_t s) { return __byte_perm(a, b, s); }
__device__ __forceinline__ float ldbf(const __nv_bfloat16* p) { return blo((uint32_t)__ldg((const unsigned short*)p)); }
__device__ __forceinline__ uint32_t sum4(uint32_t a, uint32_t b, uint32_t c, uint32_t d) {
  return pack((blo(a) + blo(b)) + (blo(c) + blo(d)), (bhi(a) + bhi(b)) + (bhi(c) + bhi(d)));
}
__device__ __forceinline__ void mma16816(float (&c)[4], const uint32_t (&a)[4], uint32_t b0, uint32_t b1) {
  asm volatile("mma.sync.aligned.m16n8k16.row.col.f32.bf16.bf16.f32 {%0,%1,%2,%3}, {%4,%5,%6,%7}, {%8,%9}, {%0,%1,%2,%3};"
               : "+f"(c[0]), "+f"(c[1]), "+f"(c[2]), "+f"(c[3]) : "r"(a[0]), "r"(a[1]), "r"(a[2]), "r"(a[3]), "r"(b0), "r"(b1));
}
__device__ __forceinline__ void bar_sync(int id, int n) { asm volatile("bar.sync %0, %1;" :: "r"(id), "r"(n) : "memory"); }
__device__ __forceinline__ void bar_arrive(int id, int n) { asm volatile("bar.arrive %0, %1;" :: "r"(id), "r"(n) : "memory"); }
__device__ __forceinline__ void cluster_arrive() { asm volatile("barrier.cluster.arrive.relaxed.aligned;" ::: "memory"); }
__device__ __forceinline__ void cluster_wait() { asm volatile("barrier.cluster.wait.aligned;" ::: "memory"); }
__device__ __forceinline__ void fence_async() { asm volatile("fence.proxy.async.shared::cta;" ::: "memory"); }
__device__ __forceinline__ void fence_mbinit() { asm volatile("fence.mbarrier_init.release.cluster;" ::: "memory"); }
__device__ __forceinline__ uint32_t mapa(uint32_t a, uint32_t rank) { uint32_t r; asm("mapa.shared::cluster.u32 %0, %1, %2;" : "=r"(r) : "r"(a), "r"(rank)); return r; }
__device__ __forceinline__ void st_async4(uint32_t a, uint32_t x, uint32_t y, uint32_t z, uint32_t w, uint32_t mbar) {
  asm volatile("st.async.weak.shared::cluster.mbarrier::complete_tx::bytes.v4.b32 [%0], {%1,%2,%3,%4}, [%5];"
               :: "r"(a), "r"(x), "r"(y), "r"(z), "r"(w), "r"(mbar) : "memory");
}
__device__ __forceinline__ void mbar_init(uint32_t m, uint32_t cnt) { asm volatile("mbarrier.init.shared::cta.b64 [%0], %1;" :: "r"(m), "r"(cnt) : "memory"); }
__device__ __forceinline__ void mbar_expect(uint32_t m, uint32_t bytes) { asm volatile("mbarrier.arrive.expect_tx.shared::cta.b64 _, [%0], %1;" :: "r"(m), "r"(bytes) : "memory"); }
__device__ __forceinline__ void mbar_arrive(uint32_t m) { asm volatile("mbarrier.arrive.shared::cta.b64 _, [%0];" :: "r"(m) : "memory"); }
__device__ __forceinline__ void mbar_wait(uint32_t m) {
  uint32_t done;
  int it = 0;
  do {
    asm volatile("{.reg .pred p; mbarrier.try_wait.parity.shared::cta.b64 p, [%1], 0; selp.u32 %0, 1, 0, p;}" : "=r"(done) : "r"(m) : "memory");
    if (++it > (1 << 22)) __trap();
  } while (!done);
}
__device__ __forceinline__ void tma_load4(uint32_t dst, const CUtensorMap* tm, int c0, int c3, uint32_t mbar) {
  asm volatile("cp.async.bulk.tensor.4d.shared::cluster.global.mbarrier::complete_tx::bytes [%0], [%1, {%3, %4, %4, %5}], [%2];"
               :: "r"(dst), "l"(tm), "r"(mbar), "r"(c0), "r"(0), "r"(c3) : "memory");
}
__device__ __forceinline__ void tma_store4(const CUtensorMap* tm, int c0, int c3, uint32_t src) {
  asm volatile("cp.async.bulk.tensor.4d.global.shared::cta.bulk_group [%0, {%2, %3, %3, %4}], [%1];"
               :: "l"(tm), "r"(src), "r"(c0), "r"(0), "r"(c3) : "memory");
}
__device__ __forceinline__ void bulk_load(uint32_t dst, const void* src, uint32_t bytes, uint32_t mbar) {
  asm volatile("cp.async.bulk.shared::cluster.global.mbarrier::complete_tx::bytes [%0], [%1], %2, [%3];"
               :: "r"(dst), "l"(src), "r"(bytes), "r"(mbar) : "memory");
}
__device__ __forceinline__ void wg_fence() { asm volatile("wgmma.fence.sync.aligned;" ::: "memory"); }
__device__ __forceinline__ void wg_commit() { asm volatile("wgmma.commit_group.sync.aligned;" ::: "memory"); }
template <int N> __device__ __forceinline__ void wg_wait() { asm volatile("wgmma.wait_group.sync.aligned %0;" :: "n"(N) : "memory"); }
#define WG_REGS "{%0,%1,%2,%3,%4,%5,%6,%7,%8,%9,%10,%11,%12,%13,%14,%15}, {%16,%17,%18,%19}, %20, "
__device__ __forceinline__ void wgmma32_acc(float* d, const uint32_t* a, uint64_t db) {
  asm volatile("wgmma.mma_async.sync.aligned.m64n32k16.f32.bf16.bf16 " WG_REGS "1, 1, 1, 0;"
               : "+f"(d[0]), "+f"(d[1]), "+f"(d[2]), "+f"(d[3]), "+f"(d[4]), "+f"(d[5]), "+f"(d[6]), "+f"(d[7]),
                 "+f"(d[8]), "+f"(d[9]), "+f"(d[10]), "+f"(d[11]), "+f"(d[12]), "+f"(d[13]), "+f"(d[14]), "+f"(d[15])
               : "r"(a[0]), "r"(a[1]), "r"(a[2]), "r"(a[3]), "l"(db));
}
__device__ __forceinline__ void wgmma32_set(float* d, const uint32_t* a, uint64_t db) {
  asm volatile("wgmma.mma_async.sync.aligned.m64n32k16.f32.bf16.bf16 " WG_REGS "0, 1, 1, 0;"
               : "=f"(d[0]), "=f"(d[1]), "=f"(d[2]), "=f"(d[3]), "=f"(d[4]), "=f"(d[5]), "=f"(d[6]), "=f"(d[7]),
                 "=f"(d[8]), "=f"(d[9]), "=f"(d[10]), "=f"(d[11]), "=f"(d[12]), "=f"(d[13]), "=f"(d[14]), "=f"(d[15])
               : "r"(a[0]), "r"(a[1]), "r"(a[2]), "r"(a[3]), "l"(db));
}

__device__ __forceinline__ void tie(float& x) { asm volatile("" : "+f"(x) :: "memory"); }
__device__ __forceinline__ constexpr int aoff(int k) { return 256 * (k >> 2) + ((k & 3) == 0 ? 16 : (k & 3) == 1 ? 144 : (k & 3) == 2 ? 0 : 128); }
template <int ES, int E0, int E1>
__device__ __forceinline__ void epi_tiles(float (&E)[32], float& cy0, float& cy1, uint32_t pw) {
#pragma unroll
  for (int e = E0; e < E1; e++) {
    tie(E[4 * e]); tie(E[4 * e + 1]); tie(E[4 * e + 2]); tie(E[4 * e + 3]);
    float v0 = E[4 * e], v1 = E[4 * e + 1];
    if (e > 0) { v0 += E[4 * e - 2]; v1 += E[4 * e - 1]; } else if (ES > 0) { v0 += cy0; v1 += cy1; }
    sts32(pw + 16 * (8 * ES + e), pack(v0, v1));
    if (e == 7) { cy0 = E[30]; cy1 = E[31]; }
  }
}
template <int S, int MQ, int L0, int L1, int ES, int E0, int E1>
__device__ __forceinline__ void block(float (&acc)[32], const uint32_t (&Q)[16], uint64_t db, uint32_t (&LQ)[16], uint32_t la,
                                      float (&E)[32], float& cy0, float& cy1, uint32_t pw) {
  wg_fence();
#pragma unroll
  for (int mm = 0; mm < 4; mm++) {
#pragma unroll
    for (int jj = 1; jj >= 0; jj--) {
      const int m = 4 * MQ + mm, j = 2 * S + jj;
      if (m < 2 * (j + 1)) {
        if (m == 0) wgmma32_set(acc + 16 * jj, Q + 4 * mm, db + (uint64_t)(16 + 32 * j - 16 * m));
        else wgmma32_acc(acc + 16 * jj, Q + 4 * mm, db + (uint64_t)(16 + 32 * j - 16 * m));
      }
    }
  }
  wg_commit();
  wg_wait<1>();
#pragma unroll
  for (int l = L0; l < L1; l++) LQ[l] = lds32(la + aoff(l));
  epi_tiles<ES, E0, E1>(E, cy0, cy1, pw);
}

struct cf { float x, y; };
__device__ __forceinline__ cf cmul(cf a, cf b) { cf r; r.x = fmaf(a.x, b.x, -a.y * b.y); r.y = fmaf(a.x, b.y, a.y * b.x); return r; }
__device__ __forceinline__ cf cexp_p(float lr2, float lt, float p) {
  float m = exp2f(lr2 * p);
  float t = lt * p;
  t = (t - rintf(t)) * 6.283185307179586f;
  cf r; r.x = m * __cosf(t); r.y = m * __sinf(t); return r;
}
__device__ __forceinline__ void store8(uint32_t a, const cf (&v)[8]) {
  sts128(a, pack(v[0].x, v[1].x), pack(v[2].x, v[3].x), pack(v[4].x, v[5].x), pack(v[6].x, v[7].x));
  sts128(a + KTAB / 2, pack(v[0].y, v[1].y), pack(v[2].y, v[3].y), pack(v[4].y, v[5].y), pack(v[6].y, v[7].y));
}
__device__ __forceinline__ float sigmoidf_(float s) { return 1.f / (1.f + __expf(-s)); }

__global__ void __cluster_dims__(CS, 1, 1) __launch_bounds__(NTHREADS, 1) fused_kernel(const __grid_constant__ Params p) {
  extern __shared__ __align__(1024) uint8_t smem[];
  TL_INIT();
  TL(31);
  const uint32_t sb = (uint32_t)__cvta_generic_to_shared(smem);
  const uint32_t mb = sb + OFF_MB;
  const int wg = __shfl_sync(0xffffffffu, threadIdx.x >> 7, 0);
  const int tid = threadIdx.x & 127, w = __shfl_sync(0xffffffffu, tid >> 5, 0), lane = tid & 31, g = lane >> 2, t = lane & 3;
  const int cl = blockIdx.x >> 3, rank = blockIdx.x & 7;
  const int ch0 = cl * CPC;
  const int nu = min(5, (DCH - ch0) >> 3);

  const int uk0 = wg, uk1 = wg ? wg + 2 : 9;
  float pla[2], pai[2], pcr[2], pci[2], pdt[2], pds[2];
#pragma unroll
  for (int r = 0; r < 2; r++) {
    const int u = r ? uk1 : uk0;
    const int ch = (u < nu) ? ch0 + 8 * u + rank : 0;
    pla[r] = ldbf(p.logA + ch * NMODE + tid);
    pai[r] = ldbf(p.Aim + ch * NMODE + tid);
    pcr[r] = ldbf(p.Cre + ch * NMODE + tid);
    pci[r] = ldbf(p.Cim + ch * NMODE + tid);
    pdt[r] = ldbf(p.logdt + ch + (lane >> 5));
    pds[r] = ldbf(p.Dskip + ch + (lane >> 5));
  }
  uint2 swv = make_uint2(0, 0);
  uint32_t gwv = 0;
  float dval = 0.f;
  if (wg == 2) {
    if (tid < 40 && ch0 + tid < DCH) { swv = __ldg((const uint2*)(p.shift_k + (size_t)(ch0 + tid) * 4)); gwv = __ldg((const unsigned short*)(p.gate_w + ch0 + tid)); }
    if (tid < nu) dval = ldbf(p.ssm_D + ch0 + 8 * tid + rank);
    if (lane == 0) {
      if (w == 0) {
        mbar_init(mb + 8 * MB_XQ, 1);
        mbar_init(mb + 8 * (MB_XQ + 1), 1);
        fence_mbinit();
        mbar_expect(mb + 8 * MB_XQ, 10240);
        tma_load4(sb + OFF_TQ, &p.tq, ch0, 8 * rank, mb + 8 * MB_XQ);
        mbar_expect(mb + 8 * (MB_XQ + 1), 10240);
        tma_load4(sb + OFF_TQ + 10240, &p.tq, ch0, 8 * rank + 4, mb + 8 * (MB_XQ + 1));
        TL(20);
      } else if (w == 1) {
        mbar_init(mb + 8 * MB_KV, 1);
        mbar_init(mb + 8 * MB_HA, 1);
        fence_mbinit();
        mbar_expect(mb + 8 * MB_KV, 23040 + 20480);
        mbar_expect(mb + 8 * MB_HA, 5 * HPITCH);
      }
    }
  } else {
    if (lane == 0) {
      const int b = 2 * (4 * wg + w);
      mbar_init(mb + 8 * b, 1);
      mbar_init(mb + 8 * b + 8, b + 1 == MB_HRDY ? 4 : 1);
      fence_mbinit();
      mbar_expect(mb + 8 * b, b >= MB_Y ? 8192 : 4096);
      if (b + 1 != MB_HRDY) mbar_expect(mb + 8 * b + 8, b + 1 >= MB_Y ? 8192 : 4096);
    }
    if (wg == 0 && tid < 85) sts128(sb + OFF_UX + (tid / 17) * UPITCH + (tid % 17) * 16, 0, 0, 0, 0);
  }
  __syncwarp();
  cluster_arrive();
  uint32_t kid[2][9];
#pragma unroll
  for (int cc = 0; cc < 2; cc++)
#pragma unroll
    for (int i = 0; i < 9; i++) {
      const int l = 8 * (tid + 128 * cc) + i;
      kid[cc][i] = 2 * ((cc == 0 && tid < 16) ? (uint32_t)l : (pack((float)l, 0.f) - 0x4280u));
    }
  TL(0);

  const uint32_t tab = sb + (wg == 0 ? OFF_PB : wg == 1 ? OFF_HB3 : OFF_HB4);
  const uint32_t kc = sb + OFF_KC + wg * 1408;
#pragma unroll 1
  for (int r = 0; r < 2; r++) {
    const int u = r ? uk1 : uk0;
    if (u < nu) {
      const float la = r ? pla[1] : pla[0], ai = r ? pai[1] : pai[0], cr = r ? pcr[1] : pcr[0], ci = r ? pci[1] : pci[0];
      const float dt = bf16r(expf(r ? pdt[1] : pdt[0]));
      const float lr2 = (-bf16r(expf(la)) * dt) * 1.4426950408889634f;
      const float lt = (ai * dt) * 0.15915494309189535f;
      const uint32_t row = tab + tid * 16;
      if (lr2 != 123.f) TL(16 + 4 * r + 6);
      {
        const cf w1 = cexp_p(lr2, lt, 8.f);
        cf v[8];
        v[0].x = 1.f; v[0].y = 0.f; v[1] = w1; v[2] = cmul(w1, w1); v[3] = cmul(v[2], w1);
        const cf w4 = cmul(v[2], v[2]);
        v[4] = w4; v[5] = cmul(v[1], w4); v[6] = cmul(v[2], w4); v[7] = cmul(v[3], w4);
        const cf w8 = cmul(w4, w4);
        store8(row, v);
#pragma unroll
        for (int c = 1; c < 4; c++) {
#pragma unroll
          for (int i = 0; i < 8; i++) v[i] = (c == 1 && i == 0) ? w8 : cmul(v[i], w8);
          store8(row + 2048 * c, v);
        }
      }
      {
        cf z1 = cexp_p(lr2, lt, 1.f), Z = cexp_p(lr2, lt, 256.f);
        z1.y = -z1.y; Z.y = -Z.y;
        const cf z2 = cmul(z1, z1);
        cf h[8], v[8];
        h[0].x = 2.f * cr * dt; h[0].y = -2.f * ci * dt;
        h[1] = cmul(h[0], z1);
#pragma unroll
        for (int i = 2; i < 8; i++) h[i] = cmul(h[i - 2], z2);
        store8(row + 4 * 2048, h);
        v[0] = cmul(h[0], Z); v[1] = cmul(h[2], Z); v[2] = cmul(h[4], Z); v[3] = cmul(h[6], Z);
        v[4] = cmul(v[0], Z); v[5] = cmul(v[2], Z); v[6] = cmul(v[4], Z); v[7] = cmul(v[5], Z);
        store8(row + 5 * 2048, v);
        const cf Z2 = cmul(Z, Z);
        h[0] = cmul(v[4], Z2); h[1] = cmul(v[6], Z2); h[2] = cmul(h[0], Z2); h[3] = cmul(h[1], Z2); h[4] = cmul(h[2], Z2);
        h[5].x = h[5].y = h[6].x = h[6].y = h[7].x = h[7].y = 0.f;
        store8(row + 6 * 2048, h);
      }
    }
    if (r == 0 && threadIdx.x == 288) {
      tma_load4(sb + OFF_TK, &p.tk, ch0, 8 * rank - 1, mb + 8 * MB_KV);
      tma_load4(sb + OFF_TV, &p.tv, ch0, 8 * rank, mb + 8 * MB_KV);
      asm volatile("cp.async.bulk.tensor.4d.shared::cluster.global.mbarrier::complete_tx::bytes [%0], [%1, {%3, %4, %5, %6}], [%2];"
                   :: "r"(sb + OFF_RAWA - 48), "l"(&p.th), "r"(mb + 8 * MB_HA), "r"(0), "r"(-1), "r"(5 * cl), "r"(rank) : "memory");
    }
    __syncwarp();
    if (u < nu) {
      TL(16 + 4 * r + 7);
      fence_async();
      bar_sync(NB_WG0 + wg, 128);
      float c[12];
      const uint64_t da = (uint64_t)((tab & 0x3FFFF) >> 4) | ((uint64_t)(KTAB / 32) << 16) | (128ull << 32);
      wg_fence();
#pragma unroll
      for (int ks = 0; ks < 16; ks++) {
        asm volatile("{.reg .pred p; setp.ne.u32 p, %14, 0; wgmma.mma_async.sync.aligned.m64n24k16.f32.bf16.bf16 {%0,%1,%2,%3,%4,%5,%6,%7,%8,%9,%10,%11}, %12, %13, p, 1, 1, 1, 1;}"
                     : "+f"(c[0]), "+f"(c[1]), "+f"(c[2]), "+f"(c[3]), "+f"(c[4]), "+f"(c[5]), "+f"(c[6]), "+f"(c[7]), "+f"(c[8]), "+f"(c[9]), "+f"(c[10]), "+f"(c[11])
                     : "l"(da + (uint64_t)(8 * ks)), "l"(da + (uint64_t)(8 * ks + 512)), "r"(ks));
      }
      wg_commit();
      wg_wait<0>();
      if (tid == 0) c[0] += r ? pds[1] : pds[0];
      if (w < 2) {
#pragma unroll
        for (int hh = 0; hh < 2; hh++) {
          const int a = 16 * w + g + 8 * hh;
          sts32(kc + 4 * (4 * a + t), pack(c[2 * hh], c[2 * hh + 1]));
          sts32(kc + 4 * (t < 2 ? 128 + 2 * a + t : 128 + 32 * t + a), pack(c[4 + 2 * hh], c[5 + 2 * hh]));
          if (t < 3) {
            const uint32_t p0 = pack(c[8 + 2 * hh], c[9 + 2 * hh]);
            sts16(kc + 2 * (512 + 64 * t + a), p0);
            sts16(kc + 2 * (544 + 64 * t + a), p0 >> 16);
          }
        }
      }
      TL(16 + 4 * r + 8);
      bar_sync(NB_WG0 + wg, 128);
      const uint32_t hs = r ? tab : sb + OFF_HB + u * 2 * HPITCH;
      uint32_t v[2][9];
#pragma unroll
      for (int cc = 0; cc < 2; cc++)
#pragma unroll
        for (int i = 0; i < 9; i++) v[cc][i] = lds16(kc + kid[cc][i]);
#pragma unroll
      for (int cc = 0; cc < 2; cc++) {
        const uint32_t o = hs + 16 + 16 * (tid + 128 * cc);
        sts128(o + HPITCH, prmt(v[cc][0], v[cc][1], 0x5410), prmt(v[cc][2], v[cc][3], 0x5410), prmt(v[cc][4], v[cc][5], 0x5410), prmt(v[cc][6], v[cc][7], 0x5410));
        sts128(o, prmt(v[cc][1], v[cc][2], 0x5410), prmt(v[cc][3], v[cc][4], 0x5410), prmt(v[cc][5], v[cc][6], 0x5410), prmt(v[cc][7], v[cc][8], 0x5410));
      }
      if (tid == 0) { sts128(hs + HPITCH, 0, 0, 0, 0); sts128(hs, 0, 0, 0, v[0][0] << 16); }
      if (wg == 2) bar_arrive(NB_HB2 + r, 256);
    }
    TL(1 + r);
    if (wg == 0) break;
  }

  const uint32_t rbase = mapa(sb, g);
  const int mi = lane >> 3, tp = (lane & 7) >> 1, jj = lane & 1;
  const uint32_t toff = (4 * (7 - 2 * mi - jj) + tp) * 80;
  cluster_wait();
  if (wg < 2) {
    if (wg == 0) {
      if (tid < 64) sts128(sb + OFF_PB + tid * 528, 0, 0, 0, 0);
      bar_arrive(NB_PB1, 256);
#pragma unroll
      for (int hf = 0; hf < 2; hf++) {
        mbar_wait(mb + 8 * (MB_XQ + hf));
        TL(13 + hf);
        const int ah = 4 * hf + w;
        uint32_t r[5][4];
#pragma unroll
        for (int u = 0; u < 5; u++) ldsm4t(r[u], sb + OFF_TQ + ah * 2560 + toff + 16 * u);
#pragma unroll
        for (int u = 0; u < 5; u++)
          if (u < nu) st_async4(rbase + OFF_UX + u * UPITCH + UPAD + 16 * (32 * rank + 4 * ah + t), r[u][0], r[u][1], r[u][2], r[u][3], rbase + OFF_MB + 8 * (MB_UX + u));
      }
      TL(15);
    } else {
      bar_sync(NB_PB1, 256);
    }
    cluster_arrive();
    bar_sync(NB_WG0 + wg, 128);
    const uint32_t haoff = 4 * (8 * w + ((g + 1) >> 1) + t);
    const uint32_t pw = sb + OFF_PB + wg * PBSZ + 4 * ((w * 8 + g) * 132 + t + w);
    const uint32_t pr = sb + OFF_PB + wg * PBSZ + w * 1056 + lane * 16;
    uint32_t ha = sb + OFF_HB + (2 * wg + (g & 1)) * HPITCH + haoff;
    uint32_t Q0[16], Q1[16], Q2[16], Q3[16];
    float X[32], Y[32], Z[32], cy0 = 0.f, cy1 = 0.f;
#pragma unroll
    for (int l = 0; l < 16; l++) Q0[l] = lds32(ha + aoff(l));
#pragma unroll
    for (int l = 0; l < 8; l++) Q1[l] = lds32(ha + 1024 + aoff(l));
    mbar_wait(mb + 8 * (MB_UX + wg));
    fence_async();
#pragma unroll 1
    for (int i = wg; i < 2 * nu; i += 2) {
      const bool isA = i >= nu;
      const int u = isA ? i - nu : i;
      const uint32_t ub = sb + (isA ? OFF_UKV : OFF_UX) + u * UPITCH;
      const uint64_t db = (uint64_t)((ub & 0x3FFFF) >> 4) | (1ull << 16) | (8ull << 32);
      TL(3 + (i >> 1));
      block<0, 0, 8, 16, 0, 0, 0>(X, Q0, db, Q1, ha + 1024, Z, cy0, cy1, pw);
      bar_sync(NB_WG0 + wg, 128);
      block<1, 0, 0, 5, 0, 0, 4>(Y, Q0, db, Q2, ha + 2048, X, cy0, cy1, pw);
      block<1, 1, 5, 10, 0, 4, 8>(Y, Q1, db, Q2, ha + 2048, X, cy0, cy1, pw);
      block<2, 0, 10, 16, 1, 0, 3>(X, Q0, db, Q2, ha + 2048, Y, cy0, cy1, pw);
      block<2, 1, 0, 6, 1, 3, 6>(X, Q1, db, Q3, ha + 3072, Y, cy0, cy1, pw);
      block<2, 2, 6, 11, 1, 6, 8>(X, Q2, db, Q3, ha + 3072, Y, cy0, cy1, pw);
      block<3, 0, 11, 16, 2, 0, 4>(Z, Q0, db, Q3, ha + 3072, X, cy0, cy1, pw);
      const int n = i + 2;
      if (!isA && (n > 2 || n >= nu) && i <= 2) bar_arrive(NB_HBFREE, 384);
      if (n < nu) {
        if (wg == 0) bar_sync(n == 2 ? NB_HB2 : NB_HB4, 256);
        ha = sb + (n == 2 ? OFF_HB + 4 * HPITCH : n == 3 ? OFF_HB3 : OFF_HB4) + (g & 1) * HPITCH + haoff;
      } else if (n < 2 * nu) {
        mbar_wait(mb + 8 * MB_HRDY);
        ha = sb + ((g & 1) ? OFF_RAWA : OFF_HB) + (n - nu) * HPITCH + haoff;
      }
      block<3, 1, 0, 8, 2, 4, 6>(Z, Q1, db, Q0, ha, X, cy0, cy1, pw);
      block<3, 2, 8, 16, 2, 6, 8>(Z, Q2, db, Q0, ha, X, cy0, cy1, pw);
      block<3, 3, 0, 8, 0, 0, 0>(Z, Q3, db, Q1, ha + 1024, X, cy0, cy1, pw);
      wg_wait<0>();
      epi_tiles<3, 0, 8>(Z, cy0, cy1, pw);
      if (!isA) {
        if (i == wg) {
          for (int k = n; k < nu; k += 2) mbar_wait(mb + 8 * (MB_UX + k));
          cluster_wait();
        }
        if (n >= nu) {
          for (int k = 0; k < nu; k++) mbar_wait(mb + 8 * (MB_UKV + k));
        }
        if (i == wg || n >= nu) fence_async();
      }
      bar_sync(NB_WG0 + wg, 128);
      uint4 pa[4], pb[4];
#pragma unroll
      for (int k = 0; k < 4; k++) { pa[k] = lds128(pr + k * 4224); pb[k] = lds128(pr + k * 4224 + 528); }
      const uint32_t yd = rbase + (isA ? OFF_YA : OFF_YB) + (8 * u + rank) * YPITCH + (8 * w + t) * 16;
      const uint32_t ym = rbase + OFF_MB + 8 * (MB_Y + u);
      st_async4(yd, sum4(pa[0].x, pa[1].x, pa[2].x, pa[3].x), sum4(pa[0].y, pa[1].y, pa[2].y, pa[3].y),
                sum4(pb[0].x, pb[1].x, pb[2].x, pb[3].x), sum4(pb[0].y, pb[1].y, pb[2].y, pb[3].y), ym);
      st_async4(yd + 64, sum4(pa[0].z, pa[1].z, pa[2].z, pa[3].z), sum4(pa[0].w, pa[1].w, pa[2].w, pa[3].w),
                sum4(pb[0].z, pb[1].z, pb[2].z, pb[3].z), sum4(pb[0].w, pb[1].w, pb[2].w, pb[3].w), ym);
      TL(8 + (i >> 1));
    }
    TL_DUMP();
  } else {
    if (tid < 40) { sts64(sb + OFF_SW + 8 * tid, swv.x, swv.y); sts16(sb + OFF_GW + 2 * tid, gwv); }
    else if (tid < 40 + 85) sts128(sb + OFF_UKV + ((tid - 40) / 17) * UPITCH + ((tid - 40) % 17) * 16, 0, 0, 0, 0);
    __syncwarp();
    cluster_arrive();
    bar_sync(NB_WG0 + 2, 128);
    mbar_wait(mb + 8 * MB_XQ);
    mbar_wait(mb + 8 * (MB_XQ + 1));
    {
      float s0 = 0.f, s1 = 0.f;
#pragma unroll
      for (int j = 0; j < 5; j++) {
        const uint4 gw = lds128(sb + OFF_GW + 16 * j);
        const uint4 x0 = lds128(sb + OFF_TQ + tid * 80 + 16 * j), x1 = lds128(sb + OFF_TQ + (tid + 128) * 80 + 16 * j);
        uint32_t m0 = hmul2(x0.x, gw.x), m1 = hmul2(x0.y, gw.y), m2 = hmul2(x0.z, gw.z), m3 = hmul2(x0.w, gw.w);
        s0 += ((blo(m0) + bhi(m0)) + (blo(m1) + bhi(m1))) + ((blo(m2) + bhi(m2)) + (blo(m3) + bhi(m3)));
        m0 = hmul2(x1.x, gw.x); m1 = hmul2(x1.y, gw.y); m2 = hmul2(x1.z, gw.z); m3 = hmul2(x1.w, gw.w);
        s1 += ((blo(m0) + bhi(m0)) + (blo(m1) + bhi(m1))) + ((blo(m2) + bhi(m2)) + (blo(m3) + bhi(m3)));
      }
      __stcg(&g_part[cl * SEQ + rank * 256 + tid], s0);
      __stcg(&g_part[cl * SEQ + rank * 256 + 128 + tid], s1);
    }
    TL(3);
    cluster_wait();
    mbar_wait(mb + 8 * MB_KV);
    TL(4);
    const uint32_t hoff = (4 * (7 - 2 * (mi & 1) - jj) + ((tp + 3) & 3)) * 80 + (tp ? 2560 : 0);
#pragma unroll 1
    for (int u = 0; u < nu; u++) {
      const uint2 sw = lds64(sb + OFF_SW + 8 * (8 * u + g));
      uint32_t E[2][6], V[2][4];
#pragma unroll
      for (int hf = 0; hf < 2; hf++) {
        const int ah = 4 * hf + w;
        uint32_t K[4];
        ldsm4t(K, sb + OFF_TK + (ah + 1) * 2560 + toff + 16 * u);
        ldsm2t(E[hf][4], E[hf][5], sb + OFF_TK + ah * 2560 + hoff + 16 * u);
        ldsm4t(V[hf], sb + OFF_TV + ah * 2560 + toff + 16 * u);
        E[hf][0] = K[0]; E[hf][1] = K[1]; E[hf][2] = K[2]; E[hf][3] = K[3];
      }
      const uint32_t w0 = prmt(sw.x, 0, 0x1010), w1 = prmt(sw.x, 0, 0x3232), w2 = prmt(sw.y, 0, 0x1010), w3 = prmt(sw.y, 0, 0x3232);
#pragma unroll
      for (int hf = 0; hf < 2; hf++) {
        uint32_t O[5], o[4];
#pragma unroll
        for (int i = 0; i < 5; i++) O[i] = prmt(E[hf][i], E[hf][i + 1], 0x5432);
#pragma unroll
        for (int i = 0; i < 4; i++) {
          uint32_t s = hmul2(O[i + 1], w3);
          s = hadd2(s, hmul2(E[hf][i + 1], w2));
          s = hadd2(s, hmul2(O[i], w1));
          s = hadd2(s, hmul2(E[hf][i], w0));
          o[i] = hmul2(s, V[hf][i]);
        }
        st_async4(rbase + OFF_UKV + u * UPITCH + UPAD + 16 * (32 * rank + 16 * hf + 4 * w + t), o[0], o[1], o[2], o[3], rbase + OFF_MB + 8 * (MB_UKV + u));
      }
    }
    TL(5);
    mbar_wait(mb + 8 * MB_HA);
    bar_sync(NB_HBFREE, 384);
    TL(6);
    unsigned g_target = 0;
#pragma unroll 1
    for (int u = 0; u < nu; u++) {
      const uint32_t ra = sb + OFF_RAWA + u * HPITCH + 16 + 16 * tid;
      const uint4 x = lds128(ra), y = lds128(ra + 2048);
      const uint32_t xn = lds32(ra + 16), yn = lds32(ra + 2048 + 16);
      const uint32_t o = sb + OFF_HB + u * HPITCH + 16 + 16 * tid;
      sts128(o, prmt(x.x, x.y, 0x5432), prmt(x.y, x.z, 0x5432), prmt(x.z, x.w, 0x5432), prmt(x.w, xn, 0x5432));
      sts128(o + 2048, prmt(y.x, y.y, 0x5432), prmt(y.y, y.z, 0x5432), prmt(y.z, y.w, 0x5432), prmt(y.w, yn, 0x5432));
    }
    if (tid < nu) {
      const uint32_t ra = sb + OFF_RAWA + tid * HPITCH + 16;
      const uint32_t h0 = pack(blo(lds16(ra)) + dval, 0.f);
      sts16(ra, h0);
      sts128(sb + OFF_HB + tid * HPITCH, 0, 0, 0, h0 << 16);
    }
    __syncwarp();
    if (lane == 0) mbar_arrive(mb + 8 * MB_HRDY);
    TL(7);
    uint32_t okflag = 1;
    if (tid == 0) {
      __threadfence();
      const unsigned old = atomicAdd(&g_cnt[rank * 32], cl == 0 ? 16 - (NCL - 1) : 1);
      g_target = (old & ~15u) + 16;
      unsigned v;
      int it = 0;
      do {
        asm volatile("ld.acquire.gpu.global.u32 %0, [%1];" : "=r"(v) : "l"(&g_cnt[rank * 32]) : "memory");
      } while ((int)(v - g_target) < 0 && ++it < 20000);
      okflag = (int)(v - g_target) >= 0;
    }
    asm volatile("{.reg .pred p, q; setp.ne.u32 p, %1, 0; bar.red.and.pred q, %2, 128, p; selp.u32 %0, 1, 0, q;}" : "=r"(okflag) : "r"(okflag), "r"(NB_WG0 + 2) : "memory");
    {
      float s[2] = {0.f, 0.f};
      if (okflag) {
        float2 v[NCL];
#pragma unroll
        for (int c = 0; c < NCL; c++) v[c] = __ldcg((const float2*)&g_part[c * SEQ + rank * 256 + 2 * tid]);
#pragma unroll
        for (int c = 0; c < NCL; c++) { s[0] += v[c].x; s[1] += v[c].y; }
      } else {
#pragma unroll 1
        for (int hf = 0; hf < 2; hf++) {
          const int slot = 2 * tid + hf;
          const int row = rank * 256 + (slot & ~31) + 8 * (slot & 3) + ((slot >> 2) & 7);
          const uint32_t* xr = (const uint32_t*)(p.q + (size_t)row * DCH);
          const uint32_t* gr = (const uint32_t*)p.gate_w;
          float a = 0.f;
#pragma unroll 1
          for (int c = 0; c < DCH / 2; c++) { const uint32_t m = hmul2(__ldg(xr + c), __ldg(gr + c)); a += blo(m) + bhi(m); }
          if (hf) s[1] = a; else s[0] = a;
        }
      }
      const float g0 = bf16r(sigmoidf_(bf16r(s[0]))), g1 = bf16r(sigmoidf_(bf16r(s[1])));
      sts128(sb + OFF_KC + 16 * tid, pack(g0, g0), pack(1.f - g0, 1.f - g0), pack(g1, g1), pack(1.f - g1, 1.f - g1));
    }
    __syncwarp();
    uint2 gg[2][4];
#pragma unroll
    for (int hh = 0; hh < 2; hh++)
#pragma unroll
      for (int i = 0; i < 4; i++) gg[hh][i] = lds64(sb + OFF_KC + 8 * (64 * w + 32 * hh + 8 * i + g));
    TL(8);
#pragma unroll 1
    for (int u = 0; u < nu; u++) {
      uint32_t qv[2][4];
      const uint32_t qa = sb + OFF_TQ + (64 * w + lane) * 80 + 16 * u;
      ldsm4(qv[0], qa);
      ldsm4(qv[1], qa + 2560);
      mbar_wait(mb + 8 * (MB_Y + u));
      uint32_t ya[2][4], yb[2][4];
      const uint32_t yo = (8 * u + (lane & 7)) * YPITCH + (8 * mi + w) * 16;
#pragma unroll
      for (int hh = 0; hh < 2; hh++) { ldsm4t(ya[hh], sb + OFF_YA + yo + 64 * hh); ldsm4t(yb[hh], sb + OFF_YB + yo + 64 * hh); }
#pragma unroll
      for (int hh = 0; hh < 2; hh++) {
        uint32_t o[4];
#pragma unroll
        for (int i = 0; i < 4; i++) o[i] = hadd2(hmul2(gg[hh][i].x, hmul2(qv[hh][i], ya[hh][i])), hmul2(gg[hh][i].y, yb[hh][i]));
        stsm4(qa + 2560 * hh, o);
      }
      TL(9 + u);
    }
    fence_async();
    __syncwarp();
    if (lane == 0) {
      tma_store4(&p.to, ch0, 8 * rank + 2 * w, sb + OFF_TQ + w * 5120);
      asm volatile("cp.async.bulk.commit_group;" ::: "memory");
      asm volatile("cp.async.bulk.wait_group.read 0;" ::: "memory");
    }
    TL(14);
    TL_DUMP();
  }
}

typedef CUresult (*EncodeFn)(CUtensorMap*, CUtensorMapDataType, cuuint32_t, void*, const cuuint64_t*, const cuuint64_t*,
                             const cuuint32_t*, const cuuint32_t*, CUtensorMapInterleave, CUtensorMapSwizzle,
                             CUtensorMapL2promotion, CUtensorMapFloatOOBfill);

void make_map(EncodeFn fn, CUtensorMap* tm, const void* ptr, int nhi) {
  cuuint64_t dims[4] = {DCH, 4, 8, SEQ / 32};
  cuuint64_t strides[3] = {8 * DCH * 2, DCH * 2, 32 * DCH * 2};
  cuuint32_t box[4] = {CPC, 4, 8, (cuuint32_t)nhi};
  cuuint32_t es[4] = {1, 1, 1, 1};
  fn(tm, CU_TENSOR_MAP_DATA_TYPE_BFLOAT16, 4, const_cast<void*>(ptr), dims, strides, box, es, CU_TENSOR_MAP_INTERLEAVE_NONE,
     CU_TENSOR_MAP_SWIZZLE_NONE, CU_TENSOR_MAP_L2_PROMOTION_L2_128B, CU_TENSOR_MAP_FLOAT_OOB_FILL_NONE);
}

}

extern "C" void kernel_launch(void* const* d_in, const int* in_sizes, int n_in, void* d_out, int out_size) {
  (void)in_sizes; (void)n_in; (void)out_size;
  static EncodeFn fn = nullptr;
  if (!fn) {
    cudaDriverEntryPointQueryResult qr;
    cudaGetDriverEntryPoint("cuTensorMapEncodeTiled", (void**)&fn, cudaEnableDefault, &qr);
    cudaFuncSetAttribute(fused_kernel, cudaFuncAttributeMaxDynamicSharedMemorySize, SMEM_BYTES);
  }
  Params p;
  make_map(fn, &p.tq, d_in[0], 4);
  make_map(fn, &p.tk, d_in[1], 9);
  make_map(fn, &p.tv, d_in[2], 8);
  {
    cuuint64_t dims[4] = {32, SEQ / 32, DCH / 8, 8};
    cuuint64_t strides[3] = {64, 8 * SEQ * 2, SEQ * 2};
    cuuint32_t box[4] = {32, 65, 5, 1};
    cuuint32_t es[4] = {1, 1, 1, 1};
    fn(&p.th, CU_TENSOR_MAP_DATA_TYPE_BFLOAT16, 4, d_in[4], dims, strides, box, es, CU_TENSOR_MAP_INTERLEAVE_NONE,
       CU_TENSOR_MAP_SWIZZLE_NONE, CU_TENSOR_MAP_L2_PROMOTION_L2_128B, CU_TENSOR_MAP_FLOAT_OOB_FILL_NONE);
  }
  make_map(fn, &p.to, d_out, 2);
  p.q = (const __nv_bfloat16*)d_in[0];
  p.shift_k = (const __nv_bfloat16*)d_in[3];
  p.ssm_k = (const __nv_bfloat16*)d_in[4];
  p.ssm_D = (const __nv_bfloat16*)d_in[5];
  p.logA = (const __nv_bfloat16*)d_in[7];
  p.Aim = (const __nv_bfloat16*)d_in[8];
  p.Cre = (const __nv_bfloat16*)d_in[9];
  p.Cim = (const __nv_bfloat16*)d_in[10];
  p.logdt = (const __nv_bfloat16*)d_in[11];
  p.Dskip = (const __nv_bfloat16*)d_in[12];
  p.gate_w = (const __nv_bfloat16*)d_in[13];
  fused_kernel<<<NCL * CS, NTHREADS, SMEM_BYTES, cudaStreamPerThread>>>(p);
}
```

```cpp
#include <cuda_runtime.h>
#include <cuda_bf16.h>
#include <cuda.h>
#include <stdint.h>

#define TIMELINE 0

namespace {

constexpr int SEQ = 2048, DCH = 576, NMODE = 128;
constexpr int CS = 8, CPC = 40, NCL = 15, NTHREADS = 384;

constexpr int UPITCH = 4368, UPAD = 272;
constexpr int HPITCH = 4160;
constexpr int PBSZ = 16896;
constexpr int YPITCH = 528;
constexpr int KTAB = 28672;
constexpr int OFF_TQ = 0;
constexpr int OFF_TK = 20480;
constexpr int OFF_YA = OFF_TK;
constexpr int OFF_TV = 43520;
constexpr int OFF_UX = 64000;
constexpr int OFF_RAWA = OFF_UX + 5 * UPITCH + 48 + 48;
constexpr int OFF_HB = OFF_RAWA + 5 * HPITCH - 32;
constexpr int OFF_PB = OFF_HB + 6 * HPITCH;
constexpr int OFF_HB3 = OFF_PB + 2 * PBSZ;
constexpr int OFF_YB = OFF_HB3 + 2 * HPITCH;
constexpr int OFF_HB4 = OFF_YB + 40 * YPITCH;
constexpr int OFF_UKV = OFF_HB4 + 2 * HPITCH;
constexpr int OFF_KC = OFF_UKV + 5 * UPITCH;
constexpr int OFF_SW = OFF_KC + 3 * 1408;
constexpr int OFF_GW = OFF_SW + 320;
constexpr int OFF_MB = OFF_GW + 80;
constexpr int OFF_TL = OFF_MB + 32 * 8;
constexpr int SMEM_BYTES = OFF_TL + (TIMELINE ? 1536 : 0);
static_assert(((OFF_RAWA - OFF_HB) & 63) == 32, "bank offset between raw/shift copies");
static_assert(KTAB + 2048 <= 2 * PBSZ && KTAB <= OFF_HB4 - OFF_HB3 && KTAB <= OFF_KC - OFF_HB4, "ktab alias zones");
static_assert(SMEM_BYTES <= 232448, "smem");
static_assert(((OFF_RAWA - 48) & 127) == 0, "tma dst");
static_assert((OFF_RAWA & 15) == 0 && (OFF_PB & 15) == 0 && (OFF_HB & 15) == 0 && (OFF_MB & 7) == 0 && (OFF_KC & 15) == 0, "align");

enum { MB_UX = 0, MB_UKV = 5, MB_Y = 10, MB_HRDY = 15, MB_XQ = 16, MB_KV = 18, MB_HA = 19, MB_COUNT = 20 };
enum { NB_WG0 = 1, NB_HB2 = 4, NB_HB4 = 5, NB_HBFREE = 6, NB_PB1 = 7 };

struct Params {
  CUtensorMap tq, tk, tv, to, th;
  const __nv_bfloat16 *q, *shift_k, *ssm_k, *ssm_D, *logA, *Aim, *Cre, *Cim, *logdt, *Dskip, *gate_w;
};

__device__ float g_part[NCL * SEQ];
__device__ unsigned g_cnt[CS * 32];
#define TL(i) do {} while (0)
#define TL_INIT() do {} while (0)
#define TL_DUMP() do {} while (0)

__device__ __forceinline__ uint32_t lds32(uint32_t a) { uint32_t v; asm volatile("ld.shared.u32 %0, [%1];" : "=r"(v) : "r"(a) : "memory"); return v; }
__device__ __forceinline__ uint32_t lds16(uint32_t a) { uint32_t v; asm volatile("ld.shared.u16 %0, [%1];" : "=r"(v) : "r"(a) : "memory"); return v; }
__device__ __forceinline__ uint2 lds64(uint32_t a) { uint2 v; asm volatile("ld.shared.v2.u32 {%0,%1}, [%2];" : "=r"(v.x), "=r"(v.y) : "r"(a) : "memory"); return v; }
__device__ __forceinline__ uint4 lds128(uint32_t a) { uint4 v; asm volatile("ld.shared.v4.u32 {%0,%1,%2,%3}, [%4];" : "=r"(v.x), "=r"(v.y), "=r"(v.z), "=r"(v.w) : "r"(a) : "memory"); return v; }
__device__ __forceinline__ void sts16(uint32_t a, uint32_t v) { asm volatile("st.shared.u16 [%0], %1;" :: "r"(a), "r"(v) : "memory"); }
__device__ __forceinline__ void sts32(uint32_t a, uint32_t v) { asm volatile("st.shared.u32 [%0], %1;" :: "r"(a), "r"(v) : "memory"); }
__device__ __forceinline__ void sts64(uint32_t a, uint32_t x, uint32_t y) { asm volatile("st.shared.v2.u32 [%0], {%1,%2};" :: "r"(a), "r"(x), "r"(y) : "memory"); }
__device__ __forceinline__ void sts128(uint32_t a, uint32_t x, uint32_t y, uint32_t z, uint32_t w) { asm volatile("st.shared.v4.u32 [%0], {%1,%2,%3,%4};" :: "r"(a), "r"(x), "r"(y), "r"(z), "r"(w) : "memory"); }
__device__ __forceinline__ void ldsm4t(uint32_t (&r)[4], uint32_t a) { asm volatile("ldmatrix.sync.aligned.m8n8.x4.trans.shared.b16 {%0,%1,%2,%3}, [%4];" : "=r"(r[0]), "=r"(r[1]), "=r"(r[2]), "=r"(r[3]) : "r"(a) : "memory"); }
__device__ __forceinline__ void ldsm2t(uint32_t& r0, uint32_t& r1, uint32_t a) { asm volatile("ldmatrix.sync.aligned.m8n8.x2.trans.shared.b16 {%0,%1}, [%2];" : "=r"(r0), "=r"(r1) : "r"(a) : "memory"); }
__device__ __forceinline__ void ldsm4(uint32_t (&r)[4], uint32_t a) { asm volatile("ldmatrix.sync.aligned.m8n8.x4.shared.b16 {%0,%1,%2,%3}, [%4];" : "=r"(r[0]), "=r"(r[1]), "=r"(r[2]), "=r"(r[3]) : "r"(a) : "memory"); }
__device__ __forceinline__ void stsm4(uint32_t a, const uint32_t (&r)[4]) { asm volatile("stmatrix.sync.aligned.m8n8.x4.shared.b16 [%0], {%1,%2,%3,%4};" :: "r"(a), "r"(r[0]), "r"(r[1]), "r"(r[2]), "r"(r[3]) : "memory"); }
__device__ __forceinline__ uint32_t pack(float lo, float hi) { uint32_t r; asm("cvt.rn.bf16x2.f32 %0, %1, %2;" : "=r"(r) : "f"(hi), "f"(lo)); return r; }
__device__ __forceinline__ float blo(uint32_t v) { return __uint_as_float(v << 16); }
__device__ __forceinline__ float bhi(uint32_t v) { return __uint_as_float(v & 0xffff0000u); }
__device__ __forceinline__ float bf16r(float x) { return blo(pack(x, 0.f)); }
__device__ __forceinline__ uint32_t hmul2(uint32_t a, uint32_t b) { uint32_t r; asm("mul.rn.bf16x2 %0, %1, %2;" : "=r"(r) : "r"(a), "r"(b)); return r; }
__device__ __forceinline__ uint32_t hadd2(uint32_t a, uint32_t b) { uint32_t r; asm("add.rn.bf16x2 %0, %1, %2;" : "=r"(r) : "r"(a), "r"(b)); return r; }
__device__ __forceinline__ uint32_t prmt(uint32_t a, uint32_t b, uint32_t s) { return __byte_perm(a, b, s); }
__device__ __forceinline__ float ldbf(const __nv_bfloat16* p) { return blo((uint32_t)__ldg((const unsigned short*)p)); }
__device__ __forceinline__ uint32_t sum4(uint32_t a, uint32_t b, uint32_t c, uint32_t d) {
  return pack((blo(a) + blo(b)) + (blo(c) + blo(d)), (bhi(a) + bhi(b)) + (bhi(c) + bhi(d)));
}
__device__ __forceinline__ void mma16816(float (&c)[4], const uint32_t (&a)[4], uint32_t b0, uint32_t b1) {
  asm volatile("mma.sync.aligned.m16n8k16.row.col.f32.bf16.bf16.f32 {%0,%1,%2,%3}, {%4,%5,%6,%7}, {%8,%9}, {%0,%1,%2,%3};"
               : "+f"(c[0]), "+f"(c[1]), "+f"(c[2]), "+f"(c[3]) : "r"(a[0]), "r"(a[1]), "r"(a[2]), "r"(a[3]), "r"(b0), "r"(b1));
}
__device__ __forceinline__ void bar_sync(int id, int n) { asm volatile("bar.sync %0, %1;" :: "r"(id), "r"(n) : "memory"); }
__device__ __forceinline__ void bar_arrive(int id, int n) { asm volatile("bar.arrive %0, %1;" :: "r"(id), "r"(n) : "memory"); }
__device__ __forceinline__ void cluster_arrive() { asm volatile("barrier.cluster.arrive.relaxed.aligned;" ::: "memory"); }
__device__ __forceinline__ void cluster_wait() { asm volatile("barrier.cluster.wait.aligned;" ::: "memory"); }
__device__ __forceinline__ void fence_async() { asm volatile("fence.proxy.async.shared::cta;" ::: "memory"); }
__device__ __forceinline__ void fence_mbinit() { asm volatile("fence.mbarrier_init.release.cluster;" ::: "memory"); }
__device__ __forceinline__ uint32_t mapa(uint32_t a, uint32_t rank) { uint32_t r; asm("mapa.shared::cluster.u32 %0, %1, %2;" : "=r"(r) : "r"(a), "r"(rank)); return r; }
__device__ __forceinline__ void st_async4(uint32_t a, uint32_t x, uint32_t y, uint32_t z, uint32_t w, uint32_t mbar) {
  asm volatile("st.async.weak.shared::cluster.mbarrier::complete_tx::bytes.v4.b32 [%0], {%1,%2,%3,%4}, [%5];"
               :: "r"(a), "r"(x), "r"(y), "r"(z), "r"(w), "r"(mbar) : "memory");
}
__device__ __forceinline__ void mbar_init(uint32_t m, uint32_t cnt) { asm volatile("mbarrier.init.shared::cta.b64 [%0], %1;" :: "r"(m), "r"(cnt) : "memory"); }
__device__ __forceinline__ void mbar_expect(uint32_t m, uint32_t bytes) { asm volatile("mbarrier.arrive.expect_tx.shared::cta.b64 _, [%0], %1;" :: "r"(m), "r"(bytes) : "memory"); }
__device__ __forceinline__ void mbar_arrive(uint32_t m) { asm volatile("mbarrier.arrive.shared::cta.b64 _, [%0];" :: "r"(m) : "memory"); }
__device__ __forceinline__ void mbar_wait(uint32_t m) {
  uint32_t done;
  int it = 0;
  do {
    asm volatile("{.reg .pred p; mbarrier.try_wait.parity.shared::cta.b64 p, [%1], 0; selp.u32 %0, 1, 0, p;}" : "=r"(done) : "r"(m) : "memory");
    if (++it > (1 << 22)) __trap();
  } while (!done);
}
__device__ __forceinline__ void tma_load4(uint32_t dst, const CUtensorMap* tm, int c0, int c3, uint32_t mbar) {
  asm volatile("cp.async.bulk.tensor.4d.shared::cluster.global.mbarrier::complete_tx::bytes [%0], [%1, {%3, %4, %4, %5}], [%2];"
               :: "r"(dst), "l"(tm), "r"(mbar), "r"(c0), "r"(0), "r"(c3) : "memory");
}
__device__ __forceinline__ void tma_store4(const CUtensorMap* tm, int c0, int c3, uint32_t src) {
  asm volatile("cp.async.bulk.tensor.4d.global.shared::cta.bulk_group [%0, {%2, %3, %3, %4}], [%1];"
               :: "l"(tm), "r"(src), "r"(c0), "r"(0), "r"(c3) : "memory");
}
__device__ __forceinline__ void bulk_load(uint32_t dst, const void* src, uint32_t bytes, uint32_t mbar) {
  asm volatile("cp.async.bulk.shared::cluster.global.mbarrier::complete_tx::bytes [%0], [%1], %2, [%3];"
               :: "r"(dst), "l"(src), "r"(bytes), "r"(mbar) : "memory");
}
__device__ __forceinline__ void wg_fence() { asm volatile("wgmma.fence.sync.aligned;" ::: "memory"); }
__device__ __forceinline__ void wg_commit() { asm volatile("wgmma.commit_group.sync.aligned;" ::: "memory"); }
template <int N> __device__ __forceinline__ void wg_wait() { asm volatile("wgmma.wait_group.sync.aligned %0;" :: "n"(N) : "memory"); }
#define WG_REGS "{%0,%1,%2,%3,%4,%5,%6,%7,%8,%9,%10,%11,%12,%13,%14,%15}, {%16,%17,%18,%19}, %20, "
__device__ __forceinline__ void wgmma32_acc(float* d, const uint32_t* a, uint64_t db) {
  asm volatile("wgmma.mma_async.sync.aligned.m64n32k16.f32.bf16.bf16 " WG_REGS "1, 1, 1, 0;"
               : "+f"(d[0]), "+f"(d[1]), "+f"(d[2]), "+f"(d[3]), "+f"(d[4]), "+f"(d[5]), "+f"(d[6]), "+f"(d[7]),
                 "+f"(d[8]), "+f"(d[9]), "+f"(d[10]), "+f"(d[11]), "+f"(d[12]), "+f"(d[13]), "+f"(d[14]), "+f"(d[15])
               : "r"(a[0]), "r"(a[1]), "r"(a[2]), "r"(a[3]), "l"(db));
}
__device__ __forceinline__ void wgmma32_set(float* d, const uint32_t* a, uint64_t db) {
  asm volatile("wgmma.mma_async.sync.aligned.m64n32k16.f32.bf16.bf16 " WG_REGS "0, 1, 1, 0;"
               : "=f"(d[0]), "=f"(d[1]), "=f"(d[2]), "=f"(d[3]), "=f"(d[4]), "=f"(d[5]), "=f"(d[6]), "=f"(d[7]),
                 "=f"(d[8]), "=f"(d[9]), "=f"(d[10]), "=f"(d[11]), "=f"(d[12]), "=f"(d[13]), "=f"(d[14]), "=f"(d[15])
               : "r"(a[0]), "r"(a[1]), "r"(a[2]), "r"(a[3]), "l"(db));
}

__device__ __forceinline__ void tie(float& x) { asm volatile("" : "+f"(x) :: "memory"); }
__device__ __forceinline__ constexpr int aoff(int k) { return 256 * (k >> 2) + ((k & 3) == 0 ? 16 : (k & 3) == 1 ? 144 : (k & 3) == 2 ? 0 : 128); }
template <int ES, int E0, int E1>
__device__ __forceinline__ void epi_tiles(float (&E)[32], float& cy0, float& cy1, uint32_t pw) {
#pragma unroll
  for (int e = E0; e < E1; e++) {
    tie(E[4 * e]); tie(E[4 * e + 1]); tie(E[4 * e + 2]); tie(E[4 * e + 3]);
    float v0 = E[4 * e], v1 = E[4 * e + 1];
    if (e > 0) { v0 += E[4 * e - 2]; v1 += E[4 * e - 1]; } else if (ES > 0) { v0 += cy0; v1 += cy1; }
    sts32(pw + 16 * (8 * ES + e), pack(v0, v1));
    if (e == 7) { cy0 = E[30]; cy1 = E[31]; }
  }
}
template <int S, int MQ, int L0, int L1, int ES, int E0, int E1>
__device__ __forceinline__ void block(float (&acc)[32], const uint32_t (&Q)[16], uint64_t db, uint32_t (&LQ)[16], uint32_t la,
                                      float (&E)[32], float& cy0, float& cy1, uint32_t pw) {
  wg_fence();
#pragma unroll
  for (int mm = 0; mm < 4; mm++) {
#pragma unroll
    for (int jj = 1; jj >= 0; jj--) {
      const int m = 4 * MQ + mm, j = 2 * S + jj;
      if (m < 2 * (j + 1)) {
        if (m == 0) wgmma32_set(acc + 16 * jj, Q + 4 * mm, db + (uint64_t)(16 + 32 * j - 16 * m));
        else wgmma32_acc(acc + 16 * jj, Q + 4 * mm, db + (uint64_t)(16 + 32 * j - 16 * m));
      }
    }
  }
  wg_commit();
  wg_wait<1>();
#pragma unroll
  for (int l = L0; l < L1; l++) LQ[l] = lds32(la + aoff(l));
  epi_tiles<ES, E0, E1>(E, cy0, cy1, pw);
}

struct cf { float x, y; };
__device__ __forceinline__ cf cmul(cf a, cf b) { cf r; r.x = fmaf(a.x, b.x, -a.y * b.y); r.y = fmaf(a.x, b.y, a.y * b.x); return r; }
__device__ __forceinline__ cf cexp_p(float lr2, float lt, float p) {
  float m = exp2f(lr2 * p);
  float t = lt * p;
  t = (t - rintf(t)) * 6.283185307179586f;
  cf r; r.x = m * __cosf(t); r.y = m * __sinf(t); return r;
}
__device__ __forceinline__ void store8(uint32_t a, const cf (&v)[8]) {
  sts128(a, pack(v[0].x, v[1].x), pack(v[2].x, v[3].x), pack(v[4].x, v[5].x), pack(v[6].x, v[7].x));
  sts128(a + KTAB / 2, pack(v[0].y, v[1].y), pack(v[2].y, v[3].y), pack(v[4].y, v[5].y), pack(v[6].y, v[7].y));
}
__device__ __forceinline__ float sigmoidf_(float s) { return 1.f / (1.f + __expf(-s)); }

__global__ void __cluster_dims__(CS, 1, 1) __launch_bounds__(NTHREADS, 1) fused_kernel(const __grid_constant__ Params p) {
  extern __shared__ __align__(1024) uint8_t smem[];
  TL_INIT();
  TL(31);
  const uint32_t sb = (uint32_t)__cvta_generic_to_shared(smem);
  const uint32_t mb = sb + OFF_MB;
  const int wg = __shfl_sync(0xffffffffu, threadIdx.x >> 7, 0);
  const int tid = threadIdx.x & 127, w = __shfl_sync(0xffffffffu, tid >> 5, 0), lane = tid & 31, g = lane >> 2, t = lane & 3;
  const int cl = blockIdx.x >> 3, rank = blockIdx.x & 7;
  const int ch0 = cl * CPC;
  const int nu = min(5, (DCH - ch0) >> 3);

  const int uk0 = wg, uk1 = wg ? wg + 2 : 9;
  float pla[2], pai[2], pcr[2], pci[2], pdt[2], pds[2];
#pragma unroll
  for (int r = 0; r < 2; r++) {
    const int u = r ? uk1 : uk0;
    const int ch = (u < nu) ? ch0 + 8 * u + rank : 0;
    pla[r] = ldbf(p.logA + ch * NMODE + tid);
    pai[r] = ldbf(p.Aim + ch * NMODE + tid);
    pcr[r] = ldbf(p.Cre + ch * NMODE + tid);
    pci[r] = ldbf(p.Cim + ch * NMODE + tid);
    pdt[r] = ldbf(p.logdt + ch + (lane >> 5));
    pds[r] = ldbf(p.Dskip + ch + (lane >> 5));
  }
  uint2 swv = make_uint2(0, 0);
  uint32_t gwv = 0;
  float dval = 0.f;
  if (wg == 2) {
    if (tid < 40 && ch0 + tid < DCH) { swv = __ldg((const uint2*)(p.shift_k + (size_t)(ch0 + tid) * 4)); gwv = __ldg((const unsigned short*)(p.gate_w + ch0 + tid)); }
    if (tid < nu) dval = ldbf(p.ssm_D + ch0 + 8 * tid + rank);
    if (lane == 0) {
      if (w == 0) {
        mbar_init(mb + 8 * MB_XQ, 1);
        mbar_expect(mb + 8 * MB_XQ, 10240);
        tma_load4(sb + OFF_TQ, &p.tq, ch0, 8 * rank, mb + 8 * MB_XQ);
        mbar_init(mb + 8 * (MB_XQ + 1), 1);
        mbar_expect(mb + 8 * (MB_XQ + 1), 10240);
        tma_load4(sb + OFF_TQ + 10240, &p.tq, ch0, 8 * rank + 4, mb + 8 * (MB_XQ + 1));
        TL(20);
        fence_mbinit();
      } else if (w == 1) {
        mbar_init(mb + 8 * MB_KV, 1);
        mbar_init(mb + 8 * MB_HA, 1);
        fence_mbinit();
        mbar_expect(mb + 8 * MB_KV, 23040 + 20480);
        mbar_expect(mb + 8 * MB_HA, 5 * HPITCH);
      }
    }
  } else {
    if (lane == 0) {
      const int b = 2 * (4 * wg + w);
      mbar_init(mb + 8 * b, 1);
      mbar_init(mb + 8 * b + 8, b + 1 == MB_HRDY ? 4 : 1);
      fence_mbinit();
      mbar_expect(mb + 8 * b, b >= MB_Y ? 8192 : 4096);
      if (b + 1 != MB_HRDY) mbar_expect(mb + 8 * b + 8, b + 1 >= MB_Y ? 8192 : 4096);
    }
    if (wg == 0 && tid < 85) sts128(sb + OFF_UX + (tid / 17) * UPITCH + (tid % 17) * 16, 0, 0, 0, 0);
  }
  __syncwarp();
  cluster_arrive();
  uint32_t kid[2][9];
#pragma unroll
  for (int cc = 0; cc < 2; cc++)
#pragma unroll
    for (int i = 0; i < 9; i++) {
      const int l = 8 * (tid + 128 * cc) + i;
      kid[cc][i] = 2 * ((cc == 0 && tid < 16) ? (uint32_t)l : (pack((float)l, 0.f) - 0x4280u));
    }
  TL(0);

  const uint32_t rbase = mapa(sb, g);
  const int mi = lane >> 3, tp = (lane & 7) >> 1, jj = lane & 1;
  const uint32_t toff = (4 * (7 - 2 * mi - jj) + tp) * 80;
  const uint32_t tab = sb + (wg == 0 ? OFF_PB : wg == 1 ? OFF_HB3 : OFF_HB4);
  const uint32_t kc = sb + OFF_KC + wg * 1408;
#pragma unroll 1
  for (int r = 0; r < 2; r++) {
    const int u = r ? uk1 : uk0;
    if (u < nu) {
      const float la = r ? pla[1] : pla[0], ai = r ? pai[1] : pai[0], cr = r ? pcr[1] : pcr[0], ci = r ? pci[1] : pci[0];
      const float dt = bf16r(expf(r ? pdt[1] : pdt[0]));
      const float lr2 = (-bf16r(expf(la)) * dt) * 1.4426950408889634f;
      const float lt = (ai * dt) * 0.15915494309189535f;
      const uint32_t row = tab + tid * 16;
      if (lr2 != 123.f) TL(16 + 4 * r + 6);
      {
        const cf w1 = cexp_p(lr2, lt, 8.f);
        cf v[8];
        v[0].x = 1.f; v[0].y = 0.f; v[1] = w1; v[2] = cmul(w1, w1); v[3] = cmul(v[2], w1);
        const cf w4 = cmul(v[2], v[2]);
        v[4] = w4; v[5] = cmul(v[1], w4); v[6] = cmul(v[2], w4); v[7] = cmul(v[3], w4);
        const cf w8 = cmul(w4, w4);
        store8(row, v);
#pragma unroll
        for (int c = 1; c < 4; c++) {
#pragma unroll
          for (int i = 0; i < 8; i++) v[i] = (c == 1 && i == 0) ? w8 : cmul(v[i], w8);
          store8(row + 2048 * c, v);
        }
      }
      {
        cf z1 = cexp_p(lr2, lt, 1.f), Z = cexp_p(lr2, lt, 256.f);
        z1.y = -z1.y; Z.y = -Z.y;
        const cf z2 = cmul(z1, z1);
        cf h[8], v[8];
        h[0].x = 2.f * cr * dt; h[0].y = -2.f * ci * dt;
        h[1] = cmul(h[0], z1);
#pragma unroll
        for (int i = 2; i < 8; i++) h[i] = cmul(h[i - 2], z2);
        store8(row + 4 * 2048, h);
        v[0] = cmul(h[0], Z); v[1] = cmul(h[2], Z); v[2] = cmul(h[4], Z); v[3] = cmul(h[6], Z);
        v[4] = cmul(v[0], Z); v[5] = cmul(v[2], Z); v[6] = cmul(v[4], Z); v[7] = cmul(v[5], Z);
        store8(row + 5 * 2048, v);
        const cf Z2 = cmul(Z, Z);
        h[0] = cmul(v[4], Z2); h[1] = cmul(v[6], Z2); h[2] = cmul(h[0], Z2); h[3] = cmul(h[1], Z2); h[4] = cmul(h[2], Z2);
        h[5].x = h[5].y = h[6].x = h[6].y = h[7].x = h[7].y = 0.f;
        store8(row + 6 * 2048, h);
      }
    }
    if (r == 0 && threadIdx.x == 288) {
      tma_load4(sb + OFF_TK, &p.tk, ch0, 8 * rank - 1, mb + 8 * MB_KV);
      tma_load4(sb + OFF_TV, &p.tv, ch0, 8 * rank, mb + 8 * MB_KV);
      asm volatile("cp.async.bulk.tensor.4d.shared::cluster.global.mbarrier::complete_tx::bytes [%0], [%1, {%3, %4, %5, %6}], [%2];"
                   :: "r"(sb + OFF_RAWA - 48), "l"(&p.th), "r"(mb + 8 * MB_HA), "r"(0), "r"(-1), "r"(5 * cl), "r"(rank) : "memory");
    }
    __syncwarp();
    TL(16 + 4 * r + 7);
    if (r == 0) {
      cluster_wait();
      if (wg) {
        fence_async();
        mbar_wait(mb + 8 * (MB_XQ + wg - 1));
        TL(13);
        const int ah = 4 * (wg - 1) + w;
        uint32_t xr[5][4];
#pragma unroll
        for (int k = 0; k < 5; k++) ldsm4t(xr[k], sb + OFF_TQ + ah * 2560 + toff + 16 * k);
#pragma unroll
        for (int k = 0; k < 5; k++)
          if (k < nu) st_async4(rbase + OFF_UX + k * UPITCH + UPAD + 16 * (32 * rank + 4 * ah + t), xr[k][0], xr[k][1], xr[k][2], xr[k][3], rbase + OFF_MB + 8 * (MB_UX + k));
        TL(15);
      }
    }
    if (u < nu) {
      if (r || !wg) fence_async();
      bar_sync(NB_WG0 + wg, 128);
      float c[12];
      const uint64_t da = (uint64_t)((tab & 0x3FFFF) >> 4) | ((uint64_t)(KTAB / 32) << 16) | (128ull << 32);
      wg_fence();
#pragma unroll
      for (int ks = 0; ks < 16; ks++) {
        asm volatile("{.reg .pred p; setp.ne.u32 p, %14, 0; wgmma.mma_async.sync.aligned.m64n24k16.f32.bf16.bf16 {%0,%1,%2,%3,%4,%5,%6,%7,%8,%9,%10,%11}, %12, %13, p, 1, 1, 1, 1;}"
                     : "+f"(c[0]), "+f"(c[1]), "+f"(c[2]), "+f"(c[3]), "+f"(c[4]), "+f"(c[5]), "+f"(c[6]), "+f"(c[7]), "+f"(c[8]), "+f"(c[9]), "+f"(c[10]), "+f"(c[11])
                     : "l"(da + (uint64_t)(8 * ks)), "l"(da + (uint64_t)(8 * ks + 512)), "r"(ks));
      }
      wg_commit();
      wg_wait<0>();
      if (tid == 0) c[0] += r ? pds[1] : pds[0];
      if (w < 2) {
#pragma unroll
        for (int hh = 0; hh < 2; hh++) {
          const int a = 16 * w + g + 8 * hh;
          sts32(kc + 4 * (4 * a + t), pack(c[2 * hh], c[2 * hh + 1]));
          sts32(kc + 4 * (t < 2 ? 128 + 2 * a + t : 128 + 32 * t + a), pack(c[4 + 2 * hh], c[5 + 2 * hh]));
          if (t < 3) {
            const uint32_t p0 = pack(c[8 + 2 * hh], c[9 + 2 * hh]);
            sts16(kc + 2 * (512 + 64 * t + a), p0);
            sts16(kc + 2 * (544 + 64 * t + a), p0 >> 16);
          }
        }
      }
      TL(16 + 4 * r + 8);
      bar_sync(NB_WG0 + wg, 128);
      const uint32_t hs = r ? tab : sb + OFF_HB + u * 2 * HPITCH;
      uint32_t v[2][9];
#pragma unroll
      for (int cc = 0; cc < 2; cc++)
#pragma unroll
        for (int i = 0; i < 9; i++) v[cc][i] = lds16(kc + kid[cc][i]);
#pragma unroll
      for (int cc = 0; cc < 2; cc++) {
        const uint32_t o = hs + 16 + 16 * (tid + 128 * cc);
        sts128(o + HPITCH, prmt(v[cc][0], v[cc][1], 0x5410), prmt(v[cc][2], v[cc][3], 0x5410), prmt(v[cc][4], v[cc][5], 0x5410), prmt(v[cc][6], v[cc][7], 0x5410));
        sts128(o, prmt(v[cc][1], v[cc][2], 0x5410), prmt(v[cc][3], v[cc][4], 0x5410), prmt(v[cc][5], v[cc][6], 0x5410), prmt(v[cc][7], v[cc][8], 0x5410));
      }
      if (tid == 0) { sts128(hs + HPITCH, 0, 0, 0, 0); sts128(hs, 0, 0, 0, v[0][0] << 16); }
      if (wg == 2) bar_arrive(NB_HB2 + r, 256);
    }
    TL(1 + r);
    if (wg == 0) break;
  }

  if (wg < 2) {
    if (wg == 0) {
      if (tid < 64) sts128(sb + OFF_PB + tid * 528, 0, 0, 0, 0);
      bar_arrive(NB_PB1, 256);
    } else {
      bar_sync(NB_PB1, 256);
    }
    cluster_arrive();
    bar_sync(NB_WG0 + wg, 128);
    const uint32_t haoff = 4 * (8 * w + ((g + 1) >> 1) + t);
    const uint32_t pw = sb + OFF_PB + wg * PBSZ + 4 * ((w * 8 + g) * 132 + t + w);
    const uint32_t pr = sb + OFF_PB + wg * PBSZ + w * 1056 + lane * 16;
    uint32_t ha = sb + OFF_HB + (2 * wg + (g & 1)) * HPITCH + haoff;
    uint32_t Q0[16], Q1[16], Q2[16], Q3[16];
    float X[32], Y[32], Z[32], cy0 = 0.f, cy1 = 0.f;
#pragma unroll
    for (int l = 0; l < 16; l++) Q0[l] = lds32(ha + aoff(l));
#pragma unroll
    for (int l = 0; l < 8; l++) Q1[l] = lds32(ha + 1024 + aoff(l));
    mbar_wait(mb + 8 * (MB_UX + wg));
    fence_async();
#pragma unroll 1
    for (int i = wg; i < 2 * nu; i += 2) {
      const bool isA = i >= nu;
      const int u = isA ? i - nu : i;
      const uint32_t ub = sb + (isA ? OFF_UKV : OFF_UX) + u * UPITCH;
      const uint64_t db = (uint64_t)((ub & 0x3FFFF) >> 4) | (1ull << 16) | (8ull << 32);
      TL(3 + (i >> 1));
      block<0, 0, 8, 16, 0, 0, 0>(X, Q0, db, Q1, ha + 1024, Z, cy0, cy1, pw);
      bar_sync(NB_WG0 + wg, 128);
      block<1, 0, 0, 5, 0, 0, 4>(Y, Q0, db, Q2, ha + 2048, X, cy0, cy1, pw);
      block<1, 1, 5, 10, 0, 4, 8>(Y, Q1, db, Q2, ha + 2048, X, cy0, cy1, pw);
      block<2, 0, 10, 16, 1, 0, 3>(X, Q0, db, Q2, ha + 2048, Y, cy0, cy1, pw);
      block<2, 1, 0, 6, 1, 3, 6>(X, Q1, db, Q3, ha + 3072, Y, cy0, cy1, pw);
      block<2, 2, 6, 11, 1, 6, 8>(X, Q2, db, Q3, ha + 3072, Y, cy0, cy1, pw);
      block<3, 0, 11, 16, 2, 0, 4>(Z, Q0, db, Q3, ha + 3072, X, cy0, cy1, pw);
      const int n = i + 2;
      if (!isA && (n > 2 || n >= nu) && i <= 2) bar_arrive(NB_HBFREE, 384);
      if (n < nu) {
        if (wg == 0) bar_sync(n == 2 ? NB_HB2 : NB_HB4, 256);
        ha = sb + (n == 2 ? OFF_HB + 4 * HPITCH : n == 3 ? OFF_HB3 : OFF_HB4) + (g & 1) * HPITCH + haoff;
      } else if (n < 2 * nu) {
        mbar_wait(mb + 8 * MB_HRDY);
        ha = sb + ((g & 1) ? OFF_RAWA : OFF_HB) + (n - nu) * HPITCH + haoff;
      }
      block<3, 1, 0, 8, 2, 4, 6>(Z, Q1, db, Q0, ha, X, cy0, cy1, pw);
      block<3, 2, 8, 16, 2, 6, 8>(Z, Q2, db, Q0, ha, X, cy0, cy1, pw);
      block<3, 3, 0, 8, 0, 0, 0>(Z, Q3, db, Q1, ha + 1024, X, cy0, cy1, pw);
      wg_wait<0>();
      epi_tiles<3, 0, 8>(Z, cy0, cy1, pw);
      if (!isA) {
        if (i == wg) {
          for (int k = n; k < nu; k += 2) mbar_wait(mb + 8 * (MB_UX + k));
          cluster_wait();
        }
        if (n >= nu) {
          for (int k = 0; k < nu; k++) mbar_wait(mb + 8 * (MB_UKV + k));
        }
        if (i == wg || n >= nu) fence_async();
      }
      bar_sync(NB_WG0 + wg, 128);
      uint4 pa[4], pb[4];
#pragma unroll
      for (int k = 0; k < 4; k++) { pa[k] = lds128(pr + k * 4224); pb[k] = lds128(pr + k * 4224 + 528); }
      const uint32_t yd = rbase + (isA ? OFF_YA : OFF_YB) + (8 * u + rank) * YPITCH + (8 * w + t) * 16;
      const uint32_t ym = rbase + OFF_MB + 8 * (MB_Y + u);
      st_async4(yd, sum4(pa[0].x, pa[1].x, pa[2].x, pa[3].x), sum4(pa[0].y, pa[1].y, pa[2].y, pa[3].y),
                sum4(pb[0].x, pb[1].x, pb[2].x, pb[3].x), sum4(pb[0].y, pb[1].y, pb[2].y, pb[3].y), ym);
      st_async4(yd + 64, sum4(pa[0].z, pa[1].z, pa[2].z, pa[3].z), sum4(pa[0].w, pa[1].w, pa[2].w, pa[3].w),
                sum4(pb[0].z, pb[1].z, pb[2].z, pb[3].z), sum4(pb[0].w, pb[1].w, pb[2].w, pb[3].w), ym);
      TL(8 + (i >> 1));
    }
    TL_DUMP();
  } else {
    if (tid < 40) { sts64(sb + OFF_SW + 8 * tid, swv.x, swv.y); sts16(sb + OFF_GW + 2 * tid, gwv); }
    else if (tid < 40 + 85) sts128(sb + OFF_UKV + ((tid - 40) / 17) * UPITCH + ((tid - 40) % 17) * 16, 0, 0, 0, 0);
    __syncwarp();
    cluster_arrive();
    bar_sync(NB_WG0 + 2, 128);
    mbar_wait(mb + 8 * MB_XQ);
    mbar_wait(mb + 8 * (MB_XQ + 1));
    {
      float s0 = 0.f, s1 = 0.f;
#pragma unroll
      for (int j = 0; j < 5; j++) {
        const uint4 gw = lds128(sb + OFF_GW + 16 * j);
        const uint4 x0 = lds128(sb + OFF_TQ + tid * 80 + 16 * j), x1 = lds128(sb + OFF_TQ + (tid + 128) * 80 + 16 * j);
        uint32_t m0 = hmul2(x0.x, gw.x), m1 = hmul2(x0.y, gw.y), m2 = hmul2(x0.z, gw.z), m3 = hmul2(x0.w, gw.w);
        s0 += ((blo(m0) + bhi(m0)) + (blo(m1) + bhi(m1))) + ((blo(m2) + bhi(m2)) + (blo(m3) + bhi(m3)));
        m0 = hmul2(x1.x, gw.x); m1 = hmul2(x1.y, gw.y); m2 = hmul2(x1.z, gw.z); m3 = hmul2(x1.w, gw.w);
        s1 += ((blo(m0) + bhi(m0)) + (blo(m1) + bhi(m1))) + ((blo(m2) + bhi(m2)) + (blo(m3) + bhi(m3)));
      }
      __stcg(&g_part[cl * SEQ + rank * 256 + tid], s0);
      __stcg(&g_part[cl * SEQ + rank * 256 + 128 + tid], s1);
    }
    TL(3);
    cluster_wait();
    mbar_wait(mb + 8 * MB_KV);
    TL(4);
    const uint32_t hoff = (4 * (7 - 2 * (mi & 1) - jj) + ((tp + 3) & 3)) * 80 + (tp ? 2560 : 0);
#pragma unroll 1
    for (int u = 0; u < nu; u++) {
      const uint2 sw = lds64(sb + OFF_SW + 8 * (8 * u + g));
      uint32_t E[2][6], V[2][4];
#pragma unroll
      for (int hf = 0; hf < 2; hf++) {
        const int ah = 4 * hf + w;
        uint32_t K[4];
        ldsm4t(K, sb + OFF_TK + (ah + 1) * 2560 + toff + 16 * u);
        ldsm2t(E[hf][4], E[hf][5], sb + OFF_TK + ah * 2560 + hoff + 16 * u);
        ldsm4t(V[hf], sb + OFF_TV + ah * 2560 + toff + 16 * u);
        E[hf][0] = K[0]; E[hf][1] = K[1]; E[hf][2] = K[2]; E[hf][3] = K[3];
      }
      const uint32_t w0 = prmt(sw.x, 0, 0x1010), w1 = prmt(sw.x, 0, 0x3232), w2 = prmt(sw.y, 0, 0x1010), w3 = prmt(sw.y, 0, 0x3232);
#pragma unroll
      for (int hf = 0; hf < 2; hf++) {
        uint32_t O[5], o[4];
#pragma unroll
        for (int i = 0; i < 5; i++) O[i] = prmt(E[hf][i], E[hf][i + 1], 0x5432);
#pragma unroll
        for (int i = 0; i < 4; i++) {
          uint32_t s = hmul2(O[i + 1], w3);
          s = hadd2(s, hmul2(E[hf][i + 1], w2));
          s = hadd2(s, hmul2(O[i], w1));
          s = hadd2(s, hmul2(E[hf][i], w0));
          o[i] = hmul2(s, V[hf][i]);
        }
        st_async4(rbase + OFF_UKV + u * UPITCH + UPAD + 16 * (32 * rank + 16 * hf + 4 * w + t), o[0], o[1], o[2], o[3], rbase + OFF_MB + 8 * (MB_UKV + u));
      }
    }
    TL(5);
    mbar_wait(mb + 8 * MB_HA);
    bar_sync(NB_HBFREE, 384);
    TL(6);
    unsigned g_target = 0;
#pragma unroll 1
    for (int u = 0; u < nu; u++) {
      const uint32_t ra = sb + OFF_RAWA + u * HPITCH + 16 + 16 * tid;
      const uint4 x = lds128(ra), y = lds128(ra + 2048);
      const uint32_t xn = lds32(ra + 16), yn = lds32(ra + 2048 + 16);
      const uint32_t o = sb + OFF_HB + u * HPITCH + 16 + 16 * tid;
      sts128(o, prmt(x.x, x.y, 0x5432), prmt(x.y, x.z, 0x5432), prmt(x.z, x.w, 0x5432), prmt(x.w, xn, 0x5432));
      sts128(o + 2048, prmt(y.x, y.y, 0x5432), prmt(y.y, y.z, 0x5432), prmt(y.z, y.w, 0x5432), prmt(y.w, yn, 0x5432));
    }
    if (tid < nu) {
      const uint32_t ra = sb + OFF_RAWA + tid * HPITCH + 16;
      const uint32_t h0 = pack(blo(lds16(ra)) + dval, 0.f);
      sts16(ra, h0);
      sts128(sb + OFF_HB + tid * HPITCH, 0, 0, 0, h0 << 16);
    }
    __syncwarp();
    if (lane == 0) mbar_arrive(mb + 8 * MB_HRDY);
    TL(7);
    uint32_t okflag = 1;
    if (tid == 0) {
      __threadfence();
      const unsigned old = atomicAdd(&g_cnt[rank * 32], cl == 0 ? 16 - (NCL - 1) : 1);
      g_target = (old & ~15u) + 16;
      unsigned v;
      int it = 0;
      do {
        asm volatile("ld.acquire.gpu.global.u32 %0, [%1];" : "=r"(v) : "l"(&g_cnt[rank * 32]) : "memory");
      } while ((int)(v - g_target) < 0 && ++it < 20000);
      okflag = (int)(v - g_target) >= 0;
    }
    asm volatile("{.reg .pred p, q; setp.ne.u32 p, %1, 0; bar.red.and.pred q, %2, 128, p; selp.u32 %0, 1, 0, q;}" : "=r"(okflag) : "r"(okflag), "r"(NB_WG0 + 2) : "memory");
    {
      float s[2] = {0.f, 0.f};
      if (okflag) {
        float2 v[NCL];
#pragma unroll
        for (int c = 0; c < NCL; c++) v[c] = __ldcg((const float2*)&g_part[c * SEQ + rank * 256 + 2 * tid]);
#pragma unroll
        for (int c = 0; c < NCL; c++) { s[0] += v[c].x; s[1] += v[c].y; }
      } else {
#pragma unroll 1
        for (int hf = 0; hf < 2; hf++) {
          const int slot = 2 * tid + hf;
          const int row = rank * 256 + (slot & ~31) + 8 * (slot & 3) + ((slot >> 2) & 7);
          const uint32_t* xr = (const uint32_t*)(p.q + (size_t)row * DCH);
          const uint32_t* gr = (const uint32_t*)p.gate_w;
          float a = 0.f;
#pragma unroll 1
          for (int c = 0; c < DCH / 2; c++) { const uint32_t m = hmul2(__ldg(xr + c), __ldg(gr + c)); a += blo(m) + bhi(m); }
          if (hf) s[1] = a; else s[0] = a;
        }
      }
      const float g0 = bf16r(sigmoidf_(bf16r(s[0]))), g1 = bf16r(sigmoidf_(bf16r(s[1])));
      sts128(sb + OFF_KC + 16 * tid, pack(g0, g0), pack(1.f - g0, 1.f - g0), pack(g1, g1), pack(1.f - g1, 1.f - g1));
    }
    __syncwarp();
    uint2 gg[2][4];
#pragma unroll
    for (int hh = 0; hh < 2; hh++)
#pragma unroll
      for (int i = 0; i < 4; i++) gg[hh][i] = lds64(sb + OFF_KC + 8 * (64 * w + 32 * hh + 8 * i + g));
    TL(8);
#pragma unroll 1
    for (int u = 0; u < nu; u++) {
      uint32_t qv[2][4];
      const uint32_t qa = sb + OFF_TQ + (64 * w + lane) * 80 + 16 * u;
      ldsm4(qv[0], qa);
      ldsm4(qv[1], qa + 2560);
      mbar_wait(mb + 8 * (MB_Y + u));
      uint32_t ya[2][4], yb[2][4];
      const uint32_t yo = (8 * u + (lane & 7)) * YPITCH + (8 * mi + w) * 16;
#pragma unroll
      for (int hh = 0; hh < 2; hh++) { ldsm4t(ya[hh], sb + OFF_YA + yo + 64 * hh); ldsm4t(yb[hh], sb + OFF_YB + yo + 64 * hh); }
#pragma unroll
      for (int hh = 0; hh < 2; hh++) {
        uint32_t o[4];
#pragma unroll
        for (int i = 0; i < 4; i++) o[i] = hadd2(hmul2(gg[hh][i].x, hmul2(qv[hh][i], ya[hh][i])), hmul2(gg[hh][i].y, yb[hh][i]));
        stsm4(qa + 2560 * hh, o);
      }
      TL(9 + (u < 4 ? u : 8));
    }
    fence_async();
    __syncwarp();
    if (lane == 0) {
      tma_store4(&p.to, ch0, 8 * rank + 2 * w, sb + OFF_TQ + w * 5120);
      asm volatile("cp.async.bulk.commit_group;" ::: "memory");
      asm volatile("cp.async.bulk.wait_group.read 0;" ::: "memory");
    }
    TL(14);
    TL_DUMP();
  }
}

typedef CUresult (*EncodeFn)(CUtensorMap*, CUtensorMapDataType, cuuint32_t, void*, const cuuint64_t*, const cuuint64_t*,
                             const cuuint32_t*, const cuuint32_t*, CUtensorMapInterleave, CUtensorMapSwizzle,
                             CUtensorMapL2promotion, CUtensorMapFloatOOBfill);

void make_map(EncodeFn fn, CUtensorMap* tm, const void* ptr, int nhi) {
  cuuint64_t dims[4] = {DCH, 4, 8, SEQ / 32};
  cuuint64_t strides[3] = {8 * DCH * 2, DCH * 2, 32 * DCH * 2};
  cuuint32_t box[4] = {CPC, 4, 8, (cuuint32_t)nhi};
  cuuint32_t es[4] = {1, 1, 1, 1};
  fn(tm, CU_TENSOR_MAP_DATA_TYPE_BFLOAT16, 4, const_cast<void*>(ptr), dims, strides, box, es, CU_TENSOR_MAP_INTERLEAVE_NONE,
     CU_TENSOR_MAP_SWIZZLE_NONE, CU_TENSOR_MAP_L2_PROMOTION_L2_128B, CU_TENSOR_MAP_FLOAT_OOB_FILL_NONE);
}

}

extern "C" void kernel_launch(void* const* d_in, const int* in_sizes, int n_in, void* d_out, int out_size) {
  (void)in_sizes; (void)n_in; (void)out_size;
  static EncodeFn fn = nullptr;
  if (!fn) {
    cudaDriverEntryPointQueryResult qr;
    cudaGetDriverEntryPoint("cuTensorMapEncodeTiled", (void**)&fn, cudaEnableDefault, &qr);
    cudaFuncSetAttribute(fused_kernel, cudaFuncAttributeMaxDynamicSharedMemorySize, SMEM_BYTES);
  }
  Params p;
  make_map(fn, &p.tq, d_in[0], 4);
  make_map(fn, &p.tk, d_in[1], 9);
  make_map(fn, &p.tv, d_in[2], 8);
  {
    cuuint64_t dims[4] = {32, SEQ / 32, DCH / 8, 8};
    cuuint64_t strides[3] = {64, 8 * SEQ * 2, SEQ * 2};
    cuuint32_t box[4] = {32, 65, 5, 1};
    cuuint32_t es[4] = {1, 1, 1, 1};
    fn(&p.th, CU_TENSOR_MAP_DATA_TYPE_BFLOAT16, 4, d_in[4], dims, strides, box, es, CU_TENSOR_MAP_INTERLEAVE_NONE,
       CU_TENSOR_MAP_SWIZZLE_NONE, CU_TENSOR_MAP_L2_PROMOTION_L2_128B, CU_TENSOR_MAP_FLOAT_OOB_FILL_NONE);
  }
  make_map(fn, &p.to, d_out, 2);
  p.q = (const __nv_bfloat16*)d_in[0];
  p.shift_k = (const __nv_bfloat16*)d_in[3];
  p.ssm_k = (const __nv_bfloat16*)d_in[4];
  p.ssm_D = (const __nv_bfloat16*)d_in[5];
  p.logA = (const __nv_bfloat16*)d_in[7];
  p.Aim = (const __nv_bfloat16*)d_in[8];
  p.Cre = (const __nv_bfloat16*)d_in[9];
  p.Cim = (const __nv_bfloat16*)d_in[10];
  p.logdt = (const __nv_bfloat16*)d_in[11];
  p.Dskip = (const __nv_bfloat16*)d_in[12];
  p.gate_w = (const __nv_bfloat16*)d_in[13];
  fused_kernel<<<NCL * CS, NTHREADS, SMEM_BYTES, cudaStreamPerThread>>>(p);
}
```

```cpp
#include <cuda_runtime.h>
#include <cuda_bf16.h>
#include <cuda.h>
#include <stdint.h>

#define TIMELINE 0

namespace {

constexpr int SEQ = 2048, DCH = 576, NMODE = 128;
constexpr int CS = 8, CPC = 40, NCL = 15, NTHREADS = 384;

constexpr int UPITCH = 4368, UPAD = 272;
constexpr int HPITCH = 4160;
constexpr int PBSZ = 16896;
constexpr int YPITCH = 528;
constexpr int KTAB = 28672;
constexpr int OFF_TQ = 0;
constexpr int OFF_TK = 20480;
constexpr int OFF_YA = OFF_TK;
constexpr int OFF_TV = 43520;
constexpr int OFF_UX = 64000;
constexpr int OFF_RAWA = OFF_UX + 5 * UPITCH + 48 + 48;
constexpr int OFF_HB = OFF_RAWA + 5 * HPITCH - 32;
constexpr int OFF_PB = OFF_HB + 6 * HPITCH;
constexpr int OFF_HB3 = OFF_PB + 2 * PBSZ;
constexpr int OFF_YB = OFF_HB3 + 2 * HPITCH;
constexpr int OFF_HB4 = OFF_YB + 40 * YPITCH;
constexpr int OFF_UKV = OFF_HB4 + 2 * HPITCH;
constexpr int OFF_KC = OFF_UKV + 5 * UPITCH;
constexpr int OFF_SW = OFF_KC + 3 * 1408;
constexpr int OFF_GW = OFF_SW + 320;
constexpr int OFF_MB = OFF_GW + 80;
constexpr int OFF_TL = OFF_MB + 32 * 8;
constexpr int SMEM_BYTES = OFF_TL + (TIMELINE ? 1536 : 0);
static_assert(((OFF_RAWA - OFF_HB) & 63) == 32, "bank offset between raw/shift copies");
static_assert(KTAB + 2048 <= 2 * PBSZ && KTAB <= OFF_HB4 - OFF_HB3 && KTAB <= OFF_KC - OFF_HB4, "ktab alias zones");
static_assert(SMEM_BYTES <= 232448, "smem");
static_assert(((OFF_RAWA - 48) & 127) == 0, "tma dst");
static_assert((OFF_RAWA & 15) == 0 && (OFF_PB & 15) == 0 && (OFF_HB & 15) == 0 && (OFF_MB & 7) == 0 && (OFF_KC & 15) == 0, "align");

enum { MB_UX = 0, MB_UKV = 5, MB_Y = 10, MB_HRDY = 15, MB_XQ = 16, MB_KV = 18, MB_HA = 19, MB_COUNT = 20 };
enum { NB_WG0 = 1, NB_HB2 = 4, NB_HB4 = 5, NB_HBFREE = 6, NB_PB1 = 7 };

struct Params {
  CUtensorMap tq, tk, tv, to, th;
  const __nv_bfloat16 *q, *shift_k, *ssm_k, *ssm_D, *logA, *Aim, *Cre, *Cim, *logdt, *Dskip, *gate_w;
};

__device__ float g_part[NCL * SEQ];
__device__ unsigned g_cnt[CS * 32];
#define TL(i) do {} while (0)
#define TL_INIT() do {} while (0)
#define TL_DUMP() do {} while (0)

__device__ __forceinline__ uint32_t lds32(uint32_t a) { uint32_t v; asm volatile("ld.shared.u32 %0, [%1];" : "=r"(v) : "r"(a) : "memory"); return v; }
__device__ __forceinline__ uint32_t lds16(uint32_t a) { uint32_t v; asm volatile("ld.shared.u16 %0, [%1];" : "=r"(v) : "r"(a) : "memory"); return v; }
__device__ __forceinline__ uint2 lds64(uint32_t a) { uint2 v; asm volatile("ld.shared.v2.u32 {%0,%1}, [%2];" : "=r"(v.x), "=r"(v.y) : "r"(a) : "memory"); return v; }
__device__ __forceinline__ uint4 lds128(uint32_t a) { uint4 v; asm volatile("ld.shared.v4.u32 {%0,%1,%2,%3}, [%4];" : "=r"(v.x), "=r"(v.y), "=r"(v.z), "=r"(v.w) : "r"(a) : "memory"); return v; }
__device__ __forceinline__ void sts16(uint32_t a, uint32_t v) { asm volatile("st.shared.u16 [%0], %1;" :: "r"(a), "r"(v) : "memory"); }
__device__ __forceinline__ void sts32(uint32_t a, uint32_t v) { asm volatile("st.shared.u32 [%0], %1;" :: "r"(a), "r"(v) : "memory"); }
__device__ __forceinline__ void sts64(uint32_t a, uint32_t x, uint32_t y) { asm volatile("st.shared.v2.u32 [%0], {%1,%2};" :: "r"(a), "r"(x), "r"(y) : "memory"); }
__device__ __forceinline__ void sts128(uint32_t a, uint32_t x, uint32_t y, uint32_t z, uint32_t w) { asm volatile("st.shared.v4.u32 [%0], {%1,%2,%3,%4};" :: "r"(a), "r"(x), "r"(y), "r"(z), "r"(w) : "memory"); }
__device__ __forceinline__ void ldsm4t(uint32_t (&r)[4], uint32_t a) { asm volatile("ldmatrix.sync.aligned.m8n8.x4.trans.shared.b16 {%0,%1,%2,%3}, [%4];" : "=r"(r[0]), "=r"(r[1]), "=r"(r[2]), "=r"(r[3]) : "r"(a) : "memory"); }
__device__ __forceinline__ void ldsm2t(uint32_t& r0, uint32_t& r1, uint32_t a) { asm volatile("ldmatrix.sync.aligned.m8n8.x2.trans.shared.b16 {%0,%1}, [%2];" : "=r"(r0), "=r"(r1) : "r"(a) : "memory"); }
__device__ __forceinline__ void ldsm4(uint32_t (&r)[4], uint32_t a) { asm volatile("ldmatrix.sync.aligned.m8n8.x4.shared.b16 {%0,%1,%2,%3}, [%4];" : "=r"(r[0]), "=r"(r[1]), "=r"(r[2]), "=r"(r[3]) : "r"(a) : "memory"); }
__device__ __forceinline__ void stsm4(uint32_t a, const uint32_t (&r)[4]) { asm volatile("stmatrix.sync.aligned.m8n8.x4.shared.b16 [%0], {%1,%2,%3,%4};" :: "r"(a), "r"(r[0]), "r"(r[1]), "r"(r[2]), "r"(r[3]) : "memory"); }
__device__ __forceinline__ uint32_t pack(float lo, float hi) { uint32_t r; asm("cvt.rn.bf16x2.f32 %0, %1, %2;" : "=r"(r) : "f"(hi), "f"(lo)); return r; }
__device__ __forceinline__ float blo(uint32_t v) { return __uint_as_float(v << 16); }
__device__ __forceinline__ float bhi(uint32_t v) { return __uint_as_float(v & 0xffff0000u); }
__device__ __forceinline__ float bf16r(float x) { return blo(pack(x, 0.f)); }
__device__ __forceinline__ uint32_t hmul2(uint32_t a, uint32_t b) { uint32_t r; asm("mul.rn.bf16x2 %0, %1, %2;" : "=r"(r) : "r"(a), "r"(b)); return r; }
__device__ __forceinline__ uint32_t hadd2(uint32_t a, uint32_t b) { uint32_t r; asm("add.rn.bf16x2 %0, %1, %2;" : "=r"(r) : "r"(a), "r"(b)); return r; }
__device__ __forceinline__ uint32_t prmt(uint32_t a, uint32_t b, uint32_t s) { return __byte_perm(a, b, s); }
__device__ __forceinline__ float ldbf(const __nv_bfloat16* p) { return blo((uint32_t)__ldg((const unsigned short*)p)); }
__device__ __forceinline__ uint32_t sum4(uint32_t a, uint32_t b, uint32_t c, uint32_t d) {
  return pack((blo(a) + blo(b)) + (blo(c) + blo(d)), (bhi(a) + bhi(b)) + (bhi(c) + bhi(d)));
}
__device__ __forceinline__ void mma16816(float (&c)[4], const uint32_t (&a)[4], uint32_t b0, uint32_t b1) {
  asm volatile("mma.sync.aligned.m16n8k16.row.col.f32.bf16.bf16.f32 {%0,%1,%2,%3}, {%4,%5,%6,%7}, {%8,%9}, {%0,%1,%2,%3};"
               : "+f"(c[0]), "+f"(c[1]), "+f"(c[2]), "+f"(c[3]) : "r"(a[0]), "r"(a[1]), "r"(a[2]), "r"(a[3]), "r"(b0), "r"(b1));
}
__device__ __forceinline__ void bar_sync(int id, int n) { asm volatile("bar.sync %0, %1;" :: "r"(id), "r"(n) : "memory"); }
__device__ __forceinline__ void bar_arrive(int id, int n) { asm volatile("bar.arrive %0, %1;" :: "r"(id), "r"(n) : "memory"); }
__device__ __forceinline__ void cluster_arrive() { asm volatile("barrier.cluster.arrive.relaxed.aligned;" ::: "memory"); }
__device__ __forceinline__ void cluster_wait() { asm volatile("barrier.cluster.wait.aligned;" ::: "memory"); }
__device__ __forceinline__ void fence_async() { asm volatile("fence.proxy.async.shared::cta;" ::: "memory"); }
__device__ __forceinline__ void fence_mbinit() { asm volatile("fence.mbarrier_init.release.cluster;" ::: "memory"); }
__device__ __forceinline__ uint32_t mapa(uint32_t a, uint32_t rank) { uint32_t r; asm("mapa.shared::cluster.u32 %0, %1, %2;" : "=r"(r) : "r"(a), "r"(rank)); return r; }
__device__ __forceinline__ void st_async4(uint32_t a, uint32_t x, uint32_t y, uint32_t z, uint32_t w, uint32_t mbar) {
  asm volatile("st.async.weak.shared::cluster.mbarrier::complete_tx::bytes.v4.b32 [%0], {%1,%2,%3,%4}, [%5];"
               :: "r"(a), "r"(x), "r"(y), "r"(z), "r"(w), "r"(mbar) : "memory");
}
__device__ __forceinline__ void mbar_init(uint32_t m, uint32_t cnt) { asm volatile("mbarrier.init.shared::cta.b64 [%0], %1;" :: "r"(m), "r"(cnt) : "memory"); }
__device__ __forceinline__ void mbar_expect(uint32_t m, uint32_t bytes) { asm volatile("mbarrier.arrive.expect_tx.shared::cta.b64 _, [%0], %1;" :: "r"(m), "r"(bytes) : "memory"); }
__device__ __forceinline__ void mbar_arrive(uint32_t m) { asm volatile("mbarrier.arrive.shared::cta.b64 _, [%0];" :: "r"(m) : "memory"); }
__device__ __forceinline__ void mbar_wait(uint32_t m) {
  uint32_t done;
  int it = 0;
  do {
    asm volatile("{.reg .pred p; mbarrier.try_wait.parity.shared::cta.b64 p, [%1], 0; selp.u32 %0, 1, 0, p;}" : "=r"(done) : "r"(m) : "memory");
    if (++it > (1 << 22)) __trap();
  } while (!done);
}
__device__ __forceinline__ void tma_load4(uint32_t dst, const CUtensorMap* tm, int c0, int c3, uint32_t mbar) {
  asm volatile("cp.async.bulk.tensor.4d.shared::cluster.global.mbarrier::complete_tx::bytes [%0], [%1, {%3, %4, %4, %5}], [%2];"
               :: "r"(dst), "l"(tm), "r"(mbar), "r"(c0), "r"(0), "r"(c3) : "memory");
}
__device__ __forceinline__ void tma_store4(const CUtensorMap* tm, int c0, int c3, uint32_t src) {
  asm volatile("cp.async.bulk.tensor.4d.global.shared::cta.bulk_group [%0, {%2, %3, %3, %4}], [%1];"
               :: "l"(tm), "r"(src), "r"(c0), "r"(0), "r"(c3) : "memory");
}
__device__ __forceinline__ void bulk_load(uint32_t dst, const void* src, uint32_t bytes, uint32_t mbar) {
  asm volatile("cp.async.bulk.shared::cluster.global.mbarrier::complete_tx::bytes [%0], [%1], %2, [%3];"
               :: "r"(dst), "l"(src), "r"(bytes), "r"(mbar) : "memory");
}
__device__ __forceinline__ void wg_fence() { asm volatile("wgmma.fence.sync.aligned;" ::: "memory"); }
__device__ __forceinline__ void wg_commit() { asm volatile("wgmma.commit_group.sync.aligned;" ::: "memory"); }
template <int N> __device__ __forceinline__ void wg_wait() { asm volatile("wgmma.wait_group.sync.aligned %0;" :: "n"(N) : "memory"); }
#define WG_REGS "{%0,%1,%2,%3,%4,%5,%6,%7,%8,%9,%10,%11,%12,%13,%14,%15}, {%16,%17,%18,%19}, %20, "
__device__ __forceinline__ void wgmma32_acc(float* d, const uint32_t* a, uint64_t db) {
  asm volatile("wgmma.mma_async.sync.aligned.m64n32k16.f32.bf16.bf16 " WG_REGS "1, 1, 1, 0;"
               : "+f"(d[0]), "+f"(d[1]), "+f"(d[2]), "+f"(d[3]), "+f"(d[4]), "+f"(d[5]), "+f"(d[6]), "+f"(d[7]),
                 "+f"(d[8]), "+f"(d[9]), "+f"(d[10]), "+f"(d[11]), "+f"(d[12]), "+f"(d[13]), "+f"(d[14]), "+f"(d[15])
               : "r"(a[0]), "r"(a[1]), "r"(a[2]), "r"(a[3]), "l"(db));
}
__device__ __forceinline__ void wgmma32_set(float* d, const uint32_t* a, uint64_t db) {
  asm volatile("wgmma.mma_async.sync.aligned.m64n32k16.f32.bf16.bf16 " WG_REGS "0, 1, 1, 0;"
               : "=f"(d[0]), "=f"(d[1]), "=f"(d[2]), "=f"(d[3]), "=f"(d[4]), "=f"(d[5]), "=f"(d[6]), "=f"(d[7]),
                 "=f"(d[8]), "=f"(d[9]), "=f"(d[10]), "=f"(d[11]), "=f"(d[12]), "=f"(d[13]), "=f"(d[14]), "=f"(d[15])
               : "r"(a[0]), "r"(a[1]), "r"(a[2]), "r"(a[3]), "l"(db));
}

__device__ __forceinline__ void tie(float& x) { asm volatile("" : "+f"(x) :: "memory"); }
__device__ __forceinline__ constexpr int aoff(int k) { return 256 * (k >> 2) + ((k & 3) == 0 ? 16 : (k & 3) == 1 ? 144 : (k & 3) == 2 ? 0 : 128); }
template <int ES, int E0, int E1>
__device__ __forceinline__ void epi_tiles(float (&E)[32], float& cy0, float& cy1, uint32_t pw) {
#pragma unroll
  for (int e = E0; e < E1; e++) {
    tie(E[4 * e]); tie(E[4 * e + 1]); tie(E[4 * e + 2]); tie(E[4 * e + 3]);
    float v0 = E[4 * e], v1 = E[4 * e + 1];
    if (e > 0) { v0 += E[4 * e - 2]; v1 += E[4 * e - 1]; } else if (ES > 0) { v0 += cy0; v1 += cy1; }
    sts32(pw + 16 * (8 * ES + e), pack(v0, v1));
    if (e == 7) { cy0 = E[30]; cy1 = E[31]; }
  }
}
template <int S, int MQ, int L0, int L1, int ES, int E0, int E1>
__device__ __forceinline__ void block(float (&acc)[32], const uint32_t (&Q)[16], uint64_t db, uint32_t (&LQ)[16], uint32_t la,
                                      float (&E)[32], float& cy0, float& cy1, uint32_t pw) {
  wg_fence();
#pragma unroll
  for (int mm = 0; mm < 4; mm++) {
#pragma unroll
    for (int jj = 1; jj >= 0; jj--) {
      const int m = 4 * MQ + mm, j = 2 * S + jj;
      if (m < 2 * (j + 1)) {
        if (m == 0) wgmma32_set(acc + 16 * jj, Q + 4 * mm, db + (uint64_t)(16 + 32 * j - 16 * m));
        else wgmma32_acc(acc + 16 * jj, Q + 4 * mm, db + (uint64_t)(16 + 32 * j - 16 * m));
      }
    }
  }
  wg_commit();
  wg_wait<1>();
#pragma unroll
  for (int l = L0; l < L1; l++) LQ[l] = lds32(la + aoff(l));
  epi_tiles<ES, E0, E1>(E, cy0, cy1, pw);
}

template <int KS> __device__ __forceinline__ void kgen_mma(float (&c)[12], uint64_t da) {
  asm volatile("{.reg .b64 da, db; add.s64 da, %12, %13; add.s64 db, %12, %14;\n"
               "wgmma.mma_async.sync.aligned.m64n24k16.f32.bf16.bf16 {%0,%1,%2,%3,%4,%5,%6,%7,%8,%9,%10,%11}, da, db, %15, 1, 1, 1, 1;}"
               : "+f"(c[0]), "+f"(c[1]), "+f"(c[2]), "+f"(c[3]), "+f"(c[4]), "+f"(c[5]), "+f"(c[6]), "+f"(c[7]), "+f"(c[8]), "+f"(c[9]), "+f"(c[10]), "+f"(c[11])
               : "l"(da), "n"(8 * KS), "n"(8 * KS + 512), "n"(KS ? 1 : 0));
  if constexpr (KS < 15) kgen_mma<KS + 1>(c, da);
}
struct cf { float x, y; };
__device__ __forceinline__ cf cmul(cf a, cf b) { cf r; r.x = fmaf(a.x, b.x, -a.y * b.y); r.y = fmaf(a.x, b.y, a.y * b.x); return r; }
__device__ __forceinline__ cf cexp_p(float lr2, float lt, float p) {
  float m = exp2f(lr2 * p);
  float t = lt * p;
  t = (t - rintf(t)) * 6.283185307179586f;
  cf r; r.x = m * __cosf(t); r.y = m * __sinf(t); return r;
}
__device__ __forceinline__ void store8(uint32_t a, const cf (&v)[8]) {
  sts128(a, pack(v[0].x, v[1].x), pack(v[2].x, v[3].x), pack(v[4].x, v[5].x), pack(v[6].x, v[7].x));
  sts128(a + KTAB / 2, pack(v[0].y, v[1].y), pack(v[2].y, v[3].y), pack(v[4].y, v[5].y), pack(v[6].y, v[7].y));
}
__device__ __forceinline__ float sigmoidf_(float s) { return 1.f / (1.f + __expf(-s)); }

__global__ void __cluster_dims__(CS, 1, 1) __launch_bounds__(NTHREADS, 1) fused_kernel(const __grid_constant__ Params p) {
  extern __shared__ __align__(1024) uint8_t smem[];
  TL_INIT();
  TL(31);
  const uint32_t sb = (uint32_t)__cvta_generic_to_shared(smem);
  const uint32_t mb = sb + OFF_MB;
  const int wg = __shfl_sync(0xffffffffu, threadIdx.x >> 7, 0);
  const int tid = threadIdx.x & 127, w = __shfl_sync(0xffffffffu, tid >> 5, 0), lane = tid & 31, g = lane >> 2, t = lane & 3;
  const int cl = blockIdx.x >> 3, rank = blockIdx.x & 7;
  const int ch0 = cl * CPC;
  const int nu = min(5, (DCH - ch0) >> 3);

  const int uk0 = wg, uk1 = wg ? wg + 2 : 9;
  float pla[2], pai[2], pcr[2], pci[2], pdt[2], pds[2];
#pragma unroll
  for (int r = 0; r < 2; r++) {
    const int u = r ? uk1 : uk0;
    const int ch = (u < nu) ? ch0 + 8 * u + rank : 0;
    pla[r] = ldbf(p.logA + ch * NMODE + tid);
    pai[r] = ldbf(p.Aim + ch * NMODE + tid);
    pcr[r] = ldbf(p.Cre + ch * NMODE + tid);
    pci[r] = ldbf(p.Cim + ch * NMODE + tid);
    pdt[r] = ldbf(p.logdt + ch + (lane >> 5));
    pds[r] = ldbf(p.Dskip + ch + (lane >> 5));
  }
  uint2 swv = make_uint2(0, 0);
  uint32_t gwv = 0;
  float dval = 0.f;
  if (wg == 2) {
    if (tid < 40 && ch0 + tid < DCH) { swv = __ldg((const uint2*)(p.shift_k + (size_t)(ch0 + tid) * 4)); gwv = __ldg((const unsigned short*)(p.gate_w + ch0 + tid)); }
    if (tid < nu) dval = ldbf(p.ssm_D + ch0 + 8 * tid + rank);
    if (lane == 0) {
      if (w == 0) {
        mbar_init(mb + 8 * MB_XQ, 1);
        mbar_expect(mb + 8 * MB_XQ, 10240);
        tma_load4(sb + OFF_TQ, &p.tq, ch0, 8 * rank, mb + 8 * MB_XQ);
        mbar_init(mb + 8 * (MB_XQ + 1), 1);
        mbar_expect(mb + 8 * (MB_XQ + 1), 10240);
        tma_load4(sb + OFF_TQ + 10240, &p.tq, ch0, 8 * rank + 4, mb + 8 * (MB_XQ + 1));
        TL(20);
        fence_mbinit();
      } else if (w == 1) {
        mbar_init(mb + 8 * MB_KV, 1);
        mbar_init(mb + 8 * MB_HA, 1);
        fence_mbinit();
        mbar_expect(mb + 8 * MB_KV, 23040 + 20480);
        mbar_expect(mb + 8 * MB_HA, 5 * HPITCH);
      }
    }
  } else {
    if (lane == 0) {
      const int b = 2 * (4 * wg + w);
      mbar_init(mb + 8 * b, 1);
      mbar_init(mb + 8 * b + 8, b + 1 == MB_HRDY ? 4 : 1);
      fence_mbinit();
      mbar_expect(mb + 8 * b, b >= MB_Y ? 8192 : 4096);
      if (b + 1 != MB_HRDY) mbar_expect(mb + 8 * b + 8, b + 1 >= MB_Y ? 8192 : 4096);
    }
    if (wg == 0 && tid < 85) sts128(sb + OFF_UX + (tid / 17) * UPITCH + (tid % 17) * 16, 0, 0, 0, 0);
  }
  __syncwarp();
  cluster_arrive();
  uint32_t kid[9];
#pragma unroll
  for (int i = 0; i < 9; i++) {
    const int l = 8 * tid + i;
    kid[i] = pack((float)l, (float)(l + 1024)) - 0x42804280u;
    if (tid < 16) kid[i] = ((pack(128.f, (float)(l + 1024)) - 0x42804280u) & 0xffff0000u) | l;
    kid[i] *= 2;
  }
  TL(0);

  const uint32_t rbase = mapa(sb, g);
  const int mi = lane >> 3, tp = (lane & 7) >> 1, jj = lane & 1;
  const uint32_t toff = (4 * (7 - 2 * mi - jj) + tp) * 80;
  const uint32_t tab = sb + (wg == 0 ? OFF_PB : wg == 1 ? OFF_HB3 : OFF_HB4);
  const uint32_t kc = sb + OFF_KC + wg * 1408;
#pragma unroll 1
  for (int r = 0; r < 2; r++) {
    const int u = r ? uk1 : uk0;
    if (u < nu) {
      const float la = r ? pla[1] : pla[0], ai = r ? pai[1] : pai[0], cr = r ? pcr[1] : pcr[0], ci = r ? pci[1] : pci[0];
      const float dt = bf16r(expf(r ? pdt[1] : pdt[0]));
      const float lr2 = (-bf16r(expf(la)) * dt) * 1.4426950408889634f;
      const float lt = (ai * dt) * 0.15915494309189535f;
      const uint32_t row = tab + tid * 16;
      if (lr2 != 123.f) TL(16 + 4 * r + 6);
      {
        const cf w1 = cexp_p(lr2, lt, 8.f);
        cf v[8];
        v[0].x = 1.f; v[0].y = 0.f; v[1] = w1; v[2] = cmul(w1, w1); v[3] = cmul(v[2], w1);
        const cf w4 = cmul(v[2], v[2]);
        v[4] = w4; v[5] = cmul(v[1], w4); v[6] = cmul(v[2], w4); v[7] = cmul(v[3], w4);
        const cf w8 = cmul(w4, w4);
        store8(row, v);
#pragma unroll
        for (int c = 1; c < 4; c++) {
#pragma unroll
          for (int i = 0; i < 8; i++) v[i] = (c == 1 && i == 0) ? w8 : cmul(v[i], w8);
          store8(row + 2048 * c, v);
        }
      }
      {
        cf z1 = cexp_p(lr2, lt, 1.f), Z = cexp_p(lr2, lt, 256.f);
        z1.y = -z1.y; Z.y = -Z.y;
        const cf z2 = cmul(z1, z1);
        cf h[8], v[8];
        h[0].x = 2.f * cr * dt; h[0].y = -2.f * ci * dt;
        h[1] = cmul(h[0], z1);
#pragma unroll
        for (int i = 2; i < 8; i++) h[i] = cmul(h[i - 2], z2);
        store8(row + 4 * 2048, h);
        v[0] = cmul(h[0], Z); v[1] = cmul(h[2], Z); v[2] = cmul(h[4], Z); v[3] = cmul(h[6], Z);
        v[4] = cmul(v[0], Z); v[5] = cmul(v[2], Z); v[6] = cmul(v[4], Z); v[7] = cmul(v[5], Z);
        store8(row + 5 * 2048, v);
        const cf Z2 = cmul(Z, Z);
        h[0] = cmul(v[4], Z2); h[1] = cmul(v[6], Z2); h[2] = cmul(h[0], Z2); h[3] = cmul(h[1], Z2); h[4] = cmul(h[2], Z2);
        h[5].x = h[5].y = h[6].x = h[6].y = h[7].x = h[7].y = 0.f;
        store8(row + 6 * 2048, h);
      }
    }
    if (r == 0 && threadIdx.x == 288) {
      tma_load4(sb + OFF_TK, &p.tk, ch0, 8 * rank - 1, mb + 8 * MB_KV);
      tma_load4(sb + OFF_TV, &p.tv, ch0, 8 * rank, mb + 8 * MB_KV);
      asm volatile("cp.async.bulk.tensor.4d.shared::cluster.global.mbarrier::complete_tx::bytes [%0], [%1, {%3, %4, %5, %6}], [%2];"
                   :: "r"(sb + OFF_RAWA - 48), "l"(&p.th), "r"(mb + 8 * MB_HA), "r"(0), "r"(-1), "r"(5 * cl), "r"(rank) : "memory");
    }
    __syncwarp();
    TL(16 + 4 * r + 7);
    if (r == 0) {
      cluster_wait();
      if (wg) {
        fence_async();
        mbar_wait(mb + 8 * (MB_XQ + wg - 1));
        TL(13);
        const int ah = 4 * (wg - 1) + w;
        uint32_t xr[5][4];
#pragma unroll
        for (int k = 0; k < 5; k++) ldsm4t(xr[k], sb + OFF_TQ + ah * 2560 + toff + 16 * k);
#pragma unroll
        for (int k = 0; k < 5; k++)
          if (k < nu) st_async4(rbase + OFF_UX + k * UPITCH + UPAD + 16 * (32 * rank + 4 * ah + t), xr[k][0], xr[k][1], xr[k][2], xr[k][3], rbase + OFF_MB + 8 * (MB_UX + k));
        TL(15);
      }
    }
    if (u < nu) {
      if (r || !wg) fence_async();
      bar_sync(NB_WG0 + wg, 128);
      float c[12];
      const uint64_t da = (uint64_t)((tab & 0x3FFFF) >> 4) | ((uint64_t)(KTAB / 32) << 16) | (128ull << 32);
      wg_fence();
      kgen_mma<0>(c, da);
      wg_commit();
      wg_wait<0>();
      if (tid == 0) c[0] += r ? pds[1] : pds[0];
      if (w < 2) {
#pragma unroll
        for (int hh = 0; hh < 2; hh++) {
          const int a = 16 * w + g + 8 * hh;
          sts32(kc + 4 * (4 * a + t), pack(c[2 * hh], c[2 * hh + 1]));
          sts32(kc + 4 * (t < 2 ? 128 + 2 * a + t : 128 + 32 * t + a), pack(c[4 + 2 * hh], c[5 + 2 * hh]));
          if (t < 3) {
            const uint32_t p0 = pack(c[8 + 2 * hh], c[9 + 2 * hh]);
            sts16(kc + 2 * (512 + 64 * t + a), p0);
            sts16(kc + 2 * (544 + 64 * t + a), p0 >> 16);
          }
        }
      }
      TL(16 + 4 * r + 8);
      bar_sync(NB_WG0 + wg, 128);
      const uint32_t hs = r ? tab : sb + OFF_HB + u * 2 * HPITCH;
      uint32_t v[2][9];
#pragma unroll
      for (int cc = 0; cc < 2; cc++)
#pragma unroll
        for (int i = 0; i < 9; i++) v[cc][i] = lds16(kc + (cc ? kid[i] >> 16 : kid[i] & 0xffffu));
#pragma unroll
      for (int cc = 0; cc < 2; cc++) {
        const uint32_t o = hs + 16 + 16 * (tid + 128 * cc);
        sts128(o + HPITCH, prmt(v[cc][0], v[cc][1], 0x5410), prmt(v[cc][2], v[cc][3], 0x5410), prmt(v[cc][4], v[cc][5], 0x5410), prmt(v[cc][6], v[cc][7], 0x5410));
        sts128(o, prmt(v[cc][1], v[cc][2], 0x5410), prmt(v[cc][3], v[cc][4], 0x5410), prmt(v[cc][5], v[cc][6], 0x5410), prmt(v[cc][7], v[cc][8], 0x5410));
      }
      if (tid == 0) { sts128(hs + HPITCH, 0, 0, 0, 0); sts128(hs, 0, 0, 0, v[0][0] << 16); }
      if (wg == 2) bar_arrive(NB_HB2 + r, 256);
    }
    TL(1 + r);
    if (wg == 0) break;
  }

  if (wg < 2) {
    if (wg == 0) {
      if (tid < 64) sts128(sb + OFF_PB + tid * 528, 0, 0, 0, 0);
      bar_arrive(NB_PB1, 256);
    } else {
      bar_sync(NB_PB1, 256);
    }
    cluster_arrive();
    bar_sync(NB_WG0 + wg, 128);
    const uint32_t haoff = 4 * (8 * w + ((g + 1) >> 1) + t);
    const uint32_t pw = sb + OFF_PB + wg * PBSZ + 4 * ((w * 8 + g) * 132 + t + w);
    const uint32_t pr = sb + OFF_PB + wg * PBSZ + w * 1056 + lane * 16;
    uint32_t ha = sb + OFF_HB + (2 * wg + (g & 1)) * HPITCH + haoff;
    uint32_t Q0[16], Q1[16], Q2[16], Q3[16];
    float X[32], Y[32], Z[32], cy0 = 0.f, cy1 = 0.f;
#pragma unroll
    for (int l = 0; l < 16; l++) Q0[l] = lds32(ha + aoff(l));
#pragma unroll
    for (int l = 0; l < 8; l++) Q1[l] = lds32(ha + 1024 + aoff(l));
    mbar_wait(mb + 8 * (MB_UX + wg));
    fence_async();
#pragma unroll 1
    for (int i = wg; i < 2 * nu; i += 2) {
      const bool isA = i >= nu;
      const int u = isA ? i - nu : i;
      const uint32_t ub = sb + (isA ? OFF_UKV : OFF_UX) + u * UPITCH;
      const uint64_t db = (uint64_t)((ub & 0x3FFFF) >> 4) | (1ull << 16) | (8ull << 32);
      TL(3 + (i >> 1));
      block<0, 0, 8, 16, 0, 0, 0>(X, Q0, db, Q1, ha + 1024, Z, cy0, cy1, pw);
      bar_sync(NB_WG0 + wg, 128);
      block<1, 0, 0, 5, 0, 0, 4>(Y, Q0, db, Q2, ha + 2048, X, cy0, cy1, pw);
      block<1, 1, 5, 10, 0, 4, 8>(Y, Q1, db, Q2, ha + 2048, X, cy0, cy1, pw);
      block<2, 0, 10, 16, 1, 0, 3>(X, Q0, db, Q2, ha + 2048, Y, cy0, cy1, pw);
      block<2, 1, 0, 6, 1, 3, 6>(X, Q1, db, Q3, ha + 3072, Y, cy0, cy1, pw);
      block<2, 2, 6, 11, 1, 6, 8>(X, Q2, db, Q3, ha + 3072, Y, cy0, cy1, pw);
      block<3, 0, 11, 16, 2, 0, 4>(Z, Q0, db, Q3, ha + 3072, X, cy0, cy1, pw);
      const int n = i + 2;
      if (!isA && (n > 2 || n >= nu) && i <= 2) bar_arrive(NB_HBFREE, 384);
      if (n < nu) {
        if (wg == 0) bar_sync(n == 2 ? NB_HB2 : NB_HB4, 256);
        ha = sb + (n == 2 ? OFF_HB + 4 * HPITCH : n == 3 ? OFF_HB3 : OFF_HB4) + (g & 1) * HPITCH + haoff;
      } else if (n < 2 * nu) {
        mbar_wait(mb + 8 * MB_HRDY);
        ha = sb + ((g & 1) ? OFF_RAWA : OFF_HB) + (n - nu) * HPITCH + haoff;
      }
      block<3, 1, 0, 8, 2, 4, 6>(Z, Q1, db, Q0, ha, X, cy0, cy1, pw);
      block<3, 2, 8, 16, 2, 6, 8>(Z, Q2, db, Q0, ha, X, cy0, cy1, pw);
      block<3, 3, 0, 8, 0, 0, 0>(Z, Q3, db, Q1, ha + 1024, X, cy0, cy1, pw);
      wg_wait<0>();
      epi_tiles<3, 0, 8>(Z, cy0, cy1, pw);
      if (!isA) {
        if (i == wg) {
          for (int k = n; k < nu; k += 2) mbar_wait(mb + 8 * (MB_UX + k));
          cluster_wait();
        }
        if (n >= nu) {
          for (int k = 0; k < nu; k++) mbar_wait(mb + 8 * (MB_UKV + k));
        }
        if (i == wg || n >= nu) fence_async();
      }
      bar_sync(NB_WG0 + wg, 128);
      uint4 pa[4], pb[4];
#pragma unroll
      for (int k = 0; k < 4; k++) { pa[k] = lds128(pr + k * 4224); pb[k] = lds128(pr + k * 4224 + 528); }
      const uint32_t yd = rbase + (isA ? OFF_YA : OFF_YB) + (8 * u + rank) * YPITCH + (8 * w + t) * 16;
      const uint32_t ym = rbase + OFF_MB + 8 * (MB_Y + u);
      st_async4(yd, sum4(pa[0].x, pa[1].x, pa[2].x, pa[3].x), sum4(pa[0].y, pa[1].y, pa[2].y, pa[3].y),
                sum4(pb[0].x, pb[1].x, pb[2].x, pb[3].x), sum4(pb[0].y, pb[1].y, pb[2].y, pb[3].y), ym);
      st_async4(yd + 64, sum4(pa[0].z, pa[1].z, pa[2].z, pa[3].z), sum4(pa[0].w, pa[1].w, pa[2].w, pa[3].w),
                sum4(pb[0].z, pb[1].z, pb[2].z, pb[3].z), sum4(pb[0].w, pb[1].w, pb[2].w, pb[3].w), ym);
      TL(8 + (i >> 1));
    }
    TL_DUMP();
  } else {
    if (tid < 40) { sts64(sb + OFF_SW + 8 * tid, swv.x, swv.y); sts16(sb + OFF_GW + 2 * tid, gwv); }
    else if (tid < 40 + 85) sts128(sb + OFF_UKV + ((tid - 40) / 17) * UPITCH + ((tid - 40) % 17) * 16, 0, 0, 0, 0);
    __syncwarp();
    cluster_arrive();
    bar_sync(NB_WG0 + 2, 128);
    mbar_wait(mb + 8 * MB_XQ);
    mbar_wait(mb + 8 * (MB_XQ + 1));
    {
      float s0 = 0.f, s1 = 0.f;
#pragma unroll
      for (int j = 0; j < 5; j++) {
        const uint4 gw = lds128(sb + OFF_GW + 16 * j);
        const uint4 x0 = lds128(sb + OFF_TQ + tid * 80 + 16 * j), x1 = lds128(sb + OFF_TQ + (tid + 128) * 80 + 16 * j);
        uint32_t m0 = hmul2(x0.x, gw.x), m1 = hmul2(x0.y, gw.y), m2 = hmul2(x0.z, gw.z), m3 = hmul2(x0.w, gw.w);
        s0 += ((blo(m0) + bhi(m0)) + (blo(m1) + bhi(m1))) + ((blo(m2) + bhi(m2)) + (blo(m3) + bhi(m3)));
        m0 = hmul2(x1.x, gw.x); m1 = hmul2(x1.y, gw.y); m2 = hmul2(x1.z, gw.z); m3 = hmul2(x1.w, gw.w);
        s1 += ((blo(m0) + bhi(m0)) + (blo(m1) + bhi(m1))) + ((blo(m2) + bhi(m2)) + (blo(m3) + bhi(m3)));
      }
      __stcg(&g_part[cl * SEQ + rank * 256 + tid], s0);
      __stcg(&g_part[cl * SEQ + rank * 256 + 128 + tid], s1);
    }
    TL(3);
    cluster_wait();
    mbar_wait(mb + 8 * MB_KV);
    TL(4);
    const uint32_t hoff = (4 * (7 - 2 * (mi & 1) - jj) + ((tp + 3) & 3)) * 80 + (tp ? 2560 : 0);
#pragma unroll 1
    for (int u = 0; u < nu; u++) {
      const uint2 sw = lds64(sb + OFF_SW + 8 * (8 * u + g));
      uint32_t E[2][6], V[2][4];
#pragma unroll
      for (int hf = 0; hf < 2; hf++) {
        const int ah = 4 * hf + w;
        uint32_t K[4];
        ldsm4t(K, sb + OFF_TK + (ah + 1) * 2560 + toff + 16 * u);
        ldsm2t(E[hf][4], E[hf][5], sb + OFF_TK + ah * 2560 + hoff + 16 * u);
        ldsm4t(V[hf], sb + OFF_TV + ah * 2560 + toff + 16 * u);
        E[hf][0] = K[0]; E[hf][1] = K[1]; E[hf][2] = K[2]; E[hf][3] = K[3];
      }
      const uint32_t w0 = prmt(sw.x, 0, 0x1010), w1 = prmt(sw.x, 0, 0x3232), w2 = prmt(sw.y, 0, 0x1010), w3 = prmt(sw.y, 0, 0x3232);
#pragma unroll
      for (int hf = 0; hf < 2; hf++) {
        uint32_t O[5], o[4];
#pragma unroll
        for (int i = 0; i < 5; i++) O[i] = prmt(E[hf][i], E[hf][i + 1], 0x5432);
#pragma unroll
        for (int i = 0; i < 4; i++) {
          uint32_t s = hmul2(O[i + 1], w3);
          s = hadd2(s, hmul2(E[hf][i + 1], w2));
          s = hadd2(s, hmul2(O[i], w1));
          s = hadd2(s, hmul2(E[hf][i], w0));
          o[i] = hmul2(s, V[hf][i]);
        }
        st_async4(rbase + OFF_UKV + u * UPITCH + UPAD + 16 * (32 * rank + 16 * hf + 4 * w + t), o[0], o[1], o[2], o[3], rbase + OFF_MB + 8 * (MB_UKV + u));
      }
    }
    TL(5);
    mbar_wait(mb + 8 * MB_HA);
    bar_sync(NB_HBFREE, 384);
    TL(6);
    unsigned g_target = 0;
#pragma unroll 1
    for (int u = 0; u < nu; u++) {
      const uint32_t ra = sb + OFF_RAWA + u * HPITCH + 16 + 16 * tid;
      const uint4 x = lds128(ra), y = lds128(ra + 2048);
      const uint32_t xn = lds32(ra + 16), yn = lds32(ra + 2048 + 16);
      const uint32_t o = sb + OFF_HB + u * HPITCH + 16 + 16 * tid;
      sts128(o, prmt(x.x, x.y, 0x5432), prmt(x.y, x.z, 0x5432), prmt(x.z, x.w, 0x5432), prmt(x.w, xn, 0x5432));
      sts128(o + 2048, prmt(y.x, y.y, 0x5432), prmt(y.y, y.z, 0x5432), prmt(y.z, y.w, 0x5432), prmt(y.w, yn, 0x5432));
    }
    if (tid < nu) {
      const uint32_t ra = sb + OFF_RAWA + tid * HPITCH + 16;
      const uint32_t h0 = pack(blo(lds16(ra)) + dval, 0.f);
      sts16(ra, h0);
      sts128(sb + OFF_HB + tid * HPITCH, 0, 0, 0, h0 << 16);
    }
    __syncwarp();
    if (lane == 0) mbar_arrive(mb + 8 * MB_HRDY);
    TL(7);
    uint32_t okflag = 1;
    if (tid == 0) {
      __threadfence();
      const unsigned old = atomicAdd(&g_cnt[rank * 32], cl == 0 ? 16 - (NCL - 1) : 1);
      g_target = (old & ~15u) + 16;
      unsigned v;
      int it = 0;
      do {
        asm volatile("ld.acquire.gpu.global.u32 %0, [%1];" : "=r"(v) : "l"(&g_cnt[rank * 32]) : "memory");
      } while ((int)(v - g_target) < 0 && ++it < 20000);
      okflag = (int)(v - g_target) >= 0;
    }
    asm volatile("{.reg .pred p, q; setp.ne.u32 p, %1, 0; bar.red.and.pred q, %2, 128, p; selp.u32 %0, 1, 0, q;}" : "=r"(okflag) : "r"(okflag), "r"(NB_WG0 + 2) : "memory");
    {
      float s[2] = {0.f, 0.f};
      if (okflag) {
        float2 v[NCL];
#pragma unroll
        for (int c = 0; c < NCL; c++) v[c] = __ldcg((const float2*)&g_part[c * SEQ + rank * 256 + 2 * tid]);
#pragma unroll
        for (int c = 0; c < NCL; c++) { s[0] += v[c].x; s[1] += v[c].y; }
      } else {
#pragma unroll 1
        for (int hf = 0; hf < 2; hf++) {
          const int slot = 2 * tid + hf;
          const int row = rank * 256 + (slot & ~31) + 8 * (slot & 3) + ((slot >> 2) & 7);
          const uint32_t* xr = (const uint32_t*)(p.q + (size_t)row * DCH);
          const uint32_t* gr = (const uint32_t*)p.gate_w;
          float a = 0.f;
#pragma unroll 1
          for (int c = 0; c < DCH / 2; c++) { const uint32_t m = hmul2(__ldg(xr + c), __ldg(gr + c)); a += blo(m) + bhi(m); }
          if (hf) s[1] = a; else s[0] = a;
        }
      }
      const float g0 = bf16r(sigmoidf_(bf16r(s[0]))), g1 = bf16r(sigmoidf_(bf16r(s[1])));
      sts128(sb + OFF_KC + 16 * tid, pack(g0, g0), pack(1.f - g0, 1.f - g0), pack(g1, g1), pack(1.f - g1, 1.f - g1));
    }
    __syncwarp();
    uint2 gg[2][4];
#pragma unroll
    for (int hh = 0; hh < 2; hh++)
#pragma unroll
      for (int i = 0; i < 4; i++) gg[hh][i] = lds64(sb + OFF_KC + 8 * (64 * w + 32 * hh + 8 * i + g));
    TL(8);
#pragma unroll 1
    for (int u = 0; u < nu; u++) {
      uint32_t qv[2][4];
      const uint32_t qa = sb + OFF_TQ + (64 * w + lane) * 80 + 16 * u;
      ldsm4(qv[0], qa);
      ldsm4(qv[1], qa + 2560);
      mbar_wait(mb + 8 * (MB_Y + u));
      uint32_t ya[2][4], yb[2][4];
      const uint32_t yo = (8 * u + (lane & 7)) * YPITCH + (8 * mi + w) * 16;
#pragma unroll
      for (int hh = 0; hh < 2; hh++) { ldsm4t(ya[hh], sb + OFF_YA + yo + 64 * hh); ldsm4t(yb[hh], sb + OFF_YB + yo + 64 * hh); }
#pragma unroll
      for (int hh = 0; hh < 2; hh++) {
        uint32_t o[4];
#pragma unroll
        for (int i = 0; i < 4; i++) o[i] = hadd2(hmul2(gg[hh][i].x, hmul2(qv[hh][i], ya[hh][i])), hmul2(gg[hh][i].y, yb[hh][i]));
        stsm4(qa + 2560 * hh, o);
      }
      TL(9 + (u < 4 ? u : 8));
    }
    fence_async();
    __syncwarp();
    if (lane == 0) {
      tma_store4(&p.to, ch0, 8 * rank + 2 * w, sb + OFF_TQ + w * 5120);
      asm volatile("cp.async.bulk.commit_group;" ::: "memory");
      asm volatile("cp.async.bulk.wait_group.read 0;" ::: "memory");
    }
    TL(14);
    TL_DUMP();
  }
}

typedef CUresult (*EncodeFn)(CUtensorMap*, CUtensorMapDataType, cuuint32_t, void*, const cuuint64_t*, const cuuint64_t*,
                             const cuuint32_t*, const cuuint32_t*, CUtensorMapInterleave, CUtensorMapSwizzle,
                             CUtensorMapL2promotion, CUtensorMapFloatOOBfill);

void make_map(EncodeFn fn, CUtensorMap* tm, const void* ptr, int nhi) {
  cuuint64_t dims[4] = {DCH, 4, 8, SEQ / 32};
  cuuint64_t strides[3] = {8 * DCH * 2, DCH * 2, 32 * DCH * 2};
  cuuint32_t box[4] = {CPC, 4, 8, (cuuint32_t)nhi};
  cuuint32_t es[4] = {1, 1, 1, 1};
  fn(tm, CU_TENSOR_MAP_DATA_TYPE_BFLOAT16, 4, const_cast<void*>(ptr), dims, strides, box, es, CU_TENSOR_MAP_INTERLEAVE_NONE,
     CU_TENSOR_MAP_SWIZZLE_NONE, CU_TENSOR_MAP_L2_PROMOTION_L2_128B, CU_TENSOR_MAP_FLOAT_OOB_FILL_NONE);
}

}

extern "C" void kernel_launch(void* const* d_in, const int* in_sizes, int n_in, void* d_out, int out_size) {
  (void)in_sizes; (void)n_in; (void)out_size;
  static EncodeFn fn = nullptr;
  if (!fn) {
    cudaDriverEntryPointQueryResult qr;
    cudaGetDriverEntryPoint("cuTensorMapEncodeTiled", (void**)&fn, cudaEnableDefault, &qr);
    cudaFuncSetAttribute(fused_kernel, cudaFuncAttributeMaxDynamicSharedMemorySize, SMEM_BYTES);
  }
  Params p;
  make_map(fn, &p.tq, d_in[0], 4);
  make_map(fn, &p.tk, d_in[1], 9);
  make_map(fn, &p.tv, d_in[2], 8);
  {
    cuuint64_t dims[4] = {32, SEQ / 32, DCH / 8, 8};
    cuuint64_t strides[3] = {64, 8 * SEQ * 2, SEQ * 2};
    cuuint32_t box[4] = {32, 65, 5, 1};
    cuuint32_t es[4] = {1, 1, 1, 1};
    fn(&p.th, CU_TENSOR_MAP_DATA_TYPE_BFLOAT16, 4, d_in[4], dims, strides, box, es, CU_TENSOR_MAP_INTERLEAVE_NONE,
       CU_TENSOR_MAP_SWIZZLE_NONE, CU_TENSOR_MAP_L2_PROMOTION_L2_128B, CU_TENSOR_MAP_FLOAT_OOB_FILL_NONE);
  }
  make_map(fn, &p.to, d_out, 2);
  p.q = (const __nv_bfloat16*)d_in[0];
  p.shift_k = (const __nv_bfloat16*)d_in[3];
  p.ssm_k = (const __nv_bfloat16*)d_in[4];
  p.ssm_D = (const __nv_bfloat16*)d_in[5];
  p.logA = (const __nv_bfloat16*)d_in[7];
  p.Aim = (const __nv_bfloat16*)d_in[8];
  p.Cre = (const __nv_bfloat16*)d_in[9];
  p.Cim = (const __nv_bfloat16*)d_in[10];
  p.logdt = (const __nv_bfloat16*)d_in[11];
  p.Dskip = (const __nv_bfloat16*)d_in[12];
  p.gate_w = (const __nv_bfloat16*)d_in[13];
  fused_kernel<<<NCL * CS, NTHREADS, SMEM_BYTES, cudaStreamPerThread>>>(p);
}
```

```cpp
#include <cuda_runtime.h>
#include <cuda_bf16.h>
#include <cuda.h>
#include <stdint.h>

#define TIMELINE 0

namespace {

constexpr int SEQ = 2048, DCH = 576, NMODE = 128;
constexpr int CS = 8, CPC = 40, NCL = 15, NTHREADS = 384;

constexpr int UPITCH = 4368, UPAD = 272;
constexpr int HPITCH = 4160;
constexpr int PBSZ = 16896;
constexpr int YPITCH = 528;
constexpr int KTAB = 28672;
constexpr int OFF_TQ = 0;
constexpr int OFF_TK = 20480;
constexpr int OFF_YA = OFF_TK;
constexpr int OFF_TV = 43520;
constexpr int OFF_UX = 64000;
constexpr int OFF_RAWA = OFF_UX + 5 * UPITCH + 48 + 48;
constexpr int OFF_HB3 = OFF_RAWA + 5 * HPITCH - 32;
constexpr int OFF_HB = OFF_HB3 + 2 * HPITCH;
constexpr int OFF_PB = OFF_HB + 6 * HPITCH;
constexpr int OFF_YB = OFF_PB + 2 * PBSZ;
constexpr int OFF_HB4 = OFF_YB + 40 * YPITCH;
constexpr int OFF_UKV = OFF_HB4 + 2 * HPITCH;
constexpr int OFF_KC = OFF_UKV + 5 * UPITCH;
constexpr int OFF_SW = OFF_KC + 3 * 1408;
constexpr int OFF_GW = OFF_SW + 320;
constexpr int OFF_MB = OFF_GW + 80;
constexpr int OFF_TL = OFF_MB + 32 * 8;
constexpr int SMEM_BYTES = OFF_TL + (TIMELINE ? 1536 : 0);
static_assert(((OFF_RAWA - OFF_HB) & 63) == 32, "bank offset between raw/shift copies");
static_assert(KTAB + 2048 <= 2 * PBSZ && KTAB <= OFF_HB - (OFF_RAWA - 48) && KTAB <= OFF_KC - OFF_HB4, "ktab alias zones");
static_assert(SMEM_BYTES <= 232448, "smem");
static_assert(((OFF_RAWA - 48) & 127) == 0, "tma dst");
static_assert((OFF_RAWA & 15) == 0 && (OFF_PB & 15) == 0 && (OFF_HB & 15) == 0 && (OFF_MB & 7) == 0 && (OFF_KC & 15) == 0, "align");

enum { MB_UX = 0, MB_UKV = 5, MB_Y = 10, MB_HRDY = 15, MB_XQ = 16, MB_KV = 18, MB_HA = 19, MB_COUNT = 20 };
enum { NB_WG0 = 1, NB_HB2 = 4, NB_HB4 = 5, NB_HBFREE = 6, NB_PB1 = 7 };

struct Params {
  CUtensorMap tq, tk, tv, to, th;
  const __nv_bfloat16 *q, *shift_k, *ssm_k, *ssm_D, *logA, *Aim, *Cre, *Cim, *logdt, *Dskip, *gate_w;
};

__device__ float g_part[NCL * SEQ];
__device__ unsigned g_cnt[CS * 32];
#define TL(i) do {} while (0)
#define TL_INIT() do {} while (0)
#define TL_DUMP() do {} while (0)

__device__ __forceinline__ uint32_t lds32(uint32_t a) { uint32_t v; asm volatile("ld.shared.u32 %0, [%1];" : "=r"(v) : "r"(a) : "memory"); return v; }
__device__ __forceinline__ uint32_t lds16(uint32_t a) { uint32_t v; asm volatile("ld.shared.u16 %0, [%1];" : "=r"(v) : "r"(a) : "memory"); return v; }
__device__ __forceinline__ uint2 lds64(uint32_t a) { uint2 v; asm volatile("ld.shared.v2.u32 {%0,%1}, [%2];" : "=r"(v.x), "=r"(v.y) : "r"(a) : "memory"); return v; }
__device__ __forceinline__ uint4 lds128(uint32_t a) { uint4 v; asm volatile("ld.shared.v4.u32 {%0,%1,%2,%3}, [%4];" : "=r"(v.x), "=r"(v.y), "=r"(v.z), "=r"(v.w) : "r"(a) : "memory"); return v; }
__device__ __forceinline__ void sts16(uint32_t a, uint32_t v) { asm volatile("st.shared.u16 [%0], %1;" :: "r"(a), "r"(v) : "memory"); }
__device__ __forceinline__ void sts32(uint32_t a, uint32_t v) { asm volatile("st.shared.u32 [%0], %1;" :: "r"(a), "r"(v) : "memory"); }
__device__ __forceinline__ void sts64(uint32_t a, uint32_t x, uint32_t y) { asm volatile("st.shared.v2.u32 [%0], {%1,%2};" :: "r"(a), "r"(x), "r"(y) : "memory"); }
__device__ __forceinline__ void sts128(uint32_t a, uint32_t x, uint32_t y, uint32_t z, uint32_t w) { asm volatile("st.shared.v4.u32 [%0], {%1,%2,%3,%4};" :: "r"(a), "r"(x), "r"(y), "r"(z), "r"(w) : "memory"); }
__device__ __forceinline__ void ldsm4t(uint32_t (&r)[4], uint32_t a) { asm volatile("ldmatrix.sync.aligned.m8n8.x4.trans.shared.b16 {%0,%1,%2,%3}, [%4];" : "=r"(r[0]), "=r"(r[1]), "=r"(r[2]), "=r"(r[3]) : "r"(a) : "memory"); }
__device__ __forceinline__ void ldsm2t(uint32_t& r0, uint32_t& r1, uint32_t a) { asm volatile("ldmatrix.sync.aligned.m8n8.x2.trans.shared.b16 {%0,%1}, [%2];" : "=r"(r0), "=r"(r1) : "r"(a) : "memory"); }
__device__ __forceinline__ void ldsm4(uint32_t (&r)[4], uint32_t a) { asm volatile("ldmatrix.sync.aligned.m8n8.x4.shared.b16 {%0,%1,%2,%3}, [%4];" : "=r"(r[0]), "=r"(r[1]), "=r"(r[2]), "=r"(r[3]) : "r"(a) : "memory"); }
__device__ __forceinline__ void stsm4(uint32_t a, const uint32_t (&r)[4]) { asm volatile("stmatrix.sync.aligned.m8n8.x4.shared.b16 [%0], {%1,%2,%3,%4};" :: "r"(a), "r"(r[0]), "r"(r[1]), "r"(r[2]), "r"(r[3]) : "memory"); }
__device__ __forceinline__ uint32_t pack(float lo, float hi) { uint32_t r; asm("cvt.rn.bf16x2.f32 %0, %1, %2;" : "=r"(r) : "f"(hi), "f"(lo)); return r; }
__device__ __forceinline__ float blo(uint32_t v) { return __uint_as_float(v << 16); }
__device__ __forceinline__ float bhi(uint32_t v) { return __uint_as_float(v & 0xffff0000u); }
__device__ __forceinline__ float bf16r(float x) { return blo(pack(x, 0.f)); }
__device__ __forceinline__ uint32_t hmul2(uint32_t a, uint32_t b) { uint32_t r; asm("mul.rn.bf16x2 %0, %1, %2;" : "=r"(r) : "r"(a), "r"(b)); return r; }
__device__ __forceinline__ uint32_t hadd2(uint32_t a, uint32_t b) { uint32_t r; asm("add.rn.bf16x2 %0, %1, %2;" : "=r"(r) : "r"(a), "r"(b)); return r; }
__device__ __forceinline__ uint32_t prmt(uint32_t a, uint32_t b, uint32_t s) { return __byte_perm(a, b, s); }
__device__ __forceinline__ float ldbf(const __nv_bfloat16* p) { return blo((uint32_t)__ldg((const unsigned short*)p)); }
__device__ __forceinline__ uint32_t sum4(uint32_t a, uint32_t b, uint32_t c, uint32_t d) {
  return pack((blo(a) + blo(b)) + (blo(c) + blo(d)), (bhi(a) + bhi(b)) + (bhi(c) + bhi(d)));
}
__device__ __forceinline__ void mma16816(float (&c)[4], const uint32_t (&a)[4], uint32_t b0, uint32_t b1) {
  asm volatile("mma.sync.aligned.m16n8k16.row.col.f32.bf16.bf16.f32 {%0,%1,%2,%3}, {%4,%5,%6,%7}, {%8,%9}, {%0,%1,%2,%3};"
               : "+f"(c[0]), "+f"(c[1]), "+f"(c[2]), "+f"(c[3]) : "r"(a[0]), "r"(a[1]), "r"(a[2]), "r"(a[3]), "r"(b0), "r"(b1));
}
__device__ __forceinline__ void bar_sync(int id, int n) { asm volatile("bar.sync %0, %1;" :: "r"(id), "r"(n) : "memory"); }
__device__ __forceinline__ void bar_arrive(int id, int n) { asm volatile("bar.arrive %0, %1;" :: "r"(id), "r"(n) : "memory"); }
__device__ __forceinline__ void cluster_arrive() { asm volatile("barrier.cluster.arrive.relaxed.aligned;" ::: "memory"); }
__device__ __forceinline__ void cluster_wait() { asm volatile("barrier.cluster.wait.aligned;" ::: "memory"); }
__device__ __forceinline__ void fence_async() { asm volatile("fence.proxy.async.shared::cta;" ::: "memory"); }
__device__ __forceinline__ void fence_mbinit() { asm volatile("fence.mbarrier_init.release.cluster;" ::: "memory"); }
__device__ __forceinline__ uint32_t mapa(uint32_t a, uint32_t rank) { uint32_t r; asm("mapa.shared::cluster.u32 %0, %1, %2;" : "=r"(r) : "r"(a), "r"(rank)); return r; }
__device__ __forceinline__ void st_async4(uint32_t a, uint32_t x, uint32_t y, uint32_t z, uint32_t w, uint32_t mbar) {
  asm volatile("st.async.weak.shared::cluster.mbarrier::complete_tx::bytes.v4.b32 [%0], {%1,%2,%3,%4}, [%5];"
               :: "r"(a), "r"(x), "r"(y), "r"(z), "r"(w), "r"(mbar) : "memory");
}
__device__ __forceinline__ void mbar_init(uint32_t m, uint32_t cnt) { asm volatile("mbarrier.init.shared::cta.b64 [%0], %1;" :: "r"(m), "r"(cnt) : "memory"); }
__device__ __forceinline__ void mbar_expect(uint32_t m, uint32_t bytes) { asm volatile("mbarrier.arrive.expect_tx.shared::cta.b64 _, [%0], %1;" :: "r"(m), "r"(bytes) : "memory"); }
__device__ __forceinline__ void mbar_arrive(uint32_t m) { asm volatile("mbarrier.arrive.shared::cta.b64 _, [%0];" :: "r"(m) : "memory"); }
__device__ __forceinline__ void mbar_wait(uint32_t m) {
  uint32_t done;
  int it = 0;
  do {
    asm volatile("{.reg .pred p; mbarrier.try_wait.parity.shared::cta.b64 p, [%1], 0; selp.u32 %0, 1, 0, p;}" : "=r"(done) : "r"(m) : "memory");
    if (++it > (1 << 22)) __trap();
  } while (!done);
}
__device__ __forceinline__ void tma_load4(uint32_t dst, const CUtensorMap* tm, int c0, int c3, uint32_t mbar) {
  asm volatile("cp.async.bulk.tensor.4d.shared::cluster.global.mbarrier::complete_tx::bytes [%0], [%1, {%3, %4, %4, %5}], [%2];"
               :: "r"(dst), "l"(tm), "r"(mbar), "r"(c0), "r"(0), "r"(c3) : "memory");
}
__device__ __forceinline__ void tma_store4(const CUtensorMap* tm, int c0, int c3, uint32_t src) {
  asm volatile("cp.async.bulk.tensor.4d.global.shared::cta.bulk_group [%0, {%2, %3, %3, %4}], [%1];"
               :: "l"(tm), "r"(src), "r"(c0), "r"(0), "r"(c3) : "memory");
}
__device__ __forceinline__ void bulk_load(uint32_t dst, const void* src, uint32_t bytes, uint32_t mbar) {
  asm volatile("cp.async.bulk.shared::cluster.global.mbarrier::complete_tx::bytes [%0], [%1], %2, [%3];"
               :: "r"(dst), "l"(src), "r"(bytes), "r"(mbar) : "memory");
}
__device__ __forceinline__ void wg_fence() { asm volatile("wgmma.fence.sync.aligned;" ::: "memory"); }
__device__ __forceinline__ void wg_commit() { asm volatile("wgmma.commit_group.sync.aligned;" ::: "memory"); }
template <int N> __device__ __forceinline__ void wg_wait() { asm volatile("wgmma.wait_group.sync.aligned %0;" :: "n"(N) : "memory"); }
#define WG_REGS "{%0,%1,%2,%3,%4,%5,%6,%7,%8,%9,%10,%11,%12,%13,%14,%15}, {%16,%17,%18,%19}, %20, "
__device__ __forceinline__ void wgmma32_acc(float* d, const uint32_t* a, uint64_t db) {
  asm volatile("wgmma.mma_async.sync.aligned.m64n32k16.f32.bf16.bf16 " WG_REGS "1, 1, 1, 0;"
               : "+f"(d[0]), "+f"(d[1]), "+f"(d[2]), "+f"(d[3]), "+f"(d[4]), "+f"(d[5]), "+f"(d[6]), "+f"(d[7]),
                 "+f"(d[8]), "+f"(d[9]), "+f"(d[10]), "+f"(d[11]), "+f"(d[12]), "+f"(d[13]), "+f"(d[14]), "+f"(d[15])
               : "r"(a[0]), "r"(a[1]), "r"(a[2]), "r"(a[3]), "l"(db));
}
__device__ __forceinline__ void wgmma32_set(float* d, const uint32_t* a, uint64_t db) {
  asm volatile("wgmma.mma_async.sync.aligned.m64n32k16.f32.bf16.bf16 " WG_REGS "0, 1, 1, 0;"
               : "=f"(d[0]), "=f"(d[1]), "=f"(d[2]), "=f"(d[3]), "=f"(d[4]), "=f"(d[5]), "=f"(d[6]), "=f"(d[7]),
                 "=f"(d[8]), "=f"(d[9]), "=f"(d[10]), "=f"(d[11]), "=f"(d[12]), "=f"(d[13]), "=f"(d[14]), "=f"(d[15])
               : "r"(a[0]), "r"(a[1]), "r"(a[2]), "r"(a[3]), "l"(db));
}

__device__ __forceinline__ void tie(float& x) { asm volatile("" : "+f"(x) :: "memory"); }
__device__ __forceinline__ constexpr int aoff(int k) { return 256 * (k >> 2) + ((k & 3) == 0 ? 16 : (k & 3) == 1 ? 144 : (k & 3) == 2 ? 0 : 128); }
template <int ES, int E0, int E1>
__device__ __forceinline__ void epi_tiles(float (&E)[32], float& cy0, float& cy1, uint32_t pw) {
#pragma unroll
  for (int e = E0; e < E1; e++) {
    tie(E[4 * e]); tie(E[4 * e + 1]); tie(E[4 * e + 2]); tie(E[4 * e + 3]);
    float v0 = E[4 * e], v1 = E[4 * e + 1];
    if (e > 0) { v0 += E[4 * e - 2]; v1 += E[4 * e - 1]; } else if (ES > 0) { v0 += cy0; v1 += cy1; }
    sts32(pw + 16 * (8 * ES + e), pack(v0, v1));
    if (e == 7) { cy0 = E[30]; cy1 = E[31]; }
  }
}
template <int S, int MQ, int L0, int L1, int ES, int E0, int E1>
__device__ __forceinline__ void block(float (&acc)[32], const uint32_t (&Q)[16], uint64_t db, uint32_t (&LQ)[16], uint32_t la,
                                      float (&E)[32], float& cy0, float& cy1, uint32_t pw) {
  wg_fence();
#pragma unroll
  for (int mm = 0; mm < 4; mm++) {
#pragma unroll
    for (int jj = 1; jj >= 0; jj--) {
      const int m = 4 * MQ + mm, j = 2 * S + jj;
      if (m < 2 * (j + 1)) {
        if (m == 0) wgmma32_set(acc + 16 * jj, Q + 4 * mm, db + (uint64_t)(16 + 32 * j - 16 * m));
        else wgmma32_acc(acc + 16 * jj, Q + 4 * mm, db + (uint64_t)(16 + 32 * j - 16 * m));
      }
    }
  }
  wg_commit();
  wg_wait<1>();
#pragma unroll
  for (int l = L0; l < L1; l++) LQ[l] = lds32(la + aoff(l));
  epi_tiles<ES, E0, E1>(E, cy0, cy1, pw);
}

template <int KS> __device__ __forceinline__ void kgen_mma(float (&c)[12], uint64_t da) {
  asm volatile("{.reg .b64 da, db; add.s64 da, %12, %13; add.s64 db, %12, %14;\n"
               "wgmma.mma_async.sync.aligned.m64n24k16.f32.bf16.bf16 {%0,%1,%2,%3,%4,%5,%6,%7,%8,%9,%10,%11}, da, db, %15, 1, 1, 1, 1;}"
               : "+f"(c[0]), "+f"(c[1]), "+f"(c[2]), "+f"(c[3]), "+f"(c[4]), "+f"(c[5]), "+f"(c[6]), "+f"(c[7]), "+f"(c[8]), "+f"(c[9]), "+f"(c[10]), "+f"(c[11])
               : "l"(da), "n"(8 * KS), "n"(8 * KS + 512), "n"(KS ? 1 : 0));
  if constexpr (KS < 15) kgen_mma<KS + 1>(c, da);
}
struct cf { float x, y; };
__device__ __forceinline__ cf cmul(cf a, cf b) { cf r; r.x = fmaf(a.x, b.x, -a.y * b.y); r.y = fmaf(a.x, b.y, a.y * b.x); return r; }
__device__ __forceinline__ cf cexp_p(float lr2, float lt, float p) {
  float m = exp2f(lr2 * p);
  float t = lt * p;
  t = (t - rintf(t)) * 6.283185307179586f;
  cf r; r.x = m * __cosf(t); r.y = m * __sinf(t); return r;
}
__device__ __forceinline__ void store8(uint32_t a, const cf (&v)[8]) {
  sts128(a, pack(v[0].x, v[1].x), pack(v[2].x, v[3].x), pack(v[4].x, v[5].x), pack(v[6].x, v[7].x));
  sts128(a + KTAB / 2, pack(v[0].y, v[1].y), pack(v[2].y, v[3].y), pack(v[4].y, v[5].y), pack(v[6].y, v[7].y));
}
__device__ __forceinline__ float sigmoidf_(float s) { return 1.f / (1.f + __expf(-s)); }

__global__ void __cluster_dims__(CS, 1, 1) __launch_bounds__(NTHREADS, 1) fused_kernel(const __grid_constant__ Params p) {
  extern __shared__ __align__(1024) uint8_t smem[];
  TL_INIT();
  TL(31);
  const uint32_t sb = (uint32_t)__cvta_generic_to_shared(smem);
  const uint32_t mb = sb + OFF_MB;
  const int wg = __shfl_sync(0xffffffffu, threadIdx.x >> 7, 0);
  const int tid = threadIdx.x & 127, w = __shfl_sync(0xffffffffu, tid >> 5, 0), lane = tid & 31, g = lane >> 2, t = lane & 3;
  const int cl = blockIdx.x >> 3, rank = blockIdx.x & 7;
  const int ch0 = cl * CPC;
  const int nu = min(5, (DCH - ch0) >> 3);

  if (lane == 0) {
    if (wg == 2) {
      if (w < 2) {
        mbar_init(mb + 8 * (MB_XQ + w), 1);
        mbar_expect(mb + 8 * (MB_XQ + w), 10240);
        tma_load4(sb + OFF_TQ + 10240 * w, &p.tq, ch0, 8 * rank + 4 * w, mb + 8 * (MB_XQ + w));
        TL(20);
      } else {
        mbar_init(mb + 8 * (MB_XQ + w), 1);
        mbar_expect(mb + 8 * (MB_XQ + w), w == 2 ? 23040 + 20480 : 5 * HPITCH);
      }
    } else {
      const int b = 2 * (4 * wg + w);
      mbar_init(mb + 8 * b, 1);
      mbar_init(mb + 8 * b + 8, b + 1 == MB_HRDY ? 4 : 1);
      mbar_expect(mb + 8 * b, b >= MB_Y ? 8192 : 4096);
      if (b + 1 != MB_HRDY) mbar_expect(mb + 8 * b + 8, b + 1 >= MB_Y ? 8192 : 4096);
    }
    fence_mbinit();
  }
  __syncwarp();
  cluster_arrive();
  const int uk0 = wg, uk1 = wg ? wg + 2 : 9;
  float pla[2], pai[2], pcr[2], pci[2], pdt[2], pds[2];
#pragma unroll
  for (int r = 0; r < 2; r++) {
    const int u = r ? uk1 : uk0;
    const int ch = (u < nu) ? ch0 + 8 * u + rank : 0;
    pla[r] = ldbf(p.logA + ch * NMODE + tid);
    pai[r] = ldbf(p.Aim + ch * NMODE + tid);
    pcr[r] = ldbf(p.Cre + ch * NMODE + tid);
    pci[r] = ldbf(p.Cim + ch * NMODE + tid);
    pdt[r] = ldbf(p.logdt + ch + (lane >> 5));
    pds[r] = ldbf(p.Dskip + ch + (lane >> 5));
  }
  uint2 swv = make_uint2(0, 0);
  uint32_t gwv = 0;
  float dval = 0.f;
  if (wg == 2) {
    if (tid < 40 && ch0 + tid < DCH) { swv = __ldg((const uint2*)(p.shift_k + (size_t)(ch0 + tid) * 4)); gwv = __ldg((const unsigned short*)(p.gate_w + ch0 + tid)); }
    if (tid < nu) dval = ldbf(p.ssm_D + ch0 + 8 * tid + rank);
  } else if (wg == 0 && tid < 85) {
    sts128(sb + OFF_UX + (tid / 17) * UPITCH + (tid % 17) * 16, 0, 0, 0, 0);
  }
  uint32_t kid[9];
#pragma unroll
  for (int i = 0; i < 9; i++) {
    const int l = 8 * tid + i;
    kid[i] = pack((float)l, (float)(l + 1024)) - 0x42804280u;
    if (tid < 16) kid[i] = ((pack(128.f, (float)(l + 1024)) - 0x42804280u) & 0xffff0000u) | l;
    kid[i] *= 2;
  }
  TL(0);

  const uint32_t rbase = mapa(sb, g);
  const int mi = lane >> 3, tp = (lane & 7) >> 1, jj = lane & 1;
  const uint32_t toff = (4 * (7 - 2 * mi - jj) + tp) * 80;
  const uint32_t tab = sb + (wg == 0 ? OFF_PB : wg == 1 ? OFF_RAWA - 48 : OFF_HB4);
  const uint32_t kc = sb + OFF_KC + wg * 1408;
#pragma unroll 1
  for (int r = 0; r < 2; r++) {
    const int u = r ? uk1 : uk0;
    if (r == 0 && threadIdx.x == 320 && pla[0] != 12345.f) {
      tma_load4(sb + OFF_TK, &p.tk, ch0, 8 * rank - 1, mb + 8 * MB_KV);
      tma_load4(sb + OFF_TV, &p.tv, ch0, 8 * rank, mb + 8 * MB_KV);
    }
    __syncwarp();
    if (u < nu) {
      const float la = r ? pla[1] : pla[0], ai = r ? pai[1] : pai[0], cr = r ? pcr[1] : pcr[0], ci = r ? pci[1] : pci[0];
      const float dt = bf16r(expf(r ? pdt[1] : pdt[0]));
      const float lr2 = (-bf16r(expf(la)) * dt) * 1.4426950408889634f;
      const float lt = (ai * dt) * 0.15915494309189535f;
      const uint32_t row = tab + tid * 16;
      if (lr2 != 123.f) TL(16 + 4 * r + 6);
      {
        const cf w1 = cexp_p(lr2, lt, 8.f);
        cf v[8];
        v[0].x = 1.f; v[0].y = 0.f; v[1] = w1; v[2] = cmul(w1, w1); v[3] = cmul(v[2], w1);
        const cf w4 = cmul(v[2], v[2]);
        v[4] = w4; v[5] = cmul(v[1], w4); v[6] = cmul(v[2], w4); v[7] = cmul(v[3], w4);
        const cf w8 = cmul(w4, w4);
        store8(row, v);
#pragma unroll
        for (int c = 1; c < 4; c++) {
#pragma unroll
          for (int i = 0; i < 8; i++) v[i] = (c == 1 && i == 0) ? w8 : cmul(v[i], w8);
          store8(row + 2048 * c, v);
        }
      }
      {
        cf z1 = cexp_p(lr2, lt, 1.f), Z = cexp_p(lr2, lt, 256.f);
        z1.y = -z1.y; Z.y = -Z.y;
        const cf z2 = cmul(z1, z1);
        cf h[8], v[8];
        h[0].x = 2.f * cr * dt; h[0].y = -2.f * ci * dt;
        h[1] = cmul(h[0], z1);
#pragma unroll
        for (int i = 2; i < 8; i++) h[i] = cmul(h[i - 2], z2);
        store8(row + 4 * 2048, h);
        v[0] = cmul(h[0], Z); v[1] = cmul(h[2], Z); v[2] = cmul(h[4], Z); v[3] = cmul(h[6], Z);
        v[4] = cmul(v[0], Z); v[5] = cmul(v[2], Z); v[6] = cmul(v[4], Z); v[7] = cmul(v[5], Z);
        store8(row + 5 * 2048, v);
        const cf Z2 = cmul(Z, Z);
        h[0] = cmul(v[4], Z2); h[1] = cmul(v[6], Z2); h[2] = cmul(h[0], Z2); h[3] = cmul(h[1], Z2); h[4] = cmul(h[2], Z2);
        h[5].x = h[5].y = h[6].x = h[6].y = h[7].x = h[7].y = 0.f;
        store8(row + 6 * 2048, h);
      }
    }
    TL(16 + 4 * r + 7);
    if (u < nu) {
      fence_async();
      bar_sync(NB_WG0 + wg, 128);
    }
    if (r == 0) {
      cluster_wait();
      if (wg) mbar_wait(mb + 8 * (MB_XQ + wg - 1));
      TL(13);
    }
    float c[12];
    const uint64_t da = (uint64_t)((tab & 0x3FFFF) >> 4) | ((uint64_t)(KTAB / 32) << 16) | (128ull << 32);
    uint32_t xr[5][4];
    const int ah = 4 * (wg - 1) + w;
    if (r == 0 && wg) {
#pragma unroll
      for (int k = 0; k < 5; k++) ldsm4t(xr[k], sb + OFF_TQ + ah * 2560 + toff + 16 * k);
      st_async4(rbase + OFF_UX + UPAD + 16 * (32 * rank + 4 * ah + t), xr[0][0], xr[0][1], xr[0][2], xr[0][3], rbase + OFF_MB + 8 * MB_UX);
    }
    wg_fence();
    kgen_mma<0>(c, da);
    wg_commit();
    if (r == 0 && wg) {
#pragma unroll
      for (int k = 1; k < 5; k++)
        if (k < nu) st_async4(rbase + OFF_UX + k * UPITCH + UPAD + 16 * (32 * rank + 4 * ah + t), xr[k][0], xr[k][1], xr[k][2], xr[k][3], rbase + OFF_MB + 8 * (MB_UX + k));
      TL(15);
    }
    wg_wait<0>();
    if (u < nu) {
      if (tid == 0) c[0] += r ? pds[1] : pds[0];
      if (w < 2) {
#pragma unroll
        for (int hh = 0; hh < 2; hh++) {
          const int a = 16 * w + g + 8 * hh;
          sts32(kc + 4 * (4 * a + t), pack(c[2 * hh], c[2 * hh + 1]));
          sts32(kc + 4 * (t < 2 ? 128 + 2 * a + t : 128 + 32 * t + a), pack(c[4 + 2 * hh], c[5 + 2 * hh]));
          if (t < 3) {
            const uint32_t p0 = pack(c[8 + 2 * hh], c[9 + 2 * hh]);
            sts16(kc + 2 * (512 + 64 * t + a), p0);
            sts16(kc + 2 * (544 + 64 * t + a), p0 >> 16);
          }
        }
      }
      TL(16 + 4 * r + 8);
      bar_sync(NB_WG0 + wg, 128);
      const uint32_t hs = sb + (r ? (wg == 1 ? OFF_HB3 : OFF_HB4) : OFF_HB + u * 2 * HPITCH);
      uint32_t v[2][9];
#pragma unroll
      for (int cc = 0; cc < 2; cc++)
#pragma unroll
        for (int i = 0; i < 9; i++) v[cc][i] = lds16(kc + (cc ? kid[i] >> 16 : kid[i] & 0xffffu));
#pragma unroll
      for (int cc = 0; cc < 2; cc++) {
        const uint32_t o = hs + 16 + 16 * (tid + 128 * cc);
        sts128(o + HPITCH, prmt(v[cc][0], v[cc][1], 0x5410), prmt(v[cc][2], v[cc][3], 0x5410), prmt(v[cc][4], v[cc][5], 0x5410), prmt(v[cc][6], v[cc][7], 0x5410));
        sts128(o, prmt(v[cc][1], v[cc][2], 0x5410), prmt(v[cc][3], v[cc][4], 0x5410), prmt(v[cc][5], v[cc][6], 0x5410), prmt(v[cc][7], v[cc][8], 0x5410));
      }
      if (tid == 0) { sts128(hs + HPITCH, 0, 0, 0, 0); sts128(hs, 0, 0, 0, v[0][0] << 16); }
      if (wg == 2) bar_arrive(NB_HB2 + r, 256);
    }
    TL(1 + r);
    if (wg == 0) break;
  }

  if (wg < 2) {
    if (wg == 0) {
      if (tid < 64) sts128(sb + OFF_PB + tid * 528, 0, 0, 0, 0);
      bar_arrive(NB_PB1, 256);
    } else {
      if (tid == 0) {
        asm volatile("cp.async.bulk.tensor.4d.shared::cluster.global.mbarrier::complete_tx::bytes [%0], [%1, {%3, %4, %5, %6}], [%2];"
                     :: "r"(sb + OFF_RAWA - 48), "l"(&p.th), "r"(mb + 8 * MB_HA), "r"(0), "r"(-1), "r"(5 * cl), "r"(rank) : "memory");
      }
      __syncwarp();
      bar_sync(NB_PB1, 256);
    }
    cluster_arrive();
    bar_sync(NB_WG0 + wg, 128);
    const uint32_t haoff = 4 * (8 * w + ((g + 1) >> 1) + t);
    const uint32_t pw = sb + OFF_PB + wg * PBSZ + 4 * ((w * 8 + g) * 132 + t + w);
    const uint32_t pr = sb + OFF_PB + wg * PBSZ + w * 1056 + lane * 16;
    uint32_t ha = sb + OFF_HB + (2 * wg + (g & 1)) * HPITCH + haoff;
    uint32_t Q0[16], Q1[16], Q2[16], Q3[16];
    float X[32], Y[32], Z[32], cy0 = 0.f, cy1 = 0.f;
#pragma unroll
    for (int l = 0; l < 16; l++) Q0[l] = lds32(ha + aoff(l));
#pragma unroll
    for (int l = 0; l < 8; l++) Q1[l] = lds32(ha + 1024 + aoff(l));
    mbar_wait(mb + 8 * (MB_UX + wg));
    fence_async();
#pragma unroll 1
    for (int i = wg; i < 2 * nu; i += 2) {
      const bool isA = i >= nu;
      const int u = isA ? i - nu : i;
      const uint32_t ub = sb + (isA ? OFF_UKV : OFF_UX) + u * UPITCH;
      const uint64_t db = (uint64_t)((ub & 0x3FFFF) >> 4) | (1ull << 16) | (8ull << 32);
      TL(3 + (i >> 1));
      block<0, 0, 8, 16, 0, 0, 0>(X, Q0, db, Q1, ha + 1024, Z, cy0, cy1, pw);
      bar_sync(NB_WG0 + wg, 128);
      block<1, 0, 0, 5, 0, 0, 4>(Y, Q0, db, Q2, ha + 2048, X, cy0, cy1, pw);
      block<1, 1, 5, 10, 0, 4, 8>(Y, Q1, db, Q2, ha + 2048, X, cy0, cy1, pw);
      block<2, 0, 10, 16, 1, 0, 3>(X, Q0, db, Q2, ha + 2048, Y, cy0, cy1, pw);
      block<2, 1, 0, 6, 1, 3, 6>(X, Q1, db, Q3, ha + 3072, Y, cy0, cy1, pw);
      block<2, 2, 6, 11, 1, 6, 8>(X, Q2, db, Q3, ha + 3072, Y, cy0, cy1, pw);
      block<3, 0, 11, 16, 2, 0, 4>(Z, Q0, db, Q3, ha + 3072, X, cy0, cy1, pw);
      const int n = i + 2;
      if (!isA && (n > 2 || n >= nu) && i <= 2) bar_arrive(NB_HBFREE, 384);
      if (n < nu) {
        if (wg == 0) bar_sync(n == 2 ? NB_HB2 : NB_HB4, 256);
        ha = sb + (n == 2 ? OFF_HB + 4 * HPITCH : n == 3 ? OFF_HB3 : OFF_HB4) + (g & 1) * HPITCH + haoff;
      } else if (n < 2 * nu) {
        mbar_wait(mb + 8 * MB_HRDY);
        ha = sb + ((g & 1) ? OFF_RAWA : OFF_HB) + (n - nu) * HPITCH + haoff;
      }
      block<3, 1, 0, 8, 2, 4, 6>(Z, Q1, db, Q0, ha, X, cy0, cy1, pw);
      block<3, 2, 8, 16, 2, 6, 8>(Z, Q2, db, Q0, ha, X, cy0, cy1, pw);
      block<3, 3, 0, 8, 0, 0, 0>(Z, Q3, db, Q1, ha + 1024, X, cy0, cy1, pw);
      wg_wait<0>();
      epi_tiles<3, 0, 8>(Z, cy0, cy1, pw);
      if (!isA) {
        if (i == wg) {
          for (int k = n; k < nu; k += 2) mbar_wait(mb + 8 * (MB_UX + k));
        }
        if (n >= nu) {
          for (int k = 0; k < nu; k++) mbar_wait(mb + 8 * (MB_UKV + k));
        }
        if (i == wg || n >= nu) fence_async();
      }
      bar_sync(NB_WG0 + wg, 128);
      uint4 pa[4], pb[4];
#pragma unroll
      for (int k = 0; k < 4; k++) { pa[k] = lds128(pr + k * 4224); pb[k] = lds128(pr + k * 4224 + 528); }
      const uint32_t yd = rbase + (isA ? OFF_YA : OFF_YB) + (8 * u + rank) * YPITCH + (8 * w + t) * 16;
      const uint32_t ym = rbase + OFF_MB + 8 * (MB_Y + u);
      st_async4(yd, sum4(pa[0].x, pa[1].x, pa[2].x, pa[3].x), sum4(pa[0].y, pa[1].y, pa[2].y, pa[3].y),
                sum4(pb[0].x, pb[1].x, pb[2].x, pb[3].x), sum4(pb[0].y, pb[1].y, pb[2].y, pb[3].y), ym);
      st_async4(yd + 64, sum4(pa[0].z, pa[1].z, pa[2].z, pa[3].z), sum4(pa[0].w, pa[1].w, pa[2].w, pa[3].w),
                sum4(pb[0].z, pb[1].z, pb[2].z, pb[3].z), sum4(pb[0].w, pb[1].w, pb[2].w, pb[3].w), ym);
      TL(8 + (i >> 1));
    }
    TL_DUMP();
  } else {
    if (tid < 40) { sts64(sb + OFF_SW + 8 * tid, swv.x, swv.y); sts16(sb + OFF_GW + 2 * tid, gwv); }
    else if (tid < 40 + 85) sts128(sb + OFF_UKV + ((tid - 40) / 17) * UPITCH + ((tid - 40) % 17) * 16, 0, 0, 0, 0);
    __syncwarp();
    cluster_arrive();
    bar_sync(NB_WG0 + 2, 128);
    mbar_wait(mb + 8 * MB_XQ);
    mbar_wait(mb + 8 * (MB_XQ + 1));
    {
      float s0 = 0.f, s1 = 0.f;
#pragma unroll
      for (int j = 0; j < 5; j++) {
        const uint4 gw = lds128(sb + OFF_GW + 16 * j);
        const uint4 x0 = lds128(sb + OFF_TQ + tid * 80 + 16 * j), x1 = lds128(sb + OFF_TQ + (tid + 128) * 80 + 16 * j);
        uint32_t m0 = hmul2(x0.x, gw.x), m1 = hmul2(x0.y, gw.y), m2 = hmul2(x0.z, gw.z), m3 = hmul2(x0.w, gw.w);
        s0 += ((blo(m0) + bhi(m0)) + (blo(m1) + bhi(m1))) + ((blo(m2) + bhi(m2)) + (blo(m3) + bhi(m3)));
        m0 = hmul2(x1.x, gw.x); m1 = hmul2(x1.y, gw.y); m2 = hmul2(x1.z, gw.z); m3 = hmul2(x1.w, gw.w);
        s1 += ((blo(m0) + bhi(m0)) + (blo(m1) + bhi(m1))) + ((blo(m2) + bhi(m2)) + (blo(m3) + bhi(m3)));
      }
      __stcg(&g_part[cl * SEQ + rank * 256 + tid], s0);
      __stcg(&g_part[cl * SEQ + rank * 256 + 128 + tid], s1);
    }
    TL(3);
    cluster_wait();
    mbar_wait(mb + 8 * MB_KV);
    TL(4);
    const uint32_t hoff = (4 * (7 - 2 * (mi & 1) - jj) + ((tp + 3) & 3)) * 80 + (tp ? 2560 : 0);
#pragma unroll 1
    for (int u = 0; u < nu; u++) {
      const uint2 sw = lds64(sb + OFF_SW + 8 * (8 * u + g));
      uint32_t E[2][6], V[2][4];
#pragma unroll
      for (int hf = 0; hf < 2; hf++) {
        const int ah = 4 * hf + w;
        uint32_t K[4];
        ldsm4t(K, sb + OFF_TK + (ah + 1) * 2560 + toff + 16 * u);
        ldsm2t(E[hf][4], E[hf][5], sb + OFF_TK + ah * 2560 + hoff + 16 * u);
        ldsm4t(V[hf], sb + OFF_TV + ah * 2560 + toff + 16 * u);
        E[hf][0] = K[0]; E[hf][1] = K[1]; E[hf][2] = K[2]; E[hf][3] = K[3];
      }
      const uint32_t w0 = prmt(sw.x, 0, 0x1010), w1 = prmt(sw.x, 0, 0x3232), w2 = prmt(sw.y, 0, 0x1010), w3 = prmt(sw.y, 0, 0x3232);
#pragma unroll
      for (int hf = 0; hf < 2; hf++) {
        uint32_t O[5], o[4];
#pragma unroll
        for (int i = 0; i < 5; i++) O[i] = prmt(E[hf][i], E[hf][i + 1], 0x5432);
#pragma unroll
        for (int i = 0; i < 4; i++) {
          uint32_t s = hmul2(O[i + 1], w3);
          s = hadd2(s, hmul2(E[hf][i + 1], w2));
          s = hadd2(s, hmul2(O[i], w1));
          s = hadd2(s, hmul2(E[hf][i], w0));
          o[i] = hmul2(s, V[hf][i]);
        }
        st_async4(rbase + OFF_UKV + u * UPITCH + UPAD + 16 * (32 * rank + 16 * hf + 4 * w + t), o[0], o[1], o[2], o[3], rbase + OFF_MB + 8 * (MB_UKV + u));
      }
    }
    TL(5);
    mbar_wait(mb + 8 * MB_HA);
    bar_sync(NB_HBFREE, 384);
    TL(6);
    unsigned g_target = 0;
#pragma unroll 1
    for (int u = 0; u < nu; u++) {
      const uint32_t ra = sb + OFF_RAWA + u * HPITCH + 16 + 16 * tid;
      const uint4 x = lds128(ra), y = lds128(ra + 2048);
      const uint32_t xn = lds32(ra + 16), yn = lds32(ra + 2048 + 16);
      const uint32_t o = sb + OFF_HB + u * HPITCH + 16 + 16 * tid;
      sts128(o, prmt(x.x, x.y, 0x5432), prmt(x.y, x.z, 0x5432), prmt(x.z, x.w, 0x5432), prmt(x.w, xn, 0x5432));
      sts128(o + 2048, prmt(y.x, y.y, 0x5432), prmt(y.y, y.z, 0x5432), prmt(y.z, y.w, 0x5432), prmt(y.w, yn, 0x5432));
    }
    if (tid < nu) {
      const uint32_t ra = sb + OFF_RAWA + tid * HPITCH + 16;
      const uint32_t h0 = pack(blo(lds16(ra)) + dval, 0.f);
      sts16(ra, h0);
      sts128(sb + OFF_HB + tid * HPITCH, 0, 0, 0, h0 << 16);
    }
    __syncwarp();
    if (lane == 0) mbar_arrive(mb + 8 * MB_HRDY);
    TL(7);
    uint32_t okflag = 1;
    if (tid == 0) {
      __threadfence();
      const unsigned old = atomicAdd(&g_cnt[rank * 32], cl == 0 ? 16 - (NCL - 1) : 1);
      g_target = (old & ~15u) + 16;
      unsigned v;
      int it = 0;
      do {
        asm volatile("ld.acquire.gpu.global.u32 %0, [%1];" : "=r"(v) : "l"(&g_cnt[rank * 32]) : "memory");
      } while ((int)(v - g_target) < 0 && ++it < 20000);
      okflag = (int)(v - g_target) >= 0;
    }
    asm volatile("{.reg .pred p, q; setp.ne.u32 p, %1, 0; bar.red.and.pred q, %2, 128, p; selp.u32 %0, 1, 0, q;}" : "=r"(okflag) : "r"(okflag), "r"(NB_WG0 + 2) : "memory");
    {
      float s[2] = {0.f, 0.f};
      if (okflag) {
        float2 v[NCL];
#pragma unroll
        for (int c = 0; c < NCL; c++) v[c] = __ldcg((const float2*)&g_part[c * SEQ + rank * 256 + 2 * tid]);
#pragma unroll
        for (int c = 0; c < NCL; c++) { s[0] += v[c].x; s[1] += v[c].y; }
      } else {
#pragma unroll 1
        for (int hf = 0; hf < 2; hf++) {
          const int slot = 2 * tid + hf;
          const int row = rank * 256 + (slot & ~31) + 8 * (slot & 3) + ((slot >> 2) & 7);
          const uint32_t* xr = (const uint32_t*)(p.q + (size_t)row * DCH);
          const uint32_t* gr = (const uint32_t*)p.gate_w;
          float a = 0.f;
#pragma unroll 1
          for (int c = 0; c < DCH / 2; c++) { const uint32_t m = hmul2(__ldg(xr + c), __ldg(gr + c)); a += blo(m) + bhi(m); }
          if (hf) s[1] = a; else s[0] = a;
        }
      }
      const float g0 = bf16r(sigmoidf_(bf16r(s[0]))), g1 = bf16r(sigmoidf_(bf16r(s[1])));
      sts128(sb + OFF_KC + 16 * tid, pack(g0, g0), pack(1.f - g0, 1.f - g0), pack(g1, g1), pack(1.f - g1, 1.f - g1));
    }
    __syncwarp();
    uint2 gg[2][4];
#pragma unroll
    for (int hh = 0; hh < 2; hh++)
#pragma unroll
      for (int i = 0; i < 4; i++) gg[hh][i] = lds64(sb + OFF_KC + 8 * (64 * w + 32 * hh + 8 * i + g));
    TL(8);
#pragma unroll 1
    for (int u = 0; u < nu; u++) {
      uint32_t qv[2][4];
      const uint32_t qa = sb + OFF_TQ + (64 * w + lane) * 80 + 16 * u;
      ldsm4(qv[0], qa);
      ldsm4(qv[1], qa + 2560);
      mbar_wait(mb + 8 * (MB_Y + u));
      uint32_t ya[2][4], yb[2][4];
      const uint32_t yo = (8 * u + (lane & 7)) * YPITCH + (8 * mi + w) * 16;
#pragma unroll
      for (int hh = 0; hh < 2; hh++) { ldsm4t(ya[hh], sb + OFF_YA + yo + 64 * hh); ldsm4t(yb[hh], sb + OFF_YB + yo + 64 * hh); }
#pragma unroll
      for (int hh = 0; hh < 2; hh++) {
        uint32_t o[4];
#pragma unroll
        for (int i = 0; i < 4; i++) o[i] = hadd2(hmul2(gg[hh][i].x, hmul2(qv[hh][i], ya[hh][i])), hmul2(gg[hh][i].y, yb[hh][i]));
        stsm4(qa + 2560 * hh, o);
      }
      TL(9 + (u < 4 ? u : 8));
    }
    fence_async();
    __syncwarp();
    if (lane == 0) {
      tma_store4(&p.to, ch0, 8 * rank + 2 * w, sb + OFF_TQ + w * 5120);
      asm volatile("cp.async.bulk.commit_group;" ::: "memory");
      asm volatile("cp.async.bulk.wait_group.read 0;" ::: "memory");
    }
    TL(14);
    TL_DUMP();
  }
}

typedef CUresult (*EncodeFn)(CUtensorMap*, CUtensorMapDataType, cuuint32_t, void*, const cuuint64_t*, const cuuint64_t*,
                             const cuuint32_t*, const cuuint32_t*, CUtensorMapInterleave, CUtensorMapSwizzle,
                             CUtensorMapL2promotion, CUtensorMapFloatOOBfill);

void make_map(EncodeFn fn, CUtensorMap* tm, const void* ptr, int nhi) {
  cuuint64_t dims[4] = {DCH, 4, 8, SEQ / 32};
  cuuint64_t strides[3] = {8 * DCH * 2, DCH * 2, 32 * DCH * 2};
  cuuint32_t box[4] = {CPC, 4, 8, (cuuint32_t)nhi};
  cuuint32_t es[4] = {1, 1, 1, 1};
  fn(tm, CU_TENSOR_MAP_DATA_TYPE_BFLOAT16, 4, const_cast<void*>(ptr), dims, strides, box, es, CU_TENSOR_MAP_INTERLEAVE_NONE,
     CU_TENSOR_MAP_SWIZZLE_NONE, CU_TENSOR_MAP_L2_PROMOTION_L2_128B, CU_TENSOR_MAP_FLOAT_OOB_FILL_NONE);
}

}

extern "C" void kernel_launch(void* const* d_in, const int* in_sizes, int n_in, void* d_out, int out_size) {
  (void)in_sizes; (void)n_in; (void)out_size;
  static EncodeFn fn = nullptr;
  if (!fn) {
    cudaDriverEntryPointQueryResult qr;
    cudaGetDriverEntryPoint("cuTensorMapEncodeTiled", (void**)&fn, cudaEnableDefault, &qr);
    cudaFuncSetAttribute(fused_kernel, cudaFuncAttributeMaxDynamicSharedMemorySize, SMEM_BYTES);
  }
  Params p;
  make_map(fn, &p.tq, d_in[0], 4);
  make_map(fn, &p.tk, d_in[1], 9);
  make_map(fn, &p.tv, d_in[2], 8);
  {
    cuuint64_t dims[4] = {32, SEQ / 32, DCH / 8, 8};
    cuuint64_t strides[3] = {64, 8 * SEQ * 2, SEQ * 2};
    cuuint32_t box[4] = {32, 65, 5, 1};
    cuuint32_t es[4] = {1, 1, 1, 1};
    fn(&p.th, CU_TENSOR_MAP_DATA_TYPE_BFLOAT16, 4, d_in[4], dims, strides, box, es, CU_TENSOR_MAP_INTERLEAVE_NONE,
       CU_TENSOR_MAP_SWIZZLE_NONE, CU_TENSOR_MAP_L2_PROMOTION_L2_128B, CU_TENSOR_MAP_FLOAT_OOB_FILL_NONE);
  }
  make_map(fn, &p.to, d_out, 2);
  p.q = (const __nv_bfloat16*)d_in[0];
  p.shift_k = (const __nv_bfloat16*)d_in[3];
  p.ssm_k = (const __nv_bfloat16*)d_in[4];
  p.ssm_D = (const __nv_bfloat16*)d_in[5];
  p.logA = (const __nv_bfloat16*)d_in[7];
  p.Aim = (const __nv_bfloat16*)d_in[8];
  p.Cre = (const __nv_bfloat16*)d_in[9];
  p.Cim = (const __nv_bfloat16*)d_in[10];
  p.logdt = (const __nv_bfloat16*)d_in[11];
  p.Dskip = (const __nv_bfloat16*)d_in[12];
  p.gate_w = (const __nv_bfloat16*)d_in[13];
  fused_kernel<<<NCL * CS, NTHREADS, SMEM_BYTES, cudaStreamPerThread>>>(p);
}
```

```cpp
#include <cuda_runtime.h>
#include <cuda_bf16.h>
#include <cuda.h>
#include <stdint.h>

#define TIMELINE 0

namespace {

constexpr int SEQ = 2048, DCH = 576, NMODE = 128;
constexpr int CS = 8, CPC = 40, NCL = 15, NTHREADS = 384;

constexpr int UPITCH = 4368, UPAD = 272;
constexpr int HPITCH = 4160;
constexpr int PBSZ = 16896;
constexpr int YPITCH = 528;
constexpr int KTAB = 28672;
constexpr int OFF_TQ = 0;
constexpr int OFF_TK = 20480;
constexpr int OFF_YA = OFF_TK;
constexpr int OFF_TV = 43520;
constexpr int OFF_UX = 64000;
constexpr int OFF_RAWA = OFF_UX + 5 * UPITCH + 48 + 48;
constexpr int OFF_HB3 = OFF_RAWA + 5 * HPITCH - 32;
constexpr int OFF_HB = OFF_HB3 + 2 * HPITCH;
constexpr int OFF_PB = OFF_HB + 6 * HPITCH;
constexpr int OFF_YB = OFF_PB + 2 * PBSZ;
constexpr int OFF_HB4 = OFF_YB + 40 * YPITCH;
constexpr int OFF_UKV = OFF_HB4 + 2 * HPITCH;
constexpr int OFF_KC = OFF_UKV + 5 * UPITCH;
constexpr int OFF_SW = OFF_KC + 3 * 1408;
constexpr int OFF_GW = OFF_SW + 320;
constexpr int OFF_MB = OFF_GW + 80;
constexpr int OFF_TL = OFF_MB + 32 * 8;
constexpr int SMEM_BYTES = OFF_TL + (TIMELINE ? 1536 : 0);
static_assert(((OFF_RAWA - OFF_HB) & 63) == 32, "bank offset between raw/shift copies");
static_assert(KTAB + 2048 <= 2 * PBSZ && KTAB <= OFF_HB - (OFF_RAWA - 48) && KTAB <= OFF_KC - OFF_HB4, "ktab alias zones");
static_assert(SMEM_BYTES <= 232448, "smem");
static_assert(((OFF_RAWA - 48) & 127) == 0, "tma dst");
static_assert((OFF_RAWA & 15) == 0 && (OFF_PB & 15) == 0 && (OFF_HB & 15) == 0 && (OFF_MB & 7) == 0 && (OFF_KC & 15) == 0, "align");

enum { MB_UX = 0, MB_UKV = 5, MB_Y = 10, MB_HRDY = 15, MB_XQ = 16, MB_KV = 18, MB_HA = 19, MB_COUNT = 20 };
enum { NB_WG0 = 1, NB_HB2 = 4, NB_HB4 = 5, NB_HBFREE = 6, NB_PB1 = 7 };

struct Params {
  CUtensorMap tq, tk, tv, to, th;
  const __nv_bfloat16 *q, *shift_k, *ssm_k, *ssm_D, *logA, *Aim, *Cre, *Cim, *logdt, *Dskip, *gate_w;
};

__device__ float g_part[NCL * SEQ];
__device__ unsigned g_cnt[CS * 32];
#define TL(i) do {} while (0)
#define TL_INIT() do {} while (0)
#define TL_DUMP() do {} while (0)

__device__ __forceinline__ uint32_t lds32(uint32_t a) { uint32_t v; asm volatile("ld.shared.u32 %0, [%1];" : "=r"(v) : "r"(a) : "memory"); return v; }
__device__ __forceinline__ uint32_t lds16(uint32_t a) { uint32_t v; asm volatile("ld.shared.u16 %0, [%1];" : "=r"(v) : "r"(a) : "memory"); return v; }
__device__ __forceinline__ uint2 lds64(uint32_t a) { uint2 v; asm volatile("ld.shared.v2.u32 {%0,%1}, [%2];" : "=r"(v.x), "=r"(v.y) : "r"(a) : "memory"); return v; }
__device__ __forceinline__ uint4 lds128(uint32_t a) { uint4 v; asm volatile("ld.shared.v4.u32 {%0,%1,%2,%3}, [%4];" : "=r"(v.x), "=r"(v.y), "=r"(v.z), "=r"(v.w) : "r"(a) : "memory"); return v; }
__device__ __forceinline__ void sts16(uint32_t a, uint32_t v) { asm volatile("st.shared.u16 [%0], %1;" :: "r"(a), "r"(v) : "memory"); }
__device__ __forceinline__ void sts32(uint32_t a, uint32_t v) { asm volatile("st.shared.u32 [%0], %1;" :: "r"(a), "r"(v) : "memory"); }
__device__ __forceinline__ void sts64(uint32_t a, uint32_t x, uint32_t y) { asm volatile("st.shared.v2.u32 [%0], {%1,%2};" :: "r"(a), "r"(x), "r"(y) : "memory"); }
__device__ __forceinline__ void sts128(uint32_t a, uint32_t x, uint32_t y, uint32_t z, uint32_t w) { asm volatile("st.shared.v4.u32 [%0], {%1,%2,%3,%4};" :: "r"(a), "r"(x), "r"(y), "r"(z), "r"(w) : "memory"); }
__device__ __forceinline__ void ldsm4t(uint32_t (&r)[4], uint32_t a) { asm volatile("ldmatrix.sync.aligned.m8n8.x4.trans.shared.b16 {%0,%1,%2,%3}, [%4];" : "=r"(r[0]), "=r"(r[1]), "=r"(r[2]), "=r"(r[3]) : "r"(a) : "memory"); }
__device__ __forceinline__ void ldsm2t(uint32_t& r0, uint32_t& r1, uint32_t a) { asm volatile("ldmatrix.sync.aligned.m8n8.x2.trans.shared.b16 {%0,%1}, [%2];" : "=r"(r0), "=r"(r1) : "r"(a) : "memory"); }
__device__ __forceinline__ void ldsm4(uint32_t (&r)[4], uint32_t a) { asm volatile("ldmatrix.sync.aligned.m8n8.x4.shared.b16 {%0,%1,%2,%3}, [%4];" : "=r"(r[0]), "=r"(r[1]), "=r"(r[2]), "=r"(r[3]) : "r"(a) : "memory"); }
__device__ __forceinline__ void stsm4(uint32_t a, const uint32_t (&r)[4]) { asm volatile("stmatrix.sync.aligned.m8n8.x4.shared.b16 [%0], {%1,%2,%3,%4};" :: "r"(a), "r"(r[0]), "r"(r[1]), "r"(r[2]), "r"(r[3]) : "memory"); }
__device__ __forceinline__ uint32_t pack(float lo, float hi) { uint32_t r; asm("cvt.rn.bf16x2.f32 %0, %1, %2;" : "=r"(r) : "f"(hi), "f"(lo)); return r; }
__device__ __forceinline__ float blo(uint32_t v) { return __uint_as_float(v << 16); }
__device__ __forceinline__ float bhi(uint32_t v) { return __uint_as_float(v & 0xffff0000u); }
__device__ __forceinline__ float bf16r(float x) { return blo(pack(x, 0.f)); }
__device__ __forceinline__ uint32_t hmul2(uint32_t a, uint32_t b) { uint32_t r; asm("mul.rn.bf16x2 %0, %1, %2;" : "=r"(r) : "r"(a), "r"(b)); return r; }
__device__ __forceinline__ uint32_t hadd2(uint32_t a, uint32_t b) { uint32_t r; asm("add.rn.bf16x2 %0, %1, %2;" : "=r"(r) : "r"(a), "r"(b)); return r; }
__device__ __forceinline__ uint32_t prmt(uint32_t a, uint32_t b, uint32_t s) { return __byte_perm(a, b, s); }
__device__ __forceinline__ float ldbf(const __nv_bfloat16* p) { return blo((uint32_t)__ldg((const unsigned short*)p)); }
__device__ __forceinline__ uint32_t sum4(uint32_t a, uint32_t b, uint32_t c, uint32_t d) {
  return pack((blo(a) + blo(b)) + (blo(c) + blo(d)), (bhi(a) + bhi(b)) + (bhi(c) + bhi(d)));
}
__device__ __forceinline__ void mma16816(float (&c)[4], const uint32_t (&a)[4], uint32_t b0, uint32_t b1) {
  asm volatile("mma.sync.aligned.m16n8k16.row.col.f32.bf16.bf16.f32 {%0,%1,%2,%3}, {%4,%5,%6,%7}, {%8,%9}, {%0,%1,%2,%3};"
               : "+f"(c[0]), "+f"(c[1]), "+f"(c[2]), "+f"(c[3]) : "r"(a[0]), "r"(a[1]), "r"(a[2]), "r"(a[3]), "r"(b0), "r"(b1));
}
__device__ __forceinline__ void bar_sync(int id, int n) { asm volatile("bar.sync %0, %1;" :: "r"(id), "r"(n) : "memory"); }
__device__ __forceinline__ void bar_arrive(int id, int n) { asm volatile("bar.arrive %0, %1;" :: "r"(id), "r"(n) : "memory"); }
__device__ __forceinline__ void cluster_arrive() { asm volatile("barrier.cluster.arrive.relaxed.aligned;" ::: "memory"); }
__device__ __forceinline__ void cluster_wait() { asm volatile("barrier.cluster.wait.aligned;" ::: "memory"); }
__device__ __forceinline__ void fence_async() { asm volatile("fence.proxy.async.shared::cta;" ::: "memory"); }
__device__ __forceinline__ void fence_mbinit() { asm volatile("fence.mbarrier_init.release.cluster;" ::: "memory"); }
__device__ __forceinline__ uint32_t mapa(uint32_t a, uint32_t rank) { uint32_t r; asm("mapa.shared::cluster.u32 %0, %1, %2;" : "=r"(r) : "r"(a), "r"(rank)); return r; }
__device__ __forceinline__ void st_async4(uint32_t a, uint32_t x, uint32_t y, uint32_t z, uint32_t w, uint32_t mbar) {
  asm volatile("st.async.weak.shared::cluster.mbarrier::complete_tx::bytes.v4.b32 [%0], {%1,%2,%3,%4}, [%5];"
               :: "r"(a), "r"(x), "r"(y), "r"(z), "r"(w), "r"(mbar) : "memory");
}
__device__ __forceinline__ void mbar_init(uint32_t m, uint32_t cnt) { asm volatile("mbarrier.init.shared::cta.b64 [%0], %1;" :: "r"(m), "r"(cnt) : "memory"); }
__device__ __forceinline__ void mbar_expect(uint32_t m, uint32_t bytes) { asm volatile("mbarrier.arrive.expect_tx.shared::cta.b64 _, [%0], %1;" :: "r"(m), "r"(bytes) : "memory"); }
__device__ __forceinline__ void mbar_arrive(uint32_t m) { asm volatile("mbarrier.arrive.shared::cta.b64 _, [%0];" :: "r"(m) : "memory"); }
__device__ __forceinline__ void mbar_wait(uint32_t m) {
  uint32_t done;
  int it = 0;
  do {
    asm volatile("{.reg .pred p; mbarrier.try_wait.parity.shared::cta.b64 p, [%1], 0; selp.u32 %0, 1, 0, p;}" : "=r"(done) : "r"(m) : "memory");
    if (++it > (1 << 22)) __trap();
  } while (!done);
}
__device__ __forceinline__ void tma_load4(uint32_t dst, const CUtensorMap* tm, int c0, int c3, uint32_t mbar) {
  asm volatile("cp.async.bulk.tensor.4d.shared::cluster.global.mbarrier::complete_tx::bytes [%0], [%1, {%3, %4, %4, %5}], [%2];"
               :: "r"(dst), "l"(tm), "r"(mbar), "r"(c0), "r"(0), "r"(c3) : "memory");
}
__device__ __forceinline__ void tma_store4(const CUtensorMap* tm, int c0, int c3, uint32_t src) {
  asm volatile("cp.async.bulk.tensor.4d.global.shared::cta.bulk_group [%0, {%2, %3, %3, %4}], [%1];"
               :: "l"(tm), "r"(src), "r"(c0), "r"(0), "r"(c3) : "memory");
}
__device__ __forceinline__ void bulk_load(uint32_t dst, const void* src, uint32_t bytes, uint32_t mbar) {
  asm volatile("cp.async.bulk.shared::cluster.global.mbarrier::complete_tx::bytes [%0], [%1], %2, [%3];"
               :: "r"(dst), "l"(src), "r"(bytes), "r"(mbar) : "memory");
}
__device__ __forceinline__ void wg_fence() { asm volatile("wgmma.fence.sync.aligned;" ::: "memory"); }
__device__ __forceinline__ void wg_commit() { asm volatile("wgmma.commit_group.sync.aligned;" ::: "memory"); }
template <int N> __device__ __forceinline__ void wg_wait() { asm volatile("wgmma.wait_group.sync.aligned %0;" :: "n"(N) : "memory"); }
#define WG_REGS "{%0,%1,%2,%3,%4,%5,%6,%7,%8,%9,%10,%11,%12,%13,%14,%15}, {%16,%17,%18,%19}, %20, "
__device__ __forceinline__ void wgmma32_acc(float* d, const uint32_t* a, uint64_t db) {
  asm volatile("wgmma.mma_async.sync.aligned.m64n32k16.f32.bf16.bf16 " WG_REGS "1, 1, 1, 0;"
               : "+f"(d[0]), "+f"(d[1]), "+f"(d[2]), "+f"(d[3]), "+f"(d[4]), "+f"(d[5]), "+f"(d[6]), "+f"(d[7]),
                 "+f"(d[8]), "+f"(d[9]), "+f"(d[10]), "+f"(d[11]), "+f"(d[12]), "+f"(d[13]), "+f"(d[14]), "+f"(d[15])
               : "r"(a[0]), "r"(a[1]), "r"(a[2]), "r"(a[3]), "l"(db));
}
__device__ __forceinline__ void wgmma32_set(float* d, const uint32_t* a, uint64_t db) {
  asm volatile("wgmma.mma_async.sync.aligned.m64n32k16.f32.bf16.bf16 " WG_REGS "0, 1, 1, 0;"
               : "=f"(d[0]), "=f"(d[1]), "=f"(d[2]), "=f"(d[3]), "=f"(d[4]), "=f"(d[5]), "=f"(d[6]), "=f"(d[7]),
                 "=f"(d[8]), "=f"(d[9]), "=f"(d[10]), "=f"(d[11]), "=f"(d[12]), "=f"(d[13]), "=f"(d[14]), "=f"(d[15])
               : "r"(a[0]), "r"(a[1]), "r"(a[2]), "r"(a[3]), "l"(db));
}

__device__ __forceinline__ void tie(float& x) { asm volatile("" : "+f"(x) :: "memory"); }
__device__ __forceinline__ constexpr int aoff(int k) { return 256 * (k >> 2) + ((k & 3) == 0 ? 16 : (k & 3) == 1 ? 144 : (k & 3) == 2 ? 0 : 128); }
template <int ES, int E0, int E1>
__device__ __forceinline__ void epi_tiles(float (&E)[32], float& cy0, float& cy1, uint32_t pw) {
#pragma unroll
  for (int e = E0; e < E1; e++) {
    tie(E[4 * e]); tie(E[4 * e + 1]); tie(E[4 * e + 2]); tie(E[4 * e + 3]);
    float v0 = E[4 * e], v1 = E[4 * e + 1];
    if (e > 0) { v0 += E[4 * e - 2]; v1 += E[4 * e - 1]; } else if (ES > 0) { v0 += cy0; v1 += cy1; }
    sts32(pw + 16 * (8 * ES + e), pack(v0, v1));
    if (e == 7) { cy0 = E[30]; cy1 = E[31]; }
  }
}
template <int S, int MQ, int L0, int L1, int ES, int E0, int E1>
__device__ __forceinline__ void block(float (&acc)[32], const uint32_t (&Q)[16], uint64_t db, uint32_t (&LQ)[16], uint32_t la,
                                      float (&E)[32], float& cy0, float& cy1, uint32_t pw) {
  wg_fence();
#pragma unroll
  for (int mm = 0; mm < 4; mm++) {
#pragma unroll
    for (int jj = 1; jj >= 0; jj--) {
      const int m = 4 * MQ + mm, j = 2 * S + jj;
      if (m < 2 * (j + 1)) {
        if (m == 0) wgmma32_set(acc + 16 * jj, Q + 4 * mm, db + (uint64_t)(16 + 32 * j - 16 * m));
        else wgmma32_acc(acc + 16 * jj, Q + 4 * mm, db + (uint64_t)(16 + 32 * j - 16 * m));
      }
    }
  }
  wg_commit();
  wg_wait<1>();
#pragma unroll
  for (int l = L0; l < L1; l++) LQ[l] = lds32(la + aoff(l));
  epi_tiles<ES, E0, E1>(E, cy0, cy1, pw);
}

template <int KS> __device__ __forceinline__ void kgen_mma(float (&c)[12], uint64_t da) {
  asm volatile("{.reg .b64 da, db; add.s64 da, %12, %13; add.s64 db, %12, %14;\n"
               "wgmma.mma_async.sync.aligned.m64n24k16.f32.bf16.bf16 {%0,%1,%2,%3,%4,%5,%6,%7,%8,%9,%10,%11}, da, db, %15, 1, 1, 1, 1;}"
               : "+f"(c[0]), "+f"(c[1]), "+f"(c[2]), "+f"(c[3]), "+f"(c[4]), "+f"(c[5]), "+f"(c[6]), "+f"(c[7]), "+f"(c[8]), "+f"(c[9]), "+f"(c[10]), "+f"(c[11])
               : "l"(da), "n"(8 * KS), "n"(8 * KS + 512), "n"(KS ? 1 : 0));
  if constexpr (KS < 15) kgen_mma<KS + 1>(c, da);
}
struct cf { float x, y; };
__device__ __forceinline__ cf cmul(cf a, cf b) { cf r; r.x = fmaf(a.x, b.x, -a.y * b.y); r.y = fmaf(a.x, b.y, a.y * b.x); return r; }
__device__ __forceinline__ cf cexp_p(float lr2, float lt, float p) {
  float m = exp2f(lr2 * p);
  float t = lt * p;
  t = (t - rintf(t)) * 6.283185307179586f;
  cf r; r.x = m * __cosf(t); r.y = m * __sinf(t); return r;
}
__device__ __forceinline__ void store8(uint32_t a, const cf (&v)[8]) {
  sts128(a, pack(v[0].x, v[1].x), pack(v[2].x, v[3].x), pack(v[4].x, v[5].x), pack(v[6].x, v[7].x));
  sts128(a + KTAB / 2, pack(v[0].y, v[1].y), pack(v[2].y, v[3].y), pack(v[4].y, v[5].y), pack(v[6].y, v[7].y));
}
__device__ __forceinline__ float sigmoidf_(float s) { return 1.f / (1.f + __expf(-s)); }

__global__ void __cluster_dims__(CS, 1, 1) __launch_bounds__(NTHREADS, 1) fused_kernel(const __grid_constant__ Params p) {
  extern __shared__ __align__(1024) uint8_t smem[];
  TL_INIT();
  TL(31);
  const uint32_t sb = (uint32_t)__cvta_generic_to_shared(smem);
  const uint32_t mb = sb + OFF_MB;
  const int wg = __shfl_sync(0xffffffffu, threadIdx.x >> 7, 0);
  const int tid = threadIdx.x & 127, w = __shfl_sync(0xffffffffu, tid >> 5, 0), lane = tid & 31, g = lane >> 2, t = lane & 3;
  const int cl = blockIdx.x >> 3, rank = blockIdx.x & 7;
  const int ch0 = cl * CPC;
  const int nu = min(5, (DCH - ch0) >> 3);

  if (lane == 0 && wg) {
    const int b = 2 * (4 * (wg - 1) + w);
    mbar_init(mb + 8 * b, 1);
    mbar_init(mb + 8 * b + 8, b + 1 == MB_HRDY ? 4 : 1);
    if (wg == 1) mbar_init(mb + 8 * (MB_XQ + w), 1);
    fence_mbinit();
    mbar_expect(mb + 8 * b, b >= MB_Y ? 8192 : 4096);
    if (b + 1 != MB_HRDY) mbar_expect(mb + 8 * b + 8, b + 1 >= MB_Y ? 8192 : 4096);
    if (wg == 1) mbar_expect(mb + 8 * (MB_XQ + w), w < 2 ? 10240 : w == 2 ? 23040 + 20480 : 5 * HPITCH);
  }
  __syncwarp();
  cluster_arrive();
  int zero;
  asm volatile("shr.u32 %0, %1, 10;" : "=r"(zero) : "r"(threadIdx.x));
  const int uk0 = wg, uk1 = wg ? wg + 2 : 9;
  float pla[2], pai[2], pcr[2], pci[2], pdt[2], pds[2];
#pragma unroll
  for (int r = 0; r < 2; r++) {
    const int u = r ? uk1 : uk0;
    const int ch = (u < nu) ? ch0 + 8 * u + rank : 0;
    pla[r] = ldbf(p.logA + ch * NMODE + tid);
    pai[r] = ldbf(p.Aim + ch * NMODE + tid);
    pcr[r] = ldbf(p.Cre + ch * NMODE + tid);
    pci[r] = ldbf(p.Cim + ch * NMODE + tid);
    pdt[r] = ldbf(p.logdt + ch + zero);
    pds[r] = ldbf(p.Dskip + ch + zero);
  }
  uint2 swv = make_uint2(0, 0);
  uint32_t gwv = 0;
  float dval = 0.f;
  if (wg == 2) {
    if (tid < 40 && ch0 + tid < DCH) { swv = __ldg((const uint2*)(p.shift_k + (size_t)(ch0 + tid) * 4)); gwv = __ldg((const unsigned short*)(p.gate_w + ch0 + tid)); }
    if (tid < nu) dval = ldbf(p.ssm_D + ch0 + 8 * tid + rank);
  } else if (wg == 0) {
    if (tid < 85) sts128(sb + OFF_UX + (tid / 17) * UPITCH + (tid % 17) * 16, 0, 0, 0, 0);
  } else if (lane == 0 && w < 2) {
    tma_load4(sb + OFF_TQ + 10240 * w, &p.tq, ch0, 8 * rank + 4 * w, mb + 8 * (MB_XQ + w));
    TL(20);
  }
  uint32_t kid[9];
#pragma unroll
  for (int i = 0; i < 9; i++) {
    const int l = 8 * tid + i;
    kid[i] = pack((float)l, (float)(l + 1024)) - 0x42804280u;
    if (tid < 16) kid[i] = ((pack(128.f, (float)(l + 1024)) - 0x42804280u) & 0xffff0000u) | l;
    kid[i] *= 2;
  }
  TL(0);

  const uint32_t rbase = mapa(sb, g);
  const int mi = lane >> 3, tp = (lane & 7) >> 1, jj = lane & 1;
  const uint32_t toff = (4 * (7 - 2 * mi - jj) + tp) * 80;
  const uint32_t tab = sb + (wg == 0 ? OFF_PB : wg == 1 ? OFF_RAWA - 48 : OFF_HB4);
  const uint32_t kc = sb + OFF_KC + wg * 1408;
#pragma unroll 1
  for (int r = 0; r < 2; r++) {
    const int u = r ? uk1 : uk0;
    if (r == 0 && threadIdx.x == 192 && pla[0] != 12345.f) {
      tma_load4(sb + OFF_TK, &p.tk, ch0, 8 * rank - 1, mb + 8 * MB_KV);
      tma_load4(sb + OFF_TV, &p.tv, ch0, 8 * rank, mb + 8 * MB_KV);
    }
    __syncwarp();
    if (u < nu) {
      const float la = r ? pla[1] : pla[0], ai = r ? pai[1] : pai[0], cr = r ? pcr[1] : pcr[0], ci = r ? pci[1] : pci[0];
      const float dt = bf16r(expf(r ? pdt[1] : pdt[0]));
      const float lr2 = (-bf16r(expf(la)) * dt) * 1.4426950408889634f;
      const float lt = (ai * dt) * 0.15915494309189535f;
      const uint32_t row = tab + tid * 16;
      if (lr2 != 123.f) TL(16 + 4 * r + 6);
      {
        const cf w1 = cexp_p(lr2, lt, 8.f);
        cf v[8];
        v[0].x = 1.f; v[0].y = 0.f; v[1] = w1; v[2] = cmul(w1, w1); v[3] = cmul(v[2], w1);
        const cf w4 = cmul(v[2], v[2]);
        v[4] = w4; v[5] = cmul(v[1], w4); v[6] = cmul(v[2], w4); v[7] = cmul(v[3], w4);
        const cf w8 = cmul(w4, w4);
        store8(row, v);
#pragma unroll
        for (int c = 1; c < 4; c++) {
#pragma unroll
          for (int i = 0; i < 8; i++) v[i] = (c == 1 && i == 0) ? w8 : cmul(v[i], w8);
          store8(row + 2048 * c, v);
        }
      }
      {
        cf z1 = cexp_p(lr2, lt, 1.f), Z = cexp_p(lr2, lt, 256.f);
        z1.y = -z1.y; Z.y = -Z.y;
        const cf z2 = cmul(z1, z1);
        cf h[8], v[8];
        h[0].x = 2.f * cr * dt; h[0].y = -2.f * ci * dt;
        h[1] = cmul(h[0], z1);
#pragma unroll
        for (int i = 2; i < 8; i++) h[i] = cmul(h[i - 2], z2);
        store8(row + 4 * 2048, h);
        v[0] = cmul(h[0], Z); v[1] = cmul(h[2], Z); v[2] = cmul(h[4], Z); v[3] = cmul(h[6], Z);
        v[4] = cmul(v[0], Z); v[5] = cmul(v[2], Z); v[6] = cmul(v[4], Z); v[7] = cmul(v[5], Z);
        store8(row + 5 * 2048, v);
        const cf Z2 = cmul(Z, Z);
        h[0] = cmul(v[4], Z2); h[1] = cmul(v[6], Z2); h[2] = cmul(h[0], Z2); h[3] = cmul(h[1], Z2); h[4] = cmul(h[2], Z2);
        h[5].x = h[5].y = h[6].x = h[6].y = h[7].x = h[7].y = 0.f;
        store8(row + 6 * 2048, h);
      }
    }
    TL(16 + 4 * r + 7);
    if (u < nu) {
      fence_async();
      bar_sync(NB_WG0 + wg, 128);
    }
    if (r == 0) {
      cluster_wait();
      if (wg) mbar_wait(mb + 8 * (MB_XQ + wg - 1));
      TL(13);
    }
    float c[12];
    const uint64_t da = (uint64_t)((tab & 0x3FFFF) >> 4) | ((uint64_t)(KTAB / 32) << 16) | (128ull << 32);
    uint32_t xr[5][4];
    const int ah = 4 * (wg - 1) + w;
    if (r == 0 && wg) {
#pragma unroll
      for (int k = 0; k < 5; k++) ldsm4t(xr[k], sb + OFF_TQ + ah * 2560 + toff + 16 * k);
      st_async4(rbase + OFF_UX + UPAD + 16 * (32 * rank + 4 * ah + t), xr[0][0], xr[0][1], xr[0][2], xr[0][3], rbase + OFF_MB + 8 * MB_UX);
    }
    wg_fence();
    kgen_mma<0>(c, da);
    wg_commit();
    if (r == 0 && wg) {
#pragma unroll
      for (int k = 1; k < 5; k++)
        if (k < nu) st_async4(rbase + OFF_UX + k * UPITCH + UPAD + 16 * (32 * rank + 4 * ah + t), xr[k][0], xr[k][1], xr[k][2], xr[k][3], rbase + OFF_MB + 8 * (MB_UX + k));
      TL(15);
    }
    wg_wait<0>();
    if (u < nu) {
      if (tid == 0) c[0] += r ? pds[1] : pds[0];
      if (w < 2) {
#pragma unroll
        for (int hh = 0; hh < 2; hh++) {
          const int a = 16 * w + g + 8 * hh;
          sts32(kc + 4 * (4 * a + t), pack(c[2 * hh], c[2 * hh + 1]));
          sts32(kc + 4 * (t < 2 ? 128 + 2 * a + t : 128 + 32 * t + a), pack(c[4 + 2 * hh], c[5 + 2 * hh]));
          if (t < 3) {
            const uint32_t p0 = pack(c[8 + 2 * hh], c[9 + 2 * hh]);
            sts16(kc + 2 * (512 + 64 * t + a), p0);
            sts16(kc + 2 * (544 + 64 * t + a), p0 >> 16);
          }
        }
      }
      TL(16 + 4 * r + 8);
      bar_sync(NB_WG0 + wg, 128);
      const uint32_t hs = sb + (r ? (wg == 1 ? OFF_HB3 : OFF_HB4) : OFF_HB + u * 2 * HPITCH);
      uint32_t v[2][9];
#pragma unroll
      for (int cc = 0; cc < 2; cc++)
#pragma unroll
        for (int i = 0; i < 9; i++) v[cc][i] = lds16(kc + (cc ? kid[i] >> 16 : kid[i] & 0xffffu));
#pragma unroll
      for (int cc = 0; cc < 2; cc++) {
        const uint32_t o = hs + 16 + 16 * (tid + 128 * cc);
        sts128(o + HPITCH, prmt(v[cc][0], v[cc][1], 0x5410), prmt(v[cc][2], v[cc][3], 0x5410), prmt(v[cc][4], v[cc][5], 0x5410), prmt(v[cc][6], v[cc][7], 0x5410));
        sts128(o, prmt(v[cc][1], v[cc][2], 0x5410), prmt(v[cc][3], v[cc][4], 0x5410), prmt(v[cc][5], v[cc][6], 0x5410), prmt(v[cc][7], v[cc][8], 0x5410));
      }
      if (tid == 0) { sts128(hs + HPITCH, 0, 0, 0, 0); sts128(hs, 0, 0, 0, v[0][0] << 16); }
      if (wg == 2) bar_arrive(NB_HB2 + r, 256);
    }
    TL(1 + r);
    if (wg == 0) break;
  }

  if (wg < 2) {
    if (wg == 0) {
      if (tid < 64) sts128(sb + OFF_PB + tid * 528, 0, 0, 0, 0);
      bar_arrive(NB_PB1, 256);
    } else {
      if (tid == 0) {
        asm volatile("cp.async.bulk.tensor.4d.shared::cluster.global.mbarrier::complete_tx::bytes [%0], [%1, {%3, %4, %5, %6}], [%2];"
                     :: "r"(sb + OFF_RAWA - 48), "l"(&p.th), "r"(mb + 8 * MB_HA), "r"(0), "r"(-1), "r"(5 * cl), "r"(rank) : "memory");
      }
      __syncwarp();
      bar_sync(NB_PB1, 256);
    }
    cluster_arrive();
    bar_sync(NB_WG0 + wg, 128);
    const uint32_t haoff = 4 * (8 * w + ((g + 1) >> 1) + t);
    const uint32_t pw = sb + OFF_PB + wg * PBSZ + 4 * ((w * 8 + g) * 132 + t + w);
    const uint32_t pr = sb + OFF_PB + wg * PBSZ + w * 1056 + lane * 16;
    uint32_t ha = sb + OFF_HB + (2 * wg + (g & 1)) * HPITCH + haoff;
    uint32_t Q0[16], Q1[16], Q2[16], Q3[16];
    float X[32], Y[32], Z[32], cy0 = 0.f, cy1 = 0.f;
#pragma unroll
    for (int l = 0; l < 16; l++) Q0[l] = lds32(ha + aoff(l));
#pragma unroll
    for (int l = 0; l < 8; l++) Q1[l] = lds32(ha + 1024 + aoff(l));
    mbar_wait(mb + 8 * (MB_UX + wg));
    fence_async();
#pragma unroll 1
    for (int i = wg; i < 2 * nu; i += 2) {
      const bool isA = i >= nu;
      const int u = isA ? i - nu : i;
      const uint32_t ub = sb + (isA ? OFF_UKV : OFF_UX) + u * UPITCH;
      const uint64_t db = (uint64_t)((ub & 0x3FFFF) >> 4) | (1ull << 16) | (8ull << 32);
      TL(3 + (i >> 1));
      block<0, 0, 8, 16, 0, 0, 0>(X, Q0, db, Q1, ha + 1024, Z, cy0, cy1, pw);
      bar_sync(NB_WG0 + wg, 128);
      block<1, 0, 0, 5, 0, 0, 4>(Y, Q0, db, Q2, ha + 2048, X, cy0, cy1, pw);
      block<1, 1, 5, 10, 0, 4, 8>(Y, Q1, db, Q2, ha + 2048, X, cy0, cy1, pw);
      block<2, 0, 10, 16, 1, 0, 3>(X, Q0, db, Q2, ha + 2048, Y, cy0, cy1, pw);
      block<2, 1, 0, 6, 1, 3, 6>(X, Q1, db, Q3, ha + 3072, Y, cy0, cy1, pw);
      block<2, 2, 6, 11, 1, 6, 8>(X, Q2, db, Q3, ha + 3072, Y, cy0, cy1, pw);
      block<3, 0, 11, 16, 2, 0, 4>(Z, Q0, db, Q3, ha + 3072, X, cy0, cy1, pw);
      const int n = i + 2;
      if (!isA && (n > 2 || n >= nu) && i <= 2) bar_arrive(NB_HBFREE, 384);
      if (n < nu) {
        if (wg == 0) bar_sync(n == 2 ? NB_HB2 : NB_HB4, 256);
        ha = sb + (n == 2 ? OFF_HB + 4 * HPITCH : n == 3 ? OFF_HB3 : OFF_HB4) + (g & 1) * HPITCH + haoff;
      } else if (n < 2 * nu) {
        mbar_wait(mb + 8 * MB_HRDY);
        ha = sb + ((g & 1) ? OFF_RAWA : OFF_HB) + (n - nu) * HPITCH + haoff;
      }
      block<3, 1, 0, 8, 2, 4, 6>(Z, Q1, db, Q0, ha, X, cy0, cy1, pw);
      block<3, 2, 8, 16, 2, 6, 8>(Z, Q2, db, Q0, ha, X, cy0, cy1, pw);
      block<3, 3, 0, 8, 0, 0, 0>(Z, Q3, db, Q1, ha + 1024, X, cy0, cy1, pw);
      wg_wait<0>();
      epi_tiles<3, 0, 8>(Z, cy0, cy1, pw);
      if (!isA) {
        if (i == wg) {
          for (int k = n; k < nu; k += 2) mbar_wait(mb + 8 * (MB_UX + k));
        }
        if (n >= nu) {
          for (int k = 0; k < nu; k++) mbar_wait(mb + 8 * (MB_UKV + k));
        }
        if (i == wg || n >= nu) fence_async();
      }
      bar_sync(NB_WG0 + wg, 128);
      uint4 pa[4], pb[4];
#pragma unroll
      for (int k = 0; k < 4; k++) { pa[k] = lds128(pr + k * 4224); pb[k] = lds128(pr + k * 4224 + 528); }
      const uint32_t yd = rbase + (isA ? OFF_YA : OFF_YB) + (8 * u + rank) * YPITCH + (8 * w + t) * 16;
      const uint32_t ym = rbase + OFF_MB + 8 * (MB_Y + u);
      st_async4(yd, sum4(pa[0].x, pa[1].x, pa[2].x, pa[3].x), sum4(pa[0].y, pa[1].y, pa[2].y, pa[3].y),
                sum4(pb[0].x, pb[1].x, pb[2].x, pb[3].x), sum4(pb[0].y, pb[1].y, pb[2].y, pb[3].y), ym);
      st_async4(yd + 64, sum4(pa[0].z, pa[1].z, pa[2].z, pa[3].z), sum4(pa[0].w, pa[1].w, pa[2].w, pa[3].w),
                sum4(pb[0].z, pb[1].z, pb[2].z, pb[3].z), sum4(pb[0].w, pb[1].w, pb[2].w, pb[3].w), ym);
      TL(8 + (i >> 1));
    }
    TL_DUMP();
  } else {
    if (tid < 40) { sts64(sb + OFF_SW + 8 * tid, swv.x, swv.y); sts16(sb + OFF_GW + 2 * tid, gwv); }
    else if (tid < 40 + 85) sts128(sb + OFF_UKV + ((tid - 40) / 17) * UPITCH + ((tid - 40) % 17) * 16, 0, 0, 0, 0);
    __syncwarp();
    cluster_arrive();
    bar_sync(NB_WG0 + 2, 128);
    mbar_wait(mb + 8 * MB_XQ);
    mbar_wait(mb + 8 * (MB_XQ + 1));
    {
      float s0 = 0.f, s1 = 0.f;
#pragma unroll
      for (int j = 0; j < 5; j++) {
        const uint4 gw = lds128(sb + OFF_GW + 16 * j);
        const uint4 x0 = lds128(sb + OFF_TQ + tid * 80 + 16 * j), x1 = lds128(sb + OFF_TQ + (tid + 128) * 80 + 16 * j);
        uint32_t m0 = hmul2(x0.x, gw.x), m1 = hmul2(x0.y, gw.y), m2 = hmul2(x0.z, gw.z), m3 = hmul2(x0.w, gw.w);
        s0 += ((blo(m0) + bhi(m0)) + (blo(m1) + bhi(m1))) + ((blo(m2) + bhi(m2)) + (blo(m3) + bhi(m3)));
        m0 = hmul2(x1.x, gw.x); m1 = hmul2(x1.y, gw.y); m2 = hmul2(x1.z, gw.z); m3 = hmul2(x1.w, gw.w);
        s1 += ((blo(m0) + bhi(m0)) + (blo(m1) + bhi(m1))) + ((blo(m2) + bhi(m2)) + (blo(m3) + bhi(m3)));
      }
      __stcg(&g_part[cl * SEQ + rank * 256 + tid], s0);
      __stcg(&g_part[cl * SEQ + rank * 256 + 128 + tid], s1);
    }
    TL(3);
    cluster_wait();
    mbar_wait(mb + 8 * MB_KV);
    TL(4);
    const uint32_t hoff = (4 * (7 - 2 * (mi & 1) - jj) + ((tp + 3) & 3)) * 80 + (tp ? 2560 : 0);
#pragma unroll 1
    for (int u = 0; u < nu; u++) {
      const uint2 sw = lds64(sb + OFF_SW + 8 * (8 * u + g));
      uint32_t E[2][6], V[2][4];
#pragma unroll
      for (int hf = 0; hf < 2; hf++) {
        const int ah = 4 * hf + w;
        uint32_t K[4];
        ldsm4t(K, sb + OFF_TK + (ah + 1) * 2560 + toff + 16 * u);
        ldsm2t(E[hf][4], E[hf][5], sb + OFF_TK + ah * 2560 + hoff + 16 * u);
        ldsm4t(V[hf], sb + OFF_TV + ah * 2560 + toff + 16 * u);
        E[hf][0] = K[0]; E[hf][1] = K[1]; E[hf][2] = K[2]; E[hf][3] = K[3];
      }
      const uint32_t w0 = prmt(sw.x, 0, 0x1010), w1 = prmt(sw.x, 0, 0x3232), w2 = prmt(sw.y, 0, 0x1010), w3 = prmt(sw.y, 0, 0x3232);
#pragma unroll
      for (int hf = 0; hf < 2; hf++) {
        uint32_t O[5], o[4];
#pragma unroll
        for (int i = 0; i < 5; i++) O[i] = prmt(E[hf][i], E[hf][i + 1], 0x5432);
#pragma unroll
        for (int i = 0; i < 4; i++) {
          uint32_t s = hmul2(O[i + 1], w3);
          s = hadd2(s, hmul2(E[hf][i + 1], w2));
          s = hadd2(s, hmul2(O[i], w1));
          s = hadd2(s, hmul2(E[hf][i], w0));
          o[i] = hmul2(s, V[hf][i]);
        }
        st_async4(rbase + OFF_UKV + u * UPITCH + UPAD + 16 * (32 * rank + 16 * hf + 4 * w + t), o[0], o[1], o[2], o[3], rbase + OFF_MB + 8 * (MB_UKV + u));
      }
    }
    TL(5);
    mbar_wait(mb + 8 * MB_HA);
    bar_sync(NB_HBFREE, 384);
    TL(6);
    unsigned g_target = 0;
#pragma unroll 1
    for (int u = 0; u < nu; u++) {
      const uint32_t ra = sb + OFF_RAWA + u * HPITCH + 16 + 16 * tid;
      const uint4 x = lds128(ra), y = lds128(ra + 2048);
      const uint32_t xn = lds32(ra + 16), yn = lds32(ra + 2048 + 16);
      const uint32_t o = sb + OFF_HB + u * HPITCH + 16 + 16 * tid;
      sts128(o, prmt(x.x, x.y, 0x5432), prmt(x.y, x.z, 0x5432), prmt(x.z, x.w, 0x5432), prmt(x.w, xn, 0x5432));
      sts128(o + 2048, prmt(y.x, y.y, 0x5432), prmt(y.y, y.z, 0x5432), prmt(y.z, y.w, 0x5432), prmt(y.w, yn, 0x5432));
    }
    if (tid < nu) {
      const uint32_t ra = sb + OFF_RAWA + tid * HPITCH + 16;
      const uint32_t h0 = pack(blo(lds16(ra)) + dval, 0.f);
      sts16(ra, h0);
      sts128(sb + OFF_HB + tid * HPITCH, 0, 0, 0, h0 << 16);
    }
    __syncwarp();
    if (lane == 0) mbar_arrive(mb + 8 * MB_HRDY);
    TL(7);
    uint32_t okflag = 1;
    if (tid == 0) {
      __threadfence();
      const unsigned old = atomicAdd(&g_cnt[rank * 32], cl == 0 ? 16 - (NCL - 1) : 1);
      g_target = (old & ~15u) + 16;
      unsigned v;
      int it = 0;
      do {
        asm volatile("ld.acquire.gpu.global.u32 %0, [%1];" : "=r"(v) : "l"(&g_cnt[rank * 32]) : "memory");
      } while ((int)(v - g_target) < 0 && ++it < 20000);
      okflag = (int)(v - g_target) >= 0;
    }
    asm volatile("{.reg .pred p, q; setp.ne.u32 p, %1, 0; bar.red.and.pred q, %2, 128, p; selp.u32 %0, 1, 0, q;}" : "=r"(okflag) : "r"(okflag), "r"(NB_WG0 + 2) : "memory");
    {
      float s[2] = {0.f, 0.f};
      if (okflag) {
        float2 v[NCL];
#pragma unroll
        for (int c = 0; c < NCL; c++) v[c] = __ldcg((const float2*)&g_part[c * SEQ + rank * 256 + 2 * tid]);
#pragma unroll
        for (int c = 0; c < NCL; c++) { s[0] += v[c].x; s[1] += v[c].y; }
      } else {
#pragma unroll 1
        for (int hf = 0; hf < 2; hf++) {
          const int slot = 2 * tid + hf;
          const int row = rank * 256 + (slot & ~31) + 8 * (slot & 3) + ((slot >> 2) & 7);
          const uint32_t* xr = (const uint32_t*)(p.q + (size_t)row * DCH);
          const uint32_t* gr = (const uint32_t*)p.gate_w;
          float a = 0.f;
#pragma unroll 1
          for (int c = 0; c < DCH / 2; c++) { const uint32_t m = hmul2(__ldg(xr + c), __ldg(gr + c)); a += blo(m) + bhi(m); }
          if (hf) s[1] = a; else s[0] = a;
        }
      }
      const float g0 = bf16r(sigmoidf_(bf16r(s[0]))), g1 = bf16r(sigmoidf_(bf16r(s[1])));
      sts128(sb + OFF_KC + 16 * tid, pack(g0, g0), pack(1.f - g0, 1.f - g0), pack(g1, g1), pack(1.f - g1, 1.f - g1));
    }
    __syncwarp();
    uint2 gg[2][4];
#pragma unroll
    for (int hh = 0; hh < 2; hh++)
#pragma unroll
      for (int i = 0; i < 4; i++) gg[hh][i] = lds64(sb + OFF_KC + 8 * (64 * w + 32 * hh + 8 * i + g));
    TL(8);
#pragma unroll 1
    for (int u = 0; u < nu; u++) {
      uint32_t qv[2][4];
      const uint32_t qa = sb + OFF_TQ + (64 * w + lane) * 80 + 16 * u;
      ldsm4(qv[0], qa);
      ldsm4(qv[1], qa + 2560);
      mbar_wait(mb + 8 * (MB_Y + u));
      uint32_t ya[2][4], yb[2][4];
      const uint32_t yo = (8 * u + (lane & 7)) * YPITCH + (8 * mi + w) * 16;
#pragma unroll
      for (int hh = 0; hh < 2; hh++) { ldsm4t(ya[hh], sb + OFF_YA + yo + 64 * hh); ldsm4t(yb[hh], sb + OFF_YB + yo + 64 * hh); }
#pragma unroll
      for (int hh = 0; hh < 2; hh++) {
        uint32_t o[4];
#pragma unroll
        for (int i = 0; i < 4; i++) o[i] = hadd2(hmul2(gg[hh][i].x, hmul2(qv[hh][i], ya[hh][i])), hmul2(gg[hh][i].y, yb[hh][i]));
        stsm4(qa + 2560 * hh, o);
      }
      TL(9 + (u < 4 ? u : 8));
    }
    fence_async();
    __syncwarp();
    if (lane == 0) {
      tma_store4(&p.to, ch0, 8 * rank + 2 * w, sb + OFF_TQ + w * 5120);
      asm volatile("cp.async.bulk.commit_group;" ::: "memory");
      asm volatile("cp.async.bulk.wait_group.read 0;" ::: "memory");
    }
    TL(14);
    TL_DUMP();
  }
}

typedef CUresult (*EncodeFn)(CUtensorMap*, CUtensorMapDataType, cuuint32_t, void*, const cuuint64_t*, const cuuint64_t*,
                             const cuuint32_t*, const cuuint32_t*, CUtensorMapInterleave, CUtensorMapSwizzle,
                             CUtensorMapL2promotion, CUtensorMapFloatOOBfill);

void make_map(EncodeFn fn, CUtensorMap* tm, const void* ptr, int nhi) {
  cuuint64_t dims[4] = {DCH, 4, 8, SEQ / 32};
  cuuint64_t strides[3] = {8 * DCH * 2, DCH * 2, 32 * DCH * 2};
  cuuint32_t box[4] = {CPC, 4, 8, (cuuint32_t)nhi};
  cuuint32_t es[4] = {1, 1, 1, 1};
  fn(tm, CU_TENSOR_MAP_DATA_TYPE_BFLOAT16, 4, const_cast<void*>(ptr), dims, strides, box, es, CU_TENSOR_MAP_INTERLEAVE_NONE,
     CU_TENSOR_MAP_SWIZZLE_NONE, CU_TENSOR_MAP_L2_PROMOTION_L2_128B, CU_TENSOR_MAP_FLOAT_OOB_FILL_NONE);
}

}

extern "C" void kernel_launch(void* const* d_in, const int* in_sizes, int n_in, void* d_out, int out_size) {
  (void)in_sizes; (void)n_in; (void)out_size;
  static EncodeFn fn = nullptr;
  if (!fn) {
    cudaDriverEntryPointQueryResult qr;
    cudaGetDriverEntryPoint("cuTensorMapEncodeTiled", (void**)&fn, cudaEnableDefault, &qr);
    cudaFuncSetAttribute(fused_kernel, cudaFuncAttributeMaxDynamicSharedMemorySize, SMEM_BYTES);
  }
  Params p;
  make_map(fn, &p.tq, d_in[0], 4);
  make_map(fn, &p.tk, d_in[1], 9);
  make_map(fn, &p.tv, d_in[2], 8);
  {
    cuuint64_t dims[4] = {32, SEQ / 32, DCH / 8, 8};
    cuuint64_t strides[3] = {64, 8 * SEQ * 2, SEQ * 2};
    cuuint32_t box[4] = {32, 65, 5, 1};
    cuuint32_t es[4] = {1, 1, 1, 1};
    fn(&p.th, CU_TENSOR_MAP_DATA_TYPE_BFLOAT16, 4, d_in[4], dims, strides, box, es, CU_TENSOR_MAP_INTERLEAVE_NONE,
       CU_TENSOR_MAP_SWIZZLE_NONE, CU_TENSOR_MAP_L2_PROMOTION_L2_128B, CU_TENSOR_MAP_FLOAT_OOB_FILL_NONE);
  }
  make_map(fn, &p.to, d_out, 2);
  p.q = (const __nv_bfloat16*)d_in[0];
  p.shift_k = (const __nv_bfloat16*)d_in[3];
  p.ssm_k = (const __nv_bfloat16*)d_in[4];
  p.ssm_D = (const __nv_bfloat16*)d_in[5];
  p.logA = (const __nv_bfloat16*)d_in[7];
  p.Aim = (const __nv_bfloat16*)d_in[8];
  p.Cre = (const __nv_bfloat16*)d_in[9];
  p.Cim = (const __nv_bfloat16*)d_in[10];
  p.logdt = (const __nv_bfloat16*)d_in[11];
  p.Dskip = (const __nv_bfloat16*)d_in[12];
  p.gate_w = (const __nv_bfloat16*)d_in[13];
  fused_kernel<<<NCL * CS, NTHREADS, SMEM_BYTES, cudaStreamPerThread>>>(p);
}
```

```cpp
#include <cuda_runtime.h>
#include <cuda_bf16.h>
#include <cuda.h>
#include <stdint.h>

#define TIMELINE 0

namespace {

constexpr int SEQ = 2048, DCH = 576, NMODE = 128;
constexpr int CS = 8, CPC = 40, NCL = 15, NTHREADS = 384;

constexpr int UPITCH = 4368, UPAD = 272;
constexpr int HPITCH = 4160;
constexpr int PBSZ = 16896;
constexpr int YPITCH = 528;
constexpr int KTAB = 28672;
constexpr int OFF_TQ = 0;
constexpr int OFF_TK = 20480;
constexpr int OFF_YA = OFF_TK;
constexpr int OFF_TV = 43520;
constexpr int OFF_UX = 64000;
constexpr int OFF_RAWA = OFF_UX + 5 * UPITCH + 48 + 48;
constexpr int OFF_HB3 = OFF_RAWA + 5 * HPITCH - 32;
constexpr int OFF_HB = OFF_HB3 + 2 * HPITCH;
constexpr int OFF_PB = OFF_HB + 6 * HPITCH;
constexpr int OFF_YB = OFF_PB + 2 * PBSZ;
constexpr int OFF_HB4 = OFF_YB + 40 * YPITCH;
constexpr int OFF_UKV = OFF_HB4 + 2 * HPITCH;
constexpr int OFF_KC = OFF_UKV + 5 * UPITCH;
constexpr int OFF_SW = OFF_KC + 3 * 1408;
constexpr int OFF_GW = OFF_SW + 320;
constexpr int OFF_MB = OFF_GW + 80;
constexpr int OFF_TL = OFF_MB + 32 * 8;
constexpr int SMEM_BYTES = OFF_TL + (TIMELINE ? 1536 : 0);
static_assert(((OFF_RAWA - OFF_HB) & 63) == 32, "bank offset between raw/shift copies");
static_assert(KTAB + 2048 <= 2 * PBSZ && KTAB <= OFF_HB - (OFF_RAWA - 48) && KTAB <= OFF_KC - OFF_HB4, "ktab alias zones");
static_assert(SMEM_BYTES <= 232448, "smem");
static_assert(((OFF_RAWA - 48) & 127) == 0, "tma dst");
static_assert((OFF_RAWA & 15) == 0 && (OFF_PB & 15) == 0 && (OFF_HB & 15) == 0 && (OFF_MB & 7) == 0 && (OFF_KC & 15) == 0, "align");

enum { MB_UX = 0, MB_UKV = 5, MB_Y = 10, MB_HRDY = 15, MB_XQ = 16, MB_KV = 18, MB_HA = 19, MB_COUNT = 20 };
enum { NB_WG0 = 1, NB_HB2 = 4, NB_HB4 = 5, NB_HBFREE = 6, NB_PB1 = 7 };

struct Params {
  const __nv_bfloat16 *logA, *Aim, *Cre, *Cim, *logdt, *Dskip, *shift_k, *ssm_D, *gate_w, *q;
  CUtensorMap tq, tk, tv, to, th;
};

__device__ float g_part[NCL * SEQ];
__device__ unsigned g_cnt[CS * 32];
#define TL(i) do {} while (0)
#define TL_INIT() do {} while (0)
#define TL_DUMP() do {} while (0)

__device__ __forceinline__ uint32_t lds32(uint32_t a) { uint32_t v; asm volatile("ld.shared.u32 %0, [%1];" : "=r"(v) : "r"(a) : "memory"); return v; }
__device__ __forceinline__ uint32_t lds16(uint32_t a) { uint32_t v; asm volatile("ld.shared.u16 %0, [%1];" : "=r"(v) : "r"(a) : "memory"); return v; }
__device__ __forceinline__ uint2 lds64(uint32_t a) { uint2 v; asm volatile("ld.shared.v2.u32 {%0,%1}, [%2];" : "=r"(v.x), "=r"(v.y) : "r"(a) : "memory"); return v; }
__device__ __forceinline__ uint4 lds128(uint32_t a) { uint4 v; asm volatile("ld.shared.v4.u32 {%0,%1,%2,%3}, [%4];" : "=r"(v.x), "=r"(v.y), "=r"(v.z), "=r"(v.w) : "r"(a) : "memory"); return v; }
__device__ __forceinline__ void sts16(uint32_t a, uint32_t v) { asm volatile("st.shared.u16 [%0], %1;" :: "r"(a), "r"(v) : "memory"); }
__device__ __forceinline__ void sts32(uint32_t a, uint32_t v) { asm volatile("st.shared.u32 [%0], %1;" :: "r"(a), "r"(v) : "memory"); }
__device__ __forceinline__ void sts64(uint32_t a, uint32_t x, uint32_t y) { asm volatile("st.shared.v2.u32 [%0], {%1,%2};" :: "r"(a), "r"(x), "r"(y) : "memory"); }
__device__ __forceinline__ void sts128(uint32_t a, uint32_t x, uint32_t y, uint32_t z, uint32_t w) { asm volatile("st.shared.v4.u32 [%0], {%1,%2,%3,%4};" :: "r"(a), "r"(x), "r"(y), "r"(z), "r"(w) : "memory"); }
__device__ __forceinline__ void ldsm4t(uint32_t (&r)[4], uint32_t a) { asm volatile("ldmatrix.sync.aligned.m8n8.x4.trans.shared.b16 {%0,%1,%2,%3}, [%4];" : "=r"(r[0]), "=r"(r[1]), "=r"(r[2]), "=r"(r[3]) : "r"(a) : "memory"); }
__device__ __forceinline__ void ldsm2t(uint32_t& r0, uint32_t& r1, uint32_t a) { asm volatile("ldmatrix.sync.aligned.m8n8.x2.trans.shared.b16 {%0,%1}, [%2];" : "=r"(r0), "=r"(r1) : "r"(a) : "memory"); }
__device__ __forceinline__ void ldsm4(uint32_t (&r)[4], uint32_t a) { asm volatile("ldmatrix.sync.aligned.m8n8.x4.shared.b16 {%0,%1,%2,%3}, [%4];" : "=r"(r[0]), "=r"(r[1]), "=r"(r[2]), "=r"(r[3]) : "r"(a) : "memory"); }
__device__ __forceinline__ void stsm4(uint32_t a, const uint32_t (&r)[4]) { asm volatile("stmatrix.sync.aligned.m8n8.x4.shared.b16 [%0], {%1,%2,%3,%4};" :: "r"(a), "r"(r[0]), "r"(r[1]), "r"(r[2]), "r"(r[3]) : "memory"); }
__device__ __forceinline__ uint32_t pack(float lo, float hi) { uint32_t r; asm("cvt.rn.bf16x2.f32 %0, %1, %2;" : "=r"(r) : "f"(hi), "f"(lo)); return r; }
__device__ __forceinline__ float blo(uint32_t v) { return __uint_as_float(v << 16); }
__device__ __forceinline__ float bhi(uint32_t v) { return __uint_as_float(v & 0xffff0000u); }
__device__ __forceinline__ float bf16r(float x) { return blo(pack(x, 0.f)); }
__device__ __forceinline__ uint32_t hmul2(uint32_t a, uint32_t b) { uint32_t r; asm("mul.rn.bf16x2 %0, %1, %2;" : "=r"(r) : "r"(a), "r"(b)); return r; }
__device__ __forceinline__ uint32_t hadd2(uint32_t a, uint32_t b) { uint32_t r; asm("add.rn.bf16x2 %0, %1, %2;" : "=r"(r) : "r"(a), "r"(b)); return r; }
__device__ __forceinline__ uint32_t prmt(uint32_t a, uint32_t b, uint32_t s) { return __byte_perm(a, b, s); }
__device__ __forceinline__ uint32_t ldraw(const __nv_bfloat16* p) { uint32_t v; asm volatile("ld.global.nc.u16 %0, [%1];" : "=r"(v) : "l"(p)); return v; }
__device__ __forceinline__ uint32_t sum4(uint32_t a, uint32_t b, uint32_t c, uint32_t d) {
  return pack((blo(a) + blo(b)) + (blo(c) + blo(d)), (bhi(a) + bhi(b)) + (bhi(c) + bhi(d)));
}
__device__ __forceinline__ void mma16816(float (&c)[4], const uint32_t (&a)[4], uint32_t b0, uint32_t b1) {
  asm volatile("mma.sync.aligned.m16n8k16.row.col.f32.bf16.bf16.f32 {%0,%1,%2,%3}, {%4,%5,%6,%7}, {%8,%9}, {%0,%1,%2,%3};"
               : "+f"(c[0]), "+f"(c[1]), "+f"(c[2]), "+f"(c[3]) : "r"(a[0]), "r"(a[1]), "r"(a[2]), "r"(a[3]), "r"(b0), "r"(b1));
}
__device__ __forceinline__ void bar_sync(int id, int n) { asm volatile("bar.sync %0, %1;" :: "r"(id), "r"(n) : "memory"); }
__device__ __forceinline__ void bar_arrive(int id, int n) { asm volatile("bar.arrive %0, %1;" :: "r"(id), "r"(n) : "memory"); }
__device__ __forceinline__ void cluster_arrive() { asm volatile("barrier.cluster.arrive.relaxed.aligned;" ::: "memory"); }
__device__ __forceinline__ void cluster_wait() { asm volatile("barrier.cluster.wait.aligned;" ::: "memory"); }
__device__ __forceinline__ void fence_async() { asm volatile("fence.proxy.async.shared::cta;" ::: "memory"); }
__device__ __forceinline__ void fence_mbinit() { asm volatile("fence.mbarrier_init.release.cluster;" ::: "memory"); }
__device__ __forceinline__ uint32_t mapa(uint32_t a, uint32_t rank) { uint32_t r; asm("mapa.shared::cluster.u32 %0, %1, %2;" : "=r"(r) : "r"(a), "r"(rank)); return r; }
__device__ __forceinline__ void st_async4(uint32_t a, uint32_t x, uint32_t y, uint32_t z, uint32_t w, uint32_t mbar) {
  asm volatile("st.async.weak.shared::cluster.mbarrier::complete_tx::bytes.v4.b32 [%0], {%1,%2,%3,%4}, [%5];"
               :: "r"(a), "r"(x), "r"(y), "r"(z), "r"(w), "r"(mbar) : "memory");
}
__device__ __forceinline__ void mbar_init(uint32_t m, uint32_t cnt) { asm volatile("mbarrier.init.shared::cta.b64 [%0], %1;" :: "r"(m), "r"(cnt) : "memory"); }
__device__ __forceinline__ void mbar_expect(uint32_t m, uint32_t bytes) { asm volatile("mbarrier.arrive.expect_tx.shared::cta.b64 _, [%0], %1;" :: "r"(m), "r"(bytes) : "memory"); }
__device__ __forceinline__ void mbar_arrive(uint32_t m) { asm volatile("mbarrier.arrive.shared::cta.b64 _, [%0];" :: "r"(m) : "memory"); }
__device__ __forceinline__ void mbar_wait(uint32_t m) {
  uint32_t done;
  int it = 0;
  do {
    asm volatile("{.reg .pred p; mbarrier.try_wait.parity.shared::cta.b64 p, [%1], 0; selp.u32 %0, 1, 0, p;}" : "=r"(done) : "r"(m) : "memory");
    if (++it > (1 << 22)) __trap();
  } while (!done);
}
__device__ __forceinline__ void tma_load4(uint32_t dst, const CUtensorMap* tm, int c0, int c3, uint32_t mbar) {
  asm volatile("cp.async.bulk.tensor.4d.shared::cluster.global.mbarrier::complete_tx::bytes [%0], [%1, {%3, %4, %4, %5}], [%2];"
               :: "r"(dst), "l"(tm), "r"(mbar), "r"(c0), "r"(0), "r"(c3) : "memory");
}
__device__ __forceinline__ void tma_store4(const CUtensorMap* tm, int c0, int c3, uint32_t src) {
  asm volatile("cp.async.bulk.tensor.4d.global.shared::cta.bulk_group [%0, {%2, %3, %3, %4}], [%1];"
               :: "l"(tm), "r"(src), "r"(c0), "r"(0), "r"(c3) : "memory");
}
__device__ __forceinline__ void bulk_load(uint32_t dst, const void* src, uint32_t bytes, uint32_t mbar) {
  asm volatile("cp.async.bulk.shared::cluster.global.mbarrier::complete_tx::bytes [%0], [%1], %2, [%3];"
               :: "r"(dst), "l"(src), "r"(bytes), "r"(mbar) : "memory");
}
__device__ __forceinline__ void wg_fence() { asm volatile("wgmma.fence.sync.aligned;" ::: "memory"); }
__device__ __forceinline__ void wg_commit() { asm volatile("wgmma.commit_group.sync.aligned;" ::: "memory"); }
template <int N> __device__ __forceinline__ void wg_wait() { asm volatile("wgmma.wait_group.sync.aligned %0;" :: "n"(N) : "memory"); }
#define WG_REGS "{%0,%1,%2,%3,%4,%5,%6,%7,%8,%9,%10,%11,%12,%13,%14,%15}, {%16,%17,%18,%19}, %20, "
__device__ __forceinline__ void wgmma32_acc(float* d, const uint32_t* a, uint64_t db) {
  asm volatile("wgmma.mma_async.sync.aligned.m64n32k16.f32.bf16.bf16 " WG_REGS "1, 1, 1, 0;"
               : "+f"(d[0]), "+f"(d[1]), "+f"(d[2]), "+f"(d[3]), "+f"(d[4]), "+f"(d[5]), "+f"(d[6]), "+f"(d[7]),
                 "+f"(d[8]), "+f"(d[9]), "+f"(d[10]), "+f"(d[11]), "+f"(d[12]), "+f"(d[13]), "+f"(d[14]), "+f"(d[15])
               : "r"(a[0]), "r"(a[1]), "r"(a[2]), "r"(a[3]), "l"(db));
}
__device__ __forceinline__ void wgmma32_set(float* d, const uint32_t* a, uint64_t db) {
  asm volatile("wgmma.mma_async.sync.aligned.m64n32k16.f32.bf16.bf16 " WG_REGS "0, 1, 1, 0;"
               : "=f"(d[0]), "=f"(d[1]), "=f"(d[2]), "=f"(d[3]), "=f"(d[4]), "=f"(d[5]), "=f"(d[6]), "=f"(d[7]),
                 "=f"(d[8]), "=f"(d[9]), "=f"(d[10]), "=f"(d[11]), "=f"(d[12]), "=f"(d[13]), "=f"(d[14]), "=f"(d[15])
               : "r"(a[0]), "r"(a[1]), "r"(a[2]), "r"(a[3]), "l"(db));
}

__device__ __forceinline__ void tie(float& x) { asm volatile("" : "+f"(x) :: "memory"); }
__device__ __forceinline__ constexpr int aoff(int k) { return 256 * (k >> 2) + ((k & 3) == 0 ? 16 : (k & 3) == 1 ? 144 : (k & 3) == 2 ? 0 : 128); }
template <int ES, int E0, int E1>
__device__ __forceinline__ void epi_tiles(float (&E)[32], float& cy0, float& cy1, uint32_t pw) {
#pragma unroll
  for (int e = E0; e < E1; e++) {
    tie(E[4 * e]); tie(E[4 * e + 1]); tie(E[4 * e + 2]); tie(E[4 * e + 3]);
    float v0 = E[4 * e], v1 = E[4 * e + 1];
    if (e > 0) { v0 += E[4 * e - 2]; v1 += E[4 * e - 1]; } else if (ES > 0) { v0 += cy0; v1 += cy1; }
    sts32(pw + 16 * (8 * ES + e), pack(v0, v1));
    if (e == 7) { cy0 = E[30]; cy1 = E[31]; }
  }
}
template <int S, int MQ, int L0, int L1, int ES, int E0, int E1>
__device__ __forceinline__ void block(float (&acc)[32], const uint32_t (&Q)[16], uint64_t db, uint32_t (&LQ)[16], uint32_t la,
                                      float (&E)[32], float& cy0, float& cy1, uint32_t pw) {
  wg_fence();
#pragma unroll
  for (int mm = 0; mm < 4; mm++) {
#pragma unroll
    for (int jj = 1; jj >= 0; jj--) {
      const int m = 4 * MQ + mm, j = 2 * S + jj;
      if (m < 2 * (j + 1)) {
        if (m == 0) wgmma32_set(acc + 16 * jj, Q + 4 * mm, db + (uint64_t)(16 + 32 * j - 16 * m));
        else wgmma32_acc(acc + 16 * jj, Q + 4 * mm, db + (uint64_t)(16 + 32 * j - 16 * m));
      }
    }
  }
  wg_commit();
  wg_wait<1>();
#pragma unroll
  for (int l = L0; l < L1; l++) LQ[l] = lds32(la + aoff(l));
  epi_tiles<ES, E0, E1>(E, cy0, cy1, pw);
}

template <int KS> __device__ __forceinline__ void kgen_mma(float (&c)[12], uint64_t da) {
  asm volatile("{.reg .b64 da, db; add.s64 da, %12, %13; add.s64 db, %12, %14;\n"
               "wgmma.mma_async.sync.aligned.m64n24k16.f32.bf16.bf16 {%0,%1,%2,%3,%4,%5,%6,%7,%8,%9,%10,%11}, da, db, %15, 1, 1, 1, 1;}"
               : "+f"(c[0]), "+f"(c[1]), "+f"(c[2]), "+f"(c[3]), "+f"(c[4]), "+f"(c[5]), "+f"(c[6]), "+f"(c[7]), "+f"(c[8]), "+f"(c[9]), "+f"(c[10]), "+f"(c[11])
               : "l"(da), "n"(8 * KS), "n"(8 * KS + 512), "n"(KS ? 1 : 0));
  if constexpr (KS < 15) kgen_mma<KS + 1>(c, da);
}
struct cf { float x, y; };
__device__ __forceinline__ cf cmul(cf a, cf b) { cf r; r.x = fmaf(a.x, b.x, -a.y * b.y); r.y = fmaf(a.x, b.y, a.y * b.x); return r; }
__device__ __forceinline__ cf cexp_p(float lr2, float lt, float p) {
  float m = exp2f(lr2 * p);
  float t = lt * p;
  t = (t - rintf(t)) * 6.283185307179586f;
  cf r; r.x = m * __cosf(t); r.y = m * __sinf(t); return r;
}
__device__ __forceinline__ void store8(uint32_t a, const cf (&v)[8]) {
  sts128(a, pack(v[0].x, v[1].x), pack(v[2].x, v[3].x), pack(v[4].x, v[5].x), pack(v[6].x, v[7].x));
  sts128(a + KTAB / 2, pack(v[0].y, v[1].y), pack(v[2].y, v[3].y), pack(v[4].y, v[5].y), pack(v[6].y, v[7].y));
}
__device__ __forceinline__ float sigmoidf_(float s) { return 1.f / (1.f + __expf(-s)); }

__global__ void __cluster_dims__(CS, 1, 1) __launch_bounds__(NTHREADS, 1) fused_kernel(const __grid_constant__ Params p) {
  extern __shared__ __align__(1024) uint8_t smem[];
  TL_INIT();
  TL(31);
  const uint32_t sb = (uint32_t)__cvta_generic_to_shared(smem);
  const uint32_t mb = sb + OFF_MB;
  const int wg = __shfl_sync(0xffffffffu, threadIdx.x >> 7, 0);
  const int tid = threadIdx.x & 127, w = __shfl_sync(0xffffffffu, tid >> 5, 0), lane = tid & 31, g = lane >> 2, t = lane & 3;
  const int cl = blockIdx.x >> 3, rank = blockIdx.x & 7;
  const int ch0 = cl * CPC;
  const int nu = min(5, (DCH - ch0) >> 3);

  if (lane == 0 && wg) {
    const int b = 2 * (4 * (wg - 1) + w);
    mbar_init(mb + 8 * b, 1);
    mbar_init(mb + 8 * b + 8, b + 1 == MB_HRDY ? 4 : 1);
    if (wg == 1) mbar_init(mb + 8 * (MB_XQ + w), 1);
    fence_mbinit();
    mbar_expect(mb + 8 * b, b >= MB_Y ? 8192 : 4096);
    if (b + 1 != MB_HRDY) mbar_expect(mb + 8 * b + 8, b + 1 >= MB_Y ? 8192 : 4096);
    if (wg == 1) mbar_expect(mb + 8 * (MB_XQ + w), w < 2 ? 10240 : w == 2 ? 23040 + 20480 : 5 * HPITCH);
  }
  __syncwarp();
  cluster_arrive();
  const int uk0 = wg, uk1 = wg ? wg + 2 : 9;
  uint32_t pla[2], pai[2], pcr[2], pci[2], pdt[2], pds[2];
#pragma unroll
  for (int r = 0; r < 2; r++) {
    const int u = r ? uk1 : uk0;
    const int ch = (u < nu) ? ch0 + 8 * u + rank : 0;
    pla[r] = ldraw(p.logA + ch * NMODE + tid);
    pai[r] = ldraw(p.Aim + ch * NMODE + tid);
    pcr[r] = ldraw(p.Cre + ch * NMODE + tid);
    pci[r] = ldraw(p.Cim + ch * NMODE + tid);
    pdt[r] = ldraw(p.logdt + ch);
    pds[r] = ldraw(p.Dskip + ch);
  }
  uint2 swv = make_uint2(0, 0);
  uint32_t gwv = 0;
  uint32_t dval = 0;
  if (wg == 2) {
    if (tid < 40 && ch0 + tid < DCH) { swv = __ldg((const uint2*)(p.shift_k + (size_t)(ch0 + tid) * 4)); gwv = __ldg((const unsigned short*)(p.gate_w + ch0 + tid)); }
    if (tid < nu) dval = ldraw(p.ssm_D + ch0 + 8 * tid + rank);
  } else if (wg == 0) {
    if (tid < 85) sts128(sb + OFF_UX + (tid / 17) * UPITCH + (tid % 17) * 16, 0, 0, 0, 0);
  } else if (lane == 0 && w < 2) {
    tma_load4(sb + OFF_TQ + 10240 * w, &p.tq, ch0, 8 * rank + 4 * w, mb + 8 * (MB_XQ + w));
    TL(20);
  }
  uint32_t kid[9];
#pragma unroll
  for (int i = 0; i < 9; i++) {
    const int l = 8 * tid + i;
    kid[i] = pack((float)l, (float)(l + 1024)) - 0x42804280u;
    if (tid < 16) kid[i] = ((pack(128.f, (float)(l + 1024)) - 0x42804280u) & 0xffff0000u) | l;
    kid[i] *= 2;
  }
  TL(0);

  const uint32_t rbase = mapa(sb, g);
  const int mi = lane >> 3, tp = (lane & 7) >> 1, jj = lane & 1;
  const uint32_t toff = (4 * (7 - 2 * mi - jj) + tp) * 80;
  const uint32_t tab = sb + (wg == 0 ? OFF_PB : wg == 1 ? OFF_RAWA - 48 : OFF_HB4);
  const uint32_t kc = sb + OFF_KC + wg * 1408;
#pragma unroll 1
  for (int r = 0; r < 2; r++) {
    const int u = r ? uk1 : uk0;
    const uint32_t rla = r ? pla[1] : pla[0];
    if (threadIdx.x == 192 && (rla | (r << 16)) < 0x10000u) {
      tma_load4(sb + OFF_TK, &p.tk, ch0, 8 * rank - 1, mb + 8 * MB_KV);
      tma_load4(sb + OFF_TV, &p.tv, ch0, 8 * rank, mb + 8 * MB_KV);
    }
    __syncwarp();
    if (u < nu) {
      const float la = blo(rla), ai = blo(r ? pai[1] : pai[0]), cr = blo(r ? pcr[1] : pcr[0]), ci = blo(r ? pci[1] : pci[0]);
      const float dt = bf16r(expf(blo(r ? pdt[1] : pdt[0])));
      const float lr2 = (-bf16r(expf(la)) * dt) * 1.4426950408889634f;
      const float lt = (ai * dt) * 0.15915494309189535f;
      const uint32_t row = tab + tid * 16;
      if (lr2 != 123.f) TL(16 + 4 * r + 6);
      {
        const cf w1 = cexp_p(lr2, lt, 8.f);
        cf v[8];
        v[0].x = 1.f; v[0].y = 0.f; v[1] = w1; v[2] = cmul(w1, w1); v[3] = cmul(v[2], w1);
        const cf w4 = cmul(v[2], v[2]);
        v[4] = w4; v[5] = cmul(v[1], w4); v[6] = cmul(v[2], w4); v[7] = cmul(v[3], w4);
        const cf w8 = cmul(w4, w4);
        store8(row, v);
#pragma unroll
        for (int c = 1; c < 4; c++) {
#pragma unroll
          for (int i = 0; i < 8; i++) v[i] = (c == 1 && i == 0) ? w8 : cmul(v[i], w8);
          store8(row + 2048 * c, v);
        }
      }
      {
        cf z1 = cexp_p(lr2, lt, 1.f), Z = cexp_p(lr2, lt, 256.f);
        z1.y = -z1.y; Z.y = -Z.y;
        const cf z2 = cmul(z1, z1);
        cf h[8], v[8];
        h[0].x = 2.f * cr * dt; h[0].y = -2.f * ci * dt;
        h[1] = cmul(h[0], z1);
#pragma unroll
        for (int i = 2; i < 8; i++) h[i] = cmul(h[i - 2], z2);
        store8(row + 4 * 2048, h);
        v[0] = cmul(h[0], Z); v[1] = cmul(h[2], Z); v[2] = cmul(h[4], Z); v[3] = cmul(h[6], Z);
        v[4] = cmul(v[0], Z); v[5] = cmul(v[2], Z); v[6] = cmul(v[4], Z); v[7] = cmul(v[5], Z);
        store8(row + 5 * 2048, v);
        const cf Z2 = cmul(Z, Z);
        h[0] = cmul(v[4], Z2); h[1] = cmul(v[6], Z2); h[2] = cmul(h[0], Z2); h[3] = cmul(h[1], Z2); h[4] = cmul(h[2], Z2);
        h[5].x = h[5].y = h[6].x = h[6].y = h[7].x = h[7].y = 0.f;
        store8(row + 6 * 2048, h);
      }
    }
    TL(16 + 4 * r + 7);
    if (u < nu) {
      fence_async();
      bar_sync(NB_WG0 + wg, 128);
    }
    if (r == 0) {
      cluster_wait();
      if (wg) mbar_wait(mb + 8 * (MB_XQ + wg - 1));
      TL(13);
    }
    float c[12];
    const uint64_t da = (uint64_t)((tab & 0x3FFFF) >> 4) | ((uint64_t)(KTAB / 32) << 16) | (128ull << 32);
    uint32_t xr[5][4];
    const int ah = 4 * (wg - 1) + w;
    if (r == 0 && wg) {
#pragma unroll
      for (int k = 0; k < 5; k++) ldsm4t(xr[k], sb + OFF_TQ + ah * 2560 + toff + 16 * k);
      st_async4(rbase + OFF_UX + UPAD + 16 * (32 * rank + 4 * ah + t), xr[0][0], xr[0][1], xr[0][2], xr[0][3], rbase + OFF_MB + 8 * MB_UX);
    }
    wg_fence();
    kgen_mma<0>(c, da);
    wg_commit();
    if (r == 0 && wg) {
#pragma unroll
      for (int k = 1; k < 5; k++)
        if (k < nu) st_async4(rbase + OFF_UX + k * UPITCH + UPAD + 16 * (32 * rank + 4 * ah + t), xr[k][0], xr[k][1], xr[k][2], xr[k][3], rbase + OFF_MB + 8 * (MB_UX + k));
      TL(15);
    }
    wg_wait<0>();
    if (u < nu) {
      if (tid == 0) c[0] += blo(r ? pds[1] : pds[0]);
      if (w < 2) {
#pragma unroll
        for (int hh = 0; hh < 2; hh++) {
          const int a = 16 * w + g + 8 * hh;
          sts32(kc + 4 * (4 * a + t), pack(c[2 * hh], c[2 * hh + 1]));
          sts32(kc + 4 * (t < 2 ? 128 + 2 * a + t : 128 + 32 * t + a), pack(c[4 + 2 * hh], c[5 + 2 * hh]));
          if (t < 3) {
            const uint32_t p0 = pack(c[8 + 2 * hh], c[9 + 2 * hh]);
            sts16(kc + 2 * (512 + 64 * t + a), p0);
            sts16(kc + 2 * (544 + 64 * t + a), p0 >> 16);
          }
        }
      }
      TL(16 + 4 * r + 8);
      bar_sync(NB_WG0 + wg, 128);
      const uint32_t hs = sb + (r ? (wg == 1 ? OFF_HB3 : OFF_HB4) : OFF_HB + u * 2 * HPITCH);
      uint32_t v[2][9];
#pragma unroll
      for (int cc = 0; cc < 2; cc++)
#pragma unroll
        for (int i = 0; i < 9; i++) v[cc][i] = lds16(kc + (cc ? kid[i] >> 16 : kid[i] & 0xffffu));
#pragma unroll
      for (int cc = 0; cc < 2; cc++) {
        const uint32_t o = hs + 16 + 16 * (tid + 128 * cc);
        sts128(o + HPITCH, prmt(v[cc][0], v[cc][1], 0x5410), prmt(v[cc][2], v[cc][3], 0x5410), prmt(v[cc][4], v[cc][5], 0x5410), prmt(v[cc][6], v[cc][7], 0x5410));
        sts128(o, prmt(v[cc][1], v[cc][2], 0x5410), prmt(v[cc][3], v[cc][4], 0x5410), prmt(v[cc][5], v[cc][6], 0x5410), prmt(v[cc][7], v[cc][8], 0x5410));
      }
      if (tid == 0) { sts128(hs + HPITCH, 0, 0, 0, 0); sts128(hs, 0, 0, 0, v[0][0] << 16); }
      if (wg == 2) bar_arrive(NB_HB2 + r, 256);
    }
    TL(1 + r);
    if (wg == 0) break;
  }

  if (wg < 2) {
    if (wg == 0) {
      if (tid < 64) sts128(sb + OFF_PB + tid * 528, 0, 0, 0, 0);
      bar_arrive(NB_PB1, 256);
    } else {
      if (tid == 0) {
        asm volatile("cp.async.bulk.tensor.4d.shared::cluster.global.mbarrier::complete_tx::bytes [%0], [%1, {%3, %4, %5, %6}], [%2];"
                     :: "r"(sb + OFF_RAWA - 48), "l"(&p.th), "r"(mb + 8 * MB_HA), "r"(0), "r"(-1), "r"(5 * cl), "r"(rank) : "memory");
      }
      __syncwarp();
      bar_sync(NB_PB1, 256);
    }
    cluster_arrive();
    bar_sync(NB_WG0 + wg, 128);
    const uint32_t haoff = 4 * (8 * w + ((g + 1) >> 1) + t);
    const uint32_t pw = sb + OFF_PB + wg * PBSZ + 4 * ((w * 8 + g) * 132 + t + w);
    const uint32_t pr = sb + OFF_PB + wg * PBSZ + w * 1056 + lane * 16;
    uint32_t ha = sb + OFF_HB + (2 * wg + (g & 1)) * HPITCH + haoff;
    uint32_t Q0[16], Q1[16], Q2[16], Q3[16];
    float X[32], Y[32], Z[32], cy0 = 0.f, cy1 = 0.f;
#pragma unroll
    for (int l = 0; l < 16; l++) Q0[l] = lds32(ha + aoff(l));
#pragma unroll
    for (int l = 0; l < 8; l++) Q1[l] = lds32(ha + 1024 + aoff(l));
    mbar_wait(mb + 8 * (MB_UX + wg));
    fence_async();
#pragma unroll 1
    for (int i = wg; i < 2 * nu; i += 2) {
      const bool isA = i >= nu;
      const int u = isA ? i - nu : i;
      const uint32_t ub = sb + (isA ? OFF_UKV : OFF_UX) + u * UPITCH;
      const uint64_t db = (uint64_t)((ub & 0x3FFFF) >> 4) | (1ull << 16) | (8ull << 32);
      TL(3 + (i >> 1));
      block<0, 0, 8, 16, 0, 0, 0>(X, Q0, db, Q1, ha + 1024, Z, cy0, cy1, pw);
      bar_sync(NB_WG0 + wg, 128);
      block<1, 0, 0, 5, 0, 0, 4>(Y, Q0, db, Q2, ha + 2048, X, cy0, cy1, pw);
      block<1, 1, 5, 10, 0, 4, 8>(Y, Q1, db, Q2, ha + 2048, X, cy0, cy1, pw);
      block<2, 0, 10, 16, 1, 0, 3>(X, Q0, db, Q2, ha + 2048, Y, cy0, cy1, pw);
      block<2, 1, 0, 6, 1, 3, 6>(X, Q1, db, Q3, ha + 3072, Y, cy0, cy1, pw);
      block<2, 2, 6, 11, 1, 6, 8>(X, Q2, db, Q3, ha + 3072, Y, cy0, cy1, pw);
      block<3, 0, 11, 16, 2, 0, 4>(Z, Q0, db, Q3, ha + 3072, X, cy0, cy1, pw);
      const int n = i + 2;
      if (!isA && (n > 2 || n >= nu) && i <= 2) bar_arrive(NB_HBFREE, 384);
      if (n < nu) {
        if (wg == 0) bar_sync(n == 2 ? NB_HB2 : NB_HB4, 256);
        ha = sb + (n == 2 ? OFF_HB + 4 * HPITCH : n == 3 ? OFF_HB3 : OFF_HB4) + (g & 1) * HPITCH + haoff;
      } else if (n < 2 * nu) {
        mbar_wait(mb + 8 * MB_HRDY);
        ha = sb + ((g & 1) ? OFF_RAWA : OFF_HB) + (n - nu) * HPITCH + haoff;
      }
      block<3, 1, 0, 8, 2, 4, 6>(Z, Q1, db, Q0, ha, X, cy0, cy1, pw);
      block<3, 2, 8, 16, 2, 6, 8>(Z, Q2, db, Q0, ha, X, cy0, cy1, pw);
      block<3, 3, 0, 8, 0, 0, 0>(Z, Q3, db, Q1, ha + 1024, X, cy0, cy1, pw);
      wg_wait<0>();
      epi_tiles<3, 0, 8>(Z, cy0, cy1, pw);
      if (!isA) {
        if (i == wg) {
          for (int k = n; k < nu; k += 2) mbar_wait(mb + 8 * (MB_UX + k));
        }
        if (n >= nu) {
          for (int k = 0; k < nu; k++) mbar_wait(mb + 8 * (MB_UKV + k));
        }
        if (i == wg || n >= nu) fence_async();
      }
      bar_sync(NB_WG0 + wg, 128);
      uint4 pa[4], pb[4];
#pragma unroll
      for (int k = 0; k < 4; k++) { pa[k] = lds128(pr + k * 4224); pb[k] = lds128(pr + k * 4224 + 528); }
      const uint32_t yd = rbase + (isA ? OFF_YA : OFF_YB) + (8 * u + rank) * YPITCH + (8 * w + t) * 16;
      const uint32_t ym = rbase + OFF_MB + 8 * (MB_Y + u);
      st_async4(yd, sum4(pa[0].x, pa[1].x, pa[2].x, pa[3].x), sum4(pa[0].y, pa[1].y, pa[2].y, pa[3].y),
                sum4(pb[0].x, pb[1].x, pb[2].x, pb[3].x), sum4(pb[0].y, pb[1].y, pb[2].y, pb[3].y), ym);
      st_async4(yd + 64, sum4(pa[0].z, pa[1].z, pa[2].z, pa[3].z), sum4(pa[0].w, pa[1].w, pa[2].w, pa[3].w),
                sum4(pb[0].z, pb[1].z, pb[2].z, pb[3].z), sum4(pb[0].w, pb[1].w, pb[2].w, pb[3].w), ym);
      TL(8 + (i >> 1));
    }
    TL_DUMP();
  } else {
    if (tid < 40) { sts64(sb + OFF_SW + 8 * tid, swv.x, swv.y); sts16(sb + OFF_GW + 2 * tid, gwv); }
    else if (tid < 40 + 85) sts128(sb + OFF_UKV + ((tid - 40) / 17) * UPITCH + ((tid - 40) % 17) * 16, 0, 0, 0, 0);
    __syncwarp();
    cluster_arrive();
    bar_sync(NB_WG0 + 2, 128);
    mbar_wait(mb + 8 * MB_XQ);
    mbar_wait(mb + 8 * (MB_XQ + 1));
    {
      float s0 = 0.f, s1 = 0.f;
#pragma unroll
      for (int j = 0; j < 5; j++) {
        const uint4 gw = lds128(sb + OFF_GW + 16 * j);
        const uint4 x0 = lds128(sb + OFF_TQ + tid * 80 + 16 * j), x1 = lds128(sb + OFF_TQ + (tid + 128) * 80 + 16 * j);
        uint32_t m0 = hmul2(x0.x, gw.x), m1 = hmul2(x0.y, gw.y), m2 = hmul2(x0.z, gw.z), m3 = hmul2(x0.w, gw.w);
        s0 += ((blo(m0) + bhi(m0)) + (blo(m1) + bhi(m1))) + ((blo(m2) + bhi(m2)) + (blo(m3) + bhi(m3)));
        m0 = hmul2(x1.x, gw.x); m1 = hmul2(x1.y, gw.y); m2 = hmul2(x1.z, gw.z); m3 = hmul2(x1.w, gw.w);
        s1 += ((blo(m0) + bhi(m0)) + (blo(m1) + bhi(m1))) + ((blo(m2) + bhi(m2)) + (blo(m3) + bhi(m3)));
      }
      __stcg(&g_part[cl * SEQ + rank * 256 + tid], s0);
      __stcg(&g_part[cl * SEQ + rank * 256 + 128 + tid], s1);
    }
    TL(3);
    cluster_wait();
    mbar_wait(mb + 8 * MB_KV);
    TL(4);
    const uint32_t hoff = (4 * (7 - 2 * (mi & 1) - jj) + ((tp + 3) & 3)) * 80 + (tp ? 2560 : 0);
#pragma unroll 1
    for (int u = 0; u < nu; u++) {
      const uint2 sw = lds64(sb + OFF_SW + 8 * (8 * u + g));
      uint32_t E[2][6], V[2][4];
#pragma unroll
      for (int hf = 0; hf < 2; hf++) {
        const int ah = 4 * hf + w;
        uint32_t K[4];
        ldsm4t(K, sb + OFF_TK + (ah + 1) * 2560 + toff + 16 * u);
        ldsm2t(E[hf][4], E[hf][5], sb + OFF_TK + ah * 2560 + hoff + 16 * u);
        ldsm4t(V[hf], sb + OFF_TV + ah * 2560 + toff + 16 * u);
        E[hf][0] = K[0]; E[hf][1] = K[1]; E[hf][2] = K[2]; E[hf][3] = K[3];
      }
      const uint32_t w0 = prmt(sw.x, 0, 0x1010), w1 = prmt(sw.x, 0, 0x3232), w2 = prmt(sw.y, 0, 0x1010), w3 = prmt(sw.y, 0, 0x3232);
#pragma unroll
      for (int hf = 0; hf < 2; hf++) {
        uint32_t O[5], o[4];
#pragma unroll
        for (int i = 0; i < 5; i++) O[i] = prmt(E[hf][i], E[hf][i + 1], 0x5432);
#pragma unroll
        for (int i = 0; i < 4; i++) {
          uint32_t s = hmul2(O[i + 1], w3);
          s = hadd2(s, hmul2(E[hf][i + 1], w2));
          s = hadd2(s, hmul2(O[i], w1));
          s = hadd2(s, hmul2(E[hf][i], w0));
          o[i] = hmul2(s, V[hf][i]);
        }
        st_async4(rbase + OFF_UKV + u * UPITCH + UPAD + 16 * (32 * rank + 16 * hf + 4 * w + t), o[0], o[1], o[2], o[3], rbase + OFF_MB + 8 * (MB_UKV + u));
      }
    }
    TL(5);
    mbar_wait(mb + 8 * MB_HA);
    bar_sync(NB_HBFREE, 384);
    TL(6);
    unsigned g_target = 0;
#pragma unroll 1
    for (int u = 0; u < nu; u++) {
      const uint32_t ra = sb + OFF_RAWA + u * HPITCH + 16 + 16 * tid;
      const uint4 x = lds128(ra), y = lds128(ra + 2048);
      const uint32_t xn = lds32(ra + 16), yn = lds32(ra + 2048 + 16);
      const uint32_t o = sb + OFF_HB + u * HPITCH + 16 + 16 * tid;
      sts128(o, prmt(x.x, x.y, 0x5432), prmt(x.y, x.z, 0x5432), prmt(x.z, x.w, 0x5432), prmt(x.w, xn, 0x5432));
      sts128(o + 2048, prmt(y.x, y.y, 0x5432), prmt(y.y, y.z, 0x5432), prmt(y.z, y.w, 0x5432), prmt(y.w, yn, 0x5432));
    }
    if (tid < nu) {
      const uint32_t ra = sb + OFF_RAWA + tid * HPITCH + 16;
      const uint32_t h0 = pack(blo(lds16(ra)) + blo(dval), 0.f);
      sts16(ra, h0);
      sts128(sb + OFF_HB + tid * HPITCH, 0, 0, 0, h0 << 16);
    }
    __syncwarp();
    if (lane == 0) mbar_arrive(mb + 8 * MB_HRDY);
    TL(7);
    uint32_t okflag = 1;
    if (tid == 0) {
      __threadfence();
      const unsigned old = atomicAdd(&g_cnt[rank * 32], cl == 0 ? 16 - (NCL - 1) : 1);
      g_target = (old & ~15u) + 16;
      unsigned v;
      int it = 0;
      do {
        asm volatile("ld.acquire.gpu.global.u32 %0, [%1];" : "=r"(v) : "l"(&g_cnt[rank * 32]) : "memory");
      } while ((int)(v - g_target) < 0 && ++it < 20000);
      okflag = (int)(v - g_target) >= 0;
    }
    asm volatile("{.reg .pred p, q; setp.ne.u32 p, %1, 0; bar.red.and.pred q, %2, 128, p; selp.u32 %0, 1, 0, q;}" : "=r"(okflag) : "r"(okflag), "r"(NB_WG0 + 2) : "memory");
    {
      float s[2] = {0.f, 0.f};
      if (okflag) {
        float2 v[NCL];
#pragma unroll
        for (int c = 0; c < NCL; c++) v[c] = __ldcg((const float2*)&g_part[c * SEQ + rank * 256 + 2 * tid]);
#pragma unroll
        for (int c = 0; c < NCL; c++) { s[0] += v[c].x; s[1] += v[c].y; }
      } else {
#pragma unroll 1
        for (int hf = 0; hf < 2; hf++) {
          const int slot = 2 * tid + hf;
          const int row = rank * 256 + (slot & ~31) + 8 * (slot & 3) + ((slot >> 2) & 7);
          const uint32_t* xr = (const uint32_t*)(p.q + (size_t)row * DCH);
          const uint32_t* gr = (const uint32_t*)p.gate_w;
          float a = 0.f;
#pragma unroll 1
          for (int c = 0; c < DCH / 2; c++) { const uint32_t m = hmul2(__ldg(xr + c), __ldg(gr + c)); a += blo(m) + bhi(m); }
          if (hf) s[1] = a; else s[0] = a;
        }
      }
      const float g0 = bf16r(sigmoidf_(bf16r(s[0]))), g1 = bf16r(sigmoidf_(bf16r(s[1])));
      sts128(sb + OFF_KC + 16 * tid, pack(g0, g0), pack(1.f - g0, 1.f - g0), pack(g1, g1), pack(1.f - g1, 1.f - g1));
    }
    __syncwarp();
    uint2 gg[2][4];
#pragma unroll
    for (int hh = 0; hh < 2; hh++)
#pragma unroll
      for (int i = 0; i < 4; i++) gg[hh][i] = lds64(sb + OFF_KC + 8 * (64 * w + 32 * hh + 8 * i + g));
    TL(8);
#pragma unroll 1
    for (int u = 0; u < nu; u++) {
      uint32_t qv[2][4];
      const uint32_t qa = sb + OFF_TQ + (64 * w + lane) * 80 + 16 * u;
      ldsm4(qv[0], qa);
      ldsm4(qv[1], qa + 2560);
      mbar_wait(mb + 8 * (MB_Y + u));
      uint32_t ya[2][4], yb[2][4];
      const uint32_t yo = (8 * u + (lane & 7)) * YPITCH + (8 * mi + w) * 16;
#pragma unroll
      for (int hh = 0; hh < 2; hh++) { ldsm4t(ya[hh], sb + OFF_YA + yo + 64 * hh); ldsm4t(yb[hh], sb + OFF_YB + yo + 64 * hh); }
#pragma unroll
      for (int hh = 0; hh < 2; hh++) {
        uint32_t o[4];
#pragma unroll
        for (int i = 0; i < 4; i++) o[i] = hadd2(hmul2(gg[hh][i].x, hmul2(qv[hh][i], ya[hh][i])), hmul2(gg[hh][i].y, yb[hh][i]));
        stsm4(qa + 2560 * hh, o);
      }
      TL(9 + (u < 4 ? u : 8));
    }
    fence_async();
    __syncwarp();
    if (lane == 0) {
      tma_store4(&p.to, ch0, 8 * rank + 2 * w, sb + OFF_TQ + w * 5120);
      asm volatile("cp.async.bulk.commit_group;" ::: "memory");
      asm volatile("cp.async.bulk.wait_group.read 0;" ::: "memory");
    }
    TL(14);
    TL_DUMP();
  }
}

typedef CUresult (*EncodeFn)(CUtensorMap*, CUtensorMapDataType, cuuint32_t, void*, const cuuint64_t*, const cuuint64_t*,
                             const cuuint32_t*, const cuuint32_t*, CUtensorMapInterleave, CUtensorMapSwizzle,
                             CUtensorMapL2promotion, CUtensorMapFloatOOBfill);

void make_map(EncodeFn fn, CUtensorMap* tm, const void* ptr, int nhi) {
  cuuint64_t dims[4] = {DCH, 4, 8, SEQ / 32};
  cuuint64_t strides[3] = {8 * DCH * 2, DCH * 2, 32 * DCH * 2};
  cuuint32_t box[4] = {CPC, 4, 8, (cuuint32_t)nhi};
  cuuint32_t es[4] = {1, 1, 1, 1};
  fn(tm, CU_TENSOR_MAP_DATA_TYPE_BFLOAT16, 4, const_cast<void*>(ptr), dims, strides, box, es, CU_TENSOR_MAP_INTERLEAVE_NONE,
     CU_TENSOR_MAP_SWIZZLE_NONE, CU_TENSOR_MAP_L2_PROMOTION_L2_128B, CU_TENSOR_MAP_FLOAT_OOB_FILL_NONE);
}

}

extern "C" void kernel_launch(void* const* d_in, const int* in_sizes, int n_in, void* d_out, int out_size) {
  (void)in_sizes; (void)n_in; (void)out_size;
  static EncodeFn fn = nullptr;
  if (!fn) {
    cudaDriverEntryPointQueryResult qr;
    cudaGetDriverEntryPoint("cuTensorMapEncodeTiled", (void**)&fn, cudaEnableDefault, &qr);
    cudaFuncSetAttribute(fused_kernel, cudaFuncAttributeMaxDynamicSharedMemorySize, SMEM_BYTES);
  }
  Params p;
  make_map(fn, &p.tq, d_in[0], 4);
  make_map(fn, &p.tk, d_in[1], 9);
  make_map(fn, &p.tv, d_in[2], 8);
  {
    cuuint64_t dims[4] = {32, SEQ / 32, DCH / 8, 8};
    cuuint64_t strides[3] = {64, 8 * SEQ * 2, SEQ * 2};
    cuuint32_t box[4] = {32, 65, 5, 1};
    cuuint32_t es[4] = {1, 1, 1, 1};
    fn(&p.th, CU_TENSOR_MAP_DATA_TYPE_BFLOAT16, 4, d_in[4], dims, strides, box, es, CU_TENSOR_MAP_INTERLEAVE_NONE,
       CU_TENSOR_MAP_SWIZZLE_NONE, CU_TENSOR_MAP_L2_PROMOTION_L2_128B, CU_TENSOR_MAP_FLOAT_OOB_FILL_NONE);
  }
  make_map(fn, &p.to, d_out, 2);
  p.q = (const __nv_bfloat16*)d_in[0];
  p.shift_k = (const __nv_bfloat16*)d_in[3];
  p.ssm_D = (const __nv_bfloat16*)d_in[5];
  p.logA = (const __nv_bfloat16*)d_in[7];
  p.Aim = (const __nv_bfloat16*)d_in[8];
  p.Cre = (const __nv_bfloat16*)d_in[9];
  p.Cim = (const __nv_bfloat16*)d_in[10];
  p.logdt = (const __nv_bfloat16*)d_in[11];
  p.Dskip = (const __nv_bfloat16*)d_in[12];
  p.gate_w = (const __nv_bfloat16*)d_in[13];
  fused_kernel<<<NCL * CS, NTHREADS, SMEM_BYTES, cudaStreamPerThread>>>(p);
}
```

```cpp
#include <cuda_runtime.h>
#include <cuda_bf16.h>
#include <cuda.h>
#include <stdint.h>

#define TIMELINE 0

namespace {

constexpr int SEQ = 2048, DCH = 576, NMODE = 128;
constexpr int CS = 8, CPC = 40, NCL = 15, NTHREADS = 512;

constexpr int YPITCH = 528;
constexpr int KTAB = 28672;
constexpr int OFF_T = 0;
constexpr int OFF_UKV = 2 * KTAB + 8192;
constexpr int OFF_UX = 3 * KTAB;
constexpr int OFF_HA = OFF_UX + 20480;
constexpr int OFF_CF = OFF_HA + 20480;
constexpr int OFF_CL = OFF_CF + 8192;
constexpr int OFF_TQ = OFF_CL + 4096;
constexpr int OFF_TK = OFF_TQ + 20480;
constexpr int OFF_YA = OFF_TK;
constexpr int OFF_TV = OFF_TK + 23040;
constexpr int OFF_YB = OFF_TV + 20480;
constexpr int OFF_KC = OFF_YB + 40 * YPITCH;
constexpr int OFF_SW = OFF_KC + 3 * 1408;
constexpr int OFF_GW = OFF_SW + 320;
constexpr int OFF_MB = OFF_GW + 80;
constexpr int OFF_TL = OFF_MB + 24 * 8;
constexpr int SMEM_BYTES = OFF_TL + (TIMELINE ? 2048 : 0);
static_assert(SMEM_BYTES <= 232448, "smem");
static_assert((KTAB & 1023) == 0 && (OFF_TQ & 127) == 0 && (OFF_TK & 127) == 0 && (OFF_TV & 127) == 0 && (OFF_MB & 7) == 0 && (OFF_KC & 15) == 0, "align");

enum { MB_UX = 0, MB_UKV = 5, MB_Y = 10, MB_Q2 = 15, MB_XQ = 16, MB_KV = 18, MB_HA = 19, MB_COUNT = 20 };
enum { NB_WG0 = 1, NB_CONST = 5 };

struct Params {
  const __nv_bfloat16 *logA, *Aim, *Cre, *Cim, *logdt, *Dskip, *shift_k, *ssm_D, *gate_w, *q;
  CUtensorMap tq, tk, tv, th, tq2, to;
};

__device__ float g_part[NCL * SEQ];
__device__ unsigned g_cnt[CS * 32];
#define TL(i) do {} while (0)
#define TL_INIT() do {} while (0)
#define TL_DUMP() do {} while (0)

__device__ __forceinline__ uint32_t lds16(uint32_t a) { uint32_t v; asm volatile("ld.shared.u16 %0, [%1];" : "=r"(v) : "r"(a) : "memory"); return v; }
__device__ __forceinline__ uint2 lds64(uint32_t a) { uint2 v; asm volatile("ld.shared.v2.u32 {%0,%1}, [%2];" : "=r"(v.x), "=r"(v.y) : "r"(a) : "memory"); return v; }
__device__ __forceinline__ uint4 lds128(uint32_t a) { uint4 v; asm volatile("ld.shared.v4.u32 {%0,%1,%2,%3}, [%4];" : "=r"(v.x), "=r"(v.y), "=r"(v.z), "=r"(v.w) : "r"(a) : "memory"); return v; }
__device__ __forceinline__ void sts16(uint32_t a, uint32_t v) { asm volatile("st.shared.u16 [%0], %1;" :: "r"(a), "r"(v) : "memory"); }
__device__ __forceinline__ void sts32(uint32_t a, uint32_t v) { asm volatile("st.shared.u32 [%0], %1;" :: "r"(a), "r"(v) : "memory"); }
__device__ __forceinline__ void sts64(uint32_t a, uint32_t x, uint32_t y) { asm volatile("st.shared.v2.u32 [%0], {%1,%2};" :: "r"(a), "r"(x), "r"(y) : "memory"); }
__device__ __forceinline__ void sts128(uint32_t a, uint32_t x, uint32_t y, uint32_t z, uint32_t w) { asm volatile("st.shared.v4.u32 [%0], {%1,%2,%3,%4};" :: "r"(a), "r"(x), "r"(y), "r"(z), "r"(w) : "memory"); }
__device__ __forceinline__ void ldsm4t(uint32_t (&r)[4], uint32_t a) { asm volatile("ldmatrix.sync.aligned.m8n8.x4.trans.shared.b16 {%0,%1,%2,%3}, [%4];" : "=r"(r[0]), "=r"(r[1]), "=r"(r[2]), "=r"(r[3]) : "r"(a) : "memory"); }
__device__ __forceinline__ void ldsm2t(uint32_t& r0, uint32_t& r1, uint32_t a) { asm volatile("ldmatrix.sync.aligned.m8n8.x2.trans.shared.b16 {%0,%1}, [%2];" : "=r"(r0), "=r"(r1) : "r"(a) : "memory"); }
__device__ __forceinline__ void ldsm4(uint32_t (&r)[4], uint32_t a) { asm volatile("ldmatrix.sync.aligned.m8n8.x4.shared.b16 {%0,%1,%2,%3}, [%4];" : "=r"(r[0]), "=r"(r[1]), "=r"(r[2]), "=r"(r[3]) : "r"(a) : "memory"); }
__device__ __forceinline__ void stsm4(uint32_t a, const uint32_t (&r)[4]) { asm volatile("stmatrix.sync.aligned.m8n8.x4.shared.b16 [%0], {%1,%2,%3,%4};" :: "r"(a), "r"(r[0]), "r"(r[1]), "r"(r[2]), "r"(r[3]) : "memory"); }
__device__ __forceinline__ uint32_t pack(float lo, float hi) { uint32_t r; asm("cvt.rn.bf16x2.f32 %0, %1, %2;" : "=r"(r) : "f"(hi), "f"(lo)); return r; }
__device__ __forceinline__ float blo(uint32_t v) { return __uint_as_float(v << 16); }
__device__ __forceinline__ float bhi(uint32_t v) { return __uint_as_float(v & 0xffff0000u); }
__device__ __forceinline__ float bf16r(float x) { return blo(pack(x, 0.f)); }
__device__ __forceinline__ uint32_t hmul2(uint32_t a, uint32_t b) { uint32_t r; asm("mul.rn.bf16x2 %0, %1, %2;" : "=r"(r) : "r"(a), "r"(b)); return r; }
__device__ __forceinline__ uint32_t hadd2(uint32_t a, uint32_t b) { uint32_t r; asm("add.rn.bf16x2 %0, %1, %2;" : "=r"(r) : "r"(a), "r"(b)); return r; }
__device__ __forceinline__ uint32_t hfma2(uint32_t a, uint32_t b, uint32_t c) { uint32_t r; asm("fma.rn.bf16x2 %0, %1, %2, %3;" : "=r"(r) : "r"(a), "r"(b), "r"(c)); return r; }
__device__ __forceinline__ uint32_t prmt(uint32_t a, uint32_t b, uint32_t s) { return __byte_perm(a, b, s); }
__device__ __forceinline__ uint32_t ldraw(const __nv_bfloat16* p) { uint32_t v; asm volatile("ld.global.nc.u16 %0, [%1];" : "=r"(v) : "l"(p)); return v; }
__device__ __forceinline__ void bar_sync(int id, int n) { asm volatile("bar.sync %0, %1;" :: "r"(id), "r"(n) : "memory"); }
__device__ __forceinline__ void bar_arrive(int id, int n) { asm volatile("bar.arrive %0, %1;" :: "r"(id), "r"(n) : "memory"); }
__device__ __forceinline__ void cluster_arrive() { asm volatile("barrier.cluster.arrive.relaxed.aligned;" ::: "memory"); }
__device__ __forceinline__ void cluster_wait() { asm volatile("barrier.cluster.wait.aligned;" ::: "memory"); }
__device__ __forceinline__ void fence_async() { asm volatile("fence.proxy.async.shared::cta;" ::: "memory"); }
__device__ __forceinline__ void fence_mbinit() { asm volatile("fence.mbarrier_init.release.cluster;" ::: "memory"); }
__device__ __forceinline__ uint32_t mapa(uint32_t a, uint32_t rank) { uint32_t r; asm("mapa.shared::cluster.u32 %0, %1, %2;" : "=r"(r) : "r"(a), "r"(rank)); return r; }
__device__ __forceinline__ void st_async4(uint32_t a, uint32_t x, uint32_t y, uint32_t z, uint32_t w, uint32_t mbar) {
  asm volatile("st.async.weak.shared::cluster.mbarrier::complete_tx::bytes.v4.b32 [%0], {%1,%2,%3,%4}, [%5];"
               :: "r"(a), "r"(x), "r"(y), "r"(z), "r"(w), "r"(mbar) : "memory");
}
__device__ __forceinline__ void mbar_init(uint32_t m, uint32_t cnt) { asm volatile("mbarrier.init.shared::cta.b64 [%0], %1;" :: "r"(m), "r"(cnt) : "memory"); }
__device__ __forceinline__ void mbar_expect(uint32_t m, uint32_t bytes) { asm volatile("mbarrier.arrive.expect_tx.shared::cta.b64 _, [%0], %1;" :: "r"(m), "r"(bytes) : "memory"); }
__device__ __forceinline__ void mbar_wait(uint32_t m) {
  uint32_t done;
  int it = 0;
  do {
    asm volatile("{.reg .pred p; mbarrier.try_wait.parity.shared::cta.b64 p, [%1], 0; selp.u32 %0, 1, 0, p;}" : "=r"(done) : "r"(m) : "memory");
    if (++it > (1 << 22)) __trap();
  } while (!done);
}
__device__ __forceinline__ void tma_load4(uint32_t dst, const CUtensorMap* tm, int c0, int c1, int c2, int c3, uint32_t mbar) {
  asm volatile("cp.async.bulk.tensor.4d.shared::cluster.global.mbarrier::complete_tx::bytes [%0], [%1, {%3, %4, %5, %6}], [%2];"
               :: "r"(dst), "l"(tm), "r"(mbar), "r"(c0), "r"(c1), "r"(c2), "r"(c3) : "memory");
}
__device__ __forceinline__ void tma_load3(uint32_t dst, const CUtensorMap* tm, int c0, int c1, int c2, uint32_t mbar) {
  asm volatile("cp.async.bulk.tensor.3d.shared::cluster.global.mbarrier::complete_tx::bytes [%0], [%1, {%3, %4, %5}], [%2];"
               :: "r"(dst), "l"(tm), "r"(mbar), "r"(c0), "r"(c1), "r"(c2) : "memory");
}
__device__ __forceinline__ void tma_store3(const CUtensorMap* tm, int c0, int c1, int c2, uint32_t src) {
  asm volatile("cp.async.bulk.tensor.3d.global.shared::cta.bulk_group [%0, {%2, %3, %4}], [%1];"
               :: "l"(tm), "r"(src), "r"(c0), "r"(c1), "r"(c2) : "memory");
}
__device__ __forceinline__ void wg_fence() { asm volatile("wgmma.fence.sync.aligned;" ::: "memory"); }
__device__ __forceinline__ void wg_commit() { asm volatile("wgmma.commit_group.sync.aligned;" ::: "memory"); }
template <int N> __device__ __forceinline__ void wg_wait() { asm volatile("wgmma.wait_group.sync.aligned %0;" :: "n"(N) : "memory"); }
template <int N> __device__ __forceinline__ void tie_all(float (&x)[N]) {
#pragma unroll
  for (int i = 0; i < N; i++) asm volatile("" : "+f"(x[i]) :: "memory");
}
#define R16(C, d) C(d[0]), C(d[1]), C(d[2]), C(d[3]), C(d[4]), C(d[5]), C(d[6]), C(d[7]), C(d[8]), C(d[9]), C(d[10]), C(d[11]), C(d[12]), C(d[13]), C(d[14]), C(d[15])
#define R32(C, d) R16(C, d), R16(C, (d + 16))
#define P16 "{%0,%1,%2,%3,%4,%5,%6,%7,%8,%9,%10,%11,%12,%13,%14,%15}"
#define P32 "{%0,%1,%2,%3,%4,%5,%6,%7,%8,%9,%10,%11,%12,%13,%14,%15,%16,%17,%18,%19,%20,%21,%22,%23,%24,%25,%26,%27,%28,%29,%30,%31}"
template <int SD, int TB, int OFF> __device__ __forceinline__ void rs64(float* d, const uint32_t* a, uint64_t db) {
  if (SD) asm volatile("{.reg .b64 db; add.s64 db, %36, %37; wgmma.mma_async.sync.aligned.m64n64k16.f32.bf16.bf16 " P32 ", {%32,%33,%34,%35}, db, 1, 1, 1, %38;}"
                       : R32("+f", d) : "r"(a[0]), "r"(a[1]), "r"(a[2]), "r"(a[3]), "l"(db), "n"(OFF), "n"(TB));
  else asm volatile("{.reg .b64 db; add.s64 db, %36, %37; wgmma.mma_async.sync.aligned.m64n64k16.f32.bf16.bf16 " P32 ", {%32,%33,%34,%35}, db, 0, 1, 1, %38;}"
                    : R32("=f", d) : "r"(a[0]), "r"(a[1]), "r"(a[2]), "r"(a[3]), "l"(db), "n"(OFF), "n"(TB));
}
template <int SD, int OFFA, int OFFB> __device__ __forceinline__ void ss32(float* d, uint64_t da, uint64_t db) {
  if (SD) asm volatile("{.reg .b64 da, db; add.s64 da, %16, %18; add.s64 db, %17, %19; wgmma.mma_async.sync.aligned.m64n32k16.f32.bf16.bf16 " P16 ", da, db, 1, 1, 1, 1, 1;}"
                       : R16("+f", d) : "l"(da), "l"(db), "n"(OFFA), "n"(OFFB));
  else asm volatile("{.reg .b64 da, db; add.s64 da, %16, %18; add.s64 db, %17, %19; wgmma.mma_async.sync.aligned.m64n32k16.f32.bf16.bf16 " P16 ", da, db, 0, 1, 1, 1, 1;}"
                    : R16("=f", d) : "l"(da), "l"(db), "n"(OFFA), "n"(OFFB));
}
template <int KS> __device__ __forceinline__ void kgen_mma(float (&c)[12], uint64_t da) {
  asm volatile("{.reg .b64 da, db; add.s64 da, %12, %13; add.s64 db, %12, %14;\n"
               "wgmma.mma_async.sync.aligned.m64n24k16.f32.bf16.bf16 {%0,%1,%2,%3,%4,%5,%6,%7,%8,%9,%10,%11}, da, db, %15, 1, 1, 1, 1;}"
               : "+f"(c[0]), "+f"(c[1]), "+f"(c[2]), "+f"(c[3]), "+f"(c[4]), "+f"(c[5]), "+f"(c[6]), "+f"(c[7]), "+f"(c[8]), "+f"(c[9]), "+f"(c[10]), "+f"(c[11])
               : "l"(da), "n"(8 * KS), "n"(8 * KS + 512), "n"(KS ? 1 : 0));
  if constexpr (KS < 15) kgen_mma<KS + 1>(c, da);
}
__device__ __forceinline__ uint64_t desc_lo(uint32_t a) { return (uint64_t)((a & 0x3FFFF) >> 4); }
__device__ __forceinline__ void stage1(float (&D)[32], const uint32_t (&A1)[8], uint32_t src) {
  const uint64_t du = desc_lo(src) | (128ull << 16) | (32ull << 32) | (2ull << 62);
  rs64<0, 1, 0>(D, A1, du); rs64<1, 1, 64>(D, A1 + 4, du);
}
template <int INV> __device__ __forceinline__ void stage2(float (&X)[32], const uint32_t (&F)[16], uint32_t cf) {
  constexpr int KS = INV ? 16 : 128, TB = INV ? 0 : 1;
  const uint64_t dc = desc_lo(cf) | (INV ? (8ull << 16) | (64ull << 32) : (64ull << 16) | (8ull << 32));
  rs64<0, TB, 0>(X, F, dc); rs64<1, TB, KS>(X, F + 4, dc); rs64<1, TB, 2 * KS>(X, F + 8, dc); rs64<1, TB, 3 * KS>(X, F + 12, dc);
}
__device__ __forceinline__ void fwd_mid(uint32_t (&F)[16], const float (&D)[32], const uint32_t (&tp)[12]) {
#pragma unroll
  for (int j = 0; j < 4; j++)
#pragma unroll
    for (int b = 0; b < 2; b++) {
      const int i = 4 * j + 16 * b;
      const uint32_t ar = pack(D[i], D[i + 1]), ai = pack(D[i + 2], D[i + 3]);
      F[2 * j + b] = hfma2(ar, tp[3 * j], hmul2(ai, tp[3 * j + 2]));
      F[8 + 2 * j + b] = hfma2(ar, tp[3 * j + 1], hmul2(ai, tp[3 * j]));
    }
}

struct cf { float x, y; };
__device__ __forceinline__ cf cmul(cf a, cf b) { cf r; r.x = fmaf(a.x, b.x, -a.y * b.y); r.y = fmaf(a.x, b.y, a.y * b.x); return r; }
__device__ __forceinline__ cf cexp_p(float lr2, float lt, float p) {
  float m = exp2f(lr2 * p);
  float t = lt * p;
  t = (t - rintf(t)) * 6.283185307179586f;
  cf r; r.x = m * __cosf(t); r.y = m * __sinf(t); return r;
}
__device__ __forceinline__ void store8(uint32_t a, const cf (&v)[8]) {
  sts128(a, pack(v[0].x, v[1].x), pack(v[2].x, v[3].x), pack(v[4].x, v[5].x), pack(v[6].x, v[7].x));
  sts128(a + KTAB / 2, pack(v[0].y, v[1].y), pack(v[2].y, v[3].y), pack(v[4].y, v[5].y), pack(v[6].y, v[7].y));
}
__device__ __forceinline__ float cos128(int m) { return __cosf((float)((m + 64 & 127) - 64) * 0.04908738521234052f); }
__device__ __forceinline__ float sigmoidf_(float s) { return 1.f / (1.f + __expf(-s)); }

__global__ void __cluster_dims__(CS, 1, 1) __launch_bounds__(NTHREADS, 1) fused_kernel(const __grid_constant__ Params p) {
  extern __shared__ __align__(1024) uint8_t smem[];
  TL_INIT();
  TL(31);
  const uint32_t sb = (uint32_t)__cvta_generic_to_shared(smem);
  const uint32_t mb = sb + OFF_MB;
  const int wg = __shfl_sync(0xffffffffu, threadIdx.x >> 7, 0);
  const int tid = threadIdx.x & 127, w = __shfl_sync(0xffffffffu, tid >> 5, 0), lane = tid & 31, g = lane >> 2, t = lane & 3;
  const int cl = blockIdx.x >> 3, rank = blockIdx.x & 7;
  const int ch0 = cl * CPC;
  const int nu = min(5, (DCH - ch0) >> 3);

  if (wg < 3) {
    const int ua = wg == 2 ? 0 : wg + 1;
    uint32_t pla[2], pai[2], pcr[2], pci[2], pdt[2], pd[4];
#pragma unroll
    for (int r = 0; r < 2; r++) {
      const int ch = (wg + 3 * r < nu) ? ch0 + 8 * (wg + 3 * r) + rank : 0;
      pla[r] = ldraw(p.logA + ch * NMODE + tid);
      pai[r] = ldraw(p.Aim + ch * NMODE + tid);
      pcr[r] = ldraw(p.Cre + ch * NMODE + tid);
      pci[r] = ldraw(p.Cim + ch * NMODE + tid);
      pdt[r] = ldraw(p.logdt + ch);
      pd[r] = ldraw(p.Dskip + ch);
      pd[2 + r] = ldraw(p.ssm_D + ((ua + 3 * r < nu) ? ch0 + 8 * (ua + 3 * r) + rank : 0));
    }
    cluster_arrive();
    const int kk = 4 * (8 * w + g) + 1;
    uint32_t A1[8], tp[12];
#pragma unroll
    for (int q = 0; q < 4; q++) {
      const int m = (8 * q + 2 * t) * kk;
      A1[2 * q] = pack(cos128(m), cos128(m + kk));
      A1[2 * q + 1] = pack(cos128(m + 32), cos128(m + kk + 32));
      const float a0 = (float)((m + 2048 & 4095) - 2048) * 0.0015339807878856412f, a1 = (float)((m + kk + 2048 & 4095) - 2048) * 0.0015339807878856412f;
      tp[3 * q] = pack(__cosf(a0), __cosf(a1));
      tp[3 * q + 2] = pack(__sinf(a0), __sinf(a1));
      tp[3 * q + 1] = tp[3 * q + 2] ^ 0x80008000u;
    }
    TL(0);
    const uint32_t tab = sb + OFF_T + wg * KTAB;
#pragma unroll 1
    for (int job = 0; job < 4; job++) {
      const bool isA = job >= 2;
      const int u = (isA ? ua : wg) + 3 * (job & 1);
      if (!isA && u < nu) {
        const float la = blo(job ? pla[1] : pla[0]), ai = blo(job ? pai[1] : pai[0]), cr = blo(job ? pcr[1] : pcr[0]), ci = blo(job ? pci[1] : pci[0]);
        const float dt = bf16r(expf(blo(job ? pdt[1] : pdt[0])));
        const float lr2 = (-bf16r(expf(la)) * dt) * 1.4426950408889634f;
        const float lt = (ai * dt) * 0.15915494309189535f;
        const uint32_t row = tab + tid * 16;
        if (lr2 != 123.f) TL(16 + 4 * job);
        if (job) bar_sync(NB_WG0 + wg, 128);
        {
          const cf w1 = cexp_p(lr2, lt, 8.f);
          cf v[8];
          v[0].x = 1.f; v[0].y = 0.f; v[1] = w1; v[2] = cmul(w1, w1); v[3] = cmul(v[2], w1);
          const cf w4 = cmul(v[2], v[2]);
          v[4] = w4; v[5] = cmul(v[1], w4); v[6] = cmul(v[2], w4); v[7] = cmul(v[3], w4);
          const cf w8 = cmul(w4, w4);
          store8(row, v);
#pragma unroll
          for (int c = 1; c < 4; c++) {
#pragma unroll
            for (int i = 0; i < 8; i++) v[i] = (c == 1 && i == 0) ? w8 : cmul(v[i], w8);
            store8(row + 2048 * c, v);
          }
        }
        {
          cf z1 = cexp_p(lr2, lt, 1.f), Z = cexp_p(lr2, lt, 256.f);
          z1.y = -z1.y; Z.y = -Z.y;
          const cf z2 = cmul(z1, z1);
          cf h[8], v[8];
          h[0].x = 2.f * cr * dt; h[0].y = -2.f * ci * dt;
          h[1] = cmul(h[0], z1);
#pragma unroll
          for (int i = 2; i < 8; i++) h[i] = cmul(h[i - 2], z2);
          store8(row + 4 * 2048, h);
          v[0] = cmul(h[0], Z); v[1] = cmul(h[2], Z); v[2] = cmul(h[4], Z); v[3] = cmul(h[6], Z);
          v[4] = cmul(v[0], Z); v[5] = cmul(v[2], Z); v[6] = cmul(v[4], Z); v[7] = cmul(v[5], Z);
          store8(row + 5 * 2048, v);
          const cf Z2 = cmul(Z, Z);
          h[0] = cmul(v[4], Z2); h[1] = cmul(v[6], Z2); h[2] = cmul(h[0], Z2); h[3] = cmul(h[1], Z2); h[4] = cmul(h[2], Z2);
          h[5].x = h[5].y = h[6].x = h[6].y = h[7].x = h[7].y = 0.f;
          store8(row + 6 * 2048, h);
        }
        TL(17 + 4 * job);
        fence_async();
        bar_sync(NB_WG0 + wg, 128);
        float c[12];
        wg_fence();
        kgen_mma<0>(c, desc_lo(tab) | ((uint64_t)(KTAB / 32) << 16) | (128ull << 32));
        wg_commit();
        uint32_t kid[8];
#pragma unroll
        for (int i = 0; i < 8; i++) {
          const int l = 8 * tid + i;
          kid[i] = pack((float)(tid < 16 ? 128 : l), (float)(l + 1024)) - 0x42804280u;
          if (tid < 16) kid[i] += l - 128;
        }
        wg_wait<0>();
        const uint32_t kc = sb + OFF_KC + wg * 1408;
        if (w < 2) {
#pragma unroll
          for (int hh = 0; hh < 2; hh++) {
            const int a = 16 * w + g + 8 * hh;
            sts32(kc + 4 * (4 * a + t), pack(c[2 * hh], c[2 * hh + 1]));
            sts32(kc + 4 * (t < 2 ? 128 + 2 * a + t : 128 + 32 * t + a), pack(c[4 + 2 * hh], c[5 + 2 * hh]));
            if (t < 3) {
              const uint32_t p0 = pack(c[8 + 2 * hh], c[9 + 2 * hh]);
              sts16(kc + 2 * (512 + 64 * t + a), p0);
              sts16(kc + 2 * (544 + 64 * t + a), p0 >> 16);
            }
          }
        }
        TL(18 + 4 * job);
        bar_sync(NB_WG0 + wg, 128);
        uint32_t v[2][8];
#pragma unroll
        for (int i = 0; i < 8; i++) { v[0][i] = lds16(kc + 2 * (kid[i] & 0xffffu)); v[1][i] = lds16(kc + 2 * (kid[i] >> 16)); }
#pragma unroll
        for (int cc = 0; cc < 2; cc++)
          sts128(tab + 2048 * cc + 16 * (tid ^ ((tid >> 3) & 3)), prmt(v[cc][0], v[cc][1], 0x5410), prmt(v[cc][2], v[cc][3], 0x5410),
                 prmt(v[cc][4], v[cc][5], 0x5410), prmt(v[cc][6], v[cc][7], 0x5410));
        fence_async();
        if (job) bar_sync(NB_WG0 + wg, 128);
      }
      if (job == 0) {
        cluster_wait();
        cluster_arrive();
        bar_sync(NB_WG0 + wg, 128);
        bar_sync(NB_CONST + wg, 256);
      }
      if (u >= nu) continue;
      TL(1 + job);
      float D[32], H[32], X[32];
      uint32_t F[16];
      if (isA) mbar_wait(mb + 8 * MB_HA);
      wg_fence();
      stage1(D, A1, isA ? sb + OFF_HA + u * 4096 : tab);
      wg_commit();
      wg_wait<0>(); tie_all(D);
      fwd_mid(F, D, tp);
      mbar_wait(mb + 8 * ((isA ? MB_UKV : MB_UX) + u));
      fence_async();
      TL(5 + job);
      wg_fence();
      stage2<0>(H, F, sb + OFF_CF);
      stage1(D, A1, sb + (isA ? OFF_UKV : OFF_UX) + u * 4096);
      wg_commit();
      wg_wait<0>(); tie_all(D); tie_all(H);
      fwd_mid(F, D, tp);
      wg_fence();
      stage2<0>(X, F, sb + OFF_CF);
      wg_commit();
      {
        const float dsk = blo(job == 0 ? pd[0] : job == 1 ? pd[1] : job == 2 ? pd[2] : pd[3]);
#pragma unroll
        for (int j = 0; j < 4; j++) { H[4 * j] += dsk; H[4 * j + 1] += dsk; }
      }
      wg_wait<0>(); tie_all(X);
#pragma unroll
      for (int j = 0; j < 4; j++) {
        float pr[2], pi[2], qr[2], qi[2];
#pragma unroll
        for (int n = 0; n < 2; n++) {
          const int i = 4 * j + n;
          pr[n] = fmaf(X[i], H[i], -X[i + 16] * H[i + 16]);
          pi[n] = fmaf(X[i], H[i + 16], X[i + 16] * H[i]);
          qr[n] = fmaf(X[i + 2], H[i], fmaf(-X[i + 18], H[i + 16], fmaf(X[i], H[i + 2], fmaf(-X[i + 16], H[i + 18], -pi[n]))));
          qi[n] = fmaf(X[i + 2], H[i + 16], fmaf(X[i + 18], H[i], fmaf(X[i], H[i + 18], fmaf(X[i + 16], H[i + 2], pr[n]))));
        }
        F[2 * j] = pack(pr[0], pr[1]); F[2 * j + 1] = pack(qr[0], qr[1]); F[8 + 2 * j] = pack(pi[0], pi[1]); F[9 + 2 * j] = pack(qi[0], qi[1]);
      }
      wg_fence();
      stage2<1>(H, F, sb + OFF_CF);
      wg_commit();
      wg_wait<0>(); tie_all(H);
      {
        const uint32_t va = tab + (16 * w + (lane & 15)) * 128;
        const int vx = (lane >> 4) ^ (lane & 7);
#pragma unroll
        for (int j = 0; j < 4; j++) {
          uint32_t V[4];
#pragma unroll
          for (int b = 0; b < 2; b++) {
            const int i = 4 * j + 2 * b;
            const uint32_t er = pack(H[i], H[i + 1]), ei = pack(H[i + 16], H[i + 17]);
            V[2 * b] = hfma2(er, tp[3 * j], hmul2(ei, tp[3 * j + 1]));
            V[2 * b + 1] = hfma2(ei, tp[3 * j], hmul2(er, tp[3 * j + 2]));
          }
          stsm4(va + ((vx ^ (2 * j)) << 4), V);
        }
      }
      fence_async();
      bar_sync(NB_WG0 + wg, 128);
      float O[16];
      {
        const uint64_t dv = desc_lo(tab) | (1ull << 16) | (64ull << 32) | (1ull << 62);
        const uint64_t dl = desc_lo(sb + OFF_CL) | (32ull << 16) | (8ull << 32);
        wg_fence();
        ss32<0, 0, 0>(O, dv, dl); ss32<1, 128, 64>(O, dv, dl); ss32<1, 256, 128>(O, dv, dl); ss32<1, 384, 192>(O, dv, dl);
        wg_commit();
      }
      if (job == 2) {
        for (int k = 0; k < nu; k++) mbar_wait(mb + 8 * (MB_UKV + k));
      }
      wg_wait<0>(); tie_all(O);
      {
        const uint32_t yo = (isA ? OFF_YA : OFF_YB) + (8 * u + rank) * YPITCH + (8 * w + g) * 16, ym = OFF_MB + 8 * (MB_Y + u);
        const uint32_t r0 = mapa(sb, t), r1 = mapa(sb, t + 4);
        st_async4(r0 + yo, pack(O[0], O[1]), pack(O[4], O[5]), pack(O[8], O[9]), pack(O[12], O[13]), r0 + ym);
        st_async4(r1 + yo, pack(O[2], O[3]), pack(O[6], O[7]), pack(O[10], O[11]), pack(O[14], O[15]), r1 + ym);
      }
      TL(9 + job);
    }
    TL_DUMP();
  } else {
    if (lane == 0) {
#pragma unroll
      for (int i = 0; i < 4; i++) mbar_init(mb + 8 * (4 * w + i), 1);
      mbar_init(mb + 8 * (MB_XQ + w), 1);
      fence_mbinit();
      mbar_expect(mb + 8 * (MB_XQ + w), w < 2 ? 10240 : w == 2 ? 23040 + 20480 : 20480);
      if (w < 2) tma_load4(sb + OFF_TQ + 10240 * w, &p.tq, ch0, 0, 0, 8 * rank + 4 * w, mb + 8 * (MB_XQ + w));
#pragma unroll
      for (int i = 0; i < 4; i++) { const int b = 4 * w + i; mbar_expect(mb + 8 * b, b == MB_Q2 ? 20480 : b >= MB_Y ? 8192 : 4096); }
      TL(20);
    }
    __syncwarp();
    cluster_arrive();
    uint2 swv = make_uint2(0, 0);
    uint32_t gwv = 0;
    if (tid < 40 && ch0 + tid < DCH) { swv = __ldg((const uint2*)(p.shift_k + (size_t)(ch0 + tid) * 4)); gwv = ldraw(p.gate_w + ch0 + tid); }
#pragma unroll 1
    for (int k = 0; k < 6; k++) {
      const int q = tid + 128 * k;
      int m0, d0, d1;
      if (k < 4) {
        const int r = (q >> 6) * 8 + (q & 7), cc = (q >> 3) & 7;
        d0 = 4 * (r & 31); d1 = 2 * d0;
        m0 = 8 * (cc & 3) * d0 + ((r >> 5) == (cc >> 2) ? 0 : (r >> 5) ? -32 : 32);
      } else {
        const int r = ((q - 512) >> 5) * 8 + (q & 7), pc = (q >> 3) & 3;
        d0 = 4 * (8 * (r >> 4) + (r & 7)) + 1; d1 = 8 * d0;
        m0 = 2 * pc * d0 + ((r & 8) ? 32 : 0);
      }
      sts128(sb + OFF_CF + 16 * q, pack(cos128(m0), cos128(m0 + d0)), pack(cos128(m0 + d1), cos128(m0 + d1 + d0)),
             pack(cos128(m0 + 2 * d1), cos128(m0 + 2 * d1 + d0)), pack(cos128(m0 + 3 * d1), cos128(m0 + 3 * d1 + d0)));
    }
    if (lane == 0 && w >= 2) {
      if (w == 2) {
        tma_load4(sb + OFF_TK, &p.tk, ch0, 0, 0, 8 * rank - 1, mb + 8 * MB_KV);
        tma_load4(sb + OFF_TV, &p.tv, ch0, 0, 0, 8 * rank, mb + 8 * MB_KV);
      }
    }
    __syncwarp();
    if (tid < 40) { sts64(sb + OFF_SW + 8 * tid, swv.x, swv.y); sts16(sb + OFF_GW + 2 * tid, gwv); }
    fence_async();
    bar_arrive(NB_CONST + 0, 256); bar_arrive(NB_CONST + 1, 256); bar_arrive(NB_CONST + 2, 256);
    if (tid == 96) tma_load4(sb + OFF_HA, &p.th, 0, 0, 5 * cl, rank, mb + 8 * MB_HA);
    __syncwarp();
    TL(0);
    const uint32_t rbase = mapa(sb, g);
    const int mi = lane >> 3, tq = (lane & 7) >> 1, jj = lane & 1;
    const uint32_t toff = (4 * (2 * mi + jj) + tq) * 80;
    const uint32_t uoff = 16 * (32 * rank + 4 * w + (t ^ (w >> 1)));
    cluster_wait();
    cluster_arrive();
    mbar_wait(mb + 8 * MB_XQ);
    mbar_wait(mb + 8 * (MB_XQ + 1));
    TL(1);
    {
      uint32_t xr[5][2][4];
#pragma unroll
      for (int u = 0; u < 5; u++) { ldsm4t(xr[u][0], sb + OFF_TQ + w * 2560 + toff + 16 * u); ldsm4t(xr[u][1], sb + OFF_TQ + (w + 4) * 2560 + toff + 16 * u); }
#pragma unroll
      for (int u = 0; u < 5; u++)
        if (u < nu) {
          st_async4(rbase + OFF_UX + u * 4096 + uoff, xr[u][0][0], xr[u][0][1], xr[u][0][2], xr[u][0][3], rbase + OFF_MB + 8 * (MB_UX + u));
          st_async4(rbase + OFF_UX + u * 4096 + (uoff ^ 32) + 256, xr[u][1][0], xr[u][1][1], xr[u][1][2], xr[u][1][3], rbase + OFF_MB + 8 * (MB_UX + u));
        }
    }
    TL(2);
    bar_sync(NB_WG0 + 3, 128);
    {
      float s0 = 0.f, s1 = 0.f;
#pragma unroll
      for (int j = 0; j < 5; j++) {
        const uint4 gw = lds128(sb + OFF_GW + 16 * j);
        const uint4 x0 = lds128(sb + OFF_TQ + tid * 80 + 16 * j), x1 = lds128(sb + OFF_TQ + (tid + 128) * 80 + 16 * j);
        uint32_t m0 = hmul2(x0.x, gw.x), m1 = hmul2(x0.y, gw.y), m2 = hmul2(x0.z, gw.z), m3 = hmul2(x0.w, gw.w);
        s0 += ((blo(m0) + bhi(m0)) + (blo(m1) + bhi(m1))) + ((blo(m2) + bhi(m2)) + (blo(m3) + bhi(m3)));
        m0 = hmul2(x1.x, gw.x); m1 = hmul2(x1.y, gw.y); m2 = hmul2(x1.z, gw.z); m3 = hmul2(x1.w, gw.w);
        s1 += ((blo(m0) + bhi(m0)) + (blo(m1) + bhi(m1))) + ((blo(m2) + bhi(m2)) + (blo(m3) + bhi(m3)));
      }
      const int s2 = 8 * (8 * (lane & 3) + (lane >> 2)) + w;
      __stcg(&g_part[cl * SEQ + rank * 256 + s2], s0);
      __stcg(&g_part[cl * SEQ + rank * 256 + s2 + 4], s1);
    }
    bar_sync(NB_WG0 + 3, 128);
    unsigned g_target = 0;
    if (tid == 0) tma_load3(sb + OFF_TQ, &p.tq2, ch0, 8 * rank, 0, mb + 8 * MB_Q2);
    if (tid == 96) {
      __threadfence();
      const unsigned old = atomicAdd(&g_cnt[rank * 32], cl == 0 ? 16 - (NCL - 1) : 1);
      g_target = (old & ~15u) + 16;
    }
    __syncwarp();
    TL(3);
    cluster_wait();
    mbar_wait(mb + 8 * MB_KV);
    TL(4);
    const uint32_t hoff = (4 * (4 + 2 * (mi & 1) + jj) + ((tq + 3) & 3)) * 80 + (tq ? 2560 : 0);
#pragma unroll 1
    for (int u = 0; u < nu; u++) {
      const uint2 sw = lds64(sb + OFF_SW + 8 * (8 * u + g));
      uint32_t E[2][6], V[2][4];
#pragma unroll
      for (int hf = 0; hf < 2; hf++) {
        const int ah = 4 * hf + w;
        uint32_t K[4];
        ldsm4t(K, sb + OFF_TK + (ah + 1) * 2560 + toff + 16 * u);
        ldsm2t(E[hf][0], E[hf][1], sb + OFF_TK + ah * 2560 + hoff + 16 * u);
        ldsm4t(V[hf], sb + OFF_TV + ah * 2560 + toff + 16 * u);
        E[hf][2] = K[0]; E[hf][3] = K[1]; E[hf][4] = K[2]; E[hf][5] = K[3];
      }
      const uint32_t w0 = prmt(sw.x, 0, 0x1010), w1 = prmt(sw.x, 0, 0x3232), w2 = prmt(sw.y, 0, 0x1010), w3 = prmt(sw.y, 0, 0x3232);
#pragma unroll
      for (int hf = 0; hf < 2; hf++) {
        uint32_t O[5], o[4];
#pragma unroll
        for (int i = 0; i < 5; i++) O[i] = prmt(E[hf][i], E[hf][i + 1], 0x5432);
#pragma unroll
        for (int i = 0; i < 4; i++) {
          uint32_t s = hmul2(O[i], w3);
          s = hadd2(s, hmul2(E[hf][i + 1], w2));
          s = hadd2(s, hmul2(O[i + 1], w1));
          s = hadd2(s, hmul2(E[hf][i + 2], w0));
          o[i] = hmul2(s, V[hf][i]);
        }
        st_async4(rbase + OFF_UKV + u * 4096 + (hf ? (uoff ^ 32) + 256 : uoff), o[0], o[1], o[2], o[3], rbase + OFF_MB + 8 * (MB_UKV + u));
      }
    }
    TL(5);
    uint32_t okflag = 1;
    if (tid == 96) {
      unsigned v;
      int it = 0;
      do {
        asm volatile("ld.acquire.gpu.global.u32 %0, [%1];" : "=r"(v) : "l"(&g_cnt[rank * 32]) : "memory");
      } while ((int)(v - g_target) < 0 && ++it < 20000);
      okflag = (int)(v - g_target) >= 0;
    }
    asm volatile("{.reg .pred p, q; setp.ne.u32 p, %1, 0; bar.red.and.pred q, %2, 128, p; selp.u32 %0, 1, 0, q;}" : "=r"(okflag) : "r"(okflag), "r"(NB_WG0 + 3) : "memory");
    {
      float s[2] = {0.f, 0.f};
      if (okflag) {
        float2 v[NCL];
#pragma unroll
        for (int c = 0; c < NCL; c++) v[c] = __ldcg((const float2*)&g_part[c * SEQ + rank * 256 + 2 * tid]);
#pragma unroll
        for (int c = 0; c < NCL; c++) { s[0] += v[c].x; s[1] += v[c].y; }
      } else {
#pragma unroll 1
        for (int hf = 0; hf < 2; hf++) {
          const int slot = 2 * tid + hf;
          const int row = rank * 256 + 32 * (slot & 7) + (slot >> 3);
          const uint32_t* xr = (const uint32_t*)(p.q + (size_t)row * DCH);
          const uint32_t* gr = (const uint32_t*)p.gate_w;
          float a = 0.f;
#pragma unroll 1
          for (int c = 0; c < DCH / 2; c++) { const uint32_t m = hmul2(__ldg(xr + c), __ldg(gr + c)); a += blo(m) + bhi(m); }
          if (hf) s[1] = a; else s[0] = a;
        }
      }
      const float g0 = bf16r(sigmoidf_(bf16r(s[0]))), g1 = bf16r(sigmoidf_(bf16r(s[1])));
      const float a0 = g0 * 0.0009765625f, b0 = bf16r(1.f - g0) * 0.0009765625f, a1 = g1 * 0.0009765625f, b1 = bf16r(1.f - g1) * 0.0009765625f;
      sts128(sb + OFF_TV + 16 * tid, pack(a0, a0), pack(b0, b0), pack(a1, a1), pack(b1, b1));
    }
    __syncwarp();
    uint2 gg[2][4];
#pragma unroll
    for (int hh = 0; hh < 2; hh++)
#pragma unroll
      for (int i = 0; i < 4; i++) gg[hh][i] = lds64(sb + OFF_TV + 8 * (64 * w + 32 * hh + 8 * i + g));
    mbar_wait(mb + 8 * MB_Q2);
    TL(8);
#pragma unroll 1
    for (int u = 0; u < nu; u++) {
      uint32_t qv[2][4];
      const uint32_t qa = sb + OFF_TQ + (64 * w + lane) * 80 + 16 * u;
      ldsm4(qv[0], qa);
      ldsm4(qv[1], qa + 2560);
      mbar_wait(mb + 8 * (MB_Y + u));
      uint32_t ya[2][4], yb[2][4];
      const uint32_t yo = (8 * u + (lane & 7)) * YPITCH + (8 * w + mi) * 16;
#pragma unroll
      for (int hh = 0; hh < 2; hh++) { ldsm4t(ya[hh], sb + OFF_YA + yo + 64 * hh); ldsm4t(yb[hh], sb + OFF_YB + yo + 64 * hh); }
#pragma unroll
      for (int hh = 0; hh < 2; hh++) {
        uint32_t o[4];
#pragma unroll
        for (int i = 0; i < 4; i++) o[i] = hadd2(hmul2(gg[hh][i].x, hmul2(qv[hh][i], ya[hh][i])), hmul2(gg[hh][i].y, yb[hh][i]));
        stsm4(qa + 2560 * hh, o);
      }
      TL(9 + u);
    }
    fence_async();
    __syncwarp();
    if (lane == 0) {
      tma_store3(&p.to, ch0, 8 * rank, 8 * w, sb + OFF_TQ + w * 5120);
      asm volatile("cp.async.bulk.commit_group;" ::: "memory");
      asm volatile("cp.async.bulk.wait_group.read 0;" ::: "memory");
    }
    TL(14);
    TL_DUMP();
  }
}

typedef CUresult (*EncodeFn)(CUtensorMap*, CUtensorMapDataType, cuuint32_t, void*, const cuuint64_t*, const cuuint64_t*,
                             const cuuint32_t*, const cuuint32_t*, CUtensorMapInterleave, CUtensorMapSwizzle,
                             CUtensorMapL2promotion, CUtensorMapFloatOOBfill);

void encode(EncodeFn fn, CUtensorMap* tm, const void* ptr, int nd, const cuuint64_t* dims, const cuuint64_t* strides,
            const cuuint32_t* box, CUtensorMapSwizzle swz) {
  cuuint32_t es[4] = {1, 1, 1, 1};
  fn(tm, CU_TENSOR_MAP_DATA_TYPE_BFLOAT16, nd, const_cast<void*>(ptr), dims, strides, box, es, CU_TENSOR_MAP_INTERLEAVE_NONE,
     swz, CU_TENSOR_MAP_L2_PROMOTION_L2_128B, CU_TENSOR_MAP_FLOAT_OOB_FILL_NONE);
}
void map1(EncodeFn fn, CUtensorMap* tm, const void* ptr, int nhi) {
  const cuuint64_t dims[4] = {DCH, 4, 8, SEQ / 32}, strides[3] = {8 * DCH * 2, DCH * 2, 32 * DCH * 2};
  const cuuint32_t box[4] = {CPC, 4, 8, (cuuint32_t)nhi};
  encode(fn, tm, ptr, 4, dims, strides, box, CU_TENSOR_MAP_SWIZZLE_NONE);
}
void map2(EncodeFn fn, CUtensorMap* tm, const void* ptr, int nr) {
  const cuuint64_t dims[3] = {DCH, SEQ / 32, 32}, strides[2] = {32 * DCH * 2, DCH * 2};
  const cuuint32_t box[3] = {CPC, 8, (cuuint32_t)nr};
  encode(fn, tm, ptr, 3, dims, strides, box, CU_TENSOR_MAP_SWIZZLE_NONE);
}

}

extern "C" void kernel_launch(void* const* d_in, const int* in_sizes, int n_in, void* d_out, int out_size) {
  (void)in_sizes; (void)n_in; (void)out_size;
  static EncodeFn fn = nullptr;
  if (!fn) {
    cudaDriverEntryPointQueryResult qr;
    cudaGetDriverEntryPoint("cuTensorMapEncodeTiled", (void**)&fn, cudaEnableDefault, &qr);
    cudaFuncSetAttribute(fused_kernel, cudaFuncAttributeMaxDynamicSharedMemorySize, SMEM_BYTES);
  }
  Params p;
  map1(fn, &p.tq, d_in[0], 4);
  map1(fn, &p.tk, d_in[1], 9);
  map1(fn, &p.tv, d_in[2], 8);
  map2(fn, &p.tq2, d_in[0], 32);
  map2(fn, &p.to, d_out, 8);
  {
    const cuuint64_t dims[4] = {32, SEQ / 32, DCH / 8, 8}, strides[3] = {64, 8 * SEQ * 2, SEQ * 2};
    const cuuint32_t box[4] = {32, 64, 5, 1};
    encode(fn, &p.th, d_in[4], 4, dims, strides, box, CU_TENSOR_MAP_SWIZZLE_64B);
  }
  p.q = (const __nv_bfloat16*)d_in[0];
  p.shift_k = (const __nv_bfloat16*)d_in[3];
  p.ssm_D = (const __nv_bfloat16*)d_in[5];
  p.logA = (const __nv_bfloat16*)d_in[7];
  p.Aim = (const __nv_bfloat16*)d_in[8];
  p.Cre = (const __nv_bfloat16*)d_in[9];
  p.Cim = (const __nv_bfloat16*)d_in[10];
  p.logdt = (const __nv_bfloat16*)d_in[11];
  p.Dskip = (const __nv_bfloat16*)d_in[12];
  p.gate_w = (const __nv_bfloat16*)d_in[13];
  fused_kernel<<<NCL * CS, NTHREADS, SMEM_BYTES, cudaStreamPerThread>>>(p);
}
```

```cpp
#include <cuda_runtime.h>
#include <cuda_bf16.h>
#include <cuda.h>
#include <stdint.h>

#define TIMELINE 0

namespace {

constexpr int SEQ = 2048, DCH = 576, NMODE = 128;
constexpr int CS = 8, CPC = 40, NCL = 15, NTHREADS = 512;

constexpr int YPITCH = 528;
constexpr int KTAB = 28672;
constexpr int OFF_T = 0;
constexpr int OFF_UKV = 2 * KTAB + 8192;
constexpr int OFF_UX = 3 * KTAB;
constexpr int OFF_HA = OFF_UX + 20480;
constexpr int OFF_CF = OFF_HA + 20480;
constexpr int OFF_CL = OFF_CF + 8192;
constexpr int OFF_TQ = OFF_CL + 4096;
constexpr int OFF_TK = OFF_TQ + 20480;
constexpr int OFF_YA = OFF_TK;
constexpr int OFF_TV = OFF_TK + 23040;
constexpr int OFF_YB = OFF_TV + 20480;
constexpr int OFF_KC = OFF_YB + 40 * YPITCH;
constexpr int OFF_SW = OFF_KC + 3 * 1408;
constexpr int OFF_GW = OFF_SW + 320;
constexpr int OFF_MB = OFF_GW + 80;
constexpr int OFF_TL = OFF_MB + 24 * 8;
constexpr int SMEM_BYTES = OFF_TL + (TIMELINE ? 2048 : 0);
static_assert(SMEM_BYTES <= 232448, "smem");
static_assert((KTAB & 1023) == 0 && (OFF_TQ & 127) == 0 && (OFF_TK & 127) == 0 && (OFF_TV & 127) == 0 && (OFF_MB & 7) == 0 && (OFF_KC & 15) == 0, "align");

enum { MB_UX = 0, MB_UKV = 5, MB_Y = 10, MB_Q2 = 15, MB_XQ = 16, MB_KV = 18, MB_HA = 19, MB_CF = 20, MB_COUNT = 21 };
enum { NB_WG0 = 1 };

struct Params {
  const __nv_bfloat16 *logA, *Aim, *Cre, *Cim, *logdt, *Dskip, *shift_k, *ssm_D, *gate_w, *q;
  CUtensorMap tq, tk, tv, th, tq2, to;
};

constexpr double cos_turn(int m, int n) {
  m &= n - 1;
  if (m > n / 2) m = n - m;
  double sgn = 1.0;
  if (m > n / 4) { m = n / 2 - m; sgn = -1.0; }
  if (m == n / 4) return 0.0;
  const double x = 6.283185307179586476925 * m / n;
  double term = 1.0, sum = 1.0;
  for (int k = 1; k < 14; k++) { term *= -x * x / ((2 * k - 1) * (2 * k)); sum += term; }
  return sgn * sum;
}
constexpr uint32_t bf16_bits(double v) {
  if (v == 0.0) return 0;
  uint32_t sgn = 0;
  if (v < 0) { sgn = 0x8000; v = -v; }
  int e = 127;
  while (v < 1.0) { v *= 2.0; e--; }
  while (v >= 2.0) { v *= 0.5; e++; }
  const double f = v * 128.0;
  int m = (int)f;
  if (f - m > 0.5 || (f - m == 0.5 && (m & 1))) m++;
  return sgn | (uint32_t)((e << 7) + (m - 128));
}
constexpr uint32_t pair_bits(double lo, double hi) { return bf16_bits(lo) | (bf16_bits(hi) << 16); }
struct alignas(128) Tables {
  uint32_t mat[3072];
  uint32_t thr[6][128][4];
};
constexpr Tables make_tables() {
  Tables T{};
  for (int q = 0; q < 768; q++) {
    int m0 = 0, d0 = 0, d1 = 0;
    if (q < 512) {
      const int r = (q >> 6) * 8 + (q & 7), cc = (q >> 3) & 7;
      d0 = 4 * (r & 31); d1 = 2 * d0;
      m0 = 8 * (cc & 3) * d0 + ((r >> 5) == (cc >> 2) ? 0 : (r >> 5) ? 96 : 32);
    } else {
      const int r = ((q - 512) >> 5) * 8 + (q & 7), pc = (q >> 3) & 3;
      d0 = 4 * (8 * (r >> 4) + (r & 7)) + 1; d1 = 8 * d0;
      m0 = 2 * pc * d0 + ((r & 8) ? 32 : 0);
    }
    for (int e = 0; e < 4; e++) T.mat[4 * q + e] = pair_bits(cos_turn(m0 + e * d1, 128), cos_turn(m0 + e * d1 + d0, 128));
  }
  for (int tid = 0; tid < 128; tid++) {
    const int kk = 4 * (tid >> 2) + 1, t = tid & 3;
    for (int q = 0; q < 4; q++) {
      const int m = (8 * q + 2 * t) * kk;
      T.thr[q >> 1][tid][2 * (q & 1)] = pair_bits(cos_turn(m, 128), cos_turn(m + kk, 128));
      T.thr[q >> 1][tid][2 * (q & 1) + 1] = pair_bits(cos_turn(m + 32, 128), cos_turn(m + kk + 32, 128));
      T.thr[2][tid][q] = pair_bits(cos_turn(m, 4096), cos_turn(m + kk, 4096));
      T.thr[3][tid][q] = pair_bits(cos_turn(m + 3072, 4096), cos_turn(m + kk + 3072, 4096));
    }
    for (int i = 0; i < 8; i++) {
      const int l = 8 * tid + i;
      const uint32_t lo = l < 128 ? l : bf16_bits(l) - 0x4280, hi = bf16_bits(l + 1024) - 0x4280;
      T.thr[4 + (i >> 2)][tid][i & 3] = 2 * lo | (2 * hi << 16);
    }
  }
  return T;
}
__device__ const Tables d_tab = make_tables();

__device__ uint2 g_part[NCL * SEQ];
__device__ unsigned g_cnt[CS * 32];
#define TL(i) do {} while (0)
#define TL_INIT() do {} while (0)
#define TL_DUMP() do {} while (0)

__device__ __forceinline__ uint32_t lds16(uint32_t a) { uint32_t v; asm volatile("ld.shared.u16 %0, [%1];" : "=r"(v) : "r"(a) : "memory"); return v; }
__device__ __forceinline__ uint2 lds64(uint32_t a) { uint2 v; asm volatile("ld.shared.v2.u32 {%0,%1}, [%2];" : "=r"(v.x), "=r"(v.y) : "r"(a) : "memory"); return v; }
__device__ __forceinline__ uint4 lds128(uint32_t a) { uint4 v; asm volatile("ld.shared.v4.u32 {%0,%1,%2,%3}, [%4];" : "=r"(v.x), "=r"(v.y), "=r"(v.z), "=r"(v.w) : "r"(a) : "memory"); return v; }
__device__ __forceinline__ void sts16(uint32_t a, uint32_t v) { asm volatile("st.shared.u16 [%0], %1;" :: "r"(a), "r"(v) : "memory"); }
__device__ __forceinline__ void sts32(uint32_t a, uint32_t v) { asm volatile("st.shared.u32 [%0], %1;" :: "r"(a), "r"(v) : "memory"); }
__device__ __forceinline__ void sts64(uint32_t a, uint32_t x, uint32_t y) { asm volatile("st.shared.v2.u32 [%0], {%1,%2};" :: "r"(a), "r"(x), "r"(y) : "memory"); }
__device__ __forceinline__ void sts128(uint32_t a, uint32_t x, uint32_t y, uint32_t z, uint32_t w) { asm volatile("st.shared.v4.u32 [%0], {%1,%2,%3,%4};" :: "r"(a), "r"(x), "r"(y), "r"(z), "r"(w) : "memory"); }
__device__ __forceinline__ void ldsm4t(uint32_t (&r)[4], uint32_t a) { asm volatile("ldmatrix.sync.aligned.m8n8.x4.trans.shared.b16 {%0,%1,%2,%3}, [%4];" : "=r"(r[0]), "=r"(r[1]), "=r"(r[2]), "=r"(r[3]) : "r"(a) : "memory"); }
__device__ __forceinline__ void ldsm2t(uint32_t& r0, uint32_t& r1, uint32_t a) { asm volatile("ldmatrix.sync.aligned.m8n8.x2.trans.shared.b16 {%0,%1}, [%2];" : "=r"(r0), "=r"(r1) : "r"(a) : "memory"); }
__device__ __forceinline__ void ldsm4(uint32_t (&r)[4], uint32_t a) { asm volatile("ldmatrix.sync.aligned.m8n8.x4.shared.b16 {%0,%1,%2,%3}, [%4];" : "=r"(r[0]), "=r"(r[1]), "=r"(r[2]), "=r"(r[3]) : "r"(a) : "memory"); }
__device__ __forceinline__ void stsm4(uint32_t a, const uint32_t (&r)[4]) { asm volatile("stmatrix.sync.aligned.m8n8.x4.shared.b16 [%0], {%1,%2,%3,%4};" :: "r"(a), "r"(r[0]), "r"(r[1]), "r"(r[2]), "r"(r[3]) : "memory"); }
__device__ __forceinline__ uint32_t pack(float lo, float hi) { uint32_t r; asm("cvt.rn.bf16x2.f32 %0, %1, %2;" : "=r"(r) : "f"(hi), "f"(lo)); return r; }
__device__ __forceinline__ float blo(uint32_t v) { return __uint_as_float(v << 16); }
__device__ __forceinline__ float bhi(uint32_t v) { return __uint_as_float(v & 0xffff0000u); }
__device__ __forceinline__ float bf16r(float x) { return blo(pack(x, 0.f)); }
__device__ __forceinline__ uint32_t hmul2(uint32_t a, uint32_t b) { uint32_t r; asm("mul.rn.bf16x2 %0, %1, %2;" : "=r"(r) : "r"(a), "r"(b)); return r; }
__device__ __forceinline__ uint32_t hadd2(uint32_t a, uint32_t b) { uint32_t r; asm("add.rn.bf16x2 %0, %1, %2;" : "=r"(r) : "r"(a), "r"(b)); return r; }
__device__ __forceinline__ uint32_t hfma2(uint32_t a, uint32_t b, uint32_t c) { uint32_t r; asm("fma.rn.bf16x2 %0, %1, %2, %3;" : "=r"(r) : "r"(a), "r"(b), "r"(c)); return r; }
__device__ __forceinline__ uint32_t prmt(uint32_t a, uint32_t b, uint32_t s) { return __byte_perm(a, b, s); }
__device__ __forceinline__ uint32_t ldraw(const __nv_bfloat16* p) { uint32_t v; asm volatile("ld.global.nc.u16 %0, [%1];" : "=r"(v) : "l"(p)); return v; }
__device__ __forceinline__ uint4 ldg128(const void* p) { uint4 v; asm volatile("ld.global.nc.v4.u32 {%0,%1,%2,%3}, [%4];" : "=r"(v.x), "=r"(v.y), "=r"(v.z), "=r"(v.w) : "l"(p)); return v; }
__device__ __forceinline__ void bar_sync(int id, int n) { asm volatile("bar.sync %0, %1;" :: "r"(id), "r"(n) : "memory"); }
__device__ __forceinline__ void bar_arrive(int id, int n) { asm volatile("bar.arrive %0, %1;" :: "r"(id), "r"(n) : "memory"); }
__device__ __forceinline__ void cluster_arrive() { asm volatile("barrier.cluster.arrive.relaxed.aligned;" ::: "memory"); }
__device__ __forceinline__ void cluster_wait() { asm volatile("barrier.cluster.wait.aligned;" ::: "memory"); }
__device__ __forceinline__ void fence_async() { asm volatile("fence.proxy.async.shared::cta;" ::: "memory"); }
__device__ __forceinline__ void fence_mbinit() { asm volatile("fence.mbarrier_init.release.cluster;" ::: "memory"); }
__device__ __forceinline__ uint32_t mapa(uint32_t a, uint32_t rank) { uint32_t r; asm("mapa.shared::cluster.u32 %0, %1, %2;" : "=r"(r) : "r"(a), "r"(rank)); return r; }
__device__ __forceinline__ void st_async4(uint32_t a, uint32_t x, uint32_t y, uint32_t z, uint32_t w, uint32_t mbar) {
  asm volatile("st.async.weak.shared::cluster.mbarrier::complete_tx::bytes.v4.b32 [%0], {%1,%2,%3,%4}, [%5];"
               :: "r"(a), "r"(x), "r"(y), "r"(z), "r"(w), "r"(mbar) : "memory");
}
__device__ __forceinline__ void mbar_init(uint32_t m, uint32_t cnt) { asm volatile("mbarrier.init.shared::cta.b64 [%0], %1;" :: "r"(m), "r"(cnt) : "memory"); }
__device__ __forceinline__ void mbar_expect(uint32_t m, uint32_t bytes) { asm volatile("mbarrier.arrive.expect_tx.shared::cta.b64 _, [%0], %1;" :: "r"(m), "r"(bytes) : "memory"); }
__device__ __forceinline__ void mbar_wait(uint32_t m) {
  uint32_t done;
  int it = 0;
  do {
    asm volatile("{.reg .pred p; mbarrier.try_wait.parity.shared::cta.b64 p, [%1], 0; selp.u32 %0, 1, 0, p;}" : "=r"(done) : "r"(m) : "memory");
    if (++it > (1 << 22)) __trap();
  } while (!done);
}
__device__ __forceinline__ void tma_load4(uint32_t dst, const CUtensorMap* tm, int c0, int c1, int c2, int c3, uint32_t mbar) {
  asm volatile("cp.async.bulk.tensor.4d.shared::cluster.global.mbarrier::complete_tx::bytes [%0], [%1, {%3, %4, %5, %6}], [%2];"
               :: "r"(dst), "l"(tm), "r"(mbar), "r"(c0), "r"(c1), "r"(c2), "r"(c3) : "memory");
}
__device__ __forceinline__ void tma_load3(uint32_t dst, const CUtensorMap* tm, int c0, int c1, int c2, uint32_t mbar) {
  asm volatile("cp.async.bulk.tensor.3d.shared::cluster.global.mbarrier::complete_tx::bytes [%0], [%1, {%3, %4, %5}], [%2];"
               :: "r"(dst), "l"(tm), "r"(mbar), "r"(c0), "r"(c1), "r"(c2) : "memory");
}
__device__ __forceinline__ void tma_store3(const CUtensorMap* tm, int c0, int c1, int c2, uint32_t src) {
  asm volatile("cp.async.bulk.tensor.3d.global.shared::cta.bulk_group [%0, {%2, %3, %4}], [%1];"
               :: "l"(tm), "r"(src), "r"(c0), "r"(c1), "r"(c2) : "memory");
}
__device__ __forceinline__ void wg_fence() { asm volatile("wgmma.fence.sync.aligned;" ::: "memory"); }
__device__ __forceinline__ void wg_commit() { asm volatile("wgmma.commit_group.sync.aligned;" ::: "memory"); }
template <int N> __device__ __forceinline__ void wg_wait() { asm volatile("wgmma.wait_group.sync.aligned %0;" :: "n"(N) : "memory"); }
template <int N> __device__ __forceinline__ void tie_all(float (&x)[N]) {
#pragma unroll
  for (int i = 0; i < N; i++) asm volatile("" : "+f"(x[i]) :: "memory");
}
#define R16(C, d) C(d[0]), C(d[1]), C(d[2]), C(d[3]), C(d[4]), C(d[5]), C(d[6]), C(d[7]), C(d[8]), C(d[9]), C(d[10]), C(d[11]), C(d[12]), C(d[13]), C(d[14]), C(d[15])
#define R32(C, d) R16(C, d), R16(C, (d + 16))
#define P16 "{%0,%1,%2,%3,%4,%5,%6,%7,%8,%9,%10,%11,%12,%13,%14,%15}"
#define P32 "{%0,%1,%2,%3,%4,%5,%6,%7,%8,%9,%10,%11,%12,%13,%14,%15,%16,%17,%18,%19,%20,%21,%22,%23,%24,%25,%26,%27,%28,%29,%30,%31}"
template <int SD, int TB, int OFF> __device__ __forceinline__ void rs64(float* d, const uint32_t* a, uint64_t db) {
  if (SD) asm volatile("{.reg .b64 db; add.s64 db, %36, %37; wgmma.mma_async.sync.aligned.m64n64k16.f32.bf16.bf16 " P32 ", {%32,%33,%34,%35}, db, 1, 1, 1, %38;}"
                       : R32("+f", d) : "r"(a[0]), "r"(a[1]), "r"(a[2]), "r"(a[3]), "l"(db), "n"(OFF), "n"(TB));
  else asm volatile("{.reg .b64 db; add.s64 db, %36, %37; wgmma.mma_async.sync.aligned.m64n64k16.f32.bf16.bf16 " P32 ", {%32,%33,%34,%35}, db, 0, 1, 1, %38;}"
                    : R32("=f", d) : "r"(a[0]), "r"(a[1]), "r"(a[2]), "r"(a[3]), "l"(db), "n"(OFF), "n"(TB));
}
template <int SD, int OFFA, int OFFB> __device__ __forceinline__ void ss32(float* d, uint64_t da, uint64_t db) {
  if (SD) asm volatile("{.reg .b64 da, db; add.s64 da, %16, %18; add.s64 db, %17, %19; wgmma.mma_async.sync.aligned.m64n32k16.f32.bf16.bf16 " P16 ", da, db, 1, 1, 1, 1, 1;}"
                       : R16("+f", d) : "l"(da), "l"(db), "n"(OFFA), "n"(OFFB));
  else asm volatile("{.reg .b64 da, db; add.s64 da, %16, %18; add.s64 db, %17, %19; wgmma.mma_async.sync.aligned.m64n32k16.f32.bf16.bf16 " P16 ", da, db, 0, 1, 1, 1, 1;}"
                    : R16("=f", d) : "l"(da), "l"(db), "n"(OFFA), "n"(OFFB));
}
template <int KS> __device__ __forceinline__ void kgen_mma(float (&c)[24], uint64_t da) {
  asm volatile("{.reg .b64 da, db; add.s64 da, %24, %25; add.s64 db, %24, %26;\n"
               "wgmma.mma_async.sync.aligned.m64n48k16.f32.bf16.bf16 {%0,%1,%2,%3,%4,%5,%6,%7,%8,%9,%10,%11,%12,%13,%14,%15,%16,%17,%18,%19,%20,%21,%22,%23}, da, db, %27, 1, 1, 1, 1;}"
               : R16("+f", c), "+f"(c[16]), "+f"(c[17]), "+f"(c[18]), "+f"(c[19]), "+f"(c[20]), "+f"(c[21]), "+f"(c[22]), "+f"(c[23])
               : "l"(da), "n"(8 * KS), "n"(8 * KS + 512), "n"(KS ? 1 : 0));
  if constexpr (KS < 7) kgen_mma<KS + 1>(c, da);
}
__device__ __forceinline__ uint64_t desc_lo(uint32_t a) { return (uint64_t)((a & 0x3FFFF) >> 4); }
__device__ __forceinline__ void stage1(float (&D)[32], const uint32_t (&A1)[8], uint32_t src) {
  const uint64_t du = desc_lo(src) | (128ull << 16) | (32ull << 32) | (2ull << 62);
  rs64<0, 1, 0>(D, A1, du); rs64<1, 1, 64>(D, A1 + 4, du);
}
template <int INV> __device__ __forceinline__ void stage2(float (&X)[32], const uint32_t (&F)[16], uint32_t cf) {
  constexpr int KS = INV ? 16 : 128, TB = INV ? 0 : 1;
  const uint64_t dc = desc_lo(cf) | (INV ? (8ull << 16) | (64ull << 32) : (64ull << 16) | (8ull << 32));
  rs64<0, TB, 0>(X, F, dc); rs64<1, TB, KS>(X, F + 4, dc); rs64<1, TB, 2 * KS>(X, F + 8, dc); rs64<1, TB, 3 * KS>(X, F + 12, dc);
}
__device__ __forceinline__ void fwd_mid(uint32_t (&F)[16], const float (&D)[32], const uint32_t (&tp)[12]) {
#pragma unroll
  for (int j = 0; j < 4; j++)
#pragma unroll
    for (int b = 0; b < 2; b++) {
      const int i = 4 * j + 16 * b;
      const uint32_t ar = pack(D[i], D[i + 1]), ai = pack(D[i + 2], D[i + 3]);
      F[2 * j + b] = hfma2(ar, tp[3 * j], hmul2(ai, tp[3 * j + 2]));
      F[8 + 2 * j + b] = hfma2(ar, tp[3 * j + 1], hmul2(ai, tp[3 * j]));
    }
}

struct cf { float x, y; };
__device__ __forceinline__ cf cmul(cf a, cf b) { cf r; r.x = fmaf(a.x, b.x, -a.y * b.y); r.y = fmaf(a.x, b.y, a.y * b.x); return r; }
__device__ __forceinline__ cf cexp_p(float lr2, float lt, float p) {
  float m = exp2f(lr2 * p);
  float t = lt * p;
  t = (t - rintf(t)) * 6.283185307179586f;
  cf r; r.x = m * __cosf(t); r.y = m * __sinf(t); return r;
}
__device__ __forceinline__ void store8(uint32_t a, const cf (&v)[8]) {
  sts128(a, pack(v[0].x, v[1].x), pack(v[2].x, v[3].x), pack(v[4].x, v[5].x), pack(v[6].x, v[7].x));
  sts128(a + KTAB / 2, pack(v[0].y, v[1].y), pack(v[2].y, v[3].y), pack(v[4].y, v[5].y), pack(v[6].y, v[7].y));
}
__device__ __forceinline__ float sigmoidf_(float s) { return 1.f / (1.f + __expf(-s)); }

__global__ void __cluster_dims__(CS, 1, 1) __launch_bounds__(NTHREADS, 1) fused_kernel(const __grid_constant__ Params p) {
  extern __shared__ __align__(1024) uint8_t smem[];
  TL_INIT();
  TL(31);
  const uint32_t sb = (uint32_t)__cvta_generic_to_shared(smem);
  const uint32_t mb = sb + OFF_MB;
  const int wg = __shfl_sync(0xffffffffu, threadIdx.x >> 7, 0);
  const int tid = threadIdx.x & 127, w = __shfl_sync(0xffffffffu, tid >> 5, 0), lane = tid & 31, g = lane >> 2, t = lane & 3;
  const int cl = blockIdx.x >> 3, rank = blockIdx.x & 7;
  const int ch0 = cl * CPC;
  const int nu = min(5, (DCH - ch0) >> 3);

  if (wg < 3) {
    uint32_t pla[2], pai[2], pcr[2], pci[2], pdt[2];
#pragma unroll
    for (int r = 0; r < 2; r++) {
      const int ch = (wg + 3 * r < nu) ? ch0 + 8 * (wg + 3 * r) + rank : 0;
      pla[r] = ldraw(p.logA + ch * NMODE + tid);
      pai[r] = ldraw(p.Aim + ch * NMODE + tid);
      pcr[r] = ldraw(p.Cre + ch * NMODE + tid);
      pci[r] = ldraw(p.Cim + ch * NMODE + tid);
      pdt[r] = ldraw(p.logdt + ch);
    }
    cluster_arrive();
    uint32_t A1[8], tp[12];
    {
      const uint4 a = ldg128(d_tab.thr[0][tid]), b = ldg128(d_tab.thr[1][tid]), c = ldg128(d_tab.thr[2][tid]), d = ldg128(d_tab.thr[3][tid]);
      A1[0] = a.x; A1[1] = a.y; A1[2] = a.z; A1[3] = a.w; A1[4] = b.x; A1[5] = b.y; A1[6] = b.z; A1[7] = b.w;
      tp[0] = c.x; tp[3] = c.y; tp[6] = c.z; tp[9] = c.w; tp[2] = d.x; tp[5] = d.y; tp[8] = d.z; tp[11] = d.w;
      tp[1] = tp[4] = tp[7] = tp[10] = 0;
    }
    TL(0);
    const uint32_t tab = sb + OFF_T + wg * KTAB;
#pragma unroll 1
    for (int job = 0; job < 4; job++) {
      const bool isA = job >= (wg == 2 ? 1 : 2);
      const int u = wg == 2 ? (job ? 2 * job - 2 : 2) : job < 2 ? wg + 3 * job : job == 2 ? 2 * wg + 1 : 9;
      uint32_t pd = 0;
      if (u < nu) pd = ldraw((isA ? p.ssm_D : p.Dskip) + ch0 + 8 * u + rank);
      if (!isA && u < nu) {
        const float la = blo(job ? pla[1] : pla[0]), ai = blo(job ? pai[1] : pai[0]), cr = blo(job ? pcr[1] : pcr[0]), ci = blo(job ? pci[1] : pci[0]);
        const float dt = bf16r(expf(blo(job ? pdt[1] : pdt[0])));
        const float lr2 = (-bf16r(expf(la)) * dt) * 1.4426950408889634f;
        const float lt = (ai * dt) * 0.15915494309189535f;
        const uint32_t row = tab + tid * 16;
        if (lr2 != 123.f) TL(16 + 4 * job);
        if (job) bar_sync(NB_WG0 + wg, 128);
        {
          const cf w1 = cexp_p(lr2, lt, 8.f);
          cf v[8];
          v[0].x = 1.f; v[0].y = 0.f; v[1] = w1; v[2] = cmul(w1, w1); v[3] = cmul(v[2], w1);
          const cf w4 = cmul(v[2], v[2]);
          v[4] = w4; v[5] = cmul(v[1], w4); v[6] = cmul(v[2], w4); v[7] = cmul(v[3], w4);
          const cf w8 = cmul(w4, w4);
          store8(row, v);
#pragma unroll
          for (int c = 1; c < 4; c++) {
#pragma unroll
            for (int i = 0; i < 8; i++) v[i] = (c == 1 && i == 0) ? w8 : cmul(v[i], w8);
            store8(row + 2048 * c, v);
          }
        }
        {
          cf z1 = cexp_p(lr2, lt, 1.f), Z = cexp_p(lr2, lt, 256.f);
          z1.y = -z1.y; Z.y = -Z.y;
          const cf z2 = cmul(z1, z1);
          cf h[8], v[8];
          h[0].x = 2.f * cr * dt; h[0].y = -2.f * ci * dt;
          h[1] = cmul(h[0], z1);
#pragma unroll
          for (int i = 2; i < 8; i++) h[i] = cmul(h[i - 2], z2);
          store8(row + 4 * 2048, h);
          v[0] = cmul(h[0], Z); v[1] = cmul(h[2], Z); v[2] = cmul(h[4], Z); v[3] = cmul(h[6], Z);
          v[4] = cmul(v[0], Z); v[5] = cmul(v[2], Z); v[6] = cmul(v[4], Z); v[7] = cmul(v[5], Z);
          store8(row + 5 * 2048, v);
          const cf Z2 = cmul(Z, Z);
          h[0] = cmul(v[4], Z2); h[1] = cmul(v[6], Z2); h[2] = cmul(h[0], Z2); h[3] = cmul(h[1], Z2); h[4] = cmul(h[2], Z2);
          h[5].x = h[5].y = h[6].x = h[6].y = h[7].x = h[7].y = 0.f;
          store8(row + 6 * 2048, h);
        }
        TL(17 + 4 * job);
        fence_async();
        bar_sync(NB_WG0 + wg, 128);
        float c[24];
        wg_fence();
        kgen_mma<0>(c, desc_lo(tab) | ((uint64_t)(KTAB / 32) << 16) | (64ull << 32));
        wg_commit();
        const uint4 ka = ldg128(d_tab.thr[4][tid]), kb = ldg128(d_tab.thr[5][tid]);
        wg_wait<0>(); tie_all(c);
        const uint32_t kc = sb + OFF_KC + wg * 1408;
        {
          const int a = 8 * w + g;
          sts32(kc + 4 * (4 * a + t), pack(c[0] + c[6], c[1] + c[7]));
          sts32(kc + 4 * (t < 2 ? 128 + 2 * a + t : 128 + 32 * t + a), pack(c[8] + c[14], c[9] + c[15]));
          if (t < 3) {
            const uint32_t p0 = pack(c[16] + c[22], c[17] + c[23]);
            sts16(kc + 2 * (512 + 64 * t + a), p0);
            sts16(kc + 2 * (544 + 64 * t + a), p0 >> 16);
          }
        }
        const uint32_t kid[8] = {ka.x, ka.y, ka.z, ka.w, kb.x, kb.y, kb.z, kb.w};
        TL(18 + 4 * job);
        bar_sync(NB_WG0 + wg, 128);
        uint32_t v[2][8];
#pragma unroll
        for (int i = 0; i < 8; i++) { v[0][i] = lds16(kc + (kid[i] & 0xffffu)); v[1][i] = lds16(kc + (kid[i] >> 16)); }
#pragma unroll
        for (int cc = 0; cc < 2; cc++)
          sts128(tab + 2048 * cc + 16 * (tid ^ ((tid >> 3) & 3)), prmt(v[cc][0], v[cc][1], 0x5410), prmt(v[cc][2], v[cc][3], 0x5410),
                 prmt(v[cc][4], v[cc][5], 0x5410), prmt(v[cc][6], v[cc][7], 0x5410));
        fence_async();
        if (job) bar_sync(NB_WG0 + wg, 128);
      }
      if (job == 0) {
        cluster_wait();
        cluster_arrive();
        bar_sync(NB_WG0 + wg, 128);
        mbar_wait(mb + 8 * MB_CF);
#pragma unroll
        for (int j = 0; j < 4; j++) tp[3 * j + 1] = tp[3 * j + 2] ^ 0x80008000u;
      }
      if (u >= nu) continue;
      TL(1 + job);
      float D[32], H[32], X[32];
      uint32_t F[16];
      if (isA) mbar_wait(mb + 8 * MB_HA);
      wg_fence();
      stage1(D, A1, isA ? sb + OFF_HA + u * 4096 : tab);
      wg_commit();
      wg_wait<0>(); tie_all(D);
      fwd_mid(F, D, tp);
      mbar_wait(mb + 8 * ((isA ? MB_UKV : MB_UX) + u));
      fence_async();
      TL(5 + job);
      wg_fence();
      stage2<0>(H, F, sb + OFF_CF);
      stage1(D, A1, sb + (isA ? OFF_UKV : OFF_UX) + u * 4096);
      wg_commit();
      wg_wait<0>(); tie_all(D); tie_all(H);
      fwd_mid(F, D, tp);
      wg_fence();
      stage2<0>(X, F, sb + OFF_CF);
      wg_commit();
      {
        const float dsk = blo(pd);
#pragma unroll
        for (int j = 0; j < 4; j++) { H[4 * j] += dsk; H[4 * j + 1] += dsk; }
      }
      wg_wait<0>(); tie_all(X);
#pragma unroll
      for (int j = 0; j < 4; j++) {
        float pr[2], pi[2], qr[2], qi[2];
#pragma unroll
        for (int n = 0; n < 2; n++) {
          const int i = 4 * j + n;
          pr[n] = fmaf(X[i], H[i], -X[i + 16] * H[i + 16]);
          pi[n] = fmaf(X[i], H[i + 16], X[i + 16] * H[i]);
          qr[n] = fmaf(X[i + 2], H[i], fmaf(-X[i + 18], H[i + 16], fmaf(X[i], H[i + 2], fmaf(-X[i + 16], H[i + 18], -pi[n]))));
          qi[n] = fmaf(X[i + 2], H[i + 16], fmaf(X[i + 18], H[i], fmaf(X[i], H[i + 18], fmaf(X[i + 16], H[i + 2], pr[n]))));
        }
        F[2 * j] = pack(pr[0], pr[1]); F[2 * j + 1] = pack(qr[0], qr[1]); F[8 + 2 * j] = pack(pi[0], pi[1]); F[9 + 2 * j] = pack(qi[0], qi[1]);
      }
      wg_fence();
      stage2<1>(H, F, sb + OFF_CF);
      wg_commit();
      wg_wait<0>(); tie_all(H);
      {
        const uint32_t va = tab + (16 * w + (lane & 15)) * 128;
        const int vx = (lane >> 4) ^ (lane & 7);
#pragma unroll
        for (int j = 0; j < 4; j++) {
          uint32_t V[4];
#pragma unroll
          for (int b = 0; b < 2; b++) {
            const int i = 4 * j + 2 * b;
            const uint32_t er = pack(H[i], H[i + 1]), ei = pack(H[i + 16], H[i + 17]);
            V[2 * b] = hfma2(er, tp[3 * j], hmul2(ei, tp[3 * j + 1]));
            V[2 * b + 1] = hfma2(ei, tp[3 * j], hmul2(er, tp[3 * j + 2]));
          }
          stsm4(va + ((vx ^ (2 * j)) << 4), V);
        }
      }
      fence_async();
      bar_sync(NB_WG0 + wg, 128);
      float O[16];
      {
        const uint64_t dv = desc_lo(tab) | (1ull << 16) | (64ull << 32) | (1ull << 62);
        const uint64_t dl = desc_lo(sb + OFF_CL) | (32ull << 16) | (8ull << 32);
        wg_fence();
        ss32<0, 0, 0>(O, dv, dl); ss32<1, 128, 64>(O, dv, dl); ss32<1, 256, 128>(O, dv, dl); ss32<1, 384, 192>(O, dv, dl);
        wg_commit();
      }
      if (isA && job < 3) {
        for (int k = 0; k < nu; k++) mbar_wait(mb + 8 * (MB_UKV + k));
      }
      wg_wait<0>(); tie_all(O);
      {
        const uint32_t yo = (isA ? OFF_YA : OFF_YB) + (8 * u + rank) * YPITCH + (8 * w + g) * 16, ym = OFF_MB + 8 * (MB_Y + u);
        const uint32_t r0 = mapa(sb, t), r1 = mapa(sb, t + 4);
        st_async4(r0 + yo, pack(O[0], O[1]), pack(O[4], O[5]), pack(O[8], O[9]), pack(O[12], O[13]), r0 + ym);
        st_async4(r1 + yo, pack(O[2], O[3]), pack(O[6], O[7]), pack(O[10], O[11]), pack(O[14], O[15]), r1 + ym);
      }
      TL(9 + job);
    }
    TL_DUMP();
  } else {
    if (lane == 0) {
#pragma unroll
      for (int i = 0; i < 4; i++) mbar_init(mb + 8 * (4 * w + i), 1);
      mbar_init(mb + 8 * (MB_XQ + w), 1);
      if (w == 3) mbar_init(mb + 8 * MB_CF, 1);
      fence_mbinit();
      if (w == 3) {
        mbar_expect(mb + 8 * MB_CF, 12288);
        asm volatile("cp.async.bulk.shared::cluster.global.mbarrier::complete_tx::bytes [%0], [%1], %2, [%3];"
                     :: "r"(sb + OFF_CF), "l"(d_tab.mat), "r"(12288), "r"(mb + 8 * MB_CF) : "memory");
      }
#pragma unroll
      for (int i = 0; i < 4; i++) { const int b = 4 * w + i; mbar_expect(mb + 8 * b, b == MB_Q2 ? 20480 : b >= MB_Y ? 8192 : 4096); }
      mbar_expect(mb + 8 * (MB_XQ + w), w < 2 ? 10240 : w == 2 ? 23040 + 20480 : 20480);
    }
    __syncwarp();
    cluster_arrive();
    uint2 swv = make_uint2(0, 0);
    uint32_t gwv = 0, tag = 0;
    if (tid >= 64 && tid < 104 && ch0 + tid - 64 < DCH) { swv = __ldg((const uint2*)(p.shift_k + (size_t)(ch0 + tid - 64) * 4)); gwv = ldraw(p.gate_w + ch0 + tid - 64); }
    if (tid == 127) tag = (atomicAdd(&g_cnt[rank * 32], cl == 0 ? 16 - (NCL - 1) : 1) >> 4) + 1;
    if (lane == 0 && w < 2) { tma_load4(sb + OFF_TQ + 10240 * w, &p.tq, ch0, 0, 0, 8 * rank + 4 * w, mb + 8 * (MB_XQ + w)); TL(20); }
    if (tid >= 64 && tid < 104) { sts64(sb + OFF_SW + 8 * (tid - 64), swv.x, swv.y); sts16(sb + OFF_GW + 2 * (tid - 64), gwv); }
    if (tid == 127) sts32(sb + OFF_MB + 8 * MB_COUNT, tag);
    if (tid == 64) {
      tma_load4(sb + OFF_TK, &p.tk, ch0, 0, 0, 8 * rank - 1, mb + 8 * MB_KV);
      tma_load4(sb + OFF_TV, &p.tv, ch0, 0, 0, 8 * rank, mb + 8 * MB_KV);
    }
    bar_sync(NB_WG0 + 3, 128);
    if (tid == 96) tma_load4(sb + OFF_HA, &p.th, 0, 0, 5 * cl, rank, mb + 8 * MB_HA);
    tag = lds64(sb + OFF_MB + 8 * MB_COUNT).x;
    TL(0);
    const uint32_t rbase = mapa(sb, g);
    const int mi = lane >> 3, tq = (lane & 7) >> 1, jj = lane & 1;
    const uint32_t toff = (4 * (2 * mi + jj) + tq) * 80;
    const uint32_t uoff = 16 * (32 * rank + 4 * w + (t ^ (w >> 1)));
    cluster_wait();
    cluster_arrive();
    mbar_wait(mb + 8 * MB_XQ);
    mbar_wait(mb + 8 * (MB_XQ + 1));
    TL(1);
    {
      uint32_t xr[5][2][4];
#pragma unroll
      for (int u = 0; u < 5; u++) { ldsm4t(xr[u][0], sb + OFF_TQ + w * 2560 + toff + 16 * u); ldsm4t(xr[u][1], sb + OFF_TQ + (w + 4) * 2560 + toff + 16 * u); }
#pragma unroll
      for (int u = 0; u < 5; u++)
        if (u < nu) {
          st_async4(rbase + OFF_UX + u * 4096 + uoff, xr[u][0][0], xr[u][0][1], xr[u][0][2], xr[u][0][3], rbase + OFF_MB + 8 * (MB_UX + u));
          st_async4(rbase + OFF_UX + u * 4096 + (uoff ^ 32) + 256, xr[u][1][0], xr[u][1][1], xr[u][1][2], xr[u][1][3], rbase + OFF_MB + 8 * (MB_UX + u));
        }
    }
    TL(2);
    {
      float s0 = 0.f, s1 = 0.f;
#pragma unroll
      for (int j = 0; j < 5; j++) {
        const uint4 gw = lds128(sb + OFF_GW + 16 * j);
        const uint4 x0 = lds128(sb + OFF_TQ + tid * 80 + 16 * j), x1 = lds128(sb + OFF_TQ + (tid + 128) * 80 + 16 * j);
        uint32_t m0 = hmul2(x0.x, gw.x), m1 = hmul2(x0.y, gw.y), m2 = hmul2(x0.z, gw.z), m3 = hmul2(x0.w, gw.w);
        s0 += ((blo(m0) + bhi(m0)) + (blo(m1) + bhi(m1))) + ((blo(m2) + bhi(m2)) + (blo(m3) + bhi(m3)));
        m0 = hmul2(x1.x, gw.x); m1 = hmul2(x1.y, gw.y); m2 = hmul2(x1.z, gw.z); m3 = hmul2(x1.w, gw.w);
        s1 += ((blo(m0) + bhi(m0)) + (blo(m1) + bhi(m1))) + ((blo(m2) + bhi(m2)) + (blo(m3) + bhi(m3)));
      }
      const int s2 = 8 * (8 * (lane & 3) + (lane >> 2)) + w;
      asm volatile("st.relaxed.gpu.global.u64 [%0], %1;" :: "l"(&g_part[cl * SEQ + rank * 256 + s2]), "l"(((uint64_t)tag << 32) | __float_as_uint(s0)) : "memory");
      asm volatile("st.relaxed.gpu.global.u64 [%0], %1;" :: "l"(&g_part[cl * SEQ + rank * 256 + s2 + 4]), "l"(((uint64_t)tag << 32) | __float_as_uint(s1)) : "memory");
    }
    bar_sync(NB_WG0 + 3, 128);
    if (tid == 0) tma_load3(sb + OFF_TQ, &p.tq2, ch0, 8 * rank, 0, mb + 8 * MB_Q2);
    __syncwarp();
    TL(3);
    cluster_wait();
    mbar_wait(mb + 8 * MB_KV);
    TL(4);
    const uint32_t hoff = (4 * (4 + 2 * (mi & 1) + jj) + ((tq + 3) & 3)) * 80 + (tq ? 2560 : 0);
#pragma unroll 1
    for (int u = 0; u < nu; u++) {
      const uint2 sw = lds64(sb + OFF_SW + 8 * (8 * u + g));
      uint32_t E[2][6], V[2][4];
#pragma unroll
      for (int hf = 0; hf < 2; hf++) {
        const int ah = 4 * hf + w;
        uint32_t K[4];
        ldsm4t(K, sb + OFF_TK + (ah + 1) * 2560 + toff + 16 * u);
        ldsm2t(E[hf][0], E[hf][1], sb + OFF_TK + ah * 2560 + hoff + 16 * u);
        ldsm4t(V[hf], sb + OFF_TV + ah * 2560 + toff + 16 * u);
        E[hf][2] = K[0]; E[hf][3] = K[1]; E[hf][4] = K[2]; E[hf][5] = K[3];
      }
      const uint32_t w0 = prmt(sw.x, 0, 0x1010), w1 = prmt(sw.x, 0, 0x3232), w2 = prmt(sw.y, 0, 0x1010), w3 = prmt(sw.y, 0, 0x3232);
#pragma unroll
      for (int hf = 0; hf < 2; hf++) {
        uint32_t O[5], o[4];
#pragma unroll
        for (int i = 0; i < 5; i++) O[i] = prmt(E[hf][i], E[hf][i + 1], 0x5432);
#pragma unroll
        for (int i = 0; i < 4; i++) {
          uint32_t s = hmul2(O[i], w3);
          s = hadd2(s, hmul2(E[hf][i + 1], w2));
          s = hadd2(s, hmul2(O[i + 1], w1));
          s = hadd2(s, hmul2(E[hf][i + 2], w0));
          o[i] = hmul2(s, V[hf][i]);
        }
        st_async4(rbase + OFF_UKV + u * 4096 + (hf ? (uoff ^ 32) + 256 : uoff), o[0], o[1], o[2], o[3], rbase + OFF_MB + 8 * (MB_UKV + u));
      }
    }
    TL(5);
    bar_sync(NB_WG0 + 3, 128);
    {
      float s[2] = {0.f, 0.f};
      bool ok = false;
#pragma unroll 1
      for (int it = 0; it < 4000 && !ok; it++) {
        ok = true; s[0] = s[1] = 0.f;
#pragma unroll
        for (int c = 0; c < NCL; c++) {
          uint64_t a, b;
          asm volatile("ld.relaxed.gpu.global.v2.u64 {%0,%1}, [%2];" : "=l"(a), "=l"(b) : "l"(&g_part[c * SEQ + rank * 256 + 2 * tid]) : "memory");
          ok = ok && (uint32_t)(a >> 32) == tag && (uint32_t)(b >> 32) == tag;
          s[0] += __uint_as_float((uint32_t)a); s[1] += __uint_as_float((uint32_t)b);
        }
      }
      if (ok) {
      } else {
#pragma unroll 1
        for (int hf = 0; hf < 2; hf++) {
          const int slot = 2 * tid + hf;
          const int row = rank * 256 + 32 * (slot & 7) + (slot >> 3);
          const uint32_t* xr = (const uint32_t*)(p.q + (size_t)row * DCH);
          const uint32_t* gr = (const uint32_t*)p.gate_w;
          float a = 0.f;
#pragma unroll 1
          for (int c = 0; c < DCH / 2; c++) { const uint32_t m = hmul2(__ldg(xr + c), __ldg(gr + c)); a += blo(m) + bhi(m); }
          if (hf) s[1] = a; else s[0] = a;
        }
      }
      const float g0 = bf16r(sigmoidf_(bf16r(s[0]))), g1 = bf16r(sigmoidf_(bf16r(s[1])));
      const float a0 = g0 * 0.0009765625f, b0 = bf16r(1.f - g0) * 0.0009765625f, a1 = g1 * 0.0009765625f, b1 = bf16r(1.f - g1) * 0.0009765625f;
      sts128(sb + OFF_TV + 16 * tid, pack(a0, a0), pack(b0, b0), pack(a1, a1), pack(b1, b1));
    }
    __syncwarp();
    uint2 gg[2][4];
#pragma unroll
    for (int hh = 0; hh < 2; hh++)
#pragma unroll
      for (int i = 0; i < 4; i++) gg[hh][i] = lds64(sb + OFF_TV + 8 * (64 * w + 32 * hh + 8 * i + g));
    mbar_wait(mb + 8 * MB_Q2);
    TL(8);
#pragma unroll 1
    for (int u = 0; u < nu; u++) {
      uint32_t qv[2][4];
      const uint32_t qa = sb + OFF_TQ + (64 * w + lane) * 80 + 16 * u;
      ldsm4(qv[0], qa);
      ldsm4(qv[1], qa + 2560);
      mbar_wait(mb + 8 * (MB_Y + u));
      uint32_t ya[2][4], yb[2][4];
      const uint32_t yo = (8 * u + (lane & 7)) * YPITCH + (8 * w + mi) * 16;
#pragma unroll
      for (int hh = 0; hh < 2; hh++) { ldsm4t(ya[hh], sb + OFF_YA + yo + 64 * hh); ldsm4t(yb[hh], sb + OFF_YB + yo + 64 * hh); }
#pragma unroll
      for (int hh = 0; hh < 2; hh++) {
        uint32_t o[4];
#pragma unroll
        for (int i = 0; i < 4; i++) o[i] = hadd2(hmul2(gg[hh][i].x, hmul2(qv[hh][i], ya[hh][i])), hmul2(gg[hh][i].y, yb[hh][i]));
        stsm4(qa + 2560 * hh, o);
      }
      TL(9 + u);
    }
    fence_async();
    __syncwarp();
    if (lane == 0) {
      tma_store3(&p.to, ch0, 8 * rank, 8 * w, sb + OFF_TQ + w * 5120);
      asm volatile("cp.async.bulk.commit_group;" ::: "memory");
      asm volatile("cp.async.bulk.wait_group.read 0;" ::: "memory");
    }
    TL(14);
    TL_DUMP();
  }
}

typedef CUresult (*EncodeFn)(CUtensorMap*, CUtensorMapDataType, cuuint32_t, void*, const cuuint64_t*, const cuuint64_t*,
                             const cuuint32_t*, const cuuint32_t*, CUtensorMapInterleave, CUtensorMapSwizzle,
                             CUtensorMapL2promotion, CUtensorMapFloatOOBfill);

void encode(EncodeFn fn, CUtensorMap* tm, const void* ptr, int nd, const cuuint64_t* dims, const cuuint64_t* strides,
            const cuuint32_t* box, CUtensorMapSwizzle swz) {
  cuuint32_t es[4] = {1, 1, 1, 1};
  fn(tm, CU_TENSOR_MAP_DATA_TYPE_BFLOAT16, nd, const_cast<void*>(ptr), dims, strides, box, es, CU_TENSOR_MAP_INTERLEAVE_NONE,
     swz, CU_TENSOR_MAP_L2_PROMOTION_L2_128B, CU_TENSOR_MAP_FLOAT_OOB_FILL_NONE);
}
void map1(EncodeFn fn, CUtensorMap* tm, const void* ptr, int nhi) {
  const cuuint64_t dims[4] = {DCH, 4, 8, SEQ / 32}, strides[3] = {8 * DCH * 2, DCH * 2, 32 * DCH * 2};
  const cuuint32_t box[4] = {CPC, 4, 8, (cuuint32_t)nhi};
  encode(fn, tm, ptr, 4, dims, strides, box, CU_TENSOR_MAP_SWIZZLE_NONE);
}
void map2(EncodeFn fn, CUtensorMap* tm, const void* ptr, int nr) {
  const cuuint64_t dims[3] = {DCH, SEQ / 32, 32}, strides[2] = {32 * DCH * 2, DCH * 2};
  const cuuint32_t box[3] = {CPC, 8, (cuuint32_t)nr};
  encode(fn, tm, ptr, 3, dims, strides, box, CU_TENSOR_MAP_SWIZZLE_NONE);
}

}

extern "C" void kernel_launch(void* const* d_in, const int* in_sizes, int n_in, void* d_out, int out_size) {
  (void)in_sizes; (void)n_in; (void)out_size;
  static EncodeFn fn = nullptr;
  if (!fn) {
    cudaDriverEntryPointQueryResult qr;
    cudaGetDriverEntryPoint("cuTensorMapEncodeTiled", (void**)&fn, cudaEnableDefault, &qr);
    cudaFuncSetAttribute(fused_kernel, cudaFuncAttributeMaxDynamicSharedMemorySize, SMEM_BYTES);
  }
  Params p;
  map1(fn, &p.tq, d_in[0], 4);
  map1(fn, &p.tk, d_in[1], 9);
  map1(fn, &p.tv, d_in[2], 8);
  map2(fn, &p.tq2, d_in[0], 32);
  map2(fn, &p.to, d_out, 8);
  {
    const cuuint64_t dims[4] = {32, SEQ / 32, DCH / 8, 8}, strides[3] = {64, 8 * SEQ * 2, SEQ * 2};
    const cuuint32_t box[4] = {32, 64, 5, 1};
    encode(fn, &p.th, d_in[4], 4, dims, strides, box, CU_TENSOR_MAP_SWIZZLE_64B);
  }
  p.q = (const __nv_bfloat16*)d_in[0];
  p.shift_k = (const __nv_bfloat16*)d_in[3];
  p.ssm_D = (const __nv_bfloat16*)d_in[5];
  p.logA = (const __nv_bfloat16*)d_in[7];
  p.Aim = (const __nv_bfloat16*)d_in[8];
  p.Cre = (const __nv_bfloat16*)d_in[9];
  p.Cim = (const __nv_bfloat16*)d_in[10];
  p.logdt = (const __nv_bfloat16*)d_in[11];
  p.Dskip = (const __nv_bfloat16*)d_in[12];
  p.gate_w = (const __nv_bfloat16*)d_in[13];
  fused_kernel<<<NCL * CS, NTHREADS, SMEM_BYTES, cudaStreamPerThread>>>(p);
}
```

```cpp
#include <cuda_runtime.h>
#include <cuda_bf16.h>
#include <cuda.h>
#include <stdint.h>

#define TIMELINE 0

namespace {

constexpr int SEQ = 2048, DCH = 576, NMODE = 128;
constexpr int CS = 8, CPC = 40, NCL = 15, NTHREADS = 512;

constexpr int YPITCH = 528;
constexpr int KTAB = 28672;
constexpr int OFF_T = 0;
constexpr int OFF_UKV = 2 * KTAB + 8192;
constexpr int OFF_UX = 3 * KTAB;
constexpr int OFF_HA = OFF_UX + 20480;
constexpr int OFF_CF = OFF_HA + 20480;
constexpr int OFF_CL = OFF_CF + 8192;
constexpr int OFF_TQ = OFF_CL + 4096;
constexpr int OFF_TK = OFF_TQ + 20480;
constexpr int OFF_YA = OFF_TK;
constexpr int OFF_TV = OFF_TK + 23040;
constexpr int OFF_YB = OFF_TV + 20480;
constexpr int OFF_KC = OFF_YB + 40 * YPITCH;
constexpr int OFF_SW = OFF_KC + 3 * 1408;
constexpr int OFF_GW = OFF_SW + 320;
constexpr int OFF_SD = OFF_GW + 80;
constexpr int OFF_MB = OFF_SD + 32;
constexpr int OFF_TL = OFF_MB + 24 * 8;
constexpr int SMEM_BYTES = OFF_TL + (TIMELINE ? 2048 : 0);
static_assert(SMEM_BYTES <= 232448, "smem");
static_assert((KTAB & 1023) == 0 && (OFF_TQ & 127) == 0 && (OFF_TK & 127) == 0 && (OFF_TV & 127) == 0 && (OFF_MB & 7) == 0 && (OFF_KC & 15) == 0, "align");

enum { MB_UX = 0, MB_UKV = 5, MB_Y = 10, MB_Q2 = 15, MB_XQ = 16, MB_KV = 18, MB_HA = 19, MB_CF = 20, MB_COUNT = 21 };
enum { NB_WG0 = 1 };

constexpr double cos_turn(int m, int n) {
  m &= n - 1;
  if (m > n / 2) m = n - m;
  double sgn = 1.0;
  if (m > n / 4) { m = n / 2 - m; sgn = -1.0; }
  if (m == n / 4) return 0.0;
  const double x = 6.283185307179586476925 * m / n;
  double term = 1.0, sum = 1.0;
  for (int k = 1; k < 14; k++) { term *= -x * x / ((2 * k - 1) * (2 * k)); sum += term; }
  return sgn * sum;
}
constexpr uint32_t bf16_bits(double v) {
  if (v == 0.0) return 0;
  uint32_t sgn = 0;
  if (v < 0) { sgn = 0x8000; v = -v; }
  int e = 127;
  while (v < 1.0) { v *= 2.0; e--; }
  while (v >= 2.0) { v *= 0.5; e++; }
  const double f = v * 128.0;
  int m = (int)f;
  if (f - m > 0.5 || (f - m == 0.5 && (m & 1))) m++;
  return sgn | (uint32_t)((e << 7) + (m - 128));
}
constexpr uint32_t pair_bits(double lo, double hi) { return bf16_bits(lo) | (bf16_bits(hi) << 16); }
struct alignas(128) Tables {
  uint32_t mat[3072];
  uint32_t thr[4][128][4];
};
constexpr Tables make_tables() {
  Tables T{};
  for (int q = 0; q < 768; q++) {
    int m0 = 0, d0 = 0, d1 = 0;
    if (q < 512) {
      const int r = (q >> 6) * 8 + (q & 7), cc = (q >> 3) & 7;
      d0 = 4 * (r & 31); d1 = 2 * d0;
      m0 = 8 * (cc & 3) * d0 + ((r >> 5) == (cc >> 2) ? 0 : (r >> 5) ? 96 : 32);
    } else {
      const int r = ((q - 512) >> 5) * 8 + (q & 7), pc = (q >> 3) & 3;
      d0 = 4 * (8 * (r >> 4) + (r & 7)) + 1; d1 = 8 * d0;
      m0 = 2 * pc * d0 + ((r & 8) ? 32 : 0);
    }
    for (int e = 0; e < 4; e++) T.mat[4 * q + e] = pair_bits(cos_turn(m0 + e * d1, 128), cos_turn(m0 + e * d1 + d0, 128));
  }
  for (int tid = 0; tid < 128; tid++) {
    const int kk = 4 * (tid >> 2) + 1, t = tid & 3;
    for (int q = 0; q < 4; q++) {
      const int m = (8 * q + 2 * t) * kk;
      T.thr[q >> 1][tid][2 * (q & 1)] = pair_bits(cos_turn(m, 128), cos_turn(m + kk, 128));
      T.thr[q >> 1][tid][2 * (q & 1) + 1] = pair_bits(cos_turn(m + 32, 128), cos_turn(m + kk + 32, 128));
      T.thr[2][tid][q] = pair_bits(cos_turn(m, 4096), cos_turn(m + kk, 4096));
      T.thr[3][tid][q] = pair_bits(cos_turn(m + 3072, 4096), cos_turn(m + kk + 3072, 4096));
    }
  }
  return T;
}
__device__ const Tables d_tab = make_tables();

struct Params {
  const __nv_bfloat16 *logA, *Aim, *Cre, *Cim, *logdt;
  const Tables* tab;
  unsigned* cnt;
  const __nv_bfloat16 *Dskip, *shift_k, *ssm_D, *gate_w, *q;
  uint2* part;
  CUtensorMap tq, tk, tv, th, tq2, to;
};

__device__ uint2 g_part[NCL * SEQ];
__device__ unsigned g_cnt[CS * 32];
#define TL(i) do {} while (0)
#define TL_INIT() do {} while (0)
#define TL_DUMP() do {} while (0)

__device__ __forceinline__ uint32_t lds16(uint32_t a) { uint32_t v; asm volatile("ld.shared.u16 %0, [%1];" : "=r"(v) : "r"(a) : "memory"); return v; }
__device__ __forceinline__ uint2 lds64(uint32_t a) { uint2 v; asm volatile("ld.shared.v2.u32 {%0,%1}, [%2];" : "=r"(v.x), "=r"(v.y) : "r"(a) : "memory"); return v; }
__device__ __forceinline__ uint4 lds128(uint32_t a) { uint4 v; asm volatile("ld.shared.v4.u32 {%0,%1,%2,%3}, [%4];" : "=r"(v.x), "=r"(v.y), "=r"(v.z), "=r"(v.w) : "r"(a) : "memory"); return v; }
__device__ __forceinline__ void sts16(uint32_t a, uint32_t v) { asm volatile("st.shared.u16 [%0], %1;" :: "r"(a), "r"(v) : "memory"); }
__device__ __forceinline__ void sts32(uint32_t a, uint32_t v) { asm volatile("st.shared.u32 [%0], %1;" :: "r"(a), "r"(v) : "memory"); }
__device__ __forceinline__ void sts64(uint32_t a, uint32_t x, uint32_t y) { asm volatile("st.shared.v2.u32 [%0], {%1,%2};" :: "r"(a), "r"(x), "r"(y) : "memory"); }
__device__ __forceinline__ void sts128(uint32_t a, uint32_t x, uint32_t y, uint32_t z, uint32_t w) { asm volatile("st.shared.v4.u32 [%0], {%1,%2,%3,%4};" :: "r"(a), "r"(x), "r"(y), "r"(z), "r"(w) : "memory"); }
__device__ __forceinline__ void ldsm4t(uint32_t (&r)[4], uint32_t a) { asm volatile("ldmatrix.sync.aligned.m8n8.x4.trans.shared.b16 {%0,%1,%2,%3}, [%4];" : "=r"(r[0]), "=r"(r[1]), "=r"(r[2]), "=r"(r[3]) : "r"(a) : "memory"); }
__device__ __forceinline__ void ldsm2t(uint32_t& r0, uint32_t& r1, uint32_t a) { asm volatile("ldmatrix.sync.aligned.m8n8.x2.trans.shared.b16 {%0,%1}, [%2];" : "=r"(r0), "=r"(r1) : "r"(a) : "memory"); }
__device__ __forceinline__ void ldsm4(uint32_t (&r)[4], uint32_t a) { asm volatile("ldmatrix.sync.aligned.m8n8.x4.shared.b16 {%0,%1,%2,%3}, [%4];" : "=r"(r[0]), "=r"(r[1]), "=r"(r[2]), "=r"(r[3]) : "r"(a) : "memory"); }
__device__ __forceinline__ void stsm4(uint32_t a, const uint32_t (&r)[4]) { asm volatile("stmatrix.sync.aligned.m8n8.x4.shared.b16 [%0], {%1,%2,%3,%4};" :: "r"(a), "r"(r[0]), "r"(r[1]), "r"(r[2]), "r"(r[3]) : "memory"); }
__device__ __forceinline__ uint32_t pack(float lo, float hi) { uint32_t r; asm("cvt.rn.bf16x2.f32 %0, %1, %2;" : "=r"(r) : "f"(hi), "f"(lo)); return r; }
__device__ __forceinline__ float blo(uint32_t v) { return __uint_as_float(v << 16); }
__device__ __forceinline__ float bhi(uint32_t v) { return __uint_as_float(v & 0xffff0000u); }
__device__ __forceinline__ float bf16r(float x) { return blo(pack(x, 0.f)); }
__device__ __forceinline__ uint32_t hmul2(uint32_t a, uint32_t b) { uint32_t r; asm("mul.rn.bf16x2 %0, %1, %2;" : "=r"(r) : "r"(a), "r"(b)); return r; }
__device__ __forceinline__ uint32_t hadd2(uint32_t a, uint32_t b) { uint32_t r; asm("add.rn.bf16x2 %0, %1, %2;" : "=r"(r) : "r"(a), "r"(b)); return r; }
__device__ __forceinline__ uint32_t hfma2(uint32_t a, uint32_t b, uint32_t c) { uint32_t r; asm("fma.rn.bf16x2 %0, %1, %2, %3;" : "=r"(r) : "r"(a), "r"(b), "r"(c)); return r; }
__device__ __forceinline__ uint32_t prmt(uint32_t a, uint32_t b, uint32_t s) { return __byte_perm(a, b, s); }
__device__ __forceinline__ uint32_t ldraw(const __nv_bfloat16* p) { uint32_t v; asm volatile("ld.global.nc.u16 %0, [%1];" : "=r"(v) : "l"(p)); return v; }
__device__ __forceinline__ uint4 ldg128(const void* p) { uint4 v; asm volatile("ld.global.nc.v4.u32 {%0,%1,%2,%3}, [%4];" : "=r"(v.x), "=r"(v.y), "=r"(v.z), "=r"(v.w) : "l"(p)); return v; }
__device__ __forceinline__ void bar_sync(int id, int n) { asm volatile("bar.sync %0, %1;" :: "r"(id), "r"(n) : "memory"); }
__device__ __forceinline__ void bar_arrive(int id, int n) { asm volatile("bar.arrive %0, %1;" :: "r"(id), "r"(n) : "memory"); }
__device__ __forceinline__ void cluster_arrive() { asm volatile("barrier.cluster.arrive.relaxed.aligned;" ::: "memory"); }
__device__ __forceinline__ void cluster_wait() { asm volatile("barrier.cluster.wait.aligned;" ::: "memory"); }
__device__ __forceinline__ void fence_async() { asm volatile("fence.proxy.async.shared::cta;" ::: "memory"); }
__device__ __forceinline__ void fence_mbinit() { asm volatile("fence.mbarrier_init.release.cluster;" ::: "memory"); }
__device__ __forceinline__ uint32_t mapa(uint32_t a, uint32_t rank) { uint32_t r; asm("mapa.shared::cluster.u32 %0, %1, %2;" : "=r"(r) : "r"(a), "r"(rank)); return r; }
__device__ __forceinline__ void st_async4(uint32_t a, uint32_t x, uint32_t y, uint32_t z, uint32_t w, uint32_t mbar) {
  asm volatile("st.async.weak.shared::cluster.mbarrier::complete_tx::bytes.v4.b32 [%0], {%1,%2,%3,%4}, [%5];"
               :: "r"(a), "r"(x), "r"(y), "r"(z), "r"(w), "r"(mbar) : "memory");
}
__device__ __forceinline__ void mbar_init(uint32_t m, uint32_t cnt) { asm volatile("mbarrier.init.shared::cta.b64 [%0], %1;" :: "r"(m), "r"(cnt) : "memory"); }
__device__ __forceinline__ void mbar_expect(uint32_t m, uint32_t bytes) { asm volatile("mbarrier.arrive.expect_tx.shared::cta.b64 _, [%0], %1;" :: "r"(m), "r"(bytes) : "memory"); }
__device__ __forceinline__ void mbar_wait(uint32_t m) {
  uint32_t done;
  int it = 0;
  do {
    asm volatile("{.reg .pred p; mbarrier.try_wait.parity.shared::cta.b64 p, [%1], 0; selp.u32 %0, 1, 0, p;}" : "=r"(done) : "r"(m) : "memory");
    if (++it > (1 << 22)) __trap();
  } while (!done);
}
__device__ __forceinline__ void tma_load4(uint32_t dst, const CUtensorMap* tm, int c0, int c1, int c2, int c3, uint32_t mbar) {
  asm volatile("cp.async.bulk.tensor.4d.shared::cluster.global.mbarrier::complete_tx::bytes [%0], [%1, {%3, %4, %5, %6}], [%2];"
               :: "r"(dst), "l"(tm), "r"(mbar), "r"(c0), "r"(c1), "r"(c2), "r"(c3) : "memory");
}
__device__ __forceinline__ void tma_load3(uint32_t dst, const CUtensorMap* tm, int c0, int c1, int c2, uint32_t mbar) {
  asm volatile("cp.async.bulk.tensor.3d.shared::cluster.global.mbarrier::complete_tx::bytes [%0], [%1, {%3, %4, %5}], [%2];"
               :: "r"(dst), "l"(tm), "r"(mbar), "r"(c0), "r"(c1), "r"(c2) : "memory");
}
__device__ __forceinline__ void tma_store3(const CUtensorMap* tm, int c0, int c1, int c2, uint32_t src) {
  asm volatile("cp.async.bulk.tensor.3d.global.shared::cta.bulk_group [%0, {%2, %3, %4}], [%1];"
               :: "l"(tm), "r"(src), "r"(c0), "r"(c1), "r"(c2) : "memory");
}
__device__ __forceinline__ void wg_fence() { asm volatile("wgmma.fence.sync.aligned;" ::: "memory"); }
__device__ __forceinline__ void wg_commit() { asm volatile("wgmma.commit_group.sync.aligned;" ::: "memory"); }
template <int N> __device__ __forceinline__ void wg_wait() { asm volatile("wgmma.wait_group.sync.aligned %0;" :: "n"(N) : "memory"); }
template <int N> __device__ __forceinline__ void tie_all(float (&x)[N]) {
#pragma unroll
  for (int i = 0; i < N; i++) asm volatile("" : "+f"(x[i]) :: "memory");
}
#define R16(C, d) C(d[0]), C(d[1]), C(d[2]), C(d[3]), C(d[4]), C(d[5]), C(d[6]), C(d[7]), C(d[8]), C(d[9]), C(d[10]), C(d[11]), C(d[12]), C(d[13]), C(d[14]), C(d[15])
#define R32(C, d) R16(C, d), R16(C, (d + 16))
#define P16 "{%0,%1,%2,%3,%4,%5,%6,%7,%8,%9,%10,%11,%12,%13,%14,%15}"
#define P32 "{%0,%1,%2,%3,%4,%5,%6,%7,%8,%9,%10,%11,%12,%13,%14,%15,%16,%17,%18,%19,%20,%21,%22,%23,%24,%25,%26,%27,%28,%29,%30,%31}"
template <int SD, int TB, int OFF> __device__ __forceinline__ void rs64(float* d, const uint32_t* a, uint64_t db) {
  if (SD) asm volatile("{.reg .b64 db; add.s64 db, %36, %37; wgmma.mma_async.sync.aligned.m64n64k16.f32.bf16.bf16 " P32 ", {%32,%33,%34,%35}, db, 1, 1, 1, %38;}"
                       : R32("+f", d) : "r"(a[0]), "r"(a[1]), "r"(a[2]), "r"(a[3]), "l"(db), "n"(OFF), "n"(TB));
  else asm volatile("{.reg .b64 db; add.s64 db, %36, %37; wgmma.mma_async.sync.aligned.m64n64k16.f32.bf16.bf16 " P32 ", {%32,%33,%34,%35}, db, 0, 1, 1, %38;}"
                    : R32("=f", d) : "r"(a[0]), "r"(a[1]), "r"(a[2]), "r"(a[3]), "l"(db), "n"(OFF), "n"(TB));
}
template <int SD, int OFFA, int OFFB> __device__ __forceinline__ void ss32(float* d, uint64_t da, uint64_t db) {
  if (SD) asm volatile("{.reg .b64 da, db; add.s64 da, %16, %18; add.s64 db, %17, %19; wgmma.mma_async.sync.aligned.m64n32k16.f32.bf16.bf16 " P16 ", da, db, 1, 1, 1, 1, 1;}"
                       : R16("+f", d) : "l"(da), "l"(db), "n"(OFFA), "n"(OFFB));
  else asm volatile("{.reg .b64 da, db; add.s64 da, %16, %18; add.s64 db, %17, %19; wgmma.mma_async.sync.aligned.m64n32k16.f32.bf16.bf16 " P16 ", da, db, 0, 1, 1, 1, 1;}"
                    : R16("=f", d) : "l"(da), "l"(db), "n"(OFFA), "n"(OFFB));
}
template <int KS> __device__ __forceinline__ void kgen_mma(float (&c)[24], uint64_t da) {
  asm volatile("{.reg .b64 da, db; add.s64 da, %24, %25; add.s64 db, %24, %26;\n"
               "wgmma.mma_async.sync.aligned.m64n48k16.f32.bf16.bf16 {%0,%1,%2,%3,%4,%5,%6,%7,%8,%9,%10,%11,%12,%13,%14,%15,%16,%17,%18,%19,%20,%21,%22,%23}, da, db, %27, 1, 1, 1, 1;}"
               : R16("+f", c), "+f"(c[16]), "+f"(c[17]), "+f"(c[18]), "+f"(c[19]), "+f"(c[20]), "+f"(c[21]), "+f"(c[22]), "+f"(c[23])
               : "l"(da), "n"(8 * KS), "n"(8 * KS + 512), "n"(KS ? 1 : 0));
  if constexpr (KS < 7) kgen_mma<KS + 1>(c, da);
}
__device__ __forceinline__ uint64_t desc_lo(uint32_t a) { return (uint64_t)((a & 0x3FFFF) >> 4); }
__device__ __forceinline__ void stage1(float (&D)[32], const uint32_t (&A1)[8], uint32_t src) {
  const uint64_t du = desc_lo(src) | (128ull << 16) | (32ull << 32) | (2ull << 62);
  rs64<0, 1, 0>(D, A1, du); rs64<1, 1, 64>(D, A1 + 4, du);
}
template <int INV> __device__ __forceinline__ void stage2(float (&X)[32], const uint32_t (&F)[16], uint32_t cf) {
  constexpr int KS = INV ? 16 : 128, TB = INV ? 0 : 1;
  const uint64_t dc = desc_lo(cf) | (INV ? (8ull << 16) | (64ull << 32) : (64ull << 16) | (8ull << 32));
  rs64<0, TB, 0>(X, F, dc); rs64<1, TB, KS>(X, F + 4, dc); rs64<1, TB, 2 * KS>(X, F + 8, dc); rs64<1, TB, 3 * KS>(X, F + 12, dc);
}
__device__ __forceinline__ void fwd_mid(uint32_t (&F)[16], const float (&D)[32], const uint32_t (&tp)[12]) {
#pragma unroll
  for (int j = 0; j < 4; j++)
#pragma unroll
    for (int b = 0; b < 2; b++) {
      const int i = 4 * j + 16 * b;
      const uint32_t ar = pack(D[i], D[i + 1]), ai = pack(D[i + 2], D[i + 3]);
      F[2 * j + b] = hfma2(ar, tp[3 * j], hmul2(ai, tp[3 * j + 2]));
      F[8 + 2 * j + b] = hfma2(ar, tp[3 * j + 1], hmul2(ai, tp[3 * j]));
    }
}

struct cf { float x, y; };
__device__ __forceinline__ cf cmul(cf a, cf b) { cf r; r.x = fmaf(a.x, b.x, -a.y * b.y); r.y = fmaf(a.x, b.y, a.y * b.x); return r; }
__device__ __forceinline__ cf cexp_p(float lr2, float lt, float p) {
  float m = exp2f(lr2 * p);
  float t = lt * p;
  t = (t - rintf(t)) * 6.283185307179586f;
  cf r; r.x = m * __cosf(t); r.y = m * __sinf(t); return r;
}
__device__ __forceinline__ void store8(uint32_t a, const cf (&v)[8]) {
  sts128(a, pack(v[0].x, v[1].x), pack(v[2].x, v[3].x), pack(v[4].x, v[5].x), pack(v[6].x, v[7].x));
  sts128(a + KTAB / 2, pack(v[0].y, v[1].y), pack(v[2].y, v[3].y), pack(v[4].y, v[5].y), pack(v[6].y, v[7].y));
}
__device__ __forceinline__ float sigmoidf_(float s) { return 1.f / (1.f + __expf(-s)); }

__global__ void __cluster_dims__(CS, 1, 1) __launch_bounds__(NTHREADS, 1) fused_kernel(const __grid_constant__ Params p) {
  extern __shared__ __align__(1024) uint8_t smem[];
  TL_INIT();
  TL(31);
  const uint32_t sb = (uint32_t)__cvta_generic_to_shared(smem);
  const uint32_t mb = sb + OFF_MB;
  const int wg = __shfl_sync(0xffffffffu, threadIdx.x >> 7, 0);
  const int tid = threadIdx.x & 127, w = __shfl_sync(0xffffffffu, tid >> 5, 0), lane = tid & 31, g = lane >> 2, t = lane & 3;
  const int cl = blockIdx.x >> 3, rank = blockIdx.x & 7;
  const int ch0 = cl * CPC;
  const int nu = min(5, (DCH - ch0) >> 3);

  if (wg < 3) {
    uint32_t pla[2], pai[2], pcr[2], pci[2], pdt[2];
#pragma unroll
    for (int r = 0; r < 2; r++) {
      const int ch = (wg + 3 * r < nu) ? ch0 + 8 * (wg + 3 * r) + rank : 0;
      pla[r] = ldraw(p.logA + ch * NMODE + tid);
      pai[r] = ldraw(p.Aim + ch * NMODE + tid);
      pcr[r] = ldraw(p.Cre + ch * NMODE + tid);
      pci[r] = ldraw(p.Cim + ch * NMODE + tid);
      pdt[r] = ldraw(p.logdt + ch);
    }
    cluster_arrive();
    uint32_t A1[8], tp[12];
    {
      const uint4 a = ldg128(p.tab->thr[0][tid]), b = ldg128(p.tab->thr[1][tid]), c = ldg128(p.tab->thr[2][tid]), d = ldg128(p.tab->thr[3][tid]);
      A1[0] = a.x; A1[1] = a.y; A1[2] = a.z; A1[3] = a.w; A1[4] = b.x; A1[5] = b.y; A1[6] = b.z; A1[7] = b.w;
      tp[0] = c.x; tp[3] = c.y; tp[6] = c.z; tp[9] = c.w; tp[2] = d.x; tp[5] = d.y; tp[8] = d.z; tp[11] = d.w;
      tp[1] = tp[4] = tp[7] = tp[10] = 0;
    }
    TL(0);
    const uint32_t tab = sb + OFF_T + wg * KTAB;
#pragma unroll 1
    for (int job = 0; job < 4; job++) {
      const bool isA = job >= (wg == 2 ? 1 : 2);
      const int u = wg == 2 ? (job ? 2 * job - 2 : 2) : job < 2 ? wg + 3 * job : job == 2 ? 2 * wg + 1 : 9;

      if (!isA && u < nu) {
        const float la = blo(job ? pla[1] : pla[0]), ai = blo(job ? pai[1] : pai[0]), cr = blo(job ? pcr[1] : pcr[0]), ci = blo(job ? pci[1] : pci[0]);
        const float dt = bf16r(expf(blo(job ? pdt[1] : pdt[0])));
        const float lr2 = (-bf16r(expf(la)) * dt) * 1.4426950408889634f;
        const float lt = (ai * dt) * 0.15915494309189535f;
        const uint32_t row = tab + tid * 16;
        if (lr2 != 123.f) TL(16 + 4 * job);
        if (job) bar_sync(NB_WG0 + wg, 128);
        {
          const cf w1 = cexp_p(lr2, lt, 8.f);
          cf v[8];
          v[0].x = 1.f; v[0].y = 0.f; v[1] = w1; v[2] = cmul(w1, w1); v[3] = cmul(v[2], w1);
          const cf w4 = cmul(v[2], v[2]);
          v[4] = w4; v[5] = cmul(v[1], w4); v[6] = cmul(v[2], w4); v[7] = cmul(v[3], w4);
          const cf w8 = cmul(w4, w4);
          store8(row, v);
#pragma unroll
          for (int c = 1; c < 4; c++) {
#pragma unroll
            for (int i = 0; i < 8; i++) v[i] = (c == 1 && i == 0) ? w8 : cmul(v[i], w8);
            store8(row + 2048 * c, v);
          }
        }
        {
          cf z1 = cexp_p(lr2, lt, 1.f), Z = cexp_p(lr2, lt, 256.f);
          z1.y = -z1.y; Z.y = -Z.y;
          const cf z2 = cmul(z1, z1);
          cf h[8], v[8];
          h[0].x = 2.f * cr * dt; h[0].y = -2.f * ci * dt;
          h[1] = cmul(h[0], z1);
#pragma unroll
          for (int i = 2; i < 8; i++) h[i] = cmul(h[i - 2], z2);
          store8(row + 4 * 2048, h);
          v[0] = cmul(h[0], Z); v[1] = cmul(h[2], Z); v[2] = cmul(h[4], Z); v[3] = cmul(h[6], Z);
          v[4] = cmul(v[0], Z); v[5] = cmul(v[2], Z); v[6] = cmul(v[4], Z); v[7] = cmul(v[5], Z);
          store8(row + 5 * 2048, v);
          const cf Z2 = cmul(Z, Z);
          h[0] = cmul(v[4], Z2); h[1] = cmul(v[6], Z2); h[2] = cmul(h[0], Z2); h[3] = cmul(h[1], Z2); h[4] = cmul(h[2], Z2);
          h[5].x = h[5].y = h[6].x = h[6].y = h[7].x = h[7].y = 0.f;
          store8(row + 6 * 2048, h);
        }
        TL(17 + 4 * job);
        fence_async();
        bar_sync(NB_WG0 + wg, 128);
        float c[24];
        wg_fence();
        kgen_mma<0>(c, desc_lo(tab) | ((uint64_t)(KTAB / 32) << 16) | (64ull << 32));
        wg_commit();
        uint32_t kid[8];
        {
          float lf = __uint_as_float(0x4b000000u | (8 * tid)) - 8388608.f;
          asm volatile("" : "+f"(lf));
          const float lo = tid < 16 ? lf + 128.f : lf;
          const uint32_t sub = tid < 16 ? 0x42804300u : 0x42804280u;
#pragma unroll
          for (int i = 0; i < 8; i++) kid[i] = 2 * (pack(lo + i, lf + (1024 + i)) - sub);
        }
        wg_wait<0>(); tie_all(c);
        const uint32_t kc = sb + OFF_KC + wg * 1408;
        {
          const int a = 8 * w + g;
          sts32(kc + 4 * (4 * a + t), pack(c[0] + c[6], c[1] + c[7]));
          sts32(kc + 4 * (t < 2 ? 128 + 2 * a + t : 128 + 32 * t + a), pack(c[8] + c[14], c[9] + c[15]));
          if (t < 3) {
            const uint32_t p0 = pack(c[16] + c[22], c[17] + c[23]);
            sts16(kc + 2 * (512 + 64 * t + a), p0);
            sts16(kc + 2 * (544 + 64 * t + a), p0 >> 16);
          }
        }
        TL(18 + 4 * job);
        bar_sync(NB_WG0 + wg, 128);
        uint32_t v[2][8];
#pragma unroll
        for (int i = 0; i < 8; i++) { v[0][i] = lds16(kc + (kid[i] & 0xffffu)); v[1][i] = lds16(kc + (kid[i] >> 16)); }
#pragma unroll
        for (int cc = 0; cc < 2; cc++)
          sts128(tab + 2048 * cc + 16 * (tid ^ ((tid >> 3) & 3)), prmt(v[cc][0], v[cc][1], 0x5410), prmt(v[cc][2], v[cc][3], 0x5410),
                 prmt(v[cc][4], v[cc][5], 0x5410), prmt(v[cc][6], v[cc][7], 0x5410));
        fence_async();
        if (job) bar_sync(NB_WG0 + wg, 128);
      }
      if (job == 0) {
        cluster_wait();
        cluster_arrive();
        bar_sync(NB_WG0 + wg, 128);
        mbar_wait(mb + 8 * MB_CF);
#pragma unroll
        for (int j = 0; j < 4; j++) tp[3 * j + 1] = tp[3 * j + 2] ^ 0x80008000u;
      }
      if (u >= nu) continue;
      TL(1 + job);
      float D[32], H[32], X[32];
      uint32_t F[16];
      if (isA) mbar_wait(mb + 8 * MB_HA);
      wg_fence();
      stage1(D, A1, isA ? sb + OFF_HA + u * 4096 : tab);
      wg_commit();
      wg_wait<0>(); tie_all(D);
      fwd_mid(F, D, tp);
      mbar_wait(mb + 8 * ((isA ? MB_UKV : MB_UX) + u));
      fence_async();
      TL(5 + job);
      wg_fence();
      stage2<0>(H, F, sb + OFF_CF);
      stage1(D, A1, sb + (isA ? OFF_UKV : OFF_UX) + u * 4096);
      wg_commit();
      wg_wait<0>(); tie_all(D); tie_all(H);
      fwd_mid(F, D, tp);
      wg_fence();
      stage2<0>(X, F, sb + OFF_CF);
      wg_commit();
      {
        const float dsk = blo(lds16(sb + OFF_SD + (isA ? 10 : 0) + 2 * u));
#pragma unroll
        for (int j = 0; j < 4; j++) { H[4 * j] += dsk; H[4 * j + 1] += dsk; }
      }
      wg_wait<0>(); tie_all(X);
#pragma unroll
      for (int j = 0; j < 4; j++) {
        float pr[2], pi[2], qr[2], qi[2];
#pragma unroll
        for (int n = 0; n < 2; n++) {
          const int i = 4 * j + n;
          pr[n] = fmaf(X[i], H[i], -X[i + 16] * H[i + 16]);
          pi[n] = fmaf(X[i], H[i + 16], X[i + 16] * H[i]);
          qr[n] = fmaf(X[i + 2], H[i], fmaf(-X[i + 18], H[i + 16], fmaf(X[i], H[i + 2], fmaf(-X[i + 16], H[i + 18], -pi[n]))));
          qi[n] = fmaf(X[i + 2], H[i + 16], fmaf(X[i + 18], H[i], fmaf(X[i], H[i + 18], fmaf(X[i + 16], H[i + 2], pr[n]))));
        }
        F[2 * j] = pack(pr[0], pr[1]); F[2 * j + 1] = pack(qr[0], qr[1]); F[8 + 2 * j] = pack(pi[0], pi[1]); F[9 + 2 * j] = pack(qi[0], qi[1]);
      }
      wg_fence();
      stage2<1>(H, F, sb + OFF_CF);
      wg_commit();
      wg_wait<0>(); tie_all(H);
      {
        const uint32_t va = tab + (16 * w + (lane & 15)) * 128;
        const int vx = (lane >> 4) ^ (lane & 7);
#pragma unroll
        for (int j = 0; j < 4; j++) {
          uint32_t V[4];
#pragma unroll
          for (int b = 0; b < 2; b++) {
            const int i = 4 * j + 2 * b;
            const uint32_t er = pack(H[i], H[i + 1]), ei = pack(H[i + 16], H[i + 17]);
            V[2 * b] = hfma2(er, tp[3 * j], hmul2(ei, tp[3 * j + 1]));
            V[2 * b + 1] = hfma2(ei, tp[3 * j], hmul2(er, tp[3 * j + 2]));
          }
          stsm4(va + ((vx ^ (2 * j)) << 4), V);
        }
      }
      fence_async();
      bar_sync(NB_WG0 + wg, 128);
      float O[16];
      {
        const uint64_t dv = desc_lo(tab) | (1ull << 16) | (64ull << 32) | (1ull << 62);
        const uint64_t dl = desc_lo(sb + OFF_CL) | (32ull << 16) | (8ull << 32);
        wg_fence();
        ss32<0, 0, 0>(O, dv, dl); ss32<1, 128, 64>(O, dv, dl); ss32<1, 256, 128>(O, dv, dl); ss32<1, 384, 192>(O, dv, dl);
        wg_commit();
      }
      if (isA && job < 3) {
        for (int k = 0; k < nu; k++) mbar_wait(mb + 8 * (MB_UKV + k));
      }
      wg_wait<0>(); tie_all(O);
      {
        const uint32_t yo = (isA ? OFF_YA : OFF_YB) + (8 * u + rank) * YPITCH + (8 * w + g) * 16, ym = OFF_MB + 8 * (MB_Y + u);
        const uint32_t r0 = mapa(sb, t), r1 = mapa(sb, t + 4);
        st_async4(r0 + yo, pack(O[0], O[1]), pack(O[4], O[5]), pack(O[8], O[9]), pack(O[12], O[13]), r0 + ym);
        st_async4(r1 + yo, pack(O[2], O[3]), pack(O[6], O[7]), pack(O[10], O[11]), pack(O[14], O[15]), r1 + ym);
      }
      TL(9 + job);
    }
    TL_DUMP();
  } else {
    if (lane == 0) {
#pragma unroll
      for (int i = 0; i < 4; i++) mbar_init(mb + 8 * (4 * w + i), 1);
      mbar_init(mb + 8 * (MB_XQ + w), 1);
      if (w == 3) mbar_init(mb + 8 * MB_CF, 2);
      fence_mbinit();
      if (w == 3) {
        mbar_expect(mb + 8 * MB_CF, 12288);
        asm volatile("cp.async.bulk.shared::cluster.global.mbarrier::complete_tx::bytes [%0], [%1], %2, [%3];"
                     :: "r"(sb + OFF_CF), "l"(p.tab->mat), "r"(12288), "r"(mb + 8 * MB_CF) : "memory");
      }
#pragma unroll
      for (int i = 0; i < 4; i++) { const int b = 4 * w + i; mbar_expect(mb + 8 * b, b == MB_Q2 ? 20480 : b >= MB_Y ? 8192 : 4096); }
      mbar_expect(mb + 8 * (MB_XQ + w), w < 2 ? 10240 : w == 2 ? 23040 + 20480 : 20480);
    }
    __syncwarp();
    cluster_arrive();
    uint2 swv = make_uint2(0, 0);
    uint32_t gwv = 0, tag = 0;
    if (tid >= 64 && tid < 104 && ch0 + tid - 64 < DCH) { swv = __ldg((const uint2*)(p.shift_k + (size_t)(ch0 + tid - 64) * 4)); gwv = ldraw(p.gate_w + ch0 + tid - 64); }
    if (tid >= 112 && tid < 122) { const int k = tid - 112, u = k < 5 ? k : k - 5; if (u < nu) gwv = ldraw((k < 5 ? p.Dskip : p.ssm_D) + ch0 + 8 * u + rank); }
    if (tid == 127) tag = (atomicAdd(&p.cnt[rank * 32], cl == 0 ? 16 - (NCL - 1) : 1) >> 4) + 1;
    if (lane == 0 && w < 2) { tma_load4(sb + OFF_TQ + 10240 * w, &p.tq, ch0, 0, 0, 8 * rank + 4 * w, mb + 8 * (MB_XQ + w)); TL(20); }
    if (tid >= 64 && tid < 104) { sts64(sb + OFF_SW + 8 * (tid - 64), swv.x, swv.y); sts16(sb + OFF_GW + 2 * (tid - 64), gwv); }
    if (tid >= 112 && tid < 122) sts16(sb + OFF_SD + 2 * (tid - 112), gwv);
    if (tid == 127) sts32(sb + OFF_MB + 8 * MB_COUNT, tag);
    if (tid == 64) {
      tma_load4(sb + OFF_TK, &p.tk, ch0, 0, 0, 8 * rank - 1, mb + 8 * MB_KV);
      tma_load4(sb + OFF_TV, &p.tv, ch0, 0, 0, 8 * rank, mb + 8 * MB_KV);
    }
    bar_sync(NB_WG0 + 3, 128);
    if (tid == 96) {
      tma_load4(sb + OFF_HA, &p.th, 0, 0, 5 * cl, rank, mb + 8 * MB_HA);
      asm volatile("mbarrier.arrive.shared::cta.b64 _, [%0];" :: "r"(mb + 8 * MB_CF) : "memory");
    }
    tag = lds64(sb + OFF_MB + 8 * MB_COUNT).x;
    TL(0);
    const uint32_t rbase = mapa(sb, g);
    const int mi = lane >> 3, tq = (lane & 7) >> 1, jj = lane & 1;
    const uint32_t toff = (4 * (2 * mi + jj) + tq) * 80;
    const uint32_t uoff = 16 * (32 * rank + 4 * w + (t ^ (w >> 1)));
    cluster_wait();
    cluster_arrive();
    mbar_wait(mb + 8 * MB_XQ);
    mbar_wait(mb + 8 * (MB_XQ + 1));
    TL(1);
    {
      uint32_t xr[5][2][4];
#pragma unroll
      for (int u = 0; u < 5; u++) { ldsm4t(xr[u][0], sb + OFF_TQ + w * 2560 + toff + 16 * u); ldsm4t(xr[u][1], sb + OFF_TQ + (w + 4) * 2560 + toff + 16 * u); }
#pragma unroll
      for (int u = 0; u < 5; u++)
        if (u < nu) {
          st_async4(rbase + OFF_UX + u * 4096 + uoff, xr[u][0][0], xr[u][0][1], xr[u][0][2], xr[u][0][3], rbase + OFF_MB + 8 * (MB_UX + u));
          st_async4(rbase + OFF_UX + u * 4096 + (uoff ^ 32) + 256, xr[u][1][0], xr[u][1][1], xr[u][1][2], xr[u][1][3], rbase + OFF_MB + 8 * (MB_UX + u));
        }
    }
    TL(2);
    {
      float s0 = 0.f, s1 = 0.f;
#pragma unroll
      for (int j = 0; j < 5; j++) {
        const uint4 gw = lds128(sb + OFF_GW + 16 * j);
        const uint4 x0 = lds128(sb + OFF_TQ + tid * 80 + 16 * j), x1 = lds128(sb + OFF_TQ + (tid + 128) * 80 + 16 * j);
        uint32_t m0 = hmul2(x0.x, gw.x), m1 = hmul2(x0.y, gw.y), m2 = hmul2(x0.z, gw.z), m3 = hmul2(x0.w, gw.w);
        s0 += ((blo(m0) + bhi(m0)) + (blo(m1) + bhi(m1))) + ((blo(m2) + bhi(m2)) + (blo(m3) + bhi(m3)));
        m0 = hmul2(x1.x, gw.x); m1 = hmul2(x1.y, gw.y); m2 = hmul2(x1.z, gw.z); m3 = hmul2(x1.w, gw.w);
        s1 += ((blo(m0) + bhi(m0)) + (blo(m1) + bhi(m1))) + ((blo(m2) + bhi(m2)) + (blo(m3) + bhi(m3)));
      }
      const int s2 = 8 * (8 * (lane & 3) + (lane >> 2)) + w;
      asm volatile("st.relaxed.gpu.global.u64 [%0], %1;" :: "l"(&p.part[cl * SEQ + rank * 256 + s2]), "l"(((uint64_t)tag << 32) | __float_as_uint(s0)) : "memory");
      asm volatile("st.relaxed.gpu.global.u64 [%0], %1;" :: "l"(&p.part[cl * SEQ + rank * 256 + s2 + 4]), "l"(((uint64_t)tag << 32) | __float_as_uint(s1)) : "memory");
    }
    bar_sync(NB_WG0 + 3, 128);
    if (tid == 0) tma_load3(sb + OFF_TQ, &p.tq2, ch0, 8 * rank, 0, mb + 8 * MB_Q2);
    __syncwarp();
    TL(3);
    cluster_wait();
    mbar_wait(mb + 8 * MB_KV);
    TL(4);
    const uint32_t hoff = (4 * (4 + 2 * (mi & 1) + jj) + ((tq + 3) & 3)) * 80 + (tq ? 2560 : 0);
#pragma unroll 1
    for (int u = 0; u < nu; u++) {
      const uint2 sw = lds64(sb + OFF_SW + 8 * (8 * u + g));
      uint32_t E[2][6], V[2][4];
#pragma unroll
      for (int hf = 0; hf < 2; hf++) {
        const int ah = 4 * hf + w;
        uint32_t K[4];
        ldsm4t(K, sb + OFF_TK + (ah + 1) * 2560 + toff + 16 * u);
        ldsm2t(E[hf][0], E[hf][1], sb + OFF_TK + ah * 2560 + hoff + 16 * u);
        ldsm4t(V[hf], sb + OFF_TV + ah * 2560 + toff + 16 * u);
        E[hf][2] = K[0]; E[hf][3] = K[1]; E[hf][4] = K[2]; E[hf][5] = K[3];
      }
      const uint32_t w0 = prmt(sw.x, 0, 0x1010), w1 = prmt(sw.x, 0, 0x3232), w2 = prmt(sw.y, 0, 0x1010), w3 = prmt(sw.y, 0, 0x3232);
#pragma unroll
      for (int hf = 0; hf < 2; hf++) {
        uint32_t O[5], o[4];
#pragma unroll
        for (int i = 0; i < 5; i++) O[i] = prmt(E[hf][i], E[hf][i + 1], 0x5432);
#pragma unroll
        for (int i = 0; i < 4; i++) {
          uint32_t s = hmul2(O[i], w3);
          s = hadd2(s, hmul2(E[hf][i + 1], w2));
          s = hadd2(s, hmul2(O[i + 1], w1));
          s = hadd2(s, hmul2(E[hf][i + 2], w0));
          o[i] = hmul2(s, V[hf][i]);
        }
        st_async4(rbase + OFF_UKV + u * 4096 + (hf ? (uoff ^ 32) + 256 : uoff), o[0], o[1], o[2], o[3], rbase + OFF_MB + 8 * (MB_UKV + u));
      }
    }
    TL(5);
    bar_sync(NB_WG0 + 3, 128);
    {
      float s[2] = {0.f, 0.f};
      bool ok = false;
#pragma unroll 1
      for (int it = 0; it < 4000 && !ok; it++) {
        ok = true; s[0] = s[1] = 0.f;
#pragma unroll
        for (int c = 0; c < NCL; c++) {
          uint64_t a, b;
          asm volatile("ld.relaxed.gpu.global.v2.u64 {%0,%1}, [%2];" : "=l"(a), "=l"(b) : "l"(&p.part[c * SEQ + rank * 256 + 2 * tid]) : "memory");
          ok = ok && (uint32_t)(a >> 32) == tag && (uint32_t)(b >> 32) == tag;
          s[0] += __uint_as_float((uint32_t)a); s[1] += __uint_as_float((uint32_t)b);
        }
      }
      if (ok) {
      } else {
#pragma unroll 1
        for (int hf = 0; hf < 2; hf++) {
          const int slot = 2 * tid + hf;
          const int row = rank * 256 + 32 * (slot & 7) + (slot >> 3);
          const uint32_t* xr = (const uint32_t*)(p.q + (size_t)row * DCH);
          const uint32_t* gr = (const uint32_t*)p.gate_w;
          float a = 0.f;
#pragma unroll 1
          for (int c = 0; c < DCH / 2; c++) { const uint32_t m = hmul2(__ldg(xr + c), __ldg(gr + c)); a += blo(m) + bhi(m); }
          if (hf) s[1] = a; else s[0] = a;
        }
      }
      const float g0 = bf16r(sigmoidf_(bf16r(s[0]))), g1 = bf16r(sigmoidf_(bf16r(s[1])));
      const float a0 = g0 * 0.0009765625f, b0 = bf16r(1.f - g0) * 0.0009765625f, a1 = g1 * 0.0009765625f, b1 = bf16r(1.f - g1) * 0.0009765625f;
      sts128(sb + OFF_TV + 16 * tid, pack(a0, a0), pack(b0, b0), pack(a1, a1), pack(b1, b1));
    }
    __syncwarp();
    uint2 gg[2][4];
#pragma unroll
    for (int hh = 0; hh < 2; hh++)
#pragma unroll
      for (int i = 0; i < 4; i++) gg[hh][i] = lds64(sb + OFF_TV + 8 * (64 * w + 32 * hh + 8 * i + g));
    mbar_wait(mb + 8 * MB_Q2);
    TL(8);
#pragma unroll 1
    for (int u = 0; u < nu; u++) {
      uint32_t qv[2][4];
      const uint32_t qa = sb + OFF_TQ + (64 * w + lane) * 80 + 16 * u;
      ldsm4(qv[0], qa);
      ldsm4(qv[1], qa + 2560);
      mbar_wait(mb + 8 * (MB_Y + u));
      uint32_t ya[2][4], yb[2][4];
      const uint32_t yo = (8 * u + (lane & 7)) * YPITCH + (8 * w + mi) * 16;
#pragma unroll
      for (int hh = 0; hh < 2; hh++) { ldsm4t(ya[hh], sb + OFF_YA + yo + 64 * hh); ldsm4t(yb[hh], sb + OFF_YB + yo + 64 * hh); }
#pragma unroll
      for (int hh = 0; hh < 2; hh++) {
        uint32_t o[4];
#pragma unroll
        for (int i = 0; i < 4; i++) o[i] = hadd2(hmul2(gg[hh][i].x, hmul2(qv[hh][i], ya[hh][i])), hmul2(gg[hh][i].y, yb[hh][i]));
        stsm4(qa + 2560 * hh, o);
      }
      TL(9 + u);
    }
    fence_async();
    __syncwarp();
    if (lane == 0) {
      tma_store3(&p.to, ch0, 8 * rank, 8 * w, sb + OFF_TQ + w * 5120);
      asm volatile("cp.async.bulk.commit_group;" ::: "memory");
      asm volatile("cp.async.bulk.wait_group.read 0;" ::: "memory");
    }
    TL(14);
    TL_DUMP();
  }
}

typedef CUresult (*EncodeFn)(CUtensorMap*, CUtensorMapDataType, cuuint32_t, void*, const cuuint64_t*, const cuuint64_t*,
                             const cuuint32_t*, const cuuint32_t*, CUtensorMapInterleave, CUtensorMapSwizzle,
                             CUtensorMapL2promotion, CUtensorMapFloatOOBfill);

void encode(EncodeFn fn, CUtensorMap* tm, const void* ptr, int nd, const cuuint64_t* dims, const cuuint64_t* strides,
            const cuuint32_t* box, CUtensorMapSwizzle swz) {
  cuuint32_t es[4] = {1, 1, 1, 1};
  fn(tm, CU_TENSOR_MAP_DATA_TYPE_BFLOAT16, nd, const_cast<void*>(ptr), dims, strides, box, es, CU_TENSOR_MAP_INTERLEAVE_NONE,
     swz, CU_TENSOR_MAP_L2_PROMOTION_L2_128B, CU_TENSOR_MAP_FLOAT_OOB_FILL_NONE);
}
void map1(EncodeFn fn, CUtensorMap* tm, const void* ptr, int nhi) {
  const cuuint64_t dims[4] = {DCH, 4, 8, SEQ / 32}, strides[3] = {8 * DCH * 2, DCH * 2, 32 * DCH * 2};
  const cuuint32_t box[4] = {CPC, 4, 8, (cuuint32_t)nhi};
  encode(fn, tm, ptr, 4, dims, strides, box, CU_TENSOR_MAP_SWIZZLE_NONE);
}
void map2(EncodeFn fn, CUtensorMap* tm, const void* ptr, int nr) {
  const cuuint64_t dims[3] = {DCH, SEQ / 32, 32}, strides[2] = {32 * DCH * 2, DCH * 2};
  const cuuint32_t box[3] = {CPC, 8, (cuuint32_t)nr};
  encode(fn, tm, ptr, 3, dims, strides, box, CU_TENSOR_MAP_SWIZZLE_NONE);
}

}

extern "C" void kernel_launch(void* const* d_in, const int* in_sizes, int n_in, void* d_out, int out_size) {
  (void)in_sizes; (void)n_in; (void)out_size;
  static EncodeFn fn = nullptr;
  static void *tab = nullptr, *cnt = nullptr, *part = nullptr;
  if (!fn) {
    cudaGetSymbolAddress(&tab, d_tab);
    cudaGetSymbolAddress(&cnt, g_cnt);
    cudaGetSymbolAddress(&part, g_part);
    cudaDriverEntryPointQueryResult qr;
    cudaGetDriverEntryPoint("cuTensorMapEncodeTiled", (void**)&fn, cudaEnableDefault, &qr);
    cudaFuncSetAttribute(fused_kernel, cudaFuncAttributeMaxDynamicSharedMemorySize, SMEM_BYTES);
  }
  Params p;
  map1(fn, &p.tq, d_in[0], 4);
  map1(fn, &p.tk, d_in[1], 9);
  map1(fn, &p.tv, d_in[2], 8);
  map2(fn, &p.tq2, d_in[0], 32);
  map2(fn, &p.to, d_out, 8);
  {
    const cuuint64_t dims[4] = {32, SEQ / 32, DCH / 8, 8}, strides[3] = {64, 8 * SEQ * 2, SEQ * 2};
    const cuuint32_t box[4] = {32, 64, 5, 1};
    encode(fn, &p.th, d_in[4], 4, dims, strides, box, CU_TENSOR_MAP_SWIZZLE_64B);
  }
  p.tab = (const Tables*)tab;
  p.cnt = (unsigned*)cnt;
  p.part = (uint2*)part;
  p.q = (const __nv_bfloat16*)d_in[0];
  p.shift_k = (const __nv_bfloat16*)d_in[3];
  p.ssm_D = (const __nv_bfloat16*)d_in[5];
  p.logA = (const __nv_bfloat16*)d_in[7];
  p.Aim = (const __nv_bfloat16*)d_in[8];
  p.Cre = (const __nv_bfloat16*)d_in[9];
  p.Cim = (const __nv_bfloat16*)d_in[10];
  p.logdt = (const __nv_bfloat16*)d_in[11];
  p.Dskip = (const __nv_bfloat16*)d_in[12];
  p.gate_w = (const __nv_bfloat16*)d_in[13];
  fused_kernel<<<NCL * CS, NTHREADS, SMEM_BYTES, cudaStreamPerThread>>>(p);
}
```

```cpp
#include <cuda_runtime.h>
#include <cuda_bf16.h>
#include <cuda.h>
#include <stdint.h>

#define TIMELINE 0

namespace {

constexpr int SEQ = 2048, DCH = 576, NMODE = 128;
constexpr int CS = 8, CPC = 40, NCL = 15, NTHREADS = 512;

constexpr int YPITCH = 528;
constexpr int KTAB = 28672;
constexpr int OFF_T = 0;
constexpr int OFF_UKV = 2 * KTAB + 8192;
constexpr int OFF_UX = 3 * KTAB;
constexpr int OFF_HA = OFF_UX + 20480;
constexpr int OFF_CF = OFF_HA + 20480;
constexpr int OFF_CL = OFF_CF + 8192;
constexpr int OFF_TQ = OFF_CL + 4096;
constexpr int OFF_TK = OFF_TQ + 20480;
constexpr int OFF_YA = OFF_TK;
constexpr int OFF_TV = OFF_TK + 23040;
constexpr int OFF_YB = OFF_TV + 20480;
constexpr int OFF_KC = OFF_YB + 40 * YPITCH;
constexpr int OFF_SW = OFF_KC + 3 * 1408;
constexpr int OFF_GW = OFF_SW + 320;
constexpr int OFF_SD = OFF_GW + 80;
constexpr int OFF_MB = OFF_SD + 32;
constexpr int OFF_TL = OFF_MB + 24 * 8;
constexpr int SMEM_BYTES = OFF_TL + (TIMELINE ? 2048 : 0);
static_assert(SMEM_BYTES <= 232448, "smem");
static_assert((KTAB & 1023) == 0 && (OFF_TQ & 127) == 0 && (OFF_TK & 127) == 0 && (OFF_TV & 127) == 0 && (OFF_MB & 7) == 0 && (OFF_KC & 15) == 0, "align");

enum { MB_UX = 0, MB_UKV = 5, MB_Y = 10, MB_Q2 = 15, MB_XQ = 16, MB_KV = 18, MB_HA = 19, MB_CF = 20, MB_COUNT = 21 };
enum { NB_WG0 = 1, NB_ROW0 = 5 };

constexpr double cos_turn(int m, int n) {
  m &= n - 1;
  if (m > n / 2) m = n - m;
  double sgn = 1.0;
  if (m > n / 4) { m = n / 2 - m; sgn = -1.0; }
  if (m == n / 4) return 0.0;
  const double x = 6.283185307179586476925 * m / n;
  double term = 1.0, sum = 1.0;
  for (int k = 1; k < 14; k++) { term *= -x * x / ((2 * k - 1) * (2 * k)); sum += term; }
  return sgn * sum;
}
constexpr uint32_t bf16_bits(double v) {
  if (v == 0.0) return 0;
  uint32_t sgn = 0;
  if (v < 0) { sgn = 0x8000; v = -v; }
  int e = 127;
  while (v < 1.0) { v *= 2.0; e--; }
  while (v >= 2.0) { v *= 0.5; e++; }
  const double f = v * 128.0;
  int m = (int)f;
  if (f - m > 0.5 || (f - m == 0.5 && (m & 1))) m++;
  return sgn | (uint32_t)((e << 7) + (m - 128));
}
constexpr uint32_t pair_bits(double lo, double hi) { return bf16_bits(lo) | (bf16_bits(hi) << 16); }
struct alignas(128) Tables {
  uint32_t mat[3072];
  uint32_t thr[4][128][4];
};
constexpr Tables make_tables() {
  Tables T{};
  for (int q = 0; q < 768; q++) {
    int m0 = 0, d0 = 0, d1 = 0;
    if (q < 512) {
      const int r = (q >> 6) * 8 + (q & 7), cc = (q >> 3) & 7;
      d0 = 4 * (r & 31); d1 = 2 * d0;
      m0 = 8 * (cc & 3) * d0 + ((r >> 5) == (cc >> 2) ? 0 : (r >> 5) ? 96 : 32);
    } else {
      const int r = ((q - 512) >> 5) * 8 + (q & 7), pc = (q >> 3) & 3;
      d0 = 4 * (8 * (r >> 4) + (r & 7)) + 1; d1 = 8 * d0;
      m0 = 2 * pc * d0 + ((r & 8) ? 32 : 0);
    }
    for (int e = 0; e < 4; e++) T.mat[4 * q + e] = pair_bits(cos_turn(m0 + e * d1, 128), cos_turn(m0 + e * d1 + d0, 128));
  }
  for (int tid = 0; tid < 128; tid++) {
    const int kk = 4 * (tid >> 2) + 1, t = tid & 3;
    for (int q = 0; q < 4; q++) {
      const int m = (8 * q + 2 * t) * kk;
      T.thr[q >> 1][tid][2 * (q & 1)] = pair_bits(cos_turn(m, 128), cos_turn(m + kk, 128));
      T.thr[q >> 1][tid][2 * (q & 1) + 1] = pair_bits(cos_turn(m + 32, 128), cos_turn(m + kk + 32, 128));
      T.thr[2][tid][q] = pair_bits(cos_turn(m, 4096), cos_turn(m + kk, 4096));
      T.thr[3][tid][q] = pair_bits(cos_turn(m + 3072, 4096), cos_turn(m + kk + 3072, 4096));
    }
  }
  return T;
}
__device__ const Tables d_tab = make_tables();

struct Params {
  const __nv_bfloat16 *logA, *Aim, *Cre, *Cim, *logdt;
  const Tables* tab;
  unsigned* cnt;
  const __nv_bfloat16 *Dskip, *shift_k, *ssm_D, *gate_w, *q;
  uint2* part;
  unsigned* tl;
  CUtensorMap tq, tk, tv, th, tq2, to;
};

__device__ uint2 g_part[NCL * SEQ];
__device__ unsigned g_cnt[CS * 32];
#define TL(i) do {} while (0)
#define TL_INIT() do {} while (0)
#define TL_DUMP() do {} while (0)

__device__ __forceinline__ uint32_t lds16(uint32_t a) { uint32_t v; asm volatile("ld.shared.u16 %0, [%1];" : "=r"(v) : "r"(a) : "memory"); return v; }
__device__ __forceinline__ uint2 lds64(uint32_t a) { uint2 v; asm volatile("ld.shared.v2.u32 {%0,%1}, [%2];" : "=r"(v.x), "=r"(v.y) : "r"(a) : "memory"); return v; }
__device__ __forceinline__ uint4 lds128(uint32_t a) { uint4 v; asm volatile("ld.shared.v4.u32 {%0,%1,%2,%3}, [%4];" : "=r"(v.x), "=r"(v.y), "=r"(v.z), "=r"(v.w) : "r"(a) : "memory"); return v; }
__device__ __forceinline__ void sts16(uint32_t a, uint32_t v) { asm volatile("st.shared.u16 [%0], %1;" :: "r"(a), "r"(v) : "memory"); }
__device__ __forceinline__ void sts32(uint32_t a, uint32_t v) { asm volatile("st.shared.u32 [%0], %1;" :: "r"(a), "r"(v) : "memory"); }
__device__ __forceinline__ void sts64(uint32_t a, uint32_t x, uint32_t y) { asm volatile("st.shared.v2.u32 [%0], {%1,%2};" :: "r"(a), "r"(x), "r"(y) : "memory"); }
__device__ __forceinline__ void sts128(uint32_t a, uint32_t x, uint32_t y, uint32_t z, uint32_t w) { asm volatile("st.shared.v4.u32 [%0], {%1,%2,%3,%4};" :: "r"(a), "r"(x), "r"(y), "r"(z), "r"(w) : "memory"); }
__device__ __forceinline__ void ldsm4t(uint32_t (&r)[4], uint32_t a) { asm volatile("ldmatrix.sync.aligned.m8n8.x4.trans.shared.b16 {%0,%1,%2,%3}, [%4];" : "=r"(r[0]), "=r"(r[1]), "=r"(r[2]), "=r"(r[3]) : "r"(a) : "memory"); }
__device__ __forceinline__ void ldsm2t(uint32_t& r0, uint32_t& r1, uint32_t a) { asm volatile("ldmatrix.sync.aligned.m8n8.x2.trans.shared.b16 {%0,%1}, [%2];" : "=r"(r0), "=r"(r1) : "r"(a) : "memory"); }
__device__ __forceinline__ void ldsm4(uint32_t (&r)[4], uint32_t a) { asm volatile("ldmatrix.sync.aligned.m8n8.x4.shared.b16 {%0,%1,%2,%3}, [%4];" : "=r"(r[0]), "=r"(r[1]), "=r"(r[2]), "=r"(r[3]) : "r"(a) : "memory"); }
__device__ __forceinline__ void stsm4(uint32_t a, const uint32_t (&r)[4]) { asm volatile("stmatrix.sync.aligned.m8n8.x4.shared.b16 [%0], {%1,%2,%3,%4};" :: "r"(a), "r"(r[0]), "r"(r[1]), "r"(r[2]), "r"(r[3]) : "memory"); }
__device__ __forceinline__ uint32_t pack(float lo, float hi) { uint32_t r; asm("cvt.rn.bf16x2.f32 %0, %1, %2;" : "=r"(r) : "f"(hi), "f"(lo)); return r; }
__device__ __forceinline__ float blo(uint32_t v) { return __uint_as_float(v << 16); }
__device__ __forceinline__ float bhi(uint32_t v) { return __uint_as_float(v & 0xffff0000u); }
__device__ __forceinline__ float bf16r(float x) { return blo(pack(x, 0.f)); }
__device__ __forceinline__ uint32_t hmul2(uint32_t a, uint32_t b) { uint32_t r; asm("mul.rn.bf16x2 %0, %1, %2;" : "=r"(r) : "r"(a), "r"(b)); return r; }
__device__ __forceinline__ uint32_t hadd2(uint32_t a, uint32_t b) { uint32_t r; asm("add.rn.bf16x2 %0, %1, %2;" : "=r"(r) : "r"(a), "r"(b)); return r; }
__device__ __forceinline__ uint32_t hfma2(uint32_t a, uint32_t b, uint32_t c) { uint32_t r; asm("fma.rn.bf16x2 %0, %1, %2, %3;" : "=r"(r) : "r"(a), "r"(b), "r"(c)); return r; }
__device__ __forceinline__ uint32_t prmt(uint32_t a, uint32_t b, uint32_t s) { return __byte_perm(a, b, s); }
__device__ __forceinline__ uint32_t ldraw(const __nv_bfloat16* p) { uint32_t v; asm volatile("ld.global.nc.u16 %0, [%1];" : "=r"(v) : "l"(p)); return v; }
__device__ __forceinline__ uint4 ldg128(const void* p) { uint4 v; asm volatile("ld.global.nc.v4.u32 {%0,%1,%2,%3}, [%4];" : "=r"(v.x), "=r"(v.y), "=r"(v.z), "=r"(v.w) : "l"(p)); return v; }
__device__ __forceinline__ void bar_sync(int id, int n) { asm volatile("bar.sync %0, %1;" :: "r"(id), "r"(n) : "memory"); }
__device__ __forceinline__ void bar_arrive(int id, int n) { asm volatile("bar.arrive %0, %1;" :: "r"(id), "r"(n) : "memory"); }
__device__ __forceinline__ void cluster_arrive() { asm volatile("barrier.cluster.arrive.relaxed.aligned;" ::: "memory"); }
__device__ __forceinline__ void cluster_wait() { asm volatile("barrier.cluster.wait.aligned;" ::: "memory"); }
__device__ __forceinline__ void fence_async() { asm volatile("fence.proxy.async.shared::cta;" ::: "memory"); }
__device__ __forceinline__ void fence_mbinit() { asm volatile("fence.mbarrier_init.release.cluster;" ::: "memory"); }
__device__ __forceinline__ uint32_t mapa(uint32_t a, uint32_t rank) { uint32_t r; asm("mapa.shared::cluster.u32 %0, %1, %2;" : "=r"(r) : "r"(a), "r"(rank)); return r; }
__device__ __forceinline__ void st_async4(uint32_t a, uint32_t x, uint32_t y, uint32_t z, uint32_t w, uint32_t mbar) {
  asm volatile("st.async.weak.shared::cluster.mbarrier::complete_tx::bytes.v4.b32 [%0], {%1,%2,%3,%4}, [%5];"
               :: "r"(a), "r"(x), "r"(y), "r"(z), "r"(w), "r"(mbar) : "memory");
}
__device__ __forceinline__ void mbar_init(uint32_t m, uint32_t cnt) { asm volatile("mbarrier.init.shared::cta.b64 [%0], %1;" :: "r"(m), "r"(cnt) : "memory"); }
__device__ __forceinline__ void mbar_expect(uint32_t m, uint32_t bytes) { asm volatile("mbarrier.arrive.expect_tx.shared::cta.b64 _, [%0], %1;" :: "r"(m), "r"(bytes) : "memory"); }
__device__ __forceinline__ void mbar_wait(uint32_t m) {
  uint32_t done;
  int it = 0;
  do {
    asm volatile("{.reg .pred p; mbarrier.try_wait.parity.shared::cta.b64 p, [%1], 0; selp.u32 %0, 1, 0, p;}" : "=r"(done) : "r"(m) : "memory");
    if (++it > (1 << 22)) __trap();
  } while (!done);
}
__device__ __forceinline__ void tma_load4(uint32_t dst, const CUtensorMap* tm, int c0, int c1, int c2, int c3, uint32_t mbar) {
  asm volatile("cp.async.bulk.tensor.4d.shared::cluster.global.mbarrier::complete_tx::bytes [%0], [%1, {%3, %4, %5, %6}], [%2];"
               :: "r"(dst), "l"(tm), "r"(mbar), "r"(c0), "r"(c1), "r"(c2), "r"(c3) : "memory");
}
__device__ __forceinline__ void tma_load3(uint32_t dst, const CUtensorMap* tm, int c0, int c1, int c2, uint32_t mbar) {
  asm volatile("cp.async.bulk.tensor.3d.shared::cluster.global.mbarrier::complete_tx::bytes [%0], [%1, {%3, %4, %5}], [%2];"
               :: "r"(dst), "l"(tm), "r"(mbar), "r"(c0), "r"(c1), "r"(c2) : "memory");
}
__device__ __forceinline__ void tma_store3(const CUtensorMap* tm, int c0, int c1, int c2, uint32_t src) {
  asm volatile("cp.async.bulk.tensor.3d.global.shared::cta.bulk_group [%0, {%2, %3, %4}], [%1];"
               :: "l"(tm), "r"(src), "r"(c0), "r"(c1), "r"(c2) : "memory");
}
__device__ __forceinline__ void wg_fence() { asm volatile("wgmma.fence.sync.aligned;" ::: "memory"); }
__device__ __forceinline__ void wg_commit() { asm volatile("wgmma.commit_group.sync.aligned;" ::: "memory"); }
template <int N> __device__ __forceinline__ void wg_wait() { asm volatile("wgmma.wait_group.sync.aligned %0;" :: "n"(N) : "memory"); }
template <int N> __device__ __forceinline__ void tie_all(float (&x)[N]) {
#pragma unroll
  for (int i = 0; i < N; i++) asm volatile("" : "+f"(x[i]) :: "memory");
}
#define R16(C, d) C(d[0]), C(d[1]), C(d[2]), C(d[3]), C(d[4]), C(d[5]), C(d[6]), C(d[7]), C(d[8]), C(d[9]), C(d[10]), C(d[11]), C(d[12]), C(d[13]), C(d[14]), C(d[15])
#define R32(C, d) R16(C, d), R16(C, (d + 16))
#define P16 "{%0,%1,%2,%3,%4,%5,%6,%7,%8,%9,%10,%11,%12,%13,%14,%15}"
#define P32 "{%0,%1,%2,%3,%4,%5,%6,%7,%8,%9,%10,%11,%12,%13,%14,%15,%16,%17,%18,%19,%20,%21,%22,%23,%24,%25,%26,%27,%28,%29,%30,%31}"
template <int SD, int TB, int OFF> __device__ __forceinline__ void rs64(float* d, const uint32_t* a, uint64_t db) {
  if (SD) asm volatile("{.reg .b64 db; add.s64 db, %36, %37; wgmma.mma_async.sync.aligned.m64n64k16.f32.bf16.bf16 " P32 ", {%32,%33,%34,%35}, db, 1, 1, 1, %38;}"
                       : R32("+f", d) : "r"(a[0]), "r"(a[1]), "r"(a[2]), "r"(a[3]), "l"(db), "n"(OFF), "n"(TB));
  else asm volatile("{.reg .b64 db; add.s64 db, %36, %37; wgmma.mma_async.sync.aligned.m64n64k16.f32.bf16.bf16 " P32 ", {%32,%33,%34,%35}, db, 0, 1, 1, %38;}"
                    : R32("=f", d) : "r"(a[0]), "r"(a[1]), "r"(a[2]), "r"(a[3]), "l"(db), "n"(OFF), "n"(TB));
}
template <int SD, int OFFA, int OFFB> __device__ __forceinline__ void ss32(float* d, uint64_t da, uint64_t db) {
  if (SD) asm volatile("{.reg .b64 da, db; add.s64 da, %16, %18; add.s64 db, %17, %19; wgmma.mma_async.sync.aligned.m64n32k16.f32.bf16.bf16 " P16 ", da, db, 1, 1, 1, 1, 1;}"
                       : R16("+f", d) : "l"(da), "l"(db), "n"(OFFA), "n"(OFFB));
  else asm volatile("{.reg .b64 da, db; add.s64 da, %16, %18; add.s64 db, %17, %19; wgmma.mma_async.sync.aligned.m64n32k16.f32.bf16.bf16 " P16 ", da, db, 0, 1, 1, 1, 1;}"
                    : R16("=f", d) : "l"(da), "l"(db), "n"(OFFA), "n"(OFFB));
}
template <int KS> __device__ __forceinline__ void kgen_mma(float (&c)[24], uint64_t da) {
  asm volatile("{.reg .b64 da, db; add.s64 da, %24, %25; add.s64 db, %24, %26;\n"
               "wgmma.mma_async.sync.aligned.m64n48k16.f32.bf16.bf16 {%0,%1,%2,%3,%4,%5,%6,%7,%8,%9,%10,%11,%12,%13,%14,%15,%16,%17,%18,%19,%20,%21,%22,%23}, da, db, %27, 1, 1, 1, 1;}"
               : R16("+f", c), "+f"(c[16]), "+f"(c[17]), "+f"(c[18]), "+f"(c[19]), "+f"(c[20]), "+f"(c[21]), "+f"(c[22]), "+f"(c[23])
               : "l"(da), "n"(8 * KS), "n"(8 * KS + 512), "n"(KS ? 1 : 0));
  if constexpr (KS < 7) kgen_mma<KS + 1>(c, da);
}
__device__ __forceinline__ uint64_t desc_lo(uint32_t a) { return (uint64_t)((a & 0x3FFFF) >> 4); }
__device__ __forceinline__ void stage1(float (&D)[32], const uint32_t (&A1)[8], uint32_t src) {
  const uint64_t du = desc_lo(src) | (128ull << 16) | (32ull << 32) | (2ull << 62);
  rs64<0, 1, 0>(D, A1, du); rs64<1, 1, 64>(D, A1 + 4, du);
}
template <int INV> __device__ __forceinline__ void stage2(float (&X)[32], const uint32_t (&F)[16], uint32_t cf) {
  constexpr int KS = INV ? 16 : 128, TB = INV ? 0 : 1;
  const uint64_t dc = desc_lo(cf) | (INV ? (8ull << 16) | (64ull << 32) : (64ull << 16) | (8ull << 32));
  rs64<0, TB, 0>(X, F, dc); rs64<1, TB, KS>(X, F + 4, dc); rs64<1, TB, 2 * KS>(X, F + 8, dc); rs64<1, TB, 3 * KS>(X, F + 12, dc);
}
__device__ __forceinline__ void fwd_mid(uint32_t (&F)[16], const float (&D)[32], const uint32_t (&tp)[12]) {
#pragma unroll
  for (int j = 0; j < 4; j++)
#pragma unroll
    for (int b = 0; b < 2; b++) {
      const int i = 4 * j + 16 * b;
      const uint32_t ar = pack(D[i], D[i + 1]), ai = pack(D[i + 2], D[i + 3]);
      F[2 * j + b] = hfma2(ar, tp[3 * j], hmul2(ai, tp[3 * j + 2]));
      F[8 + 2 * j + b] = hfma2(ar, tp[3 * j + 1], hmul2(ai, tp[3 * j]));
    }
}

struct cf { float x, y; };
__device__ __forceinline__ cf cmul(cf a, cf b) { cf r; r.x = fmaf(a.x, b.x, -a.y * b.y); r.y = fmaf(a.x, b.y, a.y * b.x); return r; }
__device__ __forceinline__ cf cexp_p(float lr2, float lt, float p) {
  float m = exp2f(lr2 * p);
  float t = lt * p;
  t = (t - rintf(t)) * 6.283185307179586f;
  cf r; r.x = m * __cosf(t); r.y = m * __sinf(t); return r;
}
__device__ __forceinline__ void store8(uint32_t a, const cf (&v)[8]) {
  sts128(a, pack(v[0].x, v[1].x), pack(v[2].x, v[3].x), pack(v[4].x, v[5].x), pack(v[6].x, v[7].x));
  sts128(a + KTAB / 2, pack(v[0].y, v[1].y), pack(v[2].y, v[3].y), pack(v[4].y, v[5].y), pack(v[6].y, v[7].y));
}
__device__ __forceinline__ float sigmoidf_(float s) { return 1.f / (1.f + __expf(-s)); }

__global__ void __cluster_dims__(CS, 1, 1) __launch_bounds__(NTHREADS, 1) fused_kernel(const __grid_constant__ Params p) {
  extern __shared__ __align__(1024) uint8_t smem[];
  TL_INIT();
  TL(31);
  const uint32_t sb = (uint32_t)__cvta_generic_to_shared(smem);
  const uint32_t mb = sb + OFF_MB;
  const int wg = __shfl_sync(0xffffffffu, threadIdx.x >> 7, 0);
  const int tid = threadIdx.x & 127, w = __shfl_sync(0xffffffffu, tid >> 5, 0), lane = tid & 31, g = lane >> 2, t = lane & 3;
  const int cl = blockIdx.x >> 3, rank = blockIdx.x & 7;
  const int ch0 = cl * CPC;
  const int nu = min(5, (DCH - ch0) >> 3);

  if (wg < 3) {
    uint32_t pla[2], pai[2], pcr[2], pci[2], pdt[2];
#pragma unroll
    for (int r = 0; r < 2; r++) {
      const int ch = (wg + 3 * r < nu) ? ch0 + 8 * (wg + 3 * r) + rank : 0;
      pla[r] = ldraw(p.logA + ch * NMODE + tid);
      pai[r] = ldraw(p.Aim + ch * NMODE + tid);
      pcr[r] = ldraw(p.Cre + ch * NMODE + tid);
      pci[r] = ldraw(p.Cim + ch * NMODE + tid);
      pdt[r] = ldraw(p.logdt + ch);
    }
    cluster_arrive();
    uint32_t A1[8], tp[12];
    {
      const uint4 a = ldg128(p.tab->thr[0][tid]), b = ldg128(p.tab->thr[1][tid]), c = ldg128(p.tab->thr[2][tid]), d = ldg128(p.tab->thr[3][tid]);
      A1[0] = a.x; A1[1] = a.y; A1[2] = a.z; A1[3] = a.w; A1[4] = b.x; A1[5] = b.y; A1[6] = b.z; A1[7] = b.w;
      tp[0] = c.x; tp[3] = c.y; tp[6] = c.z; tp[9] = c.w; tp[2] = d.x; tp[5] = d.y; tp[8] = d.z; tp[11] = d.w;
      tp[1] = tp[4] = tp[7] = tp[10] = 0;
    }
    TL(0);
    const uint32_t tab = sb + OFF_T + wg * KTAB;
#pragma unroll 1
    for (int job = 0; job < 4; job++) {
      const bool isA = job >= (wg == 2 ? 1 : 2);
      const int u = wg == 2 ? (job ? 2 * job - 2 : 2) : job < 2 ? wg + 3 * job : job == 2 ? 2 * wg + 1 : 9;

      if (!isA && u < nu) {
        const float la = blo(job ? pla[1] : pla[0]), ai = blo(job ? pai[1] : pai[0]), cr = blo(job ? pcr[1] : pcr[0]), ci = blo(job ? pci[1] : pci[0]);
        const float dt = bf16r(expf(blo(job ? pdt[1] : pdt[0])));
        const float lr2 = (-bf16r(expf(la)) * dt) * 1.4426950408889634f;
        const float lt = (ai * dt) * 0.15915494309189535f;
        const uint32_t row = tab + tid * 16;
        if (lr2 != 123.f) TL(16 + 4 * job);
        if (job) bar_sync(NB_WG0 + wg, 128);
        {
          const cf w1 = cexp_p(lr2, lt, 8.f);
          cf v[8];
          v[0].x = 1.f; v[0].y = 0.f; v[1] = w1; v[2] = cmul(w1, w1); v[3] = cmul(v[2], w1);
          const cf w4 = cmul(v[2], v[2]);
          v[4] = w4; v[5] = cmul(v[1], w4); v[6] = cmul(v[2], w4); v[7] = cmul(v[3], w4);
          const cf w8 = cmul(w4, w4);
          store8(row, v);
#pragma unroll
          for (int c = 1; c < 4; c++) {
#pragma unroll
            for (int i = 0; i < 8; i++) v[i] = (c == 1 && i == 0) ? w8 : cmul(v[i], w8);
            store8(row + 2048 * c, v);
          }
        }
        {
          cf z1 = cexp_p(lr2, lt, 1.f), Z = cexp_p(lr2, lt, 256.f);
          z1.y = -z1.y; Z.y = -Z.y;
          const cf z2 = cmul(z1, z1);
          cf h[8], v[8];
          h[0].x = 2.f * cr * dt; h[0].y = -2.f * ci * dt;
          h[1] = cmul(h[0], z1);
#pragma unroll
          for (int i = 2; i < 8; i++) h[i] = cmul(h[i - 2], z2);
          store8(row + 4 * 2048, h);
          v[0] = cmul(h[0], Z); v[1] = cmul(h[2], Z); v[2] = cmul(h[4], Z); v[3] = cmul(h[6], Z);
          v[4] = cmul(v[0], Z); v[5] = cmul(v[2], Z); v[6] = cmul(v[4], Z); v[7] = cmul(v[5], Z);
          store8(row + 5 * 2048, v);
          const cf Z2 = cmul(Z, Z);
          h[0] = cmul(v[4], Z2); h[1] = cmul(v[6], Z2); h[2] = cmul(h[0], Z2); h[3] = cmul(h[1], Z2); h[4] = cmul(h[2], Z2);
          h[5].x = h[5].y = h[6].x = h[6].y = h[7].x = h[7].y = 0.f;
          store8(row + 6 * 2048, h);
        }
        TL(17 + 4 * job);
        fence_async();
        bar_sync(NB_WG0 + wg, 128);
        float c[24];
        wg_fence();
        kgen_mma<0>(c, desc_lo(tab) | ((uint64_t)(KTAB / 32) << 16) | (64ull << 32));
        wg_commit();
        uint32_t kid[8];
        {
          float lf = __uint_as_float(0x4b000000u | (8 * tid)) - 8388608.f;
          asm volatile("" : "+f"(lf));
          const float lo = tid < 16 ? lf + 128.f : lf;
          const uint32_t sub = tid < 16 ? 0x42804300u : 0x42804280u;
#pragma unroll
          for (int i = 0; i < 8; i++) kid[i] = 2 * (pack(lo + i, lf + (1024 + i)) - sub);
        }
        wg_wait<0>(); tie_all(c);
        const uint32_t kc = sb + OFF_KC + wg * 1408;
        {
          const int a = 8 * w + g;
          sts32(kc + 4 * (4 * a + t), pack(c[0] + c[6], c[1] + c[7]));
          sts32(kc + 4 * (t < 2 ? 128 + 2 * a + t : 128 + 32 * t + a), pack(c[8] + c[14], c[9] + c[15]));
          if (t < 3) {
            const uint32_t p0 = pack(c[16] + c[22], c[17] + c[23]);
            sts16(kc + 2 * (512 + 64 * t + a), p0);
            sts16(kc + 2 * (544 + 64 * t + a), p0 >> 16);
          }
        }
        TL(18 + 4 * job);
        bar_sync(NB_WG0 + wg, 128);
        uint32_t v[2][8];
#pragma unroll
        for (int i = 0; i < 8; i++) { v[0][i] = lds16(kc + (kid[i] & 0xffffu)); v[1][i] = lds16(kc + (kid[i] >> 16)); }
#pragma unroll
        for (int cc = 0; cc < 2; cc++)
          sts128(tab + 2048 * cc + 16 * (tid ^ ((tid >> 3) & 3)), prmt(v[cc][0], v[cc][1], 0x5410), prmt(v[cc][2], v[cc][3], 0x5410),
                 prmt(v[cc][4], v[cc][5], 0x5410), prmt(v[cc][6], v[cc][7], 0x5410));
        fence_async();
        if (job) bar_sync(NB_WG0 + wg, 128);
      }
      if (job == 0) {
        cluster_wait();
        cluster_arrive();
        bar_sync(NB_WG0 + wg, 128);
        mbar_wait(mb + 8 * MB_CF);
#pragma unroll
        for (int j = 0; j < 4; j++) asm volatile("xor.b32 %0, %1, 0x80008000;" : "=r"(tp[3 * j + 1]) : "r"(tp[3 * j + 2]));
      }
      if (u >= nu) continue;
      TL(1 + job);
      float D[32], H[32], X[32];
      uint32_t F[16];
      if (isA) mbar_wait(mb + 8 * MB_HA);
      wg_fence();
      stage1(D, A1, isA ? sb + OFF_HA + u * 4096 : tab);
      wg_commit();
      wg_wait<0>(); tie_all(D);
      fwd_mid(F, D, tp);
      wg_fence();
      stage2<0>(H, F, sb + OFF_CF);
      wg_commit();
      mbar_wait(mb + 8 * ((isA ? MB_UKV : MB_UX) + u));
      fence_async();
      TL(5 + job);
      wg_fence();
      stage1(D, A1, sb + (isA ? OFF_UKV : OFF_UX) + u * 4096);
      wg_commit();
      wg_wait<0>(); tie_all(D); tie_all(H);
      fwd_mid(F, D, tp);
      wg_fence();
      stage2<0>(X, F, sb + OFF_CF);
      wg_commit();
      {
        const float dsk = blo(lds16(sb + OFF_SD + (isA ? 10 : 0) + 2 * u));
#pragma unroll
        for (int j = 0; j < 4; j++) { H[4 * j] += dsk; H[4 * j + 1] += dsk; }
      }
      wg_wait<0>(); tie_all(X);
#pragma unroll
      for (int j = 0; j < 4; j++) {
        float pr[2], pi[2], qr[2], qi[2];
#pragma unroll
        for (int n = 0; n < 2; n++) {
          const int i = 4 * j + n;
          pr[n] = fmaf(X[i], H[i], -X[i + 16] * H[i + 16]);
          pi[n] = fmaf(X[i], H[i + 16], X[i + 16] * H[i]);
          qr[n] = fmaf(X[i + 2], H[i], fmaf(-X[i + 18], H[i + 16], fmaf(X[i], H[i + 2], fmaf(-X[i + 16], H[i + 18], -pi[n]))));
          qi[n] = fmaf(X[i + 2], H[i + 16], fmaf(X[i + 18], H[i], fmaf(X[i], H[i + 18], fmaf(X[i + 16], H[i + 2], pr[n]))));
        }
        F[2 * j] = pack(pr[0], pr[1]); F[2 * j + 1] = pack(qr[0], qr[1]); F[8 + 2 * j] = pack(pi[0], pi[1]); F[9 + 2 * j] = pack(qi[0], qi[1]);
      }
      wg_fence();
      stage2<1>(H, F, sb + OFF_CF);
      wg_commit();
      wg_wait<0>(); tie_all(H);
      {
        const uint32_t va = tab + (16 * w + (lane & 15)) * 128;
        const int vx = (lane >> 4) ^ (lane & 7);
#pragma unroll
        for (int j = 0; j < 4; j++) {
          uint32_t V[4];
#pragma unroll
          for (int b = 0; b < 2; b++) {
            const int i = 4 * j + 2 * b;
            const uint32_t er = pack(H[i], H[i + 1]), ei = pack(H[i + 16], H[i + 17]);
            V[2 * b] = hfma2(er, tp[3 * j], hmul2(ei, tp[3 * j + 1]));
            V[2 * b + 1] = hfma2(ei, tp[3 * j], hmul2(er, tp[3 * j + 2]));
          }
          stsm4(va + ((vx ^ (2 * j)) << 4), V);
        }
      }
      fence_async();
      bar_sync(NB_WG0 + wg, 128);
      float O[16];
      {
        const uint64_t dv = desc_lo(tab) | (1ull << 16) | (64ull << 32) | (1ull << 62);
        const uint64_t dl = desc_lo(sb + OFF_CL) | (32ull << 16) | (8ull << 32);
        wg_fence();
        ss32<0, 0, 0>(O, dv, dl); ss32<1, 128, 64>(O, dv, dl); ss32<1, 256, 128>(O, dv, dl); ss32<1, 384, 192>(O, dv, dl);
        wg_commit();
      }
      if (isA && job < 3) {
        for (int k = 0; k < nu; k++) mbar_wait(mb + 8 * (MB_UKV + k));
      }
      wg_wait<0>(); tie_all(O);
      {
        const uint32_t yo = (isA ? OFF_YA : OFF_YB) + (8 * u + rank) * YPITCH + (8 * w + g) * 16, ym = OFF_MB + 8 * (MB_Y + u);
        const uint32_t r0 = mapa(sb, t), r1 = mapa(sb, t + 4);
        st_async4(r0 + yo, pack(O[0], O[1]), pack(O[4], O[5]), pack(O[8], O[9]), pack(O[12], O[13]), r0 + ym);
        st_async4(r1 + yo, pack(O[2], O[3]), pack(O[6], O[7]), pack(O[10], O[11]), pack(O[14], O[15]), r1 + ym);
      }
      TL(9 + job);
    }
  } else {
    if (lane == 0) {
#pragma unroll
      for (int i = 0; i < 4; i++) mbar_init(mb + 8 * (4 * w + i), 4 * w + i == MB_Q2 ? 5 : 1);
      mbar_init(mb + 8 * (MB_XQ + w), 1);
      if (w == 3) mbar_init(mb + 8 * MB_CF, 2);
      fence_mbinit();
      if (w == 3) {
        mbar_expect(mb + 8 * MB_CF, 12288);
        asm volatile("cp.async.bulk.shared::cluster.global.mbarrier::complete_tx::bytes [%0], [%1], %2, [%3];"
                     :: "r"(sb + OFF_CF), "l"(p.tab->mat), "r"(12288), "r"(mb + 8 * MB_CF) : "memory");
      }
#pragma unroll
      for (int i = 0; i < 4; i++) { const int b = 4 * w + i; mbar_expect(mb + 8 * b, b == MB_Q2 ? 20480 : b >= MB_Y ? 8192 : 4096); }
      mbar_expect(mb + 8 * (MB_XQ + w), w < 2 ? 10240 : w == 2 ? 23040 + 20480 : 20480);
    }
    __syncwarp();
    cluster_arrive();
    uint2 swv = make_uint2(0, 0);
    uint32_t gwv = 0, tag = 0;
    if (tid >= 64 && tid < 104 && ch0 + tid - 64 < DCH) { swv = __ldg((const uint2*)(p.shift_k + (size_t)(ch0 + tid - 64) * 4)); gwv = ldraw(p.gate_w + ch0 + tid - 64); }
    if (tid >= 112 && tid < 122) { const int k = tid - 112, u = k < 5 ? k : k - 5; if (u < nu) gwv = ldraw((k < 5 ? p.Dskip : p.ssm_D) + ch0 + 8 * u + rank); }
    if (tid == 1) asm volatile("atom.relaxed.gpu.global.add.u32 %0, [%1], %2;" : "=r"(tag) : "l"(&p.cnt[rank * 32]), "r"(cl == 0 ? 16 - (NCL - 1) : 1) : "memory");
    if (lane == 0 && w < 2) { tma_load4(sb + OFF_TQ + 10240 * w, &p.tq, ch0, 0, 0, 8 * rank + 4 * w, mb + 8 * (MB_XQ + w)); TL(20); }
    if (tid >= 64 && tid < 104) { sts64(sb + OFF_SW + 8 * (tid - 64), swv.x, swv.y); sts16(sb + OFF_GW + 2 * (tid - 64), gwv); }
    if (tid >= 112 && tid < 122) sts16(sb + OFF_SD + 2 * (tid - 112), gwv);
    __syncwarp();
    if (tid == 64) {
      tma_load4(sb + OFF_TK, &p.tk, ch0, 0, 0, 8 * rank - 1, mb + 8 * MB_KV);
      tma_load4(sb + OFF_TV, &p.tv, ch0, 0, 0, 8 * rank, mb + 8 * MB_KV);
    }
    if (tid == 96) asm volatile("mbarrier.arrive.shared::cta.b64 _, [%0];" :: "r"(mb + 8 * MB_CF) : "memory");
    __syncwarp();
    TL(0);
    const uint32_t rbase = mapa(sb, g);
    const int mi = lane >> 3, tq = (lane & 7) >> 1, jj = lane & 1;
    const uint32_t toff = (4 * (2 * mi + jj) + tq) * 80;
    const uint32_t uoff = 16 * (32 * rank + 4 * w + (t ^ (w >> 1)));
    cluster_wait();
    cluster_arrive();
    if (tid == 64) tma_load4(sb + OFF_HA, &p.th, 0, 0, 5 * cl, rank, mb + 8 * MB_HA);
    __syncwarp();
    mbar_wait(mb + 8 * MB_XQ);
    mbar_wait(mb + 8 * (MB_XQ + 1));
    TL(1);
    {
      uint32_t xr[5][2][4];
#pragma unroll
      for (int u = 0; u < 5; u++) { ldsm4t(xr[u][0], sb + OFF_TQ + w * 2560 + toff + 16 * u); ldsm4t(xr[u][1], sb + OFF_TQ + (w + 4) * 2560 + toff + 16 * u); }
#pragma unroll
      for (int u = 0; u < 5; u++)
        if (u < nu) {
          st_async4(rbase + OFF_UX + u * 4096 + uoff, xr[u][0][0], xr[u][0][1], xr[u][0][2], xr[u][0][3], rbase + OFF_MB + 8 * (MB_UX + u));
          st_async4(rbase + OFF_UX + u * 4096 + (uoff ^ 32) + 256, xr[u][1][0], xr[u][1][1], xr[u][1][2], xr[u][1][3], rbase + OFF_MB + 8 * (MB_UX + u));
        }
    }
    TL(2);
    if (tid == 1) sts32(sb + OFF_MB + 8 * MB_COUNT, (tag >> 4) + 1);
    bar_sync(NB_WG0 + 3, 128);
    tag = lds64(sb + OFF_MB + 8 * MB_COUNT).x;
    {
      float s0 = 0.f, s1 = 0.f;
#pragma unroll
      for (int j = 0; j < 5; j++) {
        const uint4 gw = lds128(sb + OFF_GW + 16 * j);
        const uint4 x0 = lds128(sb + OFF_TQ + tid * 80 + 16 * j), x1 = lds128(sb + OFF_TQ + (tid + 128) * 80 + 16 * j);
        uint32_t m0 = hmul2(x0.x, gw.x), m1 = hmul2(x0.y, gw.y), m2 = hmul2(x0.z, gw.z), m3 = hmul2(x0.w, gw.w);
        s0 += ((blo(m0) + bhi(m0)) + (blo(m1) + bhi(m1))) + ((blo(m2) + bhi(m2)) + (blo(m3) + bhi(m3)));
        m0 = hmul2(x1.x, gw.x); m1 = hmul2(x1.y, gw.y); m2 = hmul2(x1.z, gw.z); m3 = hmul2(x1.w, gw.w);
        s1 += ((blo(m0) + bhi(m0)) + (blo(m1) + bhi(m1))) + ((blo(m2) + bhi(m2)) + (blo(m3) + bhi(m3)));
      }
      const int s2 = 8 * (8 * (lane & 3) + (lane >> 2)) + w;
      asm volatile("st.relaxed.gpu.global.u64 [%0], %1;" :: "l"(&p.part[cl * SEQ + rank * 256 + s2]), "l"(((uint64_t)tag << 32) | __float_as_uint(s0)) : "memory");
      asm volatile("st.relaxed.gpu.global.u64 [%0], %1;" :: "l"(&p.part[cl * SEQ + rank * 256 + s2 + 4]), "l"(((uint64_t)tag << 32) | __float_as_uint(s1)) : "memory");
    }
    bar_sync(NB_WG0 + 3, 128);
    if (tid == 0) tma_load3(sb + OFF_TQ, &p.tq2, ch0, 8 * rank, 0, mb + 8 * MB_Q2);
    __syncwarp();
    TL(3);
    cluster_wait();
    mbar_wait(mb + 8 * MB_KV);
    TL(4);
    const uint32_t hoff = (4 * (4 + 2 * (mi & 1) + jj) + ((tq + 3) & 3)) * 80 + (tq ? 2560 : 0);
    uint32_t En[2][6], Vn[2][4];
    uint2 swn;
    auto kv_load = [&](int u) {
      swn = lds64(sb + OFF_SW + 8 * (8 * u + g));
#pragma unroll
      for (int hf = 0; hf < 2; hf++) {
        const int ah = 4 * hf + w;
        uint32_t K[4];
        ldsm4t(K, sb + OFF_TK + (ah + 1) * 2560 + toff + 16 * u);
        ldsm2t(En[hf][0], En[hf][1], sb + OFF_TK + ah * 2560 + hoff + 16 * u);
        ldsm4t(Vn[hf], sb + OFF_TV + ah * 2560 + toff + 16 * u);
        En[hf][2] = K[0]; En[hf][3] = K[1]; En[hf][4] = K[2]; En[hf][5] = K[3];
      }
    };
    kv_load(0);
#pragma unroll 1
    for (int u = 0; u < nu; u++) {
      uint32_t E[2][6], V[2][4];
#pragma unroll
      for (int hf = 0; hf < 2; hf++) {
#pragma unroll
        for (int i = 0; i < 6; i++) E[hf][i] = En[hf][i];
#pragma unroll
        for (int i = 0; i < 4; i++) V[hf][i] = Vn[hf][i];
      }
      const uint32_t w0 = prmt(swn.x, 0, 0x1010), w1 = prmt(swn.x, 0, 0x3232), w2 = prmt(swn.y, 0, 0x1010), w3 = prmt(swn.y, 0, 0x3232);
      if (u + 1 < nu) kv_load(u + 1);
#pragma unroll
      for (int hf = 0; hf < 2; hf++) {
        uint32_t O[5], o[4];
#pragma unroll
        for (int i = 0; i < 5; i++) O[i] = prmt(E[hf][i], E[hf][i + 1], 0x5432);
#pragma unroll
        for (int i = 0; i < 4; i++) {
          uint32_t s = hmul2(O[i], w3);
          s = hadd2(s, hmul2(E[hf][i + 1], w2));
          s = hadd2(s, hmul2(O[i + 1], w1));
          s = hadd2(s, hmul2(E[hf][i + 2], w0));
          o[i] = hmul2(s, V[hf][i]);
        }
        st_async4(rbase + OFF_UKV + u * 4096 + (hf ? (uoff ^ 32) + 256 : uoff), o[0], o[1], o[2], o[3], rbase + OFF_MB + 8 * (MB_UKV + u));
      }
    }
    TL(5);
    bar_sync(NB_WG0 + 3, 128);
    {
      float s[2] = {0.f, 0.f};
      bool ok = false;
#pragma unroll 1
      for (int it = 0; it < 4000 && !ok; it++) {
        ok = true; s[0] = s[1] = 0.f;
#pragma unroll
        for (int c = 0; c < NCL; c++) {
          uint64_t a, b;
          asm volatile("ld.relaxed.gpu.global.v2.u64 {%0,%1}, [%2];" : "=l"(a), "=l"(b) : "l"(&p.part[c * SEQ + rank * 256 + 2 * tid]) : "memory");
          ok = ok && (uint32_t)(a >> 32) == tag && (uint32_t)(b >> 32) == tag;
          s[0] += __uint_as_float((uint32_t)a); s[1] += __uint_as_float((uint32_t)b);
        }
      }
      if (ok) {
      } else {
#pragma unroll 1
        for (int hf = 0; hf < 2; hf++) {
          const int slot = 2 * tid + hf;
          const int row = rank * 256 + 32 * (slot & 7) + (slot >> 3);
          const uint32_t* xr = (const uint32_t*)(p.q + (size_t)row * DCH);
          const uint32_t* gr = (const uint32_t*)p.gate_w;
          float a = 0.f;
#pragma unroll 1
          for (int c = 0; c < DCH / 2; c++) { const uint32_t m = hmul2(__ldg(xr + c), __ldg(gr + c)); a += blo(m) + bhi(m); }
          if (hf) s[1] = a; else s[0] = a;
        }
      }
      const float g0 = bf16r(sigmoidf_(bf16r(s[0]))), g1 = bf16r(sigmoidf_(bf16r(s[1])));
      const float a0 = g0 * 0.0009765625f, b0 = bf16r(1.f - g0) * 0.0009765625f, a1 = g1 * 0.0009765625f, b1 = bf16r(1.f - g1) * 0.0009765625f;
      sts128(sb + OFF_TV + 16 * tid, pack(a0, a0), pack(b0, b0), pack(a1, a1), pack(b1, b1));
    }
    __syncwarp();
    if (lane == 0) asm volatile("mbarrier.arrive.shared::cta.b64 _, [%0];" :: "r"(mb + 8 * MB_Q2) : "memory");
  }
  mbar_wait(mb + 8 * MB_Q2);
  uint2 gg[2][4];
#pragma unroll
  for (int hh = 0; hh < 2; hh++)
#pragma unroll
    for (int i = 0; i < 4; i++) gg[hh][i] = lds64(sb + OFF_TV + 8 * (64 * w + 32 * hh + 8 * i + g));
  TL(24);
#pragma unroll 1
  for (int u = wg == 3 ? 0 : wg == 2 ? 4 : 2 * wg + 1; u < nu; u += 2) {
    uint32_t qv[2][4];
    const uint32_t qa = sb + OFF_TQ + (64 * w + lane) * 80 + 16 * u;
    ldsm4(qv[0], qa);
    ldsm4(qv[1], qa + 2560);
    mbar_wait(mb + 8 * (MB_Y + u));
    uint32_t ya[2][4], yb[2][4];
    const uint32_t yo = (8 * u + (lane & 7)) * YPITCH + (8 * w + (lane >> 3)) * 16;
#pragma unroll
    for (int hh = 0; hh < 2; hh++) { ldsm4t(ya[hh], sb + OFF_YA + yo + 64 * hh); ldsm4t(yb[hh], sb + OFF_YB + yo + 64 * hh); }
#pragma unroll
    for (int hh = 0; hh < 2; hh++) {
      uint32_t o[4];
#pragma unroll
      for (int i = 0; i < 4; i++) o[i] = hadd2(hmul2(gg[hh][i].x, hmul2(qv[hh][i], ya[hh][i])), hmul2(gg[hh][i].y, yb[hh][i]));
      stsm4(qa + 2560 * hh, o);
    }
    TL(25 + (u == 2));
    if (u) break;
  }
  fence_async();
  bar_sync(NB_ROW0 + w, 128);
  if (lane == 0) {
    tma_store3(&p.to, ch0, 8 * rank, 8 * w + 2 * wg, sb + OFF_TQ + w * 5120 + wg * 1280);
    asm volatile("cp.async.bulk.commit_group;" ::: "memory");
    asm volatile("cp.async.bulk.wait_group.read 0;" ::: "memory");
  }
  TL(27);
  TL_DUMP();
}

typedef CUresult (*EncodeFn)(CUtensorMap*, CUtensorMapDataType, cuuint32_t, void*, const cuuint64_t*, const cuuint64_t*,
                             const cuuint32_t*, const cuuint32_t*, CUtensorMapInterleave, CUtensorMapSwizzle,
                             CUtensorMapL2promotion, CUtensorMapFloatOOBfill);

void encode(EncodeFn fn, CUtensorMap* tm, const void* ptr, int nd, const cuuint64_t* dims, const cuuint64_t* strides,
            const cuuint32_t* box, CUtensorMapSwizzle swz) {
  cuuint32_t es[4] = {1, 1, 1, 1};
  fn(tm, CU_TENSOR_MAP_DATA_TYPE_BFLOAT16, nd, const_cast<void*>(ptr), dims, strides, box, es, CU_TENSOR_MAP_INTERLEAVE_NONE,
     swz, CU_TENSOR_MAP_L2_PROMOTION_L2_128B, CU_TENSOR_MAP_FLOAT_OOB_FILL_NONE);
}
void map1(EncodeFn fn, CUtensorMap* tm, const void* ptr, int nhi) {
  const cuuint64_t dims[4] = {DCH, 4, 8, SEQ / 32}, strides[3] = {8 * DCH * 2, DCH * 2, 32 * DCH * 2};
  const cuuint32_t box[4] = {CPC, 4, 8, (cuuint32_t)nhi};
  encode(fn, tm, ptr, 4, dims, strides, box, CU_TENSOR_MAP_SWIZZLE_NONE);
}
void map2(EncodeFn fn, CUtensorMap* tm, const void* ptr, int nr) {
  const cuuint64_t dims[3] = {DCH, SEQ / 32, 32}, strides[2] = {32 * DCH * 2, DCH * 2};
  const cuuint32_t box[3] = {CPC, 8, (cuuint32_t)nr};
  encode(fn, tm, ptr, 3, dims, strides, box, CU_TENSOR_MAP_SWIZZLE_NONE);
}

}

extern "C" void kernel_launch(void* const* d_in, const int* in_sizes, int n_in, void* d_out, int out_size) {
  (void)in_sizes; (void)n_in; (void)out_size;
  static EncodeFn fn = nullptr;
  static void *tab = nullptr, *cnt = nullptr, *part = nullptr;
  if (!fn) {
    cudaGetSymbolAddress(&tab, d_tab);
    cudaGetSymbolAddress(&cnt, g_cnt);
    cudaGetSymbolAddress(&part, g_part);
    cudaDriverEntryPointQueryResult qr;
    cudaGetDriverEntryPoint("cuTensorMapEncodeTiled", (void**)&fn, cudaEnableDefault, &qr);
    cudaFuncSetAttribute(fused_kernel, cudaFuncAttributeMaxDynamicSharedMemorySize, SMEM_BYTES);
  }
  Params p;
  map1(fn, &p.tq, d_in[0], 4);
  map1(fn, &p.tk, d_in[1], 9);
  map1(fn, &p.tv, d_in[2], 8);
  map2(fn, &p.tq2, d_in[0], 32);
  map2(fn, &p.to, d_out, 2);
  {
    const cuuint64_t dims[4] = {32, SEQ / 32, DCH / 8, 8}, strides[3] = {64, 8 * SEQ * 2, SEQ * 2};
    const cuuint32_t box[4] = {32, 64, 5, 1};
    encode(fn, &p.th, d_in[4], 4, dims, strides, box, CU_TENSOR_MAP_SWIZZLE_64B);
  }
  p.tab = (const Tables*)tab;
  p.cnt = (unsigned*)cnt;
  p.part = (uint2*)part;
  p.tl = nullptr;
  p.q = (const __nv_bfloat16*)d_in[0];
  p.shift_k = (const __nv_bfloat16*)d_in[3];
  p.ssm_D = (const __nv_bfloat16*)d_in[5];
  p.logA = (const __nv_bfloat16*)d_in[7];
  p.Aim = (const __nv_bfloat16*)d_in[8];
  p.Cre = (const __nv_bfloat16*)d_in[9];
  p.Cim = (const __nv_bfloat16*)d_in[10];
  p.logdt = (const __nv_bfloat16*)d_in[11];
  p.Dskip = (const __nv_bfloat16*)d_in[12];
  p.gate_w = (const __nv_bfloat16*)d_in[13];
  fused_kernel<<<NCL * CS, NTHREADS, SMEM_BYTES, cudaStreamPerThread>>>(p);
}
```

```cpp
#include <cuda_runtime.h>
#include <cuda_bf16.h>
#include <cuda.h>
#include <stdint.h>

#define TIMELINE 0

namespace {

constexpr int SEQ = 2048, DCH = 576, NMODE = 128;
constexpr int CS = 8, CPC = 40, NCL = 15, NTHREADS = 512;

constexpr int YPITCH = 528;
constexpr int KTAB = 28672;
constexpr int OFF_T = 0;
constexpr int OFF_UKV = 2 * KTAB + 8192;
constexpr int OFF_UX = 3 * KTAB;
constexpr int OFF_HA = OFF_UX + 20480;
constexpr int OFF_CF = OFF_HA + 20480;
constexpr int OFF_CL = OFF_CF + 8192;
constexpr int OFF_TQ = OFF_CL + 4096;
constexpr int OFF_TK = OFF_TQ + 20480;
constexpr int OFF_YA = OFF_TK;
constexpr int OFF_TV = OFF_TK + 23040;
constexpr int OFF_YB = OFF_TV + 20480;
constexpr int OFF_KC = OFF_YB + 40 * YPITCH;
constexpr int OFF_SW = OFF_KC + 3 * 1408;
constexpr int OFF_GW = OFF_SW + 320;
constexpr int OFF_SD = OFF_GW + 80;
constexpr int OFF_MB = OFF_SD + 32;
constexpr int OFF_TL = OFF_MB + 24 * 8;
constexpr int SMEM_BYTES = OFF_TL + (TIMELINE ? 2048 : 0);
static_assert(SMEM_BYTES <= 232448, "smem");
static_assert((KTAB & 1023) == 0 && (OFF_TQ & 127) == 0 && (OFF_TK & 127) == 0 && (OFF_TV & 127) == 0 && (OFF_MB & 7) == 0 && (OFF_KC & 15) == 0, "align");

enum { MB_UX = 0, MB_UKV = 5, MB_Y = 10, MB_Q2 = 15, MB_XQ = 16, MB_KV = 18, MB_HA = 19, MB_CF = 20, MB_COUNT = 21 };
enum { NB_WG0 = 1, NB_ROW0 = 5 };

constexpr double cos_turn(int m, int n) {
  m &= n - 1;
  if (m > n / 2) m = n - m;
  double sgn = 1.0;
  if (m > n / 4) { m = n / 2 - m; sgn = -1.0; }
  if (m == n / 4) return 0.0;
  const double x = 6.283185307179586476925 * m / n;
  double term = 1.0, sum = 1.0;
  for (int k = 1; k < 14; k++) { term *= -x * x / ((2 * k - 1) * (2 * k)); sum += term; }
  return sgn * sum;
}
constexpr uint32_t bf16_bits(double v) {
  if (v == 0.0) return 0;
  uint32_t sgn = 0;
  if (v < 0) { sgn = 0x8000; v = -v; }
  int e = 127;
  while (v < 1.0) { v *= 2.0; e--; }
  while (v >= 2.0) { v *= 0.5; e++; }
  const double f = v * 128.0;
  int m = (int)f;
  if (f - m > 0.5 || (f - m == 0.5 && (m & 1))) m++;
  return sgn | (uint32_t)((e << 7) + (m - 128));
}
constexpr uint32_t pair_bits(double lo, double hi) { return bf16_bits(lo) | (bf16_bits(hi) << 16); }
struct alignas(128) Tables {
  uint32_t mat[3072];
  uint32_t thr[4][128][4];
};
constexpr Tables make_tables() {
  Tables T{};
  for (int q = 0; q < 768; q++) {
    int m0 = 0, d0 = 0, d1 = 0;
    if (q < 512) {
      const int r = (q >> 6) * 8 + (q & 7), cc = (q >> 3) & 7;
      d0 = 4 * (r & 31); d1 = 2 * d0;
      m0 = 8 * (cc & 3) * d0 + ((r >> 5) == (cc >> 2) ? 0 : (r >> 5) ? 96 : 32);
    } else {
      const int r = ((q - 512) >> 5) * 8 + (q & 7), pc = (q >> 3) & 3;
      d0 = 4 * (8 * (r >> 4) + (r & 7)) + 1; d1 = 8 * d0;
      m0 = 2 * pc * d0 + ((r & 8) ? 32 : 0);
    }
    for (int e = 0; e < 4; e++) T.mat[4 * q + e] = pair_bits(cos_turn(m0 + e * d1, 128), cos_turn(m0 + e * d1 + d0, 128));
  }
  for (int tid = 0; tid < 128; tid++) {
    const int kk = 4 * (tid >> 2) + 1, t = tid & 3;
    for (int q = 0; q < 4; q++) {
      const int m = (8 * q + 2 * t) * kk;
      T.thr[q >> 1][tid][2 * (q & 1)] = pair_bits(cos_turn(m, 128), cos_turn(m + kk, 128));
      T.thr[q >> 1][tid][2 * (q & 1) + 1] = pair_bits(cos_turn(m + 32, 128), cos_turn(m + kk + 32, 128));
      T.thr[2][tid][q] = pair_bits(cos_turn(m, 4096), cos_turn(m + kk, 4096));
      T.thr[3][tid][q] = pair_bits(cos_turn(m + 3072, 4096), cos_turn(m + kk + 3072, 4096));
    }
  }
  return T;
}
__device__ const Tables d_tab = make_tables();

struct Params {
  const __nv_bfloat16 *logA, *Aim, *Cre, *Cim, *logdt;
  const Tables* tab;
  unsigned* cnt;
  const __nv_bfloat16 *Dskip, *shift_k, *ssm_D, *gate_w, *q;
  uint2* part;
  unsigned* tl;
  CUtensorMap tq, tk, tv, th, tq2, to;
};

__device__ uint2 g_part[NCL * SEQ];
__device__ unsigned g_cnt[CS * 32];
#define TL(i) do {} while (0)
#define TL_INIT() do {} while (0)
#define TL_DUMP() do {} while (0)

__device__ __forceinline__ uint32_t lds16(uint32_t a) { uint32_t v; asm volatile("ld.shared.u16 %0, [%1];" : "=r"(v) : "r"(a) : "memory"); return v; }
__device__ __forceinline__ uint2 lds64(uint32_t a) { uint2 v; asm volatile("ld.shared.v2.u32 {%0,%1}, [%2];" : "=r"(v.x), "=r"(v.y) : "r"(a) : "memory"); return v; }
__device__ __forceinline__ uint4 lds128(uint32_t a) { uint4 v; asm volatile("ld.shared.v4.u32 {%0,%1,%2,%3}, [%4];" : "=r"(v.x), "=r"(v.y), "=r"(v.z), "=r"(v.w) : "r"(a) : "memory"); return v; }
__device__ __forceinline__ void sts16(uint32_t a, uint32_t v) { asm volatile("st.shared.u16 [%0], %1;" :: "r"(a), "r"(v) : "memory"); }
__device__ __forceinline__ void sts32(uint32_t a, uint32_t v) { asm volatile("st.shared.u32 [%0], %1;" :: "r"(a), "r"(v) : "memory"); }
__device__ __forceinline__ void sts64(uint32_t a, uint32_t x, uint32_t y) { asm volatile("st.shared.v2.u32 [%0], {%1,%2};" :: "r"(a), "r"(x), "r"(y) : "memory"); }
__device__ __forceinline__ void sts128(uint32_t a, uint32_t x, uint32_t y, uint32_t z, uint32_t w) { asm volatile("st.shared.v4.u32 [%0], {%1,%2,%3,%4};" :: "r"(a), "r"(x), "r"(y), "r"(z), "r"(w) : "memory"); }
__device__ __forceinline__ void ldsm4t(uint32_t (&r)[4], uint32_t a) { asm volatile("ldmatrix.sync.aligned.m8n8.x4.trans.shared.b16 {%0,%1,%2,%3}, [%4];" : "=r"(r[0]), "=r"(r[1]), "=r"(r[2]), "=r"(r[3]) : "r"(a) : "memory"); }
__device__ __forceinline__ void ldsm2t(uint32_t& r0, uint32_t& r1, uint32_t a) { asm volatile("ldmatrix.sync.aligned.m8n8.x2.trans.shared.b16 {%0,%1}, [%2];" : "=r"(r0), "=r"(r1) : "r"(a) : "memory"); }
__device__ __forceinline__ void ldsm4(uint32_t (&r)[4], uint32_t a) { asm volatile("ldmatrix.sync.aligned.m8n8.x4.shared.b16 {%0,%1,%2,%3}, [%4];" : "=r"(r[0]), "=r"(r[1]), "=r"(r[2]), "=r"(r[3]) : "r"(a) : "memory"); }
__device__ __forceinline__ void stsm4(uint32_t a, const uint32_t (&r)[4]) { asm volatile("stmatrix.sync.aligned.m8n8.x4.shared.b16 [%0], {%1,%2,%3,%4};" :: "r"(a), "r"(r[0]), "r"(r[1]), "r"(r[2]), "r"(r[3]) : "memory"); }
__device__ __forceinline__ uint32_t pack(float lo, float hi) { uint32_t r; asm("cvt.rn.bf16x2.f32 %0, %1, %2;" : "=r"(r) : "f"(hi), "f"(lo)); return r; }
__device__ __forceinline__ float blo(uint32_t v) { return __uint_as_float(v << 16); }
__device__ __forceinline__ float bhi(uint32_t v) { return __uint_as_float(v & 0xffff0000u); }
__device__ __forceinline__ float bf16r(float x) { return blo(pack(x, 0.f)); }
__device__ __forceinline__ uint32_t hmul2(uint32_t a, uint32_t b) { uint32_t r; asm("mul.rn.bf16x2 %0, %1, %2;" : "=r"(r) : "r"(a), "r"(b)); return r; }
__device__ __forceinline__ uint32_t hadd2(uint32_t a, uint32_t b) { uint32_t r; asm("add.rn.bf16x2 %0, %1, %2;" : "=r"(r) : "r"(a), "r"(b)); return r; }
__device__ __forceinline__ uint32_t hfma2(uint32_t a, uint32_t b, uint32_t c) { uint32_t r; asm("fma.rn.bf16x2 %0, %1, %2, %3;" : "=r"(r) : "r"(a), "r"(b), "r"(c)); return r; }
__device__ __forceinline__ uint32_t prmt(uint32_t a, uint32_t b, uint32_t s) { return __byte_perm(a, b, s); }
__device__ __forceinline__ uint32_t ldraw(const __nv_bfloat16* p) { uint32_t v; asm volatile("ld.global.nc.u16 %0, [%1];" : "=r"(v) : "l"(p)); return v; }
__device__ __forceinline__ uint4 ldg128(const void* p) { uint4 v; asm volatile("ld.global.nc.v4.u32 {%0,%1,%2,%3}, [%4];" : "=r"(v.x), "=r"(v.y), "=r"(v.z), "=r"(v.w) : "l"(p)); return v; }
__device__ __forceinline__ void bar_sync(int id, int n) { asm volatile("bar.sync %0, %1;" :: "r"(id), "r"(n) : "memory"); }
__device__ __forceinline__ void bar_arrive(int id, int n) { asm volatile("bar.arrive %0, %1;" :: "r"(id), "r"(n) : "memory"); }
__device__ __forceinline__ void cluster_arrive() { asm volatile("barrier.cluster.arrive.relaxed.aligned;" ::: "memory"); }
__device__ __forceinline__ void cluster_wait() { asm volatile("barrier.cluster.wait.aligned;" ::: "memory"); }
__device__ __forceinline__ void fence_async() { asm volatile("fence.proxy.async.shared::cta;" ::: "memory"); }
__device__ __forceinline__ void fence_mbinit() { asm volatile("fence.mbarrier_init.release.cluster;" ::: "memory"); }
__device__ __forceinline__ uint32_t mapa(uint32_t a, uint32_t rank) { uint32_t r; asm("mapa.shared::cluster.u32 %0, %1, %2;" : "=r"(r) : "r"(a), "r"(rank)); return r; }
__device__ __forceinline__ void st_async4(uint32_t a, uint32_t x, uint32_t y, uint32_t z, uint32_t w, uint32_t mbar) {
  asm volatile("st.async.weak.shared::cluster.mbarrier::complete_tx::bytes.v4.b32 [%0], {%1,%2,%3,%4}, [%5];"
               :: "r"(a), "r"(x), "r"(y), "r"(z), "r"(w), "r"(mbar) : "memory");
}
__device__ __forceinline__ void mbar_init(uint32_t m, uint32_t cnt) { asm volatile("mbarrier.init.shared::cta.b64 [%0], %1;" :: "r"(m), "r"(cnt) : "memory"); }
__device__ __forceinline__ void mbar_expect(uint32_t m, uint32_t bytes) { asm volatile("mbarrier.arrive.expect_tx.shared::cta.b64 _, [%0], %1;" :: "r"(m), "r"(bytes) : "memory"); }
__device__ __forceinline__ void mbar_wait(uint32_t m) {
  uint32_t done;
  int it = 0;
  do {
    asm volatile("{.reg .pred p; mbarrier.try_wait.parity.shared::cta.b64 p, [%1], 0; selp.u32 %0, 1, 0, p;}" : "=r"(done) : "r"(m) : "memory");
    if (++it > (1 << 22)) __trap();
  } while (!done);
}
__device__ __forceinline__ void tma_load4(uint32_t dst, const CUtensorMap* tm, int c0, int c1, int c2, int c3, uint32_t mbar) {
  asm volatile("cp.async.bulk.tensor.4d.shared::cluster.global.mbarrier::complete_tx::bytes [%0], [%1, {%3, %4, %5, %6}], [%2];"
               :: "r"(dst), "l"(tm), "r"(mbar), "r"(c0), "r"(c1), "r"(c2), "r"(c3) : "memory");
}
__device__ __forceinline__ void tma_load3(uint32_t dst, const CUtensorMap* tm, int c0, int c1, int c2, uint32_t mbar) {
  asm volatile("cp.async.bulk.tensor.3d.shared::cluster.global.mbarrier::complete_tx::bytes [%0], [%1, {%3, %4, %5}], [%2];"
               :: "r"(dst), "l"(tm), "r"(mbar), "r"(c0), "r"(c1), "r"(c2) : "memory");
}
__device__ __forceinline__ void tma_store3(const CUtensorMap* tm, int c0, int c1, int c2, uint32_t src) {
  asm volatile("cp.async.bulk.tensor.3d.global.shared::cta.bulk_group [%0, {%2, %3, %4}], [%1];"
               :: "l"(tm), "r"(src), "r"(c0), "r"(c1), "r"(c2) : "memory");
}
__device__ __forceinline__ void wg_fence() { asm volatile("wgmma.fence.sync.aligned;" ::: "memory"); }
__device__ __forceinline__ void wg_commit() { asm volatile("wgmma.commit_group.sync.aligned;" ::: "memory"); }
template <int N> __device__ __forceinline__ void wg_wait() { asm volatile("wgmma.wait_group.sync.aligned %0;" :: "n"(N) : "memory"); }
template <int N> __device__ __forceinline__ void tie_all(float (&x)[N]) {
#pragma unroll
  for (int i = 0; i < N; i++) asm volatile("" : "+f"(x[i]) :: "memory");
}
#define R16(C, d) C(d[0]), C(d[1]), C(d[2]), C(d[3]), C(d[4]), C(d[5]), C(d[6]), C(d[7]), C(d[8]), C(d[9]), C(d[10]), C(d[11]), C(d[12]), C(d[13]), C(d[14]), C(d[15])
#define R32(C, d) R16(C, d), R16(C, (d + 16))
#define P16 "{%0,%1,%2,%3,%4,%5,%6,%7,%8,%9,%10,%11,%12,%13,%14,%15}"
#define P32 "{%0,%1,%2,%3,%4,%5,%6,%7,%8,%9,%10,%11,%12,%13,%14,%15,%16,%17,%18,%19,%20,%21,%22,%23,%24,%25,%26,%27,%28,%29,%30,%31}"
template <int SD, int TB, int OFF> __device__ __forceinline__ void rs64(float* d, const uint32_t* a, uint64_t db) {
  if (SD) asm volatile("{.reg .b64 db; add.s64 db, %36, %37; wgmma.mma_async.sync.aligned.m64n64k16.f32.bf16.bf16 " P32 ", {%32,%33,%34,%35}, db, 1, 1, 1, %38;}"
                       : R32("+f", d) : "r"(a[0]), "r"(a[1]), "r"(a[2]), "r"(a[3]), "l"(db), "n"(OFF), "n"(TB));
  else asm volatile("{.reg .b64 db; add.s64 db, %36, %37; wgmma.mma_async.sync.aligned.m64n64k16.f32.bf16.bf16 " P32 ", {%32,%33,%34,%35}, db, 0, 1, 1, %38;}"
                    : R32("=f", d) : "r"(a[0]), "r"(a[1]), "r"(a[2]), "r"(a[3]), "l"(db), "n"(OFF), "n"(TB));
}
template <int SD, int OFFA, int OFFB> __device__ __forceinline__ void ss32(float* d, uint64_t da, uint64_t db) {
  if (SD) asm volatile("{.reg .b64 da, db; add.s64 da, %16, %18; add.s64 db, %17, %19; wgmma.mma_async.sync.aligned.m64n32k16.f32.bf16.bf16 " P16 ", da, db, 1, 1, 1, 1, 1;}"
                       : R16("+f", d) : "l"(da), "l"(db), "n"(OFFA), "n"(OFFB));
  else asm volatile("{.reg .b64 da, db; add.s64 da, %16, %18; add.s64 db, %17, %19; wgmma.mma_async.sync.aligned.m64n32k16.f32.bf16.bf16 " P16 ", da, db, 0, 1, 1, 1, 1;}"
                    : R16("=f", d) : "l"(da), "l"(db), "n"(OFFA), "n"(OFFB));
}
template <int KS> __device__ __forceinline__ void kgen_mma(float (&c)[24], uint64_t da) {
  asm volatile("{.reg .b64 da, db; add.s64 da, %24, %25; add.s64 db, %24, %26;\n"
               "wgmma.mma_async.sync.aligned.m64n48k16.f32.bf16.bf16 {%0,%1,%2,%3,%4,%5,%6,%7,%8,%9,%10,%11,%12,%13,%14,%15,%16,%17,%18,%19,%20,%21,%22,%23}, da, db, %27, 1, 1, 1, 1;}"
               : R16("+f", c), "+f"(c[16]), "+f"(c[17]), "+f"(c[18]), "+f"(c[19]), "+f"(c[20]), "+f"(c[21]), "+f"(c[22]), "+f"(c[23])
               : "l"(da), "n"(8 * KS), "n"(8 * KS + 512), "n"(KS ? 1 : 0));
  if constexpr (KS < 7) kgen_mma<KS + 1>(c, da);
}
__device__ __forceinline__ uint64_t desc_lo(uint32_t a) { return (uint64_t)((a & 0x3FFFF) >> 4); }
__device__ __forceinline__ void stage1(float (&D)[32], const uint32_t (&A1)[8], uint32_t src) {
  const uint64_t du = desc_lo(src) | (128ull << 16) | (32ull << 32) | (2ull << 62);
  rs64<0, 1, 0>(D, A1, du); rs64<1, 1, 64>(D, A1 + 4, du);
}
template <int INV> __device__ __forceinline__ void stage2(float (&X)[32], const uint32_t (&F)[16], uint32_t cf) {
  constexpr int KS = INV ? 16 : 128, TB = INV ? 0 : 1;
  const uint64_t dc = desc_lo(cf) | (INV ? (8ull << 16) | (64ull << 32) : (64ull << 16) | (8ull << 32));
  rs64<0, TB, 0>(X, F, dc); rs64<1, TB, KS>(X, F + 4, dc); rs64<1, TB, 2 * KS>(X, F + 8, dc); rs64<1, TB, 3 * KS>(X, F + 12, dc);
}
__device__ __forceinline__ void fwd_mid(uint32_t (&F)[16], const float (&D)[32], const uint32_t (&tp)[12]) {
#pragma unroll
  for (int j = 0; j < 4; j++)
#pragma unroll
    for (int b = 0; b < 2; b++) {
      const int i = 4 * j + 16 * b;
      const uint32_t ar = pack(D[i], D[i + 1]), ai = pack(D[i + 2], D[i + 3]);
      F[2 * j + b] = hfma2(ar, tp[3 * j], hmul2(ai, tp[3 * j + 2]));
      F[8 + 2 * j + b] = hfma2(ar, tp[3 * j + 1], hmul2(ai, tp[3 * j]));
    }
}

struct cf { float x, y; };
__device__ __forceinline__ cf cmul(cf a, cf b) { cf r; r.x = fmaf(a.x, b.x, -a.y * b.y); r.y = fmaf(a.x, b.y, a.y * b.x); return r; }
__device__ __forceinline__ cf cexp_p(float lr2, float lt, float p) {
  float m = exp2f(lr2 * p);
  float t = lt * p;
  t = (t - rintf(t)) * 6.283185307179586f;
  cf r; r.x = m * __cosf(t); r.y = m * __sinf(t); return r;
}
__device__ __forceinline__ void store8(uint32_t a, const cf (&v)[8]) {
  sts128(a, pack(v[0].x, v[1].x), pack(v[2].x, v[3].x), pack(v[4].x, v[5].x), pack(v[6].x, v[7].x));
  sts128(a + KTAB / 2, pack(v[0].y, v[1].y), pack(v[2].y, v[3].y), pack(v[4].y, v[5].y), pack(v[6].y, v[7].y));
}
__device__ __forceinline__ float sigmoidf_(float s) { return 1.f / (1.f + __expf(-s)); }

__global__ void __cluster_dims__(CS, 1, 1) __launch_bounds__(NTHREADS, 1) fused_kernel(const __grid_constant__ Params p) {
  extern __shared__ __align__(1024) uint8_t smem[];
  TL_INIT();
  TL(31);
  uint32_t pla[2], pai[2], pcr[2], pci[2], pdt[2];
  if (threadIdx.x < 384) {
#pragma unroll
    for (int r = 0; r < 2; r++) {
      int ch = (blockIdx.x >> 3) * CPC + (blockIdx.x & 7) + 8 * (threadIdx.x >> 7) + 24 * r;
      if (ch >= DCH) ch = 0;
      const int o = ch * NMODE + (threadIdx.x & 127);
      pla[r] = ldraw(p.logA + o); pdt[r] = ldraw(p.logdt + ch); pai[r] = ldraw(p.Aim + o); pcr[r] = ldraw(p.Cre + o); pci[r] = ldraw(p.Cim + o);
    }
  }
  const uint32_t sb = (uint32_t)__cvta_generic_to_shared(smem);
  const uint32_t mb = sb + OFF_MB;
  const int wg = __shfl_sync(0xffffffffu, threadIdx.x >> 7, 0);
  const int tid = threadIdx.x & 127, w = __shfl_sync(0xffffffffu, tid >> 5, 0), lane = tid & 31, g = lane >> 2, t = lane & 3;
  const int cl = blockIdx.x >> 3, rank = blockIdx.x & 7;
  const int ch0 = cl * CPC;
  const int nu = min(5, (DCH - ch0) >> 3);

  if (wg < 3) {
    cluster_arrive();
    uint32_t A1[8], tp[12];
    {
      const uint4 a = ldg128(p.tab->thr[0][tid]), b = ldg128(p.tab->thr[1][tid]), c = ldg128(p.tab->thr[2][tid]), d = ldg128(p.tab->thr[3][tid]);
      A1[0] = a.x; A1[1] = a.y; A1[2] = a.z; A1[3] = a.w; A1[4] = b.x; A1[5] = b.y; A1[6] = b.z; A1[7] = b.w;
      tp[0] = c.x; tp[3] = c.y; tp[6] = c.z; tp[9] = c.w; tp[2] = d.x; tp[5] = d.y; tp[8] = d.z; tp[11] = d.w;
      tp[1] = tp[4] = tp[7] = tp[10] = 0;
    }
    TL(0);
    const uint32_t tab = sb + OFF_T + wg * KTAB;
#pragma unroll 1
    for (int job = 0; job < 4; job++) {
      const bool isA = job >= (wg == 2 ? 1 : 2);
      const int u = wg == 2 ? (job ? 2 * job - 2 : 2) : job < 2 ? wg + 3 * job : job == 2 ? 2 * wg + 1 : 9;

      if (!isA && u < nu) {
        const float la = blo(job ? pla[1] : pla[0]), ai = blo(job ? pai[1] : pai[0]), cr = blo(job ? pcr[1] : pcr[0]), ci = blo(job ? pci[1] : pci[0]);
        const float dt = bf16r(expf(blo(job ? pdt[1] : pdt[0])));
        const float lr2 = (-bf16r(expf(la)) * dt) * 1.4426950408889634f;
        const float lt = (ai * dt) * 0.15915494309189535f;
        const uint32_t row = tab + tid * 16;
        if (lr2 != 123.f) TL(16 + 4 * job);
        if (job) bar_sync(NB_WG0 + wg, 128);
        {
          const cf w1 = cexp_p(lr2, lt, 8.f);
          cf v[8];
          v[0].x = 1.f; v[0].y = 0.f; v[1] = w1; v[2] = cmul(w1, w1); v[3] = cmul(v[2], w1);
          const cf w4 = cmul(v[2], v[2]);
          v[4] = w4; v[5] = cmul(v[1], w4); v[6] = cmul(v[2], w4); v[7] = cmul(v[3], w4);
          const cf w8 = cmul(w4, w4);
          store8(row, v);
#pragma unroll
          for (int c = 1; c < 4; c++) {
#pragma unroll
            for (int i = 0; i < 8; i++) v[i] = (c == 1 && i == 0) ? w8 : cmul(v[i], w8);
            store8(row + 2048 * c, v);
          }
        }
        {
          cf z1 = cexp_p(lr2, lt, 1.f), Z = cexp_p(lr2, lt, 256.f);
          z1.y = -z1.y; Z.y = -Z.y;
          const cf z2 = cmul(z1, z1);
          cf h[8], v[8];
          h[0].x = 2.f * cr * dt; h[0].y = -2.f * ci * dt;
          h[1] = cmul(h[0], z1);
#pragma unroll
          for (int i = 2; i < 8; i++) h[i] = cmul(h[i - 2], z2);
          store8(row + 4 * 2048, h);
          v[0] = cmul(h[0], Z); v[1] = cmul(h[2], Z); v[2] = cmul(h[4], Z); v[3] = cmul(h[6], Z);
          v[4] = cmul(v[0], Z); v[5] = cmul(v[2], Z); v[6] = cmul(v[4], Z); v[7] = cmul(v[5], Z);
          store8(row + 5 * 2048, v);
          const cf Z2 = cmul(Z, Z);
          h[0] = cmul(v[4], Z2); h[1] = cmul(v[6], Z2); h[2] = cmul(h[0], Z2); h[3] = cmul(h[1], Z2); h[4] = cmul(h[2], Z2);
          h[5].x = h[5].y = h[6].x = h[6].y = h[7].x = h[7].y = 0.f;
          store8(row + 6 * 2048, h);
        }
        TL(17 + 4 * job);
        fence_async();
        bar_sync(NB_WG0 + wg, 128);
        float c[24];
        wg_fence();
        kgen_mma<0>(c, desc_lo(tab) | ((uint64_t)(KTAB / 32) << 16) | (64ull << 32));
        wg_commit();
        uint32_t kid[8];
        {
          float lf = __uint_as_float(0x4b000000u | (8 * tid)) - 8388608.f;
          asm volatile("" : "+f"(lf));
          const float lo = tid < 16 ? lf + 128.f : lf;
          const uint32_t sub = tid < 16 ? 0x42804300u : 0x42804280u;
#pragma unroll
          for (int i = 0; i < 8; i++) kid[i] = 2 * (pack(lo + i, lf + (1024 + i)) - sub);
        }
        wg_wait<0>(); tie_all(c);
        const uint32_t kc = sb + OFF_KC + wg * 1408;
        {
          const int a = 8 * w + g;
          sts32(kc + 4 * (4 * a + t), pack(c[0] + c[6], c[1] + c[7]));
          sts32(kc + 4 * (t < 2 ? 128 + 2 * a + t : 128 + 32 * t + a), pack(c[8] + c[14], c[9] + c[15]));
          if (t < 3) {
            const uint32_t p0 = pack(c[16] + c[22], c[17] + c[23]);
            sts16(kc + 2 * (512 + 64 * t + a), p0);
            sts16(kc + 2 * (544 + 64 * t + a), p0 >> 16);
          }
        }
        TL(18 + 4 * job);
        bar_sync(NB_WG0 + wg, 128);
        uint32_t v[2][8];
#pragma unroll
        for (int i = 0; i < 8; i++) { v[0][i] = lds16(kc + (kid[i] & 0xffffu)); v[1][i] = lds16(kc + (kid[i] >> 16)); }
#pragma unroll
        for (int cc = 0; cc < 2; cc++)
          sts128(tab + 2048 * cc + 16 * (tid ^ ((tid >> 3) & 3)), prmt(v[cc][0], v[cc][1], 0x5410), prmt(v[cc][2], v[cc][3], 0x5410),
                 prmt(v[cc][4], v[cc][5], 0x5410), prmt(v[cc][6], v[cc][7], 0x5410));
        fence_async();
        if (job) bar_sync(NB_WG0 + wg, 128);
      }
      if (job == 0) {
        cluster_wait();
        cluster_arrive();
        bar_sync(NB_WG0 + wg, 128);
        mbar_wait(mb + 8 * MB_CF);
#pragma unroll
        for (int j = 0; j < 4; j++) asm volatile("xor.b32 %0, %1, 0x80008000;" : "=r"(tp[3 * j + 1]) : "r"(tp[3 * j + 2]));
      }
      if (u >= nu) continue;
      TL(1 + job);
      float D[32], H[32], X[32];
      uint32_t F[16];
      if (isA) mbar_wait(mb + 8 * MB_HA);
      wg_fence();
      stage1(D, A1, isA ? sb + OFF_HA + u * 4096 : tab);
      wg_commit();
      wg_wait<0>(); tie_all(D);
      fwd_mid(F, D, tp);
      wg_fence();
      stage2<0>(H, F, sb + OFF_CF);
      wg_commit();
      mbar_wait(mb + 8 * ((isA ? MB_UKV : MB_UX) + u));
      fence_async();
      TL(5 + job);
      wg_fence();
      stage1(D, A1, sb + (isA ? OFF_UKV : OFF_UX) + u * 4096);
      wg_commit();
      wg_wait<0>(); tie_all(D); tie_all(H);
      fwd_mid(F, D, tp);
      wg_fence();
      stage2<0>(X, F, sb + OFF_CF);
      wg_commit();
      {
        const float dsk = blo(lds16(sb + OFF_SD + (isA ? 10 : 0) + 2 * u));
#pragma unroll
        for (int j = 0; j < 4; j++) { H[4 * j] += dsk; H[4 * j + 1] += dsk; }
      }
      wg_wait<0>(); tie_all(X);
#pragma unroll
      for (int j = 0; j < 4; j++) {
        float pr[2], pi[2], qr[2], qi[2];
#pragma unroll
        for (int n = 0; n < 2; n++) {
          const int i = 4 * j + n;
          pr[n] = fmaf(X[i], H[i], -X[i + 16] * H[i + 16]);
          pi[n] = fmaf(X[i], H[i + 16], X[i + 16] * H[i]);
          qr[n] = fmaf(X[i + 2], H[i], fmaf(-X[i + 18], H[i + 16], fmaf(X[i], H[i + 2], fmaf(-X[i + 16], H[i + 18], -pi[n]))));
          qi[n] = fmaf(X[i + 2], H[i + 16], fmaf(X[i + 18], H[i], fmaf(X[i], H[i + 18], fmaf(X[i + 16], H[i + 2], pr[n]))));
        }
        F[2 * j] = pack(pr[0], pr[1]); F[2 * j + 1] = pack(qr[0], qr[1]); F[8 + 2 * j] = pack(pi[0], pi[1]); F[9 + 2 * j] = pack(qi[0], qi[1]);
      }
      wg_fence();
      stage2<1>(H, F, sb + OFF_CF);
      wg_commit();
      wg_wait<0>(); tie_all(H);
      {
        const uint32_t va = tab + (16 * w + (lane & 15)) * 128;
        const int vx = (lane >> 4) ^ (lane & 7);
#pragma unroll
        for (int j = 0; j < 4; j++) {
          uint32_t V[4];
#pragma unroll
          for (int b = 0; b < 2; b++) {
            const int i = 4 * j + 2 * b;
            const uint32_t er = pack(H[i], H[i + 1]), ei = pack(H[i + 16], H[i + 17]);
            V[2 * b] = hfma2(er, tp[3 * j], hmul2(ei, tp[3 * j + 1]));
            V[2 * b + 1] = hfma2(ei, tp[3 * j], hmul2(er, tp[3 * j + 2]));
          }
          stsm4(va + ((vx ^ (2 * j)) << 4), V);
        }
      }
      fence_async();
      bar_sync(NB_WG0 + wg, 128);
      float O[16];
      {
        const uint64_t dv = desc_lo(tab) | (1ull << 16) | (64ull << 32) | (1ull << 62);
        const uint64_t dl = desc_lo(sb + OFF_CL) | (32ull << 16) | (8ull << 32);
        wg_fence();
        ss32<0, 0, 0>(O, dv, dl); ss32<1, 128, 64>(O, dv, dl); ss32<1, 256, 128>(O, dv, dl); ss32<1, 384, 192>(O, dv, dl);
        wg_commit();
      }
      if (isA && job < 3) {
        for (int k = 0; k < nu; k++) mbar_wait(mb + 8 * (MB_UKV + k));
      }
      wg_wait<0>(); tie_all(O);
      {
        const uint32_t yo = (isA ? OFF_YA : OFF_YB) + (8 * u + rank) * YPITCH + (8 * w + g) * 16, ym = OFF_MB + 8 * (MB_Y + u);
        const uint32_t r0 = mapa(sb, t), r1 = mapa(sb, t + 4);
        st_async4(r0 + yo, pack(O[0], O[1]), pack(O[4], O[5]), pack(O[8], O[9]), pack(O[12], O[13]), r0 + ym);
        st_async4(r1 + yo, pack(O[2], O[3]), pack(O[6], O[7]), pack(O[10], O[11]), pack(O[14], O[15]), r1 + ym);
      }
      TL(9 + job);
    }
  } else {
    if (lane == 0) {
#pragma unroll
      for (int i = 0; i < 4; i++) mbar_init(mb + 8 * (4 * w + i), 4 * w + i == MB_Q2 ? 5 : 1);
      mbar_init(mb + 8 * (MB_XQ + w), 1);
      if (w == 3) mbar_init(mb + 8 * MB_CF, 2);
      fence_mbinit();
      if (w == 3) {
        mbar_expect(mb + 8 * MB_CF, 12288);
        asm volatile("cp.async.bulk.shared::cluster.global.mbarrier::complete_tx::bytes [%0], [%1], %2, [%3];"
                     :: "r"(sb + OFF_CF), "l"(p.tab->mat), "r"(12288), "r"(mb + 8 * MB_CF) : "memory");
      }
#pragma unroll
      for (int i = 0; i < 4; i++) { const int b = 4 * w + i; mbar_expect(mb + 8 * b, b == MB_Q2 ? 20480 : b >= MB_Y ? 8192 : 4096); }
      mbar_expect(mb + 8 * (MB_XQ + w), w < 2 ? 10240 : w == 2 ? 23040 + 20480 : 20480);
    }
    __syncwarp();
    cluster_arrive();
    uint2 swv = make_uint2(0, 0);
    uint32_t gwv = 0, tag = 0;
    if (tid >= 64 && tid < 104 && ch0 + tid - 64 < DCH) { swv = __ldg((const uint2*)(p.shift_k + (size_t)(ch0 + tid - 64) * 4)); gwv = ldraw(p.gate_w + ch0 + tid - 64); }
    if (tid >= 112 && tid < 122) { const int k = tid - 112, u = k < 5 ? k : k - 5; if (u < nu) gwv = ldraw((k < 5 ? p.Dskip : p.ssm_D) + ch0 + 8 * u + rank); }
    if (tid == 1) asm volatile("atom.relaxed.gpu.global.add.u32 %0, [%1], %2;" : "=r"(tag) : "l"(&p.cnt[rank * 32]), "r"(cl == 0 ? 16 - (NCL - 1) : 1) : "memory");
    if (lane == 0 && w < 2) { tma_load4(sb + OFF_TQ + 10240 * w, &p.tq, ch0, 0, 0, 8 * rank + 4 * w, mb + 8 * (MB_XQ + w)); TL(20); }
    if (tid >= 64 && tid < 104) { sts64(sb + OFF_SW + 8 * (tid - 64), swv.x, swv.y); sts16(sb + OFF_GW + 2 * (tid - 64), gwv); }
    if (tid >= 112 && tid < 122) sts16(sb + OFF_SD + 2 * (tid - 112), gwv);
    __syncwarp();
    if (tid == 64) {
      tma_load4(sb + OFF_TK, &p.tk, ch0, 0, 0, 8 * rank - 1, mb + 8 * MB_KV);
      tma_load4(sb + OFF_TV, &p.tv, ch0, 0, 0, 8 * rank, mb + 8 * MB_KV);
    }
    if (tid == 96) asm volatile("mbarrier.arrive.shared::cta.b64 _, [%0];" :: "r"(mb + 8 * MB_CF) : "memory");
    __syncwarp();
    TL(0);
    const uint32_t rbase = mapa(sb, g);
    const int mi = lane >> 3, tq = (lane & 7) >> 1, jj = lane & 1;
    const uint32_t toff = (4 * (2 * mi + jj) + tq) * 80;
    const uint32_t uoff = 16 * (32 * rank + 4 * w + (t ^ (w >> 1)));
    cluster_wait();
    cluster_arrive();
    if (tid == 64) tma_load4(sb + OFF_HA, &p.th, 0, 0, 5 * cl, rank, mb + 8 * MB_HA);
    __syncwarp();
    mbar_wait(mb + 8 * MB_XQ);
    mbar_wait(mb + 8 * (MB_XQ + 1));
    TL(1);
    {
      uint32_t xr[5][2][4];
#pragma unroll
      for (int u = 0; u < 5; u++) { ldsm4t(xr[u][0], sb + OFF_TQ + w * 2560 + toff + 16 * u); ldsm4t(xr[u][1], sb + OFF_TQ + (w + 4) * 2560 + toff + 16 * u); }
#pragma unroll
      for (int u = 0; u < 5; u++)
        if (u < nu) {
          st_async4(rbase + OFF_UX + u * 4096 + uoff, xr[u][0][0], xr[u][0][1], xr[u][0][2], xr[u][0][3], rbase + OFF_MB + 8 * (MB_UX + u));
          st_async4(rbase + OFF_UX + u * 4096 + (uoff ^ 32) + 256, xr[u][1][0], xr[u][1][1], xr[u][1][2], xr[u][1][3], rbase + OFF_MB + 8 * (MB_UX + u));
        }
    }
    TL(2);
    if (tid == 1) sts32(sb + OFF_MB + 8 * MB_COUNT, tag);
    bar_sync(NB_WG0 + 3, 128);
    tag = (lds64(sb + OFF_MB + 8 * MB_COUNT).x >> 4) + 1;
    {
      float s0 = 0.f, s1 = 0.f;
#pragma unroll
      for (int j = 0; j < 5; j++) {
        const uint4 gw = lds128(sb + OFF_GW + 16 * j);
        const uint4 x0 = lds128(sb + OFF_TQ + tid * 80 + 16 * j), x1 = lds128(sb + OFF_TQ + (tid + 128) * 80 + 16 * j);
        uint32_t m0 = hmul2(x0.x, gw.x), m1 = hmul2(x0.y, gw.y), m2 = hmul2(x0.z, gw.z), m3 = hmul2(x0.w, gw.w);
        s0 += ((blo(m0) + bhi(m0)) + (blo(m1) + bhi(m1))) + ((blo(m2) + bhi(m2)) + (blo(m3) + bhi(m3)));
        m0 = hmul2(x1.x, gw.x); m1 = hmul2(x1.y, gw.y); m2 = hmul2(x1.z, gw.z); m3 = hmul2(x1.w, gw.w);
        s1 += ((blo(m0) + bhi(m0)) + (blo(m1) + bhi(m1))) + ((blo(m2) + bhi(m2)) + (blo(m3) + bhi(m3)));
      }
      const int s2 = 8 * (8 * (lane & 3) + (lane >> 2)) + w;
      asm volatile("st.relaxed.gpu.global.u64 [%0], %1;" :: "l"(&p.part[cl * SEQ + rank * 256 + s2]), "l"(((uint64_t)tag << 32) | __float_as_uint(s0)) : "memory");
      asm volatile("st.relaxed.gpu.global.u64 [%0], %1;" :: "l"(&p.part[cl * SEQ + rank * 256 + s2 + 4]), "l"(((uint64_t)tag << 32) | __float_as_uint(s1)) : "memory");
    }
    bar_sync(NB_WG0 + 3, 128);
    if (tid == 0) tma_load3(sb + OFF_TQ, &p.tq2, ch0, 8 * rank, 0, mb + 8 * MB_Q2);
    __syncwarp();
    TL(3);
    cluster_wait();
    mbar_wait(mb + 8 * MB_KV);
    TL(4);
    const uint32_t hoff = (4 * (4 + 2 * (mi & 1) + jj) + ((tq + 3) & 3)) * 80 + (tq ? 2560 : 0);
    uint32_t En[2][6], Vn[2][4];
    uint2 swn;
    auto kv_load = [&](int u) {
      swn = lds64(sb + OFF_SW + 8 * (8 * u + g));
#pragma unroll
      for (int hf = 0; hf < 2; hf++) {
        const int ah = 4 * hf + w;
        uint32_t K[4];
        ldsm4t(K, sb + OFF_TK + (ah + 1) * 2560 + toff + 16 * u);
        ldsm2t(En[hf][0], En[hf][1], sb + OFF_TK + ah * 2560 + hoff + 16 * u);
        ldsm4t(Vn[hf], sb + OFF_TV + ah * 2560 + toff + 16 * u);
        En[hf][2] = K[0]; En[hf][3] = K[1]; En[hf][4] = K[2]; En[hf][5] = K[3];
      }
    };
    kv_load(0);
#pragma unroll 1
    for (int u = 0; u < nu; u++) {
      uint32_t E[2][6], V[2][4];
#pragma unroll
      for (int hf = 0; hf < 2; hf++) {
#pragma unroll
        for (int i = 0; i < 6; i++) E[hf][i] = En[hf][i];
#pragma unroll
        for (int i = 0; i < 4; i++) V[hf][i] = Vn[hf][i];
      }
      const uint32_t w0 = prmt(swn.x, 0, 0x1010), w1 = prmt(swn.x, 0, 0x3232), w2 = prmt(swn.y, 0, 0x1010), w3 = prmt(swn.y, 0, 0x3232);
      if (u + 1 < nu) kv_load(u + 1);
#pragma unroll
      for (int hf = 0; hf < 2; hf++) {
        uint32_t O[5], o[4];
#pragma unroll
        for (int i = 0; i < 5; i++) O[i] = prmt(E[hf][i], E[hf][i + 1], 0x5432);
#pragma unroll
        for (int i = 0; i < 4; i++) {
          uint32_t s = hmul2(O[i], w3);
          s = hadd2(s, hmul2(E[hf][i + 1], w2));
          s = hadd2(s, hmul2(O[i + 1], w1));
          s = hadd2(s, hmul2(E[hf][i + 2], w0));
          o[i] = hmul2(s, V[hf][i]);
        }
        st_async4(rbase + OFF_UKV + u * 4096 + (hf ? (uoff ^ 32) + 256 : uoff), o[0], o[1], o[2], o[3], rbase + OFF_MB + 8 * (MB_UKV + u));
      }
    }
    TL(5);
    bar_sync(NB_WG0 + 3, 128);
    {
      float s[2] = {0.f, 0.f};
      bool ok = false;
#pragma unroll 1
      for (int it = 0; it < 4000 && !ok; it++) {
        ok = true; s[0] = s[1] = 0.f;
#pragma unroll
        for (int c = 0; c < NCL; c++) {
          uint64_t a, b;
          asm volatile("ld.relaxed.gpu.global.v2.u64 {%0,%1}, [%2];" : "=l"(a), "=l"(b) : "l"(&p.part[c * SEQ + rank * 256 + 2 * tid]) : "memory");
          ok = ok && (uint32_t)(a >> 32) == tag && (uint32_t)(b >> 32) == tag;
          s[0] += __uint_as_float((uint32_t)a); s[1] += __uint_as_float((uint32_t)b);
        }
      }
      if (ok) {
      } else {
#pragma unroll 1
        for (int hf = 0; hf < 2; hf++) {
          const int slot = 2 * tid + hf;
          const int row = rank * 256 + 32 * (slot & 7) + (slot >> 3);
          const uint32_t* xr = (const uint32_t*)(p.q + (size_t)row * DCH);
          const uint32_t* gr = (const uint32_t*)p.gate_w;
          float a = 0.f;
#pragma unroll 1
          for (int c = 0; c < DCH / 2; c++) { const uint32_t m = hmul2(__ldg(xr + c), __ldg(gr + c)); a += blo(m) + bhi(m); }
          if (hf) s[1] = a; else s[0] = a;
        }
      }
      const float g0 = bf16r(sigmoidf_(bf16r(s[0]))), g1 = bf16r(sigmoidf_(bf16r(s[1])));
      const float a0 = g0 * 0.0009765625f, b0 = bf16r(1.f - g0) * 0.0009765625f, a1 = g1 * 0.0009765625f, b1 = bf16r(1.f - g1) * 0.0009765625f;
      sts128(sb + OFF_TV + 16 * tid, pack(a0, a0), pack(b0, b0), pack(a1, a1), pack(b1, b1));
    }
    __syncwarp();
    if (lane == 0) asm volatile("mbarrier.arrive.shared::cta.b64 _, [%0];" :: "r"(mb + 8 * MB_Q2) : "memory");
  }
  mbar_wait(mb + 8 * MB_Q2);
  uint2 gg[2][4];
#pragma unroll
  for (int hh = 0; hh < 2; hh++)
#pragma unroll
    for (int i = 0; i < 4; i++) gg[hh][i] = lds64(sb + OFF_TV + 8 * (64 * w + 32 * hh + 8 * i + g));
  TL(24);
#pragma unroll 1
  for (int u = wg == 3 ? 0 : wg == 2 ? 4 : 2 * wg + 1; u < nu; u += 2) {
    uint32_t qv[2][4];
    const uint32_t qa = sb + OFF_TQ + (64 * w + lane) * 80 + 16 * u;
    ldsm4(qv[0], qa);
    ldsm4(qv[1], qa + 2560);
    mbar_wait(mb + 8 * (MB_Y + u));
    uint32_t ya[2][4], yb[2][4];
    const uint32_t yo = (8 * u + (lane & 7)) * YPITCH + (8 * w + (lane >> 3)) * 16;
#pragma unroll
    for (int hh = 0; hh < 2; hh++) { ldsm4t(ya[hh], sb + OFF_YA + yo + 64 * hh); ldsm4t(yb[hh], sb + OFF_YB + yo + 64 * hh); }
#pragma unroll
    for (int hh = 0; hh < 2; hh++) {
      uint32_t o[4];
#pragma unroll
      for (int i = 0; i < 4; i++) o[i] = hadd2(hmul2(gg[hh][i].x, hmul2(qv[hh][i], ya[hh][i])), hmul2(gg[hh][i].y, yb[hh][i]));
      stsm4(qa + 2560 * hh, o);
    }
    TL(25 + (u == 2));
    if (u) break;
  }
  fence_async();
  bar_sync(NB_ROW0 + w, 128);
  if (lane == 0) {
    tma_store3(&p.to, ch0, 8 * rank, 8 * w + 2 * wg, sb + OFF_TQ + w * 5120 + wg * 1280);
    asm volatile("cp.async.bulk.commit_group;" ::: "memory");
    asm volatile("cp.async.bulk.wait_group.read 0;" ::: "memory");
  }
  TL(27);
  TL_DUMP();
}

typedef CUresult (*EncodeFn)(CUtensorMap*, CUtensorMapDataType, cuuint32_t, void*, const cuuint64_t*, const cuuint64_t*,
                             const cuuint32_t*, const cuuint32_t*, CUtensorMapInterleave, CUtensorMapSwizzle,
                             CUtensorMapL2promotion, CUtensorMapFloatOOBfill);

void encode(EncodeFn fn, CUtensorMap* tm, const void* ptr, int nd, const cuuint64_t* dims, const cuuint64_t* strides,
            const cuuint32_t* box, CUtensorMapSwizzle swz) {
  cuuint32_t es[4] = {1, 1, 1, 1};
  fn(tm, CU_TENSOR_MAP_DATA_TYPE_BFLOAT16, nd, const_cast<void*>(ptr), dims, strides, box, es, CU_TENSOR_MAP_INTERLEAVE_NONE,
     swz, CU_TENSOR_MAP_L2_PROMOTION_L2_128B, CU_TENSOR_MAP_FLOAT_OOB_FILL_NONE);
}
void map1(EncodeFn fn, CUtensorMap* tm, const void* ptr, int nhi) {
  const cuuint64_t dims[4] = {DCH, 4, 8, SEQ / 32}, strides[3] = {8 * DCH * 2, DCH * 2, 32 * DCH * 2};
  const cuuint32_t box[4] = {CPC, 4, 8, (cuuint32_t)nhi};
  encode(fn, tm, ptr, 4, dims, strides, box, CU_TENSOR_MAP_SWIZZLE_NONE);
}
void map2(EncodeFn fn, CUtensorMap* tm, const void* ptr, int nr) {
  const cuuint64_t dims[3] = {DCH, SEQ / 32, 32}, strides[2] = {32 * DCH * 2, DCH * 2};
  const cuuint32_t box[3] = {CPC, 8, (cuuint32_t)nr};
  encode(fn, tm, ptr, 3, dims, strides, box, CU_TENSOR_MAP_SWIZZLE_NONE);
}

}

extern "C" void kernel_launch(void* const* d_in, const int* in_sizes, int n_in, void* d_out, int out_size) {
  (void)in_sizes; (void)n_in; (void)out_size;
  static EncodeFn fn = nullptr;
  static void *tab = nullptr, *cnt = nullptr, *part = nullptr;
  if (!fn) {
    cudaGetSymbolAddress(&tab, d_tab);
    cudaGetSymbolAddress(&cnt, g_cnt);
    cudaGetSymbolAddress(&part, g_part);
    cudaDriverEntryPointQueryResult qr;
    cudaGetDriverEntryPoint("cuTensorMapEncodeTiled", (void**)&fn, cudaEnableDefault, &qr);
    cudaFuncSetAttribute(fused_kernel, cudaFuncAttributeMaxDynamicSharedMemorySize, SMEM_BYTES);
  }
  Params p;
  map1(fn, &p.tq, d_in[0], 4);
  map1(fn, &p.tk, d_in[1], 9);
  map1(fn, &p.tv, d_in[2], 8);
  map2(fn, &p.tq2, d_in[0], 32);
  map2(fn, &p.to, d_out, 2);
  {
    const cuuint64_t dims[4] = {32, SEQ / 32, DCH / 8, 8}, strides[3] = {64, 8 * SEQ * 2, SEQ * 2};
    const cuuint32_t box[4] = {32, 64, 5, 1};
    encode(fn, &p.th, d_in[4], 4, dims, strides, box, CU_TENSOR_MAP_SWIZZLE_64B);
  }
  p.tab = (const Tables*)tab;
  p.cnt = (unsigned*)cnt;
  p.part = (uint2*)part;
  p.tl = nullptr;
  p.q = (const __nv_bfloat16*)d_in[0];
  p.shift_k = (const __nv_bfloat16*)d_in[3];
  p.ssm_D = (const __nv_bfloat16*)d_in[5];
  p.logA = (const __nv_bfloat16*)d_in[7];
  p.Aim = (const __nv_bfloat16*)d_in[8];
  p.Cre = (const __nv_bfloat16*)d_in[9];
  p.Cim = (const __nv_bfloat16*)d_in[10];
  p.logdt = (const __nv_bfloat16*)d_in[11];
  p.Dskip = (const __nv_bfloat16*)d_in[12];
  p.gate_w = (const __nv_bfloat16*)d_in[13];
  fused_kernel<<<NCL * CS, NTHREADS, SMEM_BYTES, cudaStreamPerThread>>>(p);
}
```

```cpp
#include <cuda_runtime.h>
#include <cuda_bf16.h>
#include <cuda.h>
#include <stdint.h>

#define TIMELINE 0

namespace {

constexpr int SEQ = 2048, DCH = 576, NMODE = 128;
constexpr int CS = 8, CPC = 40, NCL = 15, NTHREADS = 512;

constexpr int YPITCH = 528;
constexpr int KTAB = 28672;
constexpr int OFF_T = 0;
constexpr int OFF_UKV = 2 * KTAB + 8192;
constexpr int OFF_UX = 3 * KTAB;
constexpr int OFF_HA = OFF_UX + 20480;
constexpr int OFF_CF = OFF_HA + 20480;
constexpr int OFF_CL = OFF_CF + 8192;
constexpr int OFF_TQ = OFF_CL + 4096;
constexpr int OFF_TK = OFF_TQ + 20480;
constexpr int OFF_YA = OFF_TK;
constexpr int OFF_TV = OFF_TK + 23040;
constexpr int OFF_YB = OFF_TV + 20480;
constexpr int OFF_KC = OFF_YB + 40 * YPITCH;
constexpr int OFF_SW = OFF_KC + 3 * 1408;
constexpr int OFF_GW = OFF_SW + 320;
constexpr int OFF_SD = OFF_GW + 80;
constexpr int OFF_MB = OFF_SD + 32;
constexpr int OFF_TL = OFF_MB + 24 * 8;
constexpr int SMEM_BYTES = OFF_TL + (TIMELINE ? 2048 : 0);
static_assert(SMEM_BYTES <= 232448, "smem");
static_assert((KTAB & 1023) == 0 && (OFF_TQ & 127) == 0 && (OFF_TK & 127) == 0 && (OFF_TV & 127) == 0 && (OFF_MB & 7) == 0 && (OFF_KC & 15) == 0, "align");

enum { MB_UX = 0, MB_UKV = 5, MB_Y = 10, MB_Q2 = 15, MB_XQ = 16, MB_KV = 18, MB_HA = 19, MB_CF = 20, MB_COUNT = 21 };
enum { NB_WG0 = 1, NB_ROW0 = 5 };

constexpr double cos_turn(int m, int n) {
  m &= n - 1;
  if (m > n / 2) m = n - m;
  double sgn = 1.0;
  if (m > n / 4) { m = n / 2 - m; sgn = -1.0; }
  if (m == n / 4) return 0.0;
  const double x = 6.283185307179586476925 * m / n;
  double term = 1.0, sum = 1.0;
  for (int k = 1; k < 14; k++) { term *= -x * x / ((2 * k - 1) * (2 * k)); sum += term; }
  return sgn * sum;
}
constexpr uint32_t bf16_bits(double v) {
  if (v == 0.0) return 0;
  uint32_t sgn = 0;
  if (v < 0) { sgn = 0x8000; v = -v; }
  int e = 127;
  while (v < 1.0) { v *= 2.0; e--; }
  while (v >= 2.0) { v *= 0.5; e++; }
  const double f = v * 128.0;
  int m = (int)f;
  if (f - m > 0.5 || (f - m == 0.5 && (m & 1))) m++;
  return sgn | (uint32_t)((e << 7) + (m - 128));
}
constexpr uint32_t pair_bits(double lo, double hi) { return bf16_bits(lo) | (bf16_bits(hi) << 16); }
struct alignas(128) Tables {
  uint32_t mat[3072];
  uint32_t thr[4][128][4];
};
constexpr Tables make_tables() {
  Tables T{};
  for (int q = 0; q < 768; q++) {
    int m0 = 0, d0 = 0, d1 = 0;
    if (q < 512) {
      const int r = (q >> 6) * 8 + (q & 7), cc = (q >> 3) & 7;
      d0 = 4 * (r & 31); d1 = 2 * d0;
      m0 = 8 * (cc & 3) * d0 + ((r >> 5) == (cc >> 2) ? 0 : (r >> 5) ? 96 : 32);
    } else {
      const int r = ((q - 512) >> 5) * 8 + (q & 7), pc = (q >> 3) & 3;
      d0 = 4 * (8 * (r >> 4) + (r & 7)) + 1; d1 = 8 * d0;
      m0 = 2 * pc * d0 + ((r & 8) ? 32 : 0);
    }
    for (int e = 0; e < 4; e++) T.mat[4 * q + e] = pair_bits(cos_turn(m0 + e * d1, 128), cos_turn(m0 + e * d1 + d0, 128));
  }
  for (int tid = 0; tid < 128; tid++) {
    const int kk = 4 * (tid >> 2) + 1, t = tid & 3;
    for (int q = 0; q < 4; q++) {
      const int m = (8 * q + 2 * t) * kk;
      T.thr[q >> 1][tid][2 * (q & 1)] = pair_bits(cos_turn(m, 128), cos_turn(m + kk, 128));
      T.thr[q >> 1][tid][2 * (q & 1) + 1] = pair_bits(cos_turn(m + 32, 128), cos_turn(m + kk + 32, 128));
      T.thr[2][tid][q] = pair_bits(cos_turn(m, 4096), cos_turn(m + kk, 4096));
      T.thr[3][tid][q] = pair_bits(cos_turn(m + 3072, 4096), cos_turn(m + kk + 3072, 4096));
    }
  }
  return T;
}
__device__ const Tables d_tab = make_tables();

struct Params {
  const __nv_bfloat16 *logA, *Aim, *Cre, *Cim, *logdt;
  const Tables* tab;
  unsigned* cnt;
  const __nv_bfloat16 *Dskip, *shift_k, *ssm_D, *gate_w, *q;
  uint2* part;
  __nv_bfloat16* out;
  unsigned* tl;
  CUtensorMap tq, tk, tv, th, tq2;
};

__device__ uint2 g_part[NCL * SEQ];
__device__ unsigned g_cnt[CS * 32];
#define TL(i) do {} while (0)
#define TL_INIT() do {} while (0)
#define TL_DUMP() do {} while (0)

__device__ __forceinline__ uint32_t lds16(uint32_t a) { uint32_t v; asm volatile("ld.shared.u16 %0, [%1];" : "=r"(v) : "r"(a) : "memory"); return v; }
__device__ __forceinline__ uint2 lds64(uint32_t a) { uint2 v; asm volatile("ld.shared.v2.u32 {%0,%1}, [%2];" : "=r"(v.x), "=r"(v.y) : "r"(a) : "memory"); return v; }
__device__ __forceinline__ uint4 lds128(uint32_t a) { uint4 v; asm volatile("ld.shared.v4.u32 {%0,%1,%2,%3}, [%4];" : "=r"(v.x), "=r"(v.y), "=r"(v.z), "=r"(v.w) : "r"(a) : "memory"); return v; }
__device__ __forceinline__ void sts16(uint32_t a, uint32_t v) { asm volatile("st.shared.u16 [%0], %1;" :: "r"(a), "r"(v) : "memory"); }
__device__ __forceinline__ void sts32(uint32_t a, uint32_t v) { asm volatile("st.shared.u32 [%0], %1;" :: "r"(a), "r"(v) : "memory"); }
__device__ __forceinline__ void sts64(uint32_t a, uint32_t x, uint32_t y) { asm volatile("st.shared.v2.u32 [%0], {%1,%2};" :: "r"(a), "r"(x), "r"(y) : "memory"); }
__device__ __forceinline__ void sts128(uint32_t a, uint32_t x, uint32_t y, uint32_t z, uint32_t w) { asm volatile("st.shared.v4.u32 [%0], {%1,%2,%3,%4};" :: "r"(a), "r"(x), "r"(y), "r"(z), "r"(w) : "memory"); }
__device__ __forceinline__ void ldsm4t(uint32_t (&r)[4], uint32_t a) { asm volatile("ldmatrix.sync.aligned.m8n8.x4.trans.shared.b16 {%0,%1,%2,%3}, [%4];" : "=r"(r[0]), "=r"(r[1]), "=r"(r[2]), "=r"(r[3]) : "r"(a) : "memory"); }
__device__ __forceinline__ void ldsm2t(uint32_t& r0, uint32_t& r1, uint32_t a) { asm volatile("ldmatrix.sync.aligned.m8n8.x2.trans.shared.b16 {%0,%1}, [%2];" : "=r"(r0), "=r"(r1) : "r"(a) : "memory"); }
__device__ __forceinline__ void ldsm4(uint32_t (&r)[4], uint32_t a) { asm volatile("ldmatrix.sync.aligned.m8n8.x4.shared.b16 {%0,%1,%2,%3}, [%4];" : "=r"(r[0]), "=r"(r[1]), "=r"(r[2]), "=r"(r[3]) : "r"(a) : "memory"); }
__device__ __forceinline__ void stsm4(uint32_t a, const uint32_t (&r)[4]) { asm volatile("stmatrix.sync.aligned.m8n8.x4.shared.b16 [%0], {%1,%2,%3,%4};" :: "r"(a), "r"(r[0]), "r"(r[1]), "r"(r[2]), "r"(r[3]) : "memory"); }
__device__ __forceinline__ uint32_t pack(float lo, float hi) { uint32_t r; asm("cvt.rn.bf16x2.f32 %0, %1, %2;" : "=r"(r) : "f"(hi), "f"(lo)); return r; }
__device__ __forceinline__ float blo(uint32_t v) { return __uint_as_float(v << 16); }
__device__ __forceinline__ float bhi(uint32_t v) { return __uint_as_float(v & 0xffff0000u); }
__device__ __forceinline__ float bf16r(float x) { return blo(pack(x, 0.f)); }
__device__ __forceinline__ uint32_t hmul2(uint32_t a, uint32_t b) { uint32_t r; asm("mul.rn.bf16x2 %0, %1, %2;" : "=r"(r) : "r"(a), "r"(b)); return r; }
__device__ __forceinline__ uint32_t hadd2(uint32_t a, uint32_t b) { uint32_t r; asm("add.rn.bf16x2 %0, %1, %2;" : "=r"(r) : "r"(a), "r"(b)); return r; }
__device__ __forceinline__ uint32_t hfma2(uint32_t a, uint32_t b, uint32_t c) { uint32_t r; asm("fma.rn.bf16x2 %0, %1, %2, %3;" : "=r"(r) : "r"(a), "r"(b), "r"(c)); return r; }
__device__ __forceinline__ uint32_t prmt(uint32_t a, uint32_t b, uint32_t s) { return __byte_perm(a, b, s); }
__device__ __forceinline__ uint32_t ldraw(const __nv_bfloat16* p) { uint32_t v; asm volatile("ld.global.nc.u16 %0, [%1];" : "=r"(v) : "l"(p)); return v; }
__device__ __forceinline__ uint4 ldg128(const void* p) { uint4 v; asm volatile("ld.global.nc.v4.u32 {%0,%1,%2,%3}, [%4];" : "=r"(v.x), "=r"(v.y), "=r"(v.z), "=r"(v.w) : "l"(p)); return v; }
__device__ __forceinline__ void bar_sync(int id, int n) { asm volatile("bar.sync %0, %1;" :: "r"(id), "r"(n) : "memory"); }
__device__ __forceinline__ void bar_arrive(int id, int n) { asm volatile("bar.arrive %0, %1;" :: "r"(id), "r"(n) : "memory"); }
__device__ __forceinline__ void cluster_arrive() { asm volatile("barrier.cluster.arrive.relaxed.aligned;" ::: "memory"); }
__device__ __forceinline__ void cluster_wait() { asm volatile("barrier.cluster.wait.aligned;" ::: "memory"); }
__device__ __forceinline__ void fence_async() { asm volatile("fence.proxy.async.shared::cta;" ::: "memory"); }
__device__ __forceinline__ void fence_mbinit() { asm volatile("fence.mbarrier_init.release.cluster;" ::: "memory"); }
__device__ __forceinline__ uint32_t mapa(uint32_t a, uint32_t rank) { uint32_t r; asm("mapa.shared::cluster.u32 %0, %1, %2;" : "=r"(r) : "r"(a), "r"(rank)); return r; }
__device__ __forceinline__ void st_async4(uint32_t a, uint32_t x, uint32_t y, uint32_t z, uint32_t w, uint32_t mbar) {
  asm volatile("st.async.weak.shared::cluster.mbarrier::complete_tx::bytes.v4.b32 [%0], {%1,%2,%3,%4}, [%5];"
               :: "r"(a), "r"(x), "r"(y), "r"(z), "r"(w), "r"(mbar) : "memory");
}
__device__ __forceinline__ void mbar_init(uint32_t m, uint32_t cnt) { asm volatile("mbarrier.init.shared::cta.b64 [%0], %1;" :: "r"(m), "r"(cnt) : "memory"); }
__device__ __forceinline__ void mbar_expect(uint32_t m, uint32_t bytes) { asm volatile("mbarrier.arrive.expect_tx.shared::cta.b64 _, [%0], %1;" :: "r"(m), "r"(bytes) : "memory"); }
__device__ __forceinline__ void mbar_wait(uint32_t m) {
  uint32_t done;
  int it = 0;
  do {
    asm volatile("{.reg .pred p; mbarrier.try_wait.parity.shared::cta.b64 p, [%1], 0; selp.u32 %0, 1, 0, p;}" : "=r"(done) : "r"(m) : "memory");
    if (++it > (1 << 22)) __trap();
  } while (!done);
}
__device__ __forceinline__ void tma_load4(uint32_t dst, const CUtensorMap* tm, int c0, int c1, int c2, int c3, uint32_t mbar) {
  asm volatile("cp.async.bulk.tensor.4d.shared::cluster.global.mbarrier::complete_tx::bytes [%0], [%1, {%3, %4, %5, %6}], [%2];"
               :: "r"(dst), "l"(tm), "r"(mbar), "r"(c0), "r"(c1), "r"(c2), "r"(c3) : "memory");
}
__device__ __forceinline__ void tma_load3(uint32_t dst, const CUtensorMap* tm, int c0, int c1, int c2, uint32_t mbar) {
  asm volatile("cp.async.bulk.tensor.3d.shared::cluster.global.mbarrier::complete_tx::bytes [%0], [%1, {%3, %4, %5}], [%2];"
               :: "r"(dst), "l"(tm), "r"(mbar), "r"(c0), "r"(c1), "r"(c2) : "memory");
}
__device__ __forceinline__ void tma_store3(const CUtensorMap* tm, int c0, int c1, int c2, uint32_t src) {
  asm volatile("cp.async.bulk.tensor.3d.global.shared::cta.bulk_group [%0, {%2, %3, %4}], [%1];"
               :: "l"(tm), "r"(src), "r"(c0), "r"(c1), "r"(c2) : "memory");
}
__device__ __forceinline__ void wg_fence() { asm volatile("wgmma.fence.sync.aligned;" ::: "memory"); }
__device__ __forceinline__ void wg_commit() { asm volatile("wgmma.commit_group.sync.aligned;" ::: "memory"); }
template <int N> __device__ __forceinline__ void wg_wait() { asm volatile("wgmma.wait_group.sync.aligned %0;" :: "n"(N) : "memory"); }
template <int N> __device__ __forceinline__ void tie_all(float (&x)[N]) {
#pragma unroll
  for (int i = 0; i < N; i++) asm volatile("" : "+f"(x[i]) :: "memory");
}
#define R16(C, d) C(d[0]), C(d[1]), C(d[2]), C(d[3]), C(d[4]), C(d[5]), C(d[6]), C(d[7]), C(d[8]), C(d[9]), C(d[10]), C(d[11]), C(d[12]), C(d[13]), C(d[14]), C(d[15])
#define R32(C, d) R16(C, d), R16(C, (d + 16))
#define P16 "{%0,%1,%2,%3,%4,%5,%6,%7,%8,%9,%10,%11,%12,%13,%14,%15}"
#define P32 "{%0,%1,%2,%3,%4,%5,%6,%7,%8,%9,%10,%11,%12,%13,%14,%15,%16,%17,%18,%19,%20,%21,%22,%23,%24,%25,%26,%27,%28,%29,%30,%31}"
template <int SD, int TB, int OFF> __device__ __forceinline__ void rs64(float* d, const uint32_t* a, uint64_t db) {
  if (SD) asm volatile("{.reg .b64 db; add.s64 db, %36, %37; wgmma.mma_async.sync.aligned.m64n64k16.f32.bf16.bf16 " P32 ", {%32,%33,%34,%35}, db, 1, 1, 1, %38;}"
                       : R32("+f", d) : "r"(a[0]), "r"(a[1]), "r"(a[2]), "r"(a[3]), "l"(db), "n"(OFF), "n"(TB));
  else asm volatile("{.reg .b64 db; add.s64 db, %36, %37; wgmma.mma_async.sync.aligned.m64n64k16.f32.bf16.bf16 " P32 ", {%32,%33,%34,%35}, db, 0, 1, 1, %38;}"
                    : R32("=f", d) : "r"(a[0]), "r"(a[1]), "r"(a[2]), "r"(a[3]), "l"(db), "n"(OFF), "n"(TB));
}
template <int SD, int OFFA, int OFFB> __device__ __forceinline__ void ss32(float* d, uint64_t da, uint64_t db) {
  if (SD) asm volatile("{.reg .b64 da, db; add.s64 da, %16, %18; add.s64 db, %17, %19; wgmma.mma_async.sync.aligned.m64n32k16.f32.bf16.bf16 " P16 ", da, db, 1, 1, 1, 1, 1;}"
                       : R16("+f", d) : "l"(da), "l"(db), "n"(OFFA), "n"(OFFB));
  else asm volatile("{.reg .b64 da, db; add.s64 da, %16, %18; add.s64 db, %17, %19; wgmma.mma_async.sync.aligned.m64n32k16.f32.bf16.bf16 " P16 ", da, db, 0, 1, 1, 1, 1;}"
                    : R16("=f", d) : "l"(da), "l"(db), "n"(OFFA), "n"(OFFB));
}
template <int KS> __device__ __forceinline__ void kgen_mma(float (&c)[24], uint64_t da) {
  asm volatile("{.reg .b64 da, db; add.s64 da, %24, %25; add.s64 db, %24, %26;\n"
               "wgmma.mma_async.sync.aligned.m64n48k16.f32.bf16.bf16 {%0,%1,%2,%3,%4,%5,%6,%7,%8,%9,%10,%11,%12,%13,%14,%15,%16,%17,%18,%19,%20,%21,%22,%23}, da, db, %27, 1, 1, 1, 1;}"
               : R16("+f", c), "+f"(c[16]), "+f"(c[17]), "+f"(c[18]), "+f"(c[19]), "+f"(c[20]), "+f"(c[21]), "+f"(c[22]), "+f"(c[23])
               : "l"(da), "n"(8 * KS), "n"(8 * KS + 512), "n"(KS ? 1 : 0));
  if constexpr (KS < 7) kgen_mma<KS + 1>(c, da);
}
__device__ __forceinline__ uint64_t desc_lo(uint32_t a) { return (uint64_t)((a & 0x3FFFF) >> 4); }
__device__ __forceinline__ void stage1(float (&D)[32], const uint32_t (&A1)[8], uint32_t src) {
  const uint64_t du = desc_lo(src) | (128ull << 16) | (32ull << 32) | (2ull << 62);
  rs64<0, 1, 0>(D, A1, du); rs64<1, 1, 64>(D, A1 + 4, du);
}
template <int INV> __device__ __forceinline__ void stage2(float (&X)[32], const uint32_t (&F)[16], uint32_t cf) {
  constexpr int KS = INV ? 16 : 128, TB = INV ? 0 : 1;
  const uint64_t dc = desc_lo(cf) | (INV ? (8ull << 16) | (64ull << 32) : (64ull << 16) | (8ull << 32));
  rs64<0, TB, 0>(X, F, dc); rs64<1, TB, KS>(X, F + 4, dc); rs64<1, TB, 2 * KS>(X, F + 8, dc); rs64<1, TB, 3 * KS>(X, F + 12, dc);
}
__device__ __forceinline__ void fwd_mid(uint32_t (&F)[16], const float (&D)[32], const uint32_t (&tp)[12]) {
#pragma unroll
  for (int j = 0; j < 4; j++)
#pragma unroll
    for (int b = 0; b < 2; b++) {
      const int i = 4 * j + 16 * b;
      const uint32_t ar = pack(D[i], D[i + 1]), ai = pack(D[i + 2], D[i + 3]);
      F[2 * j + b] = hfma2(ar, tp[3 * j], hmul2(ai, tp[3 * j + 2]));
      F[8 + 2 * j + b] = hfma2(ar, tp[3 * j + 1], hmul2(ai, tp[3 * j]));
    }
}

struct cf { float x, y; };
__device__ __forceinline__ cf cmul(cf a, cf b) { cf r; r.x = fmaf(a.x, b.x, -a.y * b.y); r.y = fmaf(a.x, b.y, a.y * b.x); return r; }
__device__ __forceinline__ cf cexp_p(float lr2, float lt, float p) {
  float m = exp2f(lr2 * p);
  float t = lt * p;
  t = (t - rintf(t)) * 6.283185307179586f;
  cf r; r.x = m * __cosf(t); r.y = m * __sinf(t); return r;
}
__device__ __forceinline__ void store8(uint32_t a, const cf (&v)[8]) {
  sts128(a, pack(v[0].x, v[1].x), pack(v[2].x, v[3].x), pack(v[4].x, v[5].x), pack(v[6].x, v[7].x));
  sts128(a + KTAB / 2, pack(v[0].y, v[1].y), pack(v[2].y, v[3].y), pack(v[4].y, v[5].y), pack(v[6].y, v[7].y));
}
__device__ __forceinline__ float sigmoidf_(float s) { return 1.f / (1.f + __expf(-s)); }

__global__ void __cluster_dims__(CS, 1, 1) __launch_bounds__(NTHREADS, 1) fused_kernel(const __grid_constant__ Params p) {
  extern __shared__ __align__(1024) uint8_t smem[];
  TL_INIT();
  TL(31);
  const int wid = __shfl_sync(0xffffffffu, threadIdx.x >> 5, 0);
  uint32_t pla[2], pai[2], pcr[2], pci[2], pdt[2];
  if (threadIdx.x < 384) {
#pragma unroll
    for (int r = 0; r < 2; r++) {
      int ch = (blockIdx.x >> 3) * CPC + (blockIdx.x & 7) + 8 * (threadIdx.x >> 7) + 24 * r;
      if (ch >= DCH) ch = 0;
      const int o = ch * NMODE + (threadIdx.x & 127);
      pla[r] = ldraw(p.logA + o); pdt[r] = ldraw(p.logdt + ch); pai[r] = ldraw(p.Aim + o); pcr[r] = ldraw(p.Cre + o); pci[r] = ldraw(p.Cim + o);
    }
  }
  const uint32_t sb = (uint32_t)__cvta_generic_to_shared(smem);
  const uint32_t mb = sb + OFF_MB;
  const int wg = wid >> 2, w = wid & 3;
  const int tid = threadIdx.x & 127, lane = tid & 31, g = lane >> 2, t = lane & 3;
  const int cl = blockIdx.x >> 3, rank = blockIdx.x & 7;
  const int ch0 = cl * CPC;
  const int nu = min(5, (DCH - ch0) >> 3);

  if (wg < 3) {
    cluster_arrive();
    uint32_t A1[8], tp[12];
    {
      const uint4 a = ldg128(p.tab->thr[0][tid]), b = ldg128(p.tab->thr[1][tid]), c = ldg128(p.tab->thr[2][tid]), d = ldg128(p.tab->thr[3][tid]);
      A1[0] = a.x; A1[1] = a.y; A1[2] = a.z; A1[3] = a.w; A1[4] = b.x; A1[5] = b.y; A1[6] = b.z; A1[7] = b.w;
      tp[0] = c.x; tp[3] = c.y; tp[6] = c.z; tp[9] = c.w; tp[2] = d.x; tp[5] = d.y; tp[8] = d.z; tp[11] = d.w;
      tp[1] = tp[4] = tp[7] = tp[10] = 0;
    }
    TL(0);
    const uint32_t tab = sb + OFF_T + wg * KTAB;
#pragma unroll 1
    for (int job = 0; job < 4; job++) {
      const bool isA = job >= (wg == 2 ? 1 : 2);
      const int u = wg == 2 ? (job ? 2 * job - 2 : 2) : job < 2 ? wg + 3 * job : job == 2 ? 2 * wg + 1 : 9;

      if (!isA && u < nu) {
        const float la = blo(job ? pla[1] : pla[0]), ai = blo(job ? pai[1] : pai[0]), cr = blo(job ? pcr[1] : pcr[0]), ci = blo(job ? pci[1] : pci[0]);
        const float dt = bf16r(expf(blo(job ? pdt[1] : pdt[0])));
        const float lr2 = (-bf16r(expf(la)) * dt) * 1.4426950408889634f;
        const float lt = (ai * dt) * 0.15915494309189535f;
        const uint32_t row = tab + tid * 16;
        if (lr2 != 123.f) TL(16 + 4 * job);
        if (job) bar_sync(NB_WG0 + wg, 128);
        {
          const cf w1 = cexp_p(lr2, lt, 8.f);
          cf v[8];
          v[0].x = 1.f; v[0].y = 0.f; v[1] = w1; v[2] = cmul(w1, w1); v[3] = cmul(v[2], w1);
          const cf w4 = cmul(v[2], v[2]);
          v[4] = w4; v[5] = cmul(v[1], w4); v[6] = cmul(v[2], w4); v[7] = cmul(v[3], w4);
          const cf w8 = cmul(w4, w4);
          store8(row, v);
#pragma unroll
          for (int c = 1; c < 4; c++) {
#pragma unroll
            for (int i = 0; i < 8; i++) v[i] = (c == 1 && i == 0) ? w8 : cmul(v[i], w8);
            store8(row + 2048 * c, v);
          }
        }
        {
          cf z1 = cexp_p(lr2, lt, 1.f), Z = cexp_p(lr2, lt, 256.f);
          z1.y = -z1.y; Z.y = -Z.y;
          const cf z2 = cmul(z1, z1);
          cf h[8], v[8];
          h[0].x = 2.f * cr * dt; h[0].y = -2.f * ci * dt;
          h[1] = cmul(h[0], z1);
#pragma unroll
          for (int i = 2; i < 8; i++) h[i] = cmul(h[i - 2], z2);
          store8(row + 4 * 2048, h);
          v[0] = cmul(h[0], Z); v[1] = cmul(h[2], Z); v[2] = cmul(h[4], Z); v[3] = cmul(h[6], Z);
          v[4] = cmul(v[0], Z); v[5] = cmul(v[2], Z); v[6] = cmul(v[4], Z); v[7] = cmul(v[5], Z);
          store8(row + 5 * 2048, v);
          const cf Z2 = cmul(Z, Z);
          h[0] = cmul(v[4], Z2); h[1] = cmul(v[6], Z2); h[2] = cmul(h[0], Z2); h[3] = cmul(h[1], Z2); h[4] = cmul(h[2], Z2);
          h[5].x = h[5].y = h[6].x = h[6].y = h[7].x = h[7].y = 0.f;
          store8(row + 6 * 2048, h);
        }
        TL(17 + 4 * job);
        fence_async();
        bar_sync(NB_WG0 + wg, 128);
        float c[24];
        wg_fence();
        kgen_mma<0>(c, desc_lo(tab) | ((uint64_t)(KTAB / 32) << 16) | (64ull << 32));
        wg_commit();
        uint32_t kid[8];
        {
          float lf = __uint_as_float(0x4b000000u | (8 * tid)) - 8388608.f;
          asm volatile("" : "+f"(lf));
          const float lo = tid < 16 ? lf + 128.f : lf;
          const uint32_t sub = tid < 16 ? 0x42804300u : 0x42804280u;
#pragma unroll
          for (int i = 0; i < 8; i++) kid[i] = 2 * (pack(lo + i, lf + (1024 + i)) - sub);
        }
        wg_wait<0>(); tie_all(c);
        const uint32_t kc = sb + OFF_KC + wg * 1408;
        {
          const int a = 8 * w + g;
          sts32(kc + 4 * (4 * a + t), pack(c[0] + c[6], c[1] + c[7]));
          sts32(kc + 4 * (t < 2 ? 128 + 2 * a + t : 128 + 32 * t + a), pack(c[8] + c[14], c[9] + c[15]));
          if (t < 3) {
            const uint32_t p0 = pack(c[16] + c[22], c[17] + c[23]);
            sts16(kc + 2 * (512 + 64 * t + a), p0);
            sts16(kc + 2 * (544 + 64 * t + a), p0 >> 16);
          }
        }
        TL(18 + 4 * job);
        bar_sync(NB_WG0 + wg, 128);
        uint32_t v[2][8];
#pragma unroll
        for (int i = 0; i < 8; i++) { v[0][i] = lds16(kc + (kid[i] & 0xffffu)); v[1][i] = lds16(kc + (kid[i] >> 16)); }
#pragma unroll
        for (int cc = 0; cc < 2; cc++)
          sts128(tab + 2048 * cc + 16 * (tid ^ ((tid >> 3) & 3)), prmt(v[cc][0], v[cc][1], 0x5410), prmt(v[cc][2], v[cc][3], 0x5410),
                 prmt(v[cc][4], v[cc][5], 0x5410), prmt(v[cc][6], v[cc][7], 0x5410));
        fence_async();
        if (job) bar_sync(NB_WG0 + wg, 128);
      }
      if (job == 0) {
        cluster_wait();
        cluster_arrive();
        bar_sync(NB_WG0 + wg, 128);
        mbar_wait(mb + 8 * MB_CF);
#pragma unroll
        for (int j = 0; j < 4; j++) asm volatile("xor.b32 %0, %1, 0x80008000;" : "=r"(tp[3 * j + 1]) : "r"(tp[3 * j + 2]));
      }
      if (u >= nu) continue;
      TL(1 + job);
      float D[32], H[32], X[32];
      uint32_t F[16];
      if (isA) mbar_wait(mb + 8 * MB_HA);
      wg_fence();
      stage1(D, A1, isA ? sb + OFF_HA + u * 4096 : tab);
      wg_commit();
      wg_wait<0>(); tie_all(D);
      fwd_mid(F, D, tp);
      wg_fence();
      stage2<0>(H, F, sb + OFF_CF);
      wg_commit();
      mbar_wait(mb + 8 * ((isA ? MB_UKV : MB_UX) + u));
      fence_async();
      TL(5 + job);
      wg_fence();
      stage1(D, A1, sb + (isA ? OFF_UKV : OFF_UX) + u * 4096);
      wg_commit();
      wg_wait<0>(); tie_all(D); tie_all(H);
      fwd_mid(F, D, tp);
      wg_fence();
      stage2<0>(X, F, sb + OFF_CF);
      wg_commit();
      {
        const float dsk = blo(lds16(sb + OFF_SD + (isA ? 10 : 0) + 2 * u));
#pragma unroll
        for (int j = 0; j < 4; j++) { H[4 * j] += dsk; H[4 * j + 1] += dsk; }
      }
      wg_wait<0>(); tie_all(X);
#pragma unroll
      for (int j = 0; j < 4; j++) {
        float pr[2], pi[2], qr[2], qi[2];
#pragma unroll
        for (int n = 0; n < 2; n++) {
          const int i = 4 * j + n;
          pr[n] = fmaf(X[i], H[i], -X[i + 16] * H[i + 16]);
          pi[n] = fmaf(X[i], H[i + 16], X[i + 16] * H[i]);
          qr[n] = fmaf(X[i + 2], H[i], fmaf(-X[i + 18], H[i + 16], fmaf(X[i], H[i + 2], fmaf(-X[i + 16], H[i + 18], -pi[n]))));
          qi[n] = fmaf(X[i + 2], H[i + 16], fmaf(X[i + 18], H[i], fmaf(X[i], H[i + 18], fmaf(X[i + 16], H[i + 2], pr[n]))));
        }
        F[2 * j] = pack(pr[0], pr[1]); F[2 * j + 1] = pack(qr[0], qr[1]); F[8 + 2 * j] = pack(pi[0], pi[1]); F[9 + 2 * j] = pack(qi[0], qi[1]);
      }
      wg_fence();
      stage2<1>(H, F, sb + OFF_CF);
      wg_commit();
      wg_wait<0>(); tie_all(H);
      {
        const uint32_t va = tab + (16 * w + (lane & 15)) * 128;
        const int vx = (lane >> 4) ^ (lane & 7);
#pragma unroll
        for (int j = 0; j < 4; j++) {
          uint32_t V[4];
#pragma unroll
          for (int b = 0; b < 2; b++) {
            const int i = 4 * j + 2 * b;
            const uint32_t er = pack(H[i], H[i + 1]), ei = pack(H[i + 16], H[i + 17]);
            V[2 * b] = hfma2(er, tp[3 * j], hmul2(ei, tp[3 * j + 1]));
            V[2 * b + 1] = hfma2(ei, tp[3 * j], hmul2(er, tp[3 * j + 2]));
          }
          stsm4(va + ((vx ^ (2 * j)) << 4), V);
        }
      }
      fence_async();
      bar_sync(NB_WG0 + wg, 128);
      float O[16];
      {
        const uint64_t dv = desc_lo(tab) | (1ull << 16) | (64ull << 32) | (1ull << 62);
        const uint64_t dl = desc_lo(sb + OFF_CL) | (32ull << 16) | (8ull << 32);
        wg_fence();
        ss32<0, 0, 0>(O, dv, dl); ss32<1, 128, 64>(O, dv, dl); ss32<1, 256, 128>(O, dv, dl); ss32<1, 384, 192>(O, dv, dl);
        wg_commit();
      }
      if (isA && job < 3) {
        for (int k = 0; k < nu; k++) mbar_wait(mb + 8 * (MB_UKV + k));
      }
      wg_wait<0>(); tie_all(O);
      {
        const uint32_t yo = (isA ? OFF_YA : OFF_YB) + (8 * u + rank) * YPITCH + (8 * w + g) * 16, ym = OFF_MB + 8 * (MB_Y + u);
        const uint32_t r0 = mapa(sb, t), r1 = mapa(sb, t + 4);
        st_async4(r0 + yo, pack(O[0], O[1]), pack(O[4], O[5]), pack(O[8], O[9]), pack(O[12], O[13]), r0 + ym);
        st_async4(r1 + yo, pack(O[2], O[3]), pack(O[6], O[7]), pack(O[10], O[11]), pack(O[14], O[15]), r1 + ym);
      }
      TL(9 + job);
    }
  } else {
    if (lane == 0) {
#pragma unroll
      for (int i = 0; i < 4; i++) mbar_init(mb + 8 * (4 * w + i), 4 * w + i == MB_Q2 ? 5 : 1);
      mbar_init(mb + 8 * (MB_XQ + w), 1);
      if (w == 3) mbar_init(mb + 8 * MB_CF, 2);
      fence_mbinit();
      if (w == 3) {
        mbar_expect(mb + 8 * MB_CF, 12288);
        asm volatile("cp.async.bulk.shared::cluster.global.mbarrier::complete_tx::bytes [%0], [%1], %2, [%3];"
                     :: "r"(sb + OFF_CF), "l"(p.tab->mat), "r"(12288), "r"(mb + 8 * MB_CF) : "memory");
      }
#pragma unroll
      for (int i = 0; i < 4; i++) { const int b = 4 * w + i; mbar_expect(mb + 8 * b, b == MB_Q2 ? 20480 : b >= MB_Y ? 8192 : 4096); }
      mbar_expect(mb + 8 * (MB_XQ + w), w < 2 ? 10240 : w == 2 ? 23040 + 20480 : 20480);
    }
    __syncwarp();
    cluster_arrive();
    uint32_t tag = 0;
    if (w == 0) {
      if (lane == 1) asm volatile("atom.relaxed.gpu.global.add.u32 %0, [%1], %2;" : "=r"(tag) : "l"(&p.cnt[rank * 32 + lane]), "r"(cl == 0 ? 16 - (NCL - 1) : 1) : "memory");
      if (lane == 0) { tma_load4(sb + OFF_TQ, &p.tq, ch0, 0, 0, 8 * rank, mb + 8 * MB_XQ); TL(20); }
    } else if (w == 1) {
      uint32_t d = 0;
      const int u = lane < 5 ? lane : lane - 5;
      if (lane < 10 && u < nu) d = ldraw((lane < 5 ? p.Dskip : p.ssm_D) + ch0 + 8 * u + rank);
      if (lane == 0) tma_load4(sb + OFF_TQ + 10240, &p.tq, ch0, 0, 0, 8 * rank + 4, mb + 8 * (MB_XQ + 1));
      if (lane < 10) sts16(sb + OFF_SD + 2 * lane, d);
      __syncwarp();
      if (lane == 0) asm volatile("mbarrier.arrive.shared::cta.b64 _, [%0];" :: "r"(mb + 8 * MB_CF) : "memory");
    } else {
      uint2 swv = make_uint2(0, 0);
      uint32_t gwv = 0;
      const int c = tid - 64;
      if (c < 40 && ch0 + c < DCH) { swv = __ldg((const uint2*)(p.shift_k + (size_t)(ch0 + c) * 4)); gwv = ldraw(p.gate_w + ch0 + c); }
      if (c < 40) { sts64(sb + OFF_SW + 8 * c, swv.x, swv.y); sts16(sb + OFF_GW + 2 * c, gwv); }
      if (c == 0) {
        tma_load4(sb + OFF_TK, &p.tk, ch0, 0, 0, 8 * rank - 1, mb + 8 * MB_KV);
        tma_load4(sb + OFF_TV, &p.tv, ch0, 0, 0, 8 * rank, mb + 8 * MB_KV);
        TL(20);
      }
    }
    __syncwarp();
    TL(0);
    const uint32_t rbase = mapa(sb, g);
    const int mi = lane >> 3, tq = (lane & 7) >> 1, jj = lane & 1;
    const uint32_t toff = (4 * (2 * mi + jj) + tq) * 80;
    const uint32_t uoff = 16 * (32 * rank + 4 * w + (t ^ (w >> 1)));
    cluster_wait();
    cluster_arrive();
    if (tid == 64) tma_load4(sb + OFF_HA, &p.th, 0, 0, 5 * cl, rank, mb + 8 * MB_HA);
    __syncwarp();
    mbar_wait(mb + 8 * MB_XQ);
    mbar_wait(mb + 8 * (MB_XQ + 1));
    TL(1);
    {
      uint32_t xr[5][2][4];
#pragma unroll
      for (int u = 0; u < 5; u++) { ldsm4t(xr[u][0], sb + OFF_TQ + w * 2560 + toff + 16 * u); ldsm4t(xr[u][1], sb + OFF_TQ + (w + 4) * 2560 + toff + 16 * u); }
#pragma unroll
      for (int u = 0; u < 5; u++)
        if (u < nu) {
          st_async4(rbase + OFF_UX + u * 4096 + uoff, xr[u][0][0], xr[u][0][1], xr[u][0][2], xr[u][0][3], rbase + OFF_MB + 8 * (MB_UX + u));
          st_async4(rbase + OFF_UX + u * 4096 + (uoff ^ 32) + 256, xr[u][1][0], xr[u][1][1], xr[u][1][2], xr[u][1][3], rbase + OFF_MB + 8 * (MB_UX + u));
        }
    }
    TL(2);
    if (tid == 1) sts32(sb + OFF_MB + 8 * MB_COUNT, tag);
    bar_sync(NB_WG0 + 3, 128);
    tag = (lds64(sb + OFF_MB + 8 * MB_COUNT).x >> 4) + 1;
    {
      float s0 = 0.f, s1 = 0.f;
#pragma unroll
      for (int j = 0; j < 5; j++) {
        const uint4 gw = lds128(sb + OFF_GW + 16 * j);
        const uint4 x0 = lds128(sb + OFF_TQ + tid * 80 + 16 * j), x1 = lds128(sb + OFF_TQ + (tid + 128) * 80 + 16 * j);
        uint32_t m0 = hmul2(x0.x, gw.x), m1 = hmul2(x0.y, gw.y), m2 = hmul2(x0.z, gw.z), m3 = hmul2(x0.w, gw.w);
        s0 += ((blo(m0) + bhi(m0)) + (blo(m1) + bhi(m1))) + ((blo(m2) + bhi(m2)) + (blo(m3) + bhi(m3)));
        m0 = hmul2(x1.x, gw.x); m1 = hmul2(x1.y, gw.y); m2 = hmul2(x1.z, gw.z); m3 = hmul2(x1.w, gw.w);
        s1 += ((blo(m0) + bhi(m0)) + (blo(m1) + bhi(m1))) + ((blo(m2) + bhi(m2)) + (blo(m3) + bhi(m3)));
      }
      const int s2 = 8 * (8 * (lane & 3) + (lane >> 2)) + w;
      asm volatile("st.relaxed.gpu.global.u64 [%0], %1;" :: "l"(&p.part[cl * SEQ + rank * 256 + s2]), "l"(((uint64_t)tag << 32) | __float_as_uint(s0)) : "memory");
      asm volatile("st.relaxed.gpu.global.u64 [%0], %1;" :: "l"(&p.part[cl * SEQ + rank * 256 + s2 + 4]), "l"(((uint64_t)tag << 32) | __float_as_uint(s1)) : "memory");
    }
    bar_sync(NB_WG0 + 3, 128);
    if (tid == 0) tma_load3(sb + OFF_TQ, &p.tq2, ch0, 8 * rank, 0, mb + 8 * MB_Q2);
    __syncwarp();
    TL(3);
    cluster_wait();
    mbar_wait(mb + 8 * MB_KV);
    TL(4);
    const uint32_t hoff = (4 * (4 + 2 * (mi & 1) + jj) + ((tq + 3) & 3)) * 80 + (tq ? 2560 : 0);
    uint32_t En[2][6], Vn[2][4];
    uint2 swn;
    auto kv_load = [&](int u) {
      swn = lds64(sb + OFF_SW + 8 * (8 * u + g));
#pragma unroll
      for (int hf = 0; hf < 2; hf++) {
        const int ah = 4 * hf + w;
        uint32_t K[4];
        ldsm4t(K, sb + OFF_TK + (ah + 1) * 2560 + toff + 16 * u);
        ldsm2t(En[hf][0], En[hf][1], sb + OFF_TK + ah * 2560 + hoff + 16 * u);
        ldsm4t(Vn[hf], sb + OFF_TV + ah * 2560 + toff + 16 * u);
        En[hf][2] = K[0]; En[hf][3] = K[1]; En[hf][4] = K[2]; En[hf][5] = K[3];
      }
    };
    kv_load(0);
#pragma unroll 1
    for (int u = 0; u < nu; u++) {
      uint32_t E[2][6], V[2][4];
#pragma unroll
      for (int hf = 0; hf < 2; hf++) {
#pragma unroll
        for (int i = 0; i < 6; i++) E[hf][i] = En[hf][i];
#pragma unroll
        for (int i = 0; i < 4; i++) V[hf][i] = Vn[hf][i];
      }
      const uint32_t w0 = prmt(swn.x, 0, 0x1010), w1 = prmt(swn.x, 0, 0x3232), w2 = prmt(swn.y, 0, 0x1010), w3 = prmt(swn.y, 0, 0x3232);
      if (u + 1 < nu) kv_load(u + 1);
#pragma unroll
      for (int hf = 0; hf < 2; hf++) {
        uint32_t O[5], o[4];
#pragma unroll
        for (int i = 0; i < 5; i++) O[i] = prmt(E[hf][i], E[hf][i + 1], 0x5432);
#pragma unroll
        for (int i = 0; i < 4; i++) {
          uint32_t s = hmul2(O[i], w3);
          s = hadd2(s, hmul2(E[hf][i + 1], w2));
          s = hadd2(s, hmul2(O[i + 1], w1));
          s = hadd2(s, hmul2(E[hf][i + 2], w0));
          o[i] = hmul2(s, V[hf][i]);
        }
        st_async4(rbase + OFF_UKV + u * 4096 + (hf ? (uoff ^ 32) + 256 : uoff), o[0], o[1], o[2], o[3], rbase + OFF_MB + 8 * (MB_UKV + u));
      }
    }
    TL(5);
    bar_sync(NB_WG0 + 3, 128);
    {
      float s[2] = {0.f, 0.f};
      bool ok = false;
#pragma unroll 1
      for (int it = 0; it < 4000 && !ok; it++) {
        ok = true; s[0] = s[1] = 0.f;
#pragma unroll
        for (int c = 0; c < NCL; c++) {
          uint64_t a, b;
          asm volatile("ld.relaxed.gpu.global.v2.u64 {%0,%1}, [%2];" : "=l"(a), "=l"(b) : "l"(&p.part[c * SEQ + rank * 256 + 2 * tid]) : "memory");
          ok = ok && (uint32_t)(a >> 32) == tag && (uint32_t)(b >> 32) == tag;
          s[0] += __uint_as_float((uint32_t)a); s[1] += __uint_as_float((uint32_t)b);
        }
      }
      if (ok) {
      } else {
#pragma unroll 1
        for (int hf = 0; hf < 2; hf++) {
          const int slot = 2 * tid + hf;
          const int row = rank * 256 + 32 * (slot & 7) + (slot >> 3);
          const uint32_t* xr = (const uint32_t*)(p.q + (size_t)row * DCH);
          const uint32_t* gr = (const uint32_t*)p.gate_w;
          float a = 0.f;
#pragma unroll 1
          for (int c = 0; c < DCH / 2; c++) { const uint32_t m = hmul2(__ldg(xr + c), __ldg(gr + c)); a += blo(m) + bhi(m); }
          if (hf) s[1] = a; else s[0] = a;
        }
      }
      const float g0 = bf16r(sigmoidf_(bf16r(s[0]))), g1 = bf16r(sigmoidf_(bf16r(s[1])));
      const float a0 = g0 * 0.0009765625f, b0 = bf16r(1.f - g0) * 0.0009765625f, a1 = g1 * 0.0009765625f, b1 = bf16r(1.f - g1) * 0.0009765625f;
      sts128(sb + OFF_TV + 16 * tid, pack(a0, a0), pack(b0, b0), pack(a1, a1), pack(b1, b1));
    }
    __syncwarp();
    if (lane == 0) asm volatile("mbarrier.arrive.shared::cta.b64 _, [%0];" :: "r"(mb + 8 * MB_Q2) : "memory");
  }
  mbar_wait(mb + 8 * MB_Q2);
  uint2 gg[2][4];
#pragma unroll
  for (int hh = 0; hh < 2; hh++)
#pragma unroll
    for (int i = 0; i < 4; i++) gg[hh][i] = lds64(sb + OFF_TV + 8 * (64 * w + 32 * hh + 8 * i + g));
  TL(24);
#pragma unroll 1
  for (int u = wg == 3 ? 0 : wg == 2 ? 4 : 2 * wg + 1; u < nu; u += 2) {
    uint32_t qv[2][4];
    const uint32_t qa = sb + OFF_TQ + (64 * w + lane) * 80 + 16 * u;
    ldsm4(qv[0], qa);
    ldsm4(qv[1], qa + 2560);
    mbar_wait(mb + 8 * (MB_Y + u));
    uint32_t ya[2][4], yb[2][4];
    const uint32_t yo = (8 * u + (lane & 7)) * YPITCH + (8 * w + (lane >> 3)) * 16;
#pragma unroll
    for (int hh = 0; hh < 2; hh++) { ldsm4t(ya[hh], sb + OFF_YA + yo + 64 * hh); ldsm4t(yb[hh], sb + OFF_YB + yo + 64 * hh); }
#pragma unroll
    for (int hh = 0; hh < 2; hh++) {
      uint32_t o[4];
#pragma unroll
      for (int i = 0; i < 4; i++) o[i] = hadd2(hmul2(gg[hh][i].x, hmul2(qv[hh][i], ya[hh][i])), hmul2(gg[hh][i].y, yb[hh][i]));
      stsm4(qa + 2560 * hh, o);
    }
    TL(25 + (u == 2));
    if (u) break;
  }
  bar_sync(NB_ROW0 + w, 128);
  TL(28);
  {
    uint4 v[3];
#pragma unroll
    for (int k = 0; k < 3; k++) if (lane + 32 * k < 80) v[k] = lds128(sb + OFF_TQ + (64 * w + 16 * wg) * 80 + (lane + 32 * k) * 16);
#pragma unroll
    for (int k = 0; k < 3; k++) {
      const int i = lane + 32 * k, sl = (i * 205) >> 10, c = i - 5 * sl, slot = 64 * w + 16 * wg + sl;
      if (i < 80 && c < nu) *(uint4*)(p.out + (size_t)(256 * rank + 32 * (slot & 7) + (slot >> 3)) * DCH + ch0 + 8 * c) = v[k];
    }
  }
  TL(27);
  TL_DUMP();
}

typedef CUresult (*EncodeFn)(CUtensorMap*, CUtensorMapDataType, cuuint32_t, void*, const cuuint64_t*, const cuuint64_t*,
                             const cuuint32_t*, const cuuint32_t*, CUtensorMapInterleave, CUtensorMapSwizzle,
                             CUtensorMapL2promotion, CUtensorMapFloatOOBfill);

void encode(EncodeFn fn, CUtensorMap* tm, const void* ptr, int nd, const cuuint64_t* dims, const cuuint64_t* strides,
            const cuuint32_t* box, CUtensorMapSwizzle swz) {
  cuuint32_t es[4] = {1, 1, 1, 1};
  fn(tm, CU_TENSOR_MAP_DATA_TYPE_BFLOAT16, nd, const_cast<void*>(ptr), dims, strides, box, es, CU_TENSOR_MAP_INTERLEAVE_NONE,
     swz, CU_TENSOR_MAP_L2_PROMOTION_L2_128B, CU_TENSOR_MAP_FLOAT_OOB_FILL_NONE);
}
void map1(EncodeFn fn, CUtensorMap* tm, const void* ptr, int nhi) {
  const cuuint64_t dims[4] = {DCH, 4, 8, SEQ / 32}, strides[3] = {8 * DCH * 2, DCH * 2, 32 * DCH * 2};
  const cuuint32_t box[4] = {CPC, 4, 8, (cuuint32_t)nhi};
  encode(fn, tm, ptr, 4, dims, strides, box, CU_TENSOR_MAP_SWIZZLE_NONE);
}
void map2(EncodeFn fn, CUtensorMap* tm, const void* ptr, int nr) {
  const cuuint64_t dims[3] = {DCH, SEQ / 32, 32}, strides[2] = {32 * DCH * 2, DCH * 2};
  const cuuint32_t box[3] = {CPC, 8, (cuuint32_t)nr};
  encode(fn, tm, ptr, 3, dims, strides, box, CU_TENSOR_MAP_SWIZZLE_NONE);
}

}

extern "C" void kernel_launch(void* const* d_in, const int* in_sizes, int n_in, void* d_out, int out_size) {
  (void)in_sizes; (void)n_in; (void)out_size;
  static EncodeFn fn = nullptr;
  static void *tab = nullptr, *cnt = nullptr, *part = nullptr;
  if (!fn) {
    cudaGetSymbolAddress(&tab, d_tab);
    cudaGetSymbolAddress(&cnt, g_cnt);
    cudaGetSymbolAddress(&part, g_part);
    cudaDriverEntryPointQueryResult qr;
    cudaGetDriverEntryPoint("cuTensorMapEncodeTiled", (void**)&fn, cudaEnableDefault, &qr);
    cudaFuncSetAttribute(fused_kernel, cudaFuncAttributeMaxDynamicSharedMemorySize, SMEM_BYTES);
  }
  Params p;
  map1(fn, &p.tq, d_in[0], 4);
  map1(fn, &p.tk, d_in[1], 9);
  map1(fn, &p.tv, d_in[2], 8);
  map2(fn, &p.tq2, d_in[0], 32);
  p.out = (__nv_bfloat16*)d_out;
  {
    const cuuint64_t dims[4] = {32, SEQ / 32, DCH / 8, 8}, strides[3] = {64, 8 * SEQ * 2, SEQ * 2};
    const cuuint32_t box[4] = {32, 64, 5, 1};
    encode(fn, &p.th, d_in[4], 4, dims, strides, box, CU_TENSOR_MAP_SWIZZLE_64B);
  }
  p.tab = (const Tables*)tab;
  p.cnt = (unsigned*)cnt;
  p.part = (uint2*)part;
  p.tl = nullptr;
  p.q = (const __nv_bfloat16*)d_in[0];
  p.shift_k = (const __nv_bfloat16*)d_in[3];
  p.ssm_D = (const __nv_bfloat16*)d_in[5];
  p.logA = (const __nv_bfloat16*)d_in[7];
  p.Aim = (const __nv_bfloat16*)d_in[8];
  p.Cre = (const __nv_bfloat16*)d_in[9];
  p.Cim = (const __nv_bfloat16*)d_in[10];
  p.logdt = (const __nv_bfloat16*)d_in[11];
  p.Dskip = (const __nv_bfloat16*)d_in[12];
  p.gate_w = (const __nv_bfloat16*)d_in[13];
  fused_kernel<<<NCL * CS, NTHREADS, SMEM_BYTES, cudaStreamPerThread>>>(p);
}
```

```cpp
#include <cuda_runtime.h>
#include <cuda_bf16.h>
#include <cuda.h>
#include <stdint.h>

#define TIMELINE 0

namespace {

constexpr int SEQ = 2048, DCH = 576, NMODE = 128;
constexpr int CS = 8, CPC = 40, NCL = 15, NTHREADS = 512;

constexpr int YPITCH = 528;
constexpr int KTAB = 28672;
constexpr int OFF_T = 0;
constexpr int OFF_UKV = 2 * KTAB + 8192;
constexpr int OFF_UX = 3 * KTAB;
constexpr int OFF_HA = OFF_UX + 20480;
constexpr int OFF_CF = OFF_HA + 20480;
constexpr int OFF_CL = OFF_CF + 8192;
constexpr int OFF_TQ = OFF_CL + 4096;
constexpr int OFF_TK = OFF_TQ + 20480;
constexpr int OFF_YA = OFF_TK;
constexpr int OFF_TV = OFF_TK + 23040;
constexpr int OFF_YB = OFF_TV + 20480;
constexpr int OFF_KC = OFF_YB + 40 * YPITCH;
constexpr int OFF_SW = OFF_KC + 3 * 1408;
constexpr int OFF_GW = OFF_SW + 320;
constexpr int OFF_SD = OFF_GW + 80;
constexpr int OFF_MB = OFF_SD + 32;
constexpr int OFF_TL = OFF_MB + 24 * 8;
constexpr int SMEM_BYTES = OFF_TL + (TIMELINE ? 2048 : 0);
static_assert(SMEM_BYTES <= 232448, "smem");
static_assert((KTAB & 1023) == 0 && (OFF_TQ & 127) == 0 && (OFF_TK & 127) == 0 && (OFF_TV & 127) == 0 && (OFF_MB & 7) == 0 && (OFF_KC & 15) == 0, "align");

enum { MB_UX = 0, MB_UKV = 5, MB_Y = 10, MB_Q2 = 15, MB_XQ = 16, MB_KV = 18, MB_HA = 19, MB_CF = 20, MB_COUNT = 21 };
enum { NB_WG0 = 1, NB_ROW0 = 5 };

constexpr double cos_turn(int m, int n) {
  m &= n - 1;
  if (m > n / 2) m = n - m;
  double sgn = 1.0;
  if (m > n / 4) { m = n / 2 - m; sgn = -1.0; }
  if (m == n / 4) return 0.0;
  const double x = 6.283185307179586476925 * m / n;
  double term = 1.0, sum = 1.0;
  for (int k = 1; k < 14; k++) { term *= -x * x / ((2 * k - 1) * (2 * k)); sum += term; }
  return sgn * sum;
}
constexpr uint32_t bf16_bits(double v) {
  if (v == 0.0) return 0;
  uint32_t sgn = 0;
  if (v < 0) { sgn = 0x8000; v = -v; }
  int e = 127;
  while (v < 1.0) { v *= 2.0; e--; }
  while (v >= 2.0) { v *= 0.5; e++; }
  const double f = v * 128.0;
  int m = (int)f;
  if (f - m > 0.5 || (f - m == 0.5 && (m & 1))) m++;
  return sgn | (uint32_t)((e << 7) + (m - 128));
}
constexpr uint32_t pair_bits(double lo, double hi) { return bf16_bits(lo) | (bf16_bits(hi) << 16); }
struct alignas(128) Tables {
  uint32_t mat[3072];
  uint32_t thr[4][128][4];
};
constexpr Tables make_tables() {
  Tables T{};
  for (int q = 0; q < 768; q++) {
    int m0 = 0, d0 = 0, d1 = 0;
    if (q < 512) {
      const int r = (q >> 6) * 8 + (q & 7), cc = (q >> 3) & 7;
      d0 = 4 * (r & 31); d1 = 2 * d0;
      m0 = 8 * (cc & 3) * d0 + ((r >> 5) == (cc >> 2) ? 0 : (r >> 5) ? 96 : 32);
    } else {
      const int r = ((q - 512) >> 5) * 8 + (q & 7), pc = (q >> 3) & 3;
      d0 = 4 * (8 * (r >> 4) + (r & 7)) + 1; d1 = 8 * d0;
      m0 = 2 * pc * d0 + ((r & 8) ? 32 : 0);
    }
    for (int e = 0; e < 4; e++) T.mat[4 * q + e] = pair_bits(cos_turn(m0 + e * d1, 128), cos_turn(m0 + e * d1 + d0, 128));
  }
  for (int tid = 0; tid < 128; tid++) {
    const int kk = 4 * (tid >> 2) + 1, t = tid & 3;
    for (int q = 0; q < 4; q++) {
      const int m = (8 * q + 2 * t) * kk;
      T.thr[q >> 1][tid][2 * (q & 1)] = pair_bits(cos_turn(m, 128), cos_turn(m + kk, 128));
      T.thr[q >> 1][tid][2 * (q & 1) + 1] = pair_bits(cos_turn(m + 32, 128), cos_turn(m + kk + 32, 128));
      T.thr[2][tid][q] = pair_bits(cos_turn(m, 4096), cos_turn(m + kk, 4096));
      T.thr[3][tid][q] = pair_bits(cos_turn(m + 3072, 4096), cos_turn(m + kk + 3072, 4096));
    }
  }
  return T;
}
__device__ const Tables d_tab = make_tables();

struct Params {
  const __nv_bfloat16 *logA, *Aim, *Cre, *Cim, *logdt;
  const Tables* tab;
  unsigned* cnt;
  const __nv_bfloat16 *Dskip, *shift_k, *ssm_D, *gate_w, *q;
  uint2* part;
  __nv_bfloat16* out;
  unsigned* tl;
  CUtensorMap tq, tk, tv, th, tq2;
};

__device__ uint2 g_part[NCL * SEQ];
__device__ unsigned g_cnt[CS * 32];
#define TL(i) do {} while (0)
#define TL_INIT() do {} while (0)
#define TL_DUMP() do {} while (0)

__device__ __forceinline__ uint32_t lds16(uint32_t a) { uint32_t v; asm volatile("ld.shared.u16 %0, [%1];" : "=r"(v) : "r"(a) : "memory"); return v; }
__device__ __forceinline__ uint2 lds64(uint32_t a) { uint2 v; asm volatile("ld.shared.v2.u32 {%0,%1}, [%2];" : "=r"(v.x), "=r"(v.y) : "r"(a) : "memory"); return v; }
__device__ __forceinline__ uint4 lds128(uint32_t a) { uint4 v; asm volatile("ld.shared.v4.u32 {%0,%1,%2,%3}, [%4];" : "=r"(v.x), "=r"(v.y), "=r"(v.z), "=r"(v.w) : "r"(a) : "memory"); return v; }
__device__ __forceinline__ void sts16(uint32_t a, uint32_t v) { asm volatile("st.shared.u16 [%0], %1;" :: "r"(a), "r"(v) : "memory"); }
__device__ __forceinline__ void sts32(uint32_t a, uint32_t v) { asm volatile("st.shared.u32 [%0], %1;" :: "r"(a), "r"(v) : "memory"); }
__device__ __forceinline__ void sts64(uint32_t a, uint32_t x, uint32_t y) { asm volatile("st.shared.v2.u32 [%0], {%1,%2};" :: "r"(a), "r"(x), "r"(y) : "memory"); }
__device__ __forceinline__ void sts128(uint32_t a, uint32_t x, uint32_t y, uint32_t z, uint32_t w) { asm volatile("st.shared.v4.u32 [%0], {%1,%2,%3,%4};" :: "r"(a), "r"(x), "r"(y), "r"(z), "r"(w) : "memory"); }
__device__ __forceinline__ void ldsm4t(uint32_t (&r)[4], uint32_t a) { asm volatile("ldmatrix.sync.aligned.m8n8.x4.trans.shared.b16 {%0,%1,%2,%3}, [%4];" : "=r"(r[0]), "=r"(r[1]), "=r"(r[2]), "=r"(r[3]) : "r"(a) : "memory"); }
__device__ __forceinline__ void ldsm2t(uint32_t& r0, uint32_t& r1, uint32_t a) { asm volatile("ldmatrix.sync.aligned.m8n8.x2.trans.shared.b16 {%0,%1}, [%2];" : "=r"(r0), "=r"(r1) : "r"(a) : "memory"); }
__device__ __forceinline__ void ldsm4(uint32_t (&r)[4], uint32_t a) { asm volatile("ldmatrix.sync.aligned.m8n8.x4.shared.b16 {%0,%1,%2,%3}, [%4];" : "=r"(r[0]), "=r"(r[1]), "=r"(r[2]), "=r"(r[3]) : "r"(a) : "memory"); }
__device__ __forceinline__ void stsm4(uint32_t a, const uint32_t (&r)[4]) { asm volatile("stmatrix.sync.aligned.m8n8.x4.shared.b16 [%0], {%1,%2,%3,%4};" :: "r"(a), "r"(r[0]), "r"(r[1]), "r"(r[2]), "r"(r[3]) : "memory"); }
__device__ __forceinline__ uint32_t pack(float lo, float hi) { uint32_t r; asm("cvt.rn.bf16x2.f32 %0, %1, %2;" : "=r"(r) : "f"(hi), "f"(lo)); return r; }
__device__ __forceinline__ float blo(uint32_t v) { return __uint_as_float(v << 16); }
__device__ __forceinline__ float bhi(uint32_t v) { return __uint_as_float(v & 0xffff0000u); }
__device__ __forceinline__ float bf16r(float x) { return blo(pack(x, 0.f)); }
__device__ __forceinline__ uint32_t hmul2(uint32_t a, uint32_t b) { uint32_t r; asm("mul.rn.bf16x2 %0, %1, %2;" : "=r"(r) : "r"(a), "r"(b)); return r; }
__device__ __forceinline__ uint32_t hadd2(uint32_t a, uint32_t b) { uint32_t r; asm("add.rn.bf16x2 %0, %1, %2;" : "=r"(r) : "r"(a), "r"(b)); return r; }
__device__ __forceinline__ uint32_t hfma2(uint32_t a, uint32_t b, uint32_t c) { uint32_t r; asm("fma.rn.bf16x2 %0, %1, %2, %3;" : "=r"(r) : "r"(a), "r"(b), "r"(c)); return r; }
__device__ __forceinline__ uint32_t prmt(uint32_t a, uint32_t b, uint32_t s) { return __byte_perm(a, b, s); }
__device__ __forceinline__ uint32_t ldraw(const __nv_bfloat16* p) { uint32_t v; asm volatile("ld.global.nc.u16 %0, [%1];" : "=r"(v) : "l"(p)); return v; }
__device__ __forceinline__ uint4 ldg128(const void* p) { uint4 v; asm volatile("ld.global.nc.v4.u32 {%0,%1,%2,%3}, [%4];" : "=r"(v.x), "=r"(v.y), "=r"(v.z), "=r"(v.w) : "l"(p)); return v; }
__device__ __forceinline__ void bar_sync(int id, int n) { asm volatile("bar.sync %0, %1;" :: "r"(id), "r"(n) : "memory"); }
__device__ __forceinline__ void bar_arrive(int id, int n) { asm volatile("bar.arrive %0, %1;" :: "r"(id), "r"(n) : "memory"); }
__device__ __forceinline__ void cluster_arrive() { asm volatile("barrier.cluster.arrive.relaxed.aligned;" ::: "memory"); }
__device__ __forceinline__ void cluster_wait() { asm volatile("barrier.cluster.wait.aligned;" ::: "memory"); }
__device__ __forceinline__ void fence_async() { asm volatile("fence.proxy.async.shared::cta;" ::: "memory"); }
__device__ __forceinline__ void fence_mbinit() { asm volatile("fence.mbarrier_init.release.cluster;" ::: "memory"); }
__device__ __forceinline__ uint32_t mapa(uint32_t a, uint32_t rank) { uint32_t r; asm("mapa.shared::cluster.u32 %0, %1, %2;" : "=r"(r) : "r"(a), "r"(rank)); return r; }
__device__ __forceinline__ void st_async4(uint32_t a, uint32_t x, uint32_t y, uint32_t z, uint32_t w, uint32_t mbar) {
  asm volatile("st.async.weak.shared::cluster.mbarrier::complete_tx::bytes.v4.b32 [%0], {%1,%2,%3,%4}, [%5];"
               :: "r"(a), "r"(x), "r"(y), "r"(z), "r"(w), "r"(mbar) : "memory");
}
__device__ __forceinline__ void mbar_init(uint32_t m, uint32_t cnt) { asm volatile("mbarrier.init.shared::cta.b64 [%0], %1;" :: "r"(m), "r"(cnt) : "memory"); }
__device__ __forceinline__ void mbar_expect(uint32_t m, uint32_t bytes) { asm volatile("mbarrier.arrive.expect_tx.shared::cta.b64 _, [%0], %1;" :: "r"(m), "r"(bytes) : "memory"); }
__device__ __forceinline__ void mbar_wait(uint32_t m) {
  uint32_t done;
  int it = 0;
  do {
    asm volatile("{.reg .pred p; mbarrier.try_wait.parity.shared::cta.b64 p, [%1], 0; selp.u32 %0, 1, 0, p;}" : "=r"(done) : "r"(m) : "memory");
    if (++it > (1 << 22)) __trap();
  } while (!done);
}
__device__ __forceinline__ void tma_load4(uint32_t dst, const CUtensorMap* tm, int c0, int c1, int c2, int c3, uint32_t mbar) {
  asm volatile("cp.async.bulk.tensor.4d.shared::cluster.global.mbarrier::complete_tx::bytes [%0], [%1, {%3, %4, %5, %6}], [%2];"
               :: "r"(dst), "l"(tm), "r"(mbar), "r"(c0), "r"(c1), "r"(c2), "r"(c3) : "memory");
}
__device__ __forceinline__ void tma_load3(uint32_t dst, const CUtensorMap* tm, int c0, int c1, int c2, uint32_t mbar) {
  asm volatile("cp.async.bulk.tensor.3d.shared::cluster.global.mbarrier::complete_tx::bytes [%0], [%1, {%3, %4, %5}], [%2];"
               :: "r"(dst), "l"(tm), "r"(mbar), "r"(c0), "r"(c1), "r"(c2) : "memory");
}
__device__ __forceinline__ void tma_store3(const CUtensorMap* tm, int c0, int c1, int c2, uint32_t src) {
  asm volatile("cp.async.bulk.tensor.3d.global.shared::cta.bulk_group [%0, {%2, %3, %4}], [%1];"
               :: "l"(tm), "r"(src), "r"(c0), "r"(c1), "r"(c2) : "memory");
}
__device__ __forceinline__ void wg_fence() { asm volatile("wgmma.fence.sync.aligned;" ::: "memory"); }
__device__ __forceinline__ void wg_commit() { asm volatile("wgmma.commit_group.sync.aligned;" ::: "memory"); }
template <int N> __device__ __forceinline__ void wg_wait() { asm volatile("wgmma.wait_group.sync.aligned %0;" :: "n"(N) : "memory"); }
template <int N> __device__ __forceinline__ void tie_all(float (&x)[N]) {
#pragma unroll
  for (int i = 0; i < N; i++) asm volatile("" : "+f"(x[i]) :: "memory");
}
#define R16(C, d) C(d[0]), C(d[1]), C(d[2]), C(d[3]), C(d[4]), C(d[5]), C(d[6]), C(d[7]), C(d[8]), C(d[9]), C(d[10]), C(d[11]), C(d[12]), C(d[13]), C(d[14]), C(d[15])
#define R32(C, d) R16(C, d), R16(C, (d + 16))
#define P16 "{%0,%1,%2,%3,%4,%5,%6,%7,%8,%9,%10,%11,%12,%13,%14,%15}"
#define P32 "{%0,%1,%2,%3,%4,%5,%6,%7,%8,%9,%10,%11,%12,%13,%14,%15,%16,%17,%18,%19,%20,%21,%22,%23,%24,%25,%26,%27,%28,%29,%30,%31}"
template <int SD, int TB, int OFF> __device__ __forceinline__ void rs64(float* d, const uint32_t* a, uint64_t db) {
  if (SD) asm volatile("{.reg .b64 db; add.s64 db, %36, %37; wgmma.mma_async.sync.aligned.m64n64k16.f32.bf16.bf16 " P32 ", {%32,%33,%34,%35}, db, 1, 1, 1, %38;}"
                       : R32("+f", d) : "r"(a[0]), "r"(a[1]), "r"(a[2]), "r"(a[3]), "l"(db), "n"(OFF), "n"(TB));
  else asm volatile("{.reg .b64 db; add.s64 db, %36, %37; wgmma.mma_async.sync.aligned.m64n64k16.f32.bf16.bf16 " P32 ", {%32,%33,%34,%35}, db, 0, 1, 1, %38;}"
                    : R32("=f", d) : "r"(a[0]), "r"(a[1]), "r"(a[2]), "r"(a[3]), "l"(db), "n"(OFF), "n"(TB));
}
template <int SD, int OFFA, int OFFB> __device__ __forceinline__ void ss32(float* d, uint64_t da, uint64_t db) {
  if (SD) asm volatile("{.reg .b64 da, db; add.s64 da, %16, %18; add.s64 db, %17, %19; wgmma.mma_async.sync.aligned.m64n32k16.f32.bf16.bf16 " P16 ", da, db, 1, 1, 1, 1, 1;}"
                       : R16("+f", d) : "l"(da), "l"(db), "n"(OFFA), "n"(OFFB));
  else asm volatile("{.reg .b64 da, db; add.s64 da, %16, %18; add.s64 db, %17, %19; wgmma.mma_async.sync.aligned.m64n32k16.f32.bf16.bf16 " P16 ", da, db, 0, 1, 1, 1, 1;}"
                    : R16("=f", d) : "l"(da), "l"(db), "n"(OFFA), "n"(OFFB));
}
template <int KS> __device__ __forceinline__ void kgen_mma(float (&c)[24], uint64_t da) {
  asm volatile("{.reg .b64 da, db; add.s64 da, %24, %25; add.s64 db, %24, %26;\n"
               "wgmma.mma_async.sync.aligned.m64n48k16.f32.bf16.bf16 {%0,%1,%2,%3,%4,%5,%6,%7,%8,%9,%10,%11,%12,%13,%14,%15,%16,%17,%18,%19,%20,%21,%22,%23}, da, db, %27, 1, 1, 1, 1;}"
               : R16("+f", c), "+f"(c[16]), "+f"(c[17]), "+f"(c[18]), "+f"(c[19]), "+f"(c[20]), "+f"(c[21]), "+f"(c[22]), "+f"(c[23])
               : "l"(da), "n"(8 * KS), "n"(8 * KS + 512), "n"(KS ? 1 : 0));
  if constexpr (KS < 7) kgen_mma<KS + 1>(c, da);
}
__device__ __forceinline__ uint64_t desc_lo(uint32_t a) { return (uint64_t)((a & 0x3FFFF) >> 4); }
__device__ __forceinline__ void stage1(float (&D)[32], const uint32_t (&A1)[8], uint32_t src) {
  const uint64_t du = desc_lo(src) | (128ull << 16) | (32ull << 32) | (2ull << 62);
  rs64<0, 1, 0>(D, A1, du); rs64<1, 1, 64>(D, A1 + 4, du);
}
template <int INV> __device__ __forceinline__ void stage2(float (&X)[32], const uint32_t (&F)[16], uint32_t cf) {
  constexpr int KS = INV ? 16 : 128, TB = INV ? 0 : 1;
  const uint64_t dc = desc_lo(cf) | (INV ? (8ull << 16) | (64ull << 32) : (64ull << 16) | (8ull << 32));
  rs64<0, TB, 0>(X, F, dc); rs64<1, TB, KS>(X, F + 4, dc); rs64<1, TB, 2 * KS>(X, F + 8, dc); rs64<1, TB, 3 * KS>(X, F + 12, dc);
}
__device__ __forceinline__ void fwd_mid(uint32_t (&F)[16], const float (&D)[32], const uint32_t (&tp)[12]) {
#pragma unroll
  for (int j = 0; j < 4; j++)
#pragma unroll
    for (int b = 0; b < 2; b++) {
      const int i = 4 * j + 16 * b;
      const uint32_t ar = pack(D[i], D[i + 1]), ai = pack(D[i + 2], D[i + 3]);
      F[2 * j + b] = hfma2(ar, tp[3 * j], hmul2(ai, tp[3 * j + 2]));
      F[8 + 2 * j + b] = hfma2(ar, tp[3 * j + 1], hmul2(ai, tp[3 * j]));
    }
}

struct cf { float x, y; };
__device__ __forceinline__ cf cmul(cf a, cf b) { cf r; r.x = fmaf(a.x, b.x, -a.y * b.y); r.y = fmaf(a.x, b.y, a.y * b.x); return r; }
__device__ __forceinline__ cf cexp_p(float lr2, float lt, float p) {
  float m = exp2f(lr2 * p);
  float t = lt * p;
  t = (t - rintf(t)) * 6.283185307179586f;
  cf r; r.x = m * __cosf(t); r.y = m * __sinf(t); return r;
}
__device__ __forceinline__ void store8(uint32_t a, const cf (&v)[8]) {
  sts128(a, pack(v[0].x, v[1].x), pack(v[2].x, v[3].x), pack(v[4].x, v[5].x), pack(v[6].x, v[7].x));
  sts128(a + KTAB / 2, pack(v[0].y, v[1].y), pack(v[2].y, v[3].y), pack(v[4].y, v[5].y), pack(v[6].y, v[7].y));
}
__device__ __forceinline__ float sigmoidf_(float s) { return 1.f / (1.f + __expf(-s)); }

__global__ void __cluster_dims__(CS, 1, 1) __launch_bounds__(NTHREADS, 1) fused_kernel(const __grid_constant__ Params p) {
  extern __shared__ __align__(1024) uint8_t smem[];
  TL_INIT();
  TL(31);
  const int wid = __shfl_sync(0xffffffffu, threadIdx.x >> 5, 0);
  uint32_t pla[2], pai[2], pcr[2], pci[2], pdt[2];
  if (threadIdx.x < 384) {
#pragma unroll
    for (int r = 0; r < 2; r++) {
      int ch = (blockIdx.x >> 3) * CPC + (blockIdx.x & 7) + 8 * (threadIdx.x >> 7) + 24 * r;
      if (ch >= DCH) ch = 0;
      const int o = ch * NMODE + (threadIdx.x & 127);
      pla[r] = ldraw(p.logA + o); pdt[r] = ldraw(p.logdt + ch); pai[r] = ldraw(p.Aim + o); pcr[r] = ldraw(p.Cre + o); pci[r] = ldraw(p.Cim + o);
    }
  }
  const uint32_t sb = (uint32_t)__cvta_generic_to_shared(smem);
  const uint32_t mb = sb + OFF_MB;
  const int wg = wid >> 2, w = wid & 3;
  const int tid = threadIdx.x & 127, lane = tid & 31, g = lane >> 2, t = lane & 3;
  const int cl = blockIdx.x >> 3, rank = blockIdx.x & 7;
  const int ch0 = cl * CPC;
  const int nu = min(5, (DCH - ch0) >> 3);

  if (wg < 3) {
    cluster_arrive();
    uint32_t A1[8], tp[12];
    {
      const uint4 a = ldg128(p.tab->thr[0][tid]), b = ldg128(p.tab->thr[1][tid]), c = ldg128(p.tab->thr[2][tid]), d = ldg128(p.tab->thr[3][tid]);
      A1[0] = a.x; A1[1] = a.y; A1[2] = a.z; A1[3] = a.w; A1[4] = b.x; A1[5] = b.y; A1[6] = b.z; A1[7] = b.w;
      tp[0] = c.x; tp[3] = c.y; tp[6] = c.z; tp[9] = c.w; tp[2] = d.x; tp[5] = d.y; tp[8] = d.z; tp[11] = d.w;
      tp[1] = tp[4] = tp[7] = tp[10] = 0;
    }
    TL(0);
    const uint32_t tab = sb + OFF_T + wg * KTAB;
#pragma unroll 1
    for (int job = 0; job < 4; job++) {
      const bool isA = job >= (wg == 2 ? 1 : 2);
      const int u = wg == 2 ? (job ? 2 * job - 2 : 2) : job < 2 ? wg + 3 * job : job == 2 ? 2 * wg + 1 : 9;

      if (!isA && u < nu) {
        const float la = blo(job ? pla[1] : pla[0]), ai = blo(job ? pai[1] : pai[0]), cr = blo(job ? pcr[1] : pcr[0]), ci = blo(job ? pci[1] : pci[0]);
        const float dt = bf16r(expf(blo(job ? pdt[1] : pdt[0])));
        const float lr2 = (-bf16r(expf(la)) * dt) * 1.4426950408889634f;
        const float lt = (ai * dt) * 0.15915494309189535f;
        const uint32_t row = tab + tid * 16;
        if (lr2 != 123.f) TL(16 + 4 * job);
        if (job) bar_sync(NB_WG0 + wg, 128);
        {
          const cf w1 = cexp_p(lr2, lt, 8.f);
          cf v[8];
          v[0].x = 1.f; v[0].y = 0.f; v[1] = w1; v[2] = cmul(w1, w1); v[3] = cmul(v[2], w1);
          const cf w4 = cmul(v[2], v[2]);
          v[4] = w4; v[5] = cmul(v[1], w4); v[6] = cmul(v[2], w4); v[7] = cmul(v[3], w4);
          const cf w8 = cmul(w4, w4);
          store8(row, v);
#pragma unroll
          for (int c = 1; c < 4; c++) {
#pragma unroll
            for (int i = 0; i < 8; i++) v[i] = (c == 1 && i == 0) ? w8 : cmul(v[i], w8);
            store8(row + 2048 * c, v);
          }
        }
        {
          cf z1 = cexp_p(lr2, lt, 1.f), Z = cexp_p(lr2, lt, 256.f);
          z1.y = -z1.y; Z.y = -Z.y;
          const cf z2 = cmul(z1, z1);
          cf h[8], v[8];
          h[0].x = 2.f * cr * dt; h[0].y = -2.f * ci * dt;
          h[1] = cmul(h[0], z1);
#pragma unroll
          for (int i = 2; i < 8; i++) h[i] = cmul(h[i - 2], z2);
          store8(row + 4 * 2048, h);
          v[0] = cmul(h[0], Z); v[1] = cmul(h[2], Z); v[2] = cmul(h[4], Z); v[3] = cmul(h[6], Z);
          v[4] = cmul(v[0], Z); v[5] = cmul(v[2], Z); v[6] = cmul(v[4], Z); v[7] = cmul(v[5], Z);
          store8(row + 5 * 2048, v);
          const cf Z2 = cmul(Z, Z);
          h[0] = cmul(v[4], Z2); h[1] = cmul(v[6], Z2); h[2] = cmul(h[0], Z2); h[3] = cmul(h[1], Z2); h[4] = cmul(h[2], Z2);
          h[5].x = h[5].y = h[6].x = h[6].y = h[7].x = h[7].y = 0.f;
          store8(row + 6 * 2048, h);
        }
        TL(17 + 4 * job);
        fence_async();
        bar_sync(NB_WG0 + wg, 128);
        float c[24];
        wg_fence();
        kgen_mma<0>(c, desc_lo(tab) | ((uint64_t)(KTAB / 32) << 16) | (64ull << 32));
        wg_commit();
        uint32_t kid[8];
        {
          float lf = __uint_as_float(0x4b000000u | (8 * tid)) - 8388608.f;
          asm volatile("" : "+f"(lf));
          const float lo = tid < 16 ? lf + 128.f : lf;
          const uint32_t sub = tid < 16 ? 0x42804300u : 0x42804280u;
#pragma unroll
          for (int i = 0; i < 8; i++) kid[i] = 2 * (pack(lo + i, lf + (1024 + i)) - sub);
        }
        wg_wait<0>(); tie_all(c);
        const uint32_t kc = sb + OFF_KC + wg * 1408;
        {
          const int a = 8 * w + g;
          sts32(kc + 4 * (4 * a + t), pack(c[0] + c[6], c[1] + c[7]));
          sts32(kc + 4 * (t < 2 ? 128 + 2 * a + t : 128 + 32 * t + a), pack(c[8] + c[14], c[9] + c[15]));
          if (t < 3) {
            const uint32_t p0 = pack(c[16] + c[22], c[17] + c[23]);
            sts16(kc + 2 * (512 + 64 * t + a), p0);
            sts16(kc + 2 * (544 + 64 * t + a), p0 >> 16);
          }
        }
        TL(18 + 4 * job);
        bar_sync(NB_WG0 + wg, 128);
        uint32_t v[2][8];
#pragma unroll
        for (int i = 0; i < 8; i++) { v[0][i] = lds16(kc + (kid[i] & 0xffffu)); v[1][i] = lds16(kc + (kid[i] >> 16)); }
#pragma unroll
        for (int cc = 0; cc < 2; cc++)
          sts128(tab + 2048 * cc + 16 * (tid ^ ((tid >> 3) & 3)), prmt(v[cc][0], v[cc][1], 0x5410), prmt(v[cc][2], v[cc][3], 0x5410),
                 prmt(v[cc][4], v[cc][5], 0x5410), prmt(v[cc][6], v[cc][7], 0x5410));
        fence_async();
        if (job) bar_sync(NB_WG0 + wg, 128);
      }
      if (job == 0) {
        cluster_wait();
        cluster_arrive();
        bar_sync(NB_WG0 + wg, 128);
        mbar_wait(mb + 8 * MB_CF);
#pragma unroll
        for (int j = 0; j < 4; j++) asm volatile("xor.b32 %0, %1, 0x80008000;" : "=r"(tp[3 * j + 1]) : "r"(tp[3 * j + 2]));
      }
      if (u >= nu) continue;
      TL(1 + job);
      float D[32], H[32], X[32];
      uint32_t F[16];
      if (isA) mbar_wait(mb + 8 * MB_HA);
      wg_fence();
      stage1(D, A1, isA ? sb + OFF_HA + u * 4096 : tab);
      wg_commit();
      wg_wait<0>(); tie_all(D);
      fwd_mid(F, D, tp);
      wg_fence();
      stage2<0>(H, F, sb + OFF_CF);
      wg_commit();
      mbar_wait(mb + 8 * ((isA ? MB_UKV : MB_UX) + u));
      fence_async();
      TL(5 + job);
      wg_fence();
      stage1(D, A1, sb + (isA ? OFF_UKV : OFF_UX) + u * 4096);
      wg_commit();
      wg_wait<0>(); tie_all(D); tie_all(H);
      fwd_mid(F, D, tp);
      wg_fence();
      stage2<0>(X, F, sb + OFF_CF);
      wg_commit();
      {
        const float dsk = blo(lds16(sb + OFF_SD + (isA ? 10 : 0) + 2 * u));
#pragma unroll
        for (int j = 0; j < 4; j++) { H[4 * j] += dsk; H[4 * j + 1] += dsk; }
      }
      wg_wait<0>(); tie_all(X);
#pragma unroll
      for (int j = 0; j < 4; j++) {
        float pr[2], pi[2], qr[2], qi[2];
#pragma unroll
        for (int n = 0; n < 2; n++) {
          const int i = 4 * j + n;
          pr[n] = fmaf(X[i], H[i], -X[i + 16] * H[i + 16]);
          pi[n] = fmaf(X[i], H[i + 16], X[i + 16] * H[i]);
          qr[n] = fmaf(X[i + 2], H[i], fmaf(-X[i + 18], H[i + 16], fmaf(X[i], H[i + 2], fmaf(-X[i + 16], H[i + 18], -pi[n]))));
          qi[n] = fmaf(X[i + 2], H[i + 16], fmaf(X[i + 18], H[i], fmaf(X[i], H[i + 18], fmaf(X[i + 16], H[i + 2], pr[n]))));
        }
        F[2 * j] = pack(pr[0], pr[1]); F[2 * j + 1] = pack(qr[0], qr[1]); F[8 + 2 * j] = pack(pi[0], pi[1]); F[9 + 2 * j] = pack(qi[0], qi[1]);
      }
      wg_fence();
      stage2<1>(H, F, sb + OFF_CF);
      wg_commit();
      wg_wait<0>(); tie_all(H);
      {
        const uint32_t va = tab + (16 * w + (lane & 15)) * 128;
        const int vx = (lane >> 4) ^ (lane & 7);
#pragma unroll
        for (int j = 0; j < 4; j++) {
          uint32_t V[4];
#pragma unroll
          for (int b = 0; b < 2; b++) {
            const int i = 4 * j + 2 * b;
            const uint32_t er = pack(H[i], H[i + 1]), ei = pack(H[i + 16], H[i + 17]);
            V[2 * b] = hfma2(er, tp[3 * j], hmul2(ei, tp[3 * j + 1]));
            V[2 * b + 1] = hfma2(ei, tp[3 * j], hmul2(er, tp[3 * j + 2]));
          }
          stsm4(va + ((vx ^ (2 * j)) << 4), V);
        }
      }
      fence_async();
      bar_sync(NB_WG0 + wg, 128);
      float O[16];
      {
        const uint64_t dv = desc_lo(tab) | (1ull << 16) | (64ull << 32) | (1ull << 62);
        const uint64_t dl = desc_lo(sb + OFF_CL) | (32ull << 16) | (8ull << 32);
        wg_fence();
        ss32<0, 0, 0>(O, dv, dl); ss32<1, 128, 64>(O, dv, dl); ss32<1, 256, 128>(O, dv, dl); ss32<1, 384, 192>(O, dv, dl);
        wg_commit();
      }
      if (isA && job < 3) {
        for (int k = 0; k < nu; k++) mbar_wait(mb + 8 * (MB_UKV + k));
      }
      wg_wait<0>(); tie_all(O);
      {
        const uint32_t yo = (isA ? OFF_YA : OFF_YB) + (8 * u + rank) * YPITCH + (8 * w + g) * 16, ym = OFF_MB + 8 * (MB_Y + u);
        const uint32_t r0 = mapa(sb, t), r1 = mapa(sb, t + 4);
        st_async4(r0 + yo, pack(O[0], O[1]), pack(O[4], O[5]), pack(O[8], O[9]), pack(O[12], O[13]), r0 + ym);
        st_async4(r1 + yo, pack(O[2], O[3]), pack(O[6], O[7]), pack(O[10], O[11]), pack(O[14], O[15]), r1 + ym);
      }
      TL(9 + job);
    }
  } else {
    if (lane == 0) {
#pragma unroll
      for (int i = 0; i < 4; i++) mbar_init(mb + 8 * (4 * w + i), 4 * w + i == MB_Q2 ? 5 : 1);
      mbar_init(mb + 8 * (MB_XQ + w), 1);
      if (w == 3) mbar_init(mb + 8 * MB_CF, 2);
      fence_mbinit();
      if (w == 3) {
        mbar_expect(mb + 8 * MB_CF, 12288);
        asm volatile("cp.async.bulk.shared::cluster.global.mbarrier::complete_tx::bytes [%0], [%1], %2, [%3];"
                     :: "r"(sb + OFF_CF), "l"(p.tab->mat), "r"(12288), "r"(mb + 8 * MB_CF) : "memory");
      }
#pragma unroll
      for (int i = 0; i < 4; i++) { const int b = 4 * w + i; mbar_expect(mb + 8 * b, b == MB_Q2 ? 20480 : b >= MB_Y ? 8192 : 4096); }
      mbar_expect(mb + 8 * (MB_XQ + w), w < 2 ? 10240 : w == 2 ? 23040 + 20480 : 20480);
    }
    __syncwarp();
    cluster_arrive();
    uint32_t tag = 0;
    if (w == 0) {
      if (lane < 2) asm volatile("atom.relaxed.gpu.global.add.u32 %0, [%1], %2;" : "=r"(tag) : "l"(&p.cnt[rank * 32 + lane]), "r"(cl == 0 ? 16 - (NCL - 1) : 1) : "memory");
      if (lane == 0) { tma_load4(sb + OFF_TQ, &p.tq, ch0, 0, 0, 8 * rank, mb + 8 * MB_XQ); TL(20); }
    } else if (w == 1) {
      uint32_t d = 0;
      const int u = lane < 5 ? lane : lane - 5;
      if (lane < 10 && u < nu) d = ldraw((lane < 5 ? p.Dskip : p.ssm_D) + ch0 + 8 * u + rank);
      if (lane == 0) tma_load4(sb + OFF_TQ + 10240, &p.tq, ch0, 0, 0, 8 * rank + 4, mb + 8 * (MB_XQ + 1));
      if (lane < 10) sts16(sb + OFF_SD + 2 * lane, d);
      __syncwarp();
      if (lane == 0) asm volatile("mbarrier.arrive.shared::cta.b64 _, [%0];" :: "r"(mb + 8 * MB_CF) : "memory");
    } else {
      uint2 swv = make_uint2(0, 0);
      uint32_t gwv = 0;
      const int c = tid - 64;
      if (c < 40 && ch0 + c < DCH) { swv = __ldg((const uint2*)(p.shift_k + (size_t)(ch0 + c) * 4)); gwv = ldraw(p.gate_w + ch0 + c); }
      if (c < 40) { sts64(sb + OFF_SW + 8 * c, swv.x, swv.y); sts16(sb + OFF_GW + 2 * c, gwv); }
      if (c == 0) {
        tma_load4(sb + OFF_TK, &p.tk, ch0, 0, 0, 8 * rank - 1, mb + 8 * MB_KV);
        tma_load4(sb + OFF_TV, &p.tv, ch0, 0, 0, 8 * rank, mb + 8 * MB_KV);
        TL(20);
      }
    }
    __syncwarp();
    TL(0);
    const uint32_t rbase = mapa(sb, g);
    const int mi = lane >> 3, tq = (lane & 7) >> 1, jj = lane & 1;
    const uint32_t toff = (4 * (2 * mi + jj) + tq) * 80;
    const uint32_t uoff = 16 * (32 * rank + 4 * w + (t ^ (w >> 1)));
    cluster_wait();
    cluster_arrive();
    if (tid == 64) tma_load4(sb + OFF_HA, &p.th, 0, 0, 5 * cl, rank, mb + 8 * MB_HA);
    __syncwarp();
    mbar_wait(mb + 8 * MB_XQ);
    mbar_wait(mb + 8 * (MB_XQ + 1));
    TL(1);
    {
      uint32_t xr[5][2][4];
#pragma unroll
      for (int u = 0; u < 5; u++) { ldsm4t(xr[u][0], sb + OFF_TQ + w * 2560 + toff + 16 * u); ldsm4t(xr[u][1], sb + OFF_TQ + (w + 4) * 2560 + toff + 16 * u); }
#pragma unroll
      for (int u = 0; u < 5; u++)
        if (u < nu) {
          st_async4(rbase + OFF_UX + u * 4096 + uoff, xr[u][0][0], xr[u][0][1], xr[u][0][2], xr[u][0][3], rbase + OFF_MB + 8 * (MB_UX + u));
          st_async4(rbase + OFF_UX + u * 4096 + (uoff ^ 32) + 256, xr[u][1][0], xr[u][1][1], xr[u][1][2], xr[u][1][3], rbase + OFF_MB + 8 * (MB_UX + u));
        }
    }
    TL(2);
    if (tid == 1) sts32(sb + OFF_MB + 8 * MB_COUNT, tag);
    bar_sync(NB_WG0 + 3, 128);
    tag = (lds64(sb + OFF_MB + 8 * MB_COUNT).x >> 4) + 1;
    {
      float s0 = 0.f, s1 = 0.f;
#pragma unroll
      for (int j = 0; j < 5; j++) {
        const uint4 gw = lds128(sb + OFF_GW + 16 * j);
        const uint4 x0 = lds128(sb + OFF_TQ + tid * 80 + 16 * j), x1 = lds128(sb + OFF_TQ + (tid + 128) * 80 + 16 * j);
        uint32_t m0 = hmul2(x0.x, gw.x), m1 = hmul2(x0.y, gw.y), m2 = hmul2(x0.z, gw.z), m3 = hmul2(x0.w, gw.w);
        s0 += ((blo(m0) + bhi(m0)) + (blo(m1) + bhi(m1))) + ((blo(m2) + bhi(m2)) + (blo(m3) + bhi(m3)));
        m0 = hmul2(x1.x, gw.x); m1 = hmul2(x1.y, gw.y); m2 = hmul2(x1.z, gw.z); m3 = hmul2(x1.w, gw.w);
        s1 += ((blo(m0) + bhi(m0)) + (blo(m1) + bhi(m1))) + ((blo(m2) + bhi(m2)) + (blo(m3) + bhi(m3)));
      }
      const int s2 = 8 * (8 * (lane & 3) + (lane >> 2)) + w;
      asm volatile("st.relaxed.gpu.global.u64 [%0], %1;" :: "l"(&p.part[cl * SEQ + rank * 256 + s2]), "l"(((uint64_t)tag << 32) | __float_as_uint(s0)) : "memory");
      asm volatile("st.relaxed.gpu.global.u64 [%0], %1;" :: "l"(&p.part[cl * SEQ + rank * 256 + s2 + 4]), "l"(((uint64_t)tag << 32) | __float_as_uint(s1)) : "memory");
    }
    bar_sync(NB_WG0 + 3, 128);
    if (tid == 0) tma_load3(sb + OFF_TQ, &p.tq2, ch0, 8 * rank, 0, mb + 8 * MB_Q2);
    __syncwarp();
    TL(3);
    cluster_wait();
    mbar_wait(mb + 8 * MB_KV);
    TL(4);
    const uint32_t hoff = (4 * (4 + 2 * (mi & 1) + jj) + ((tq + 3) & 3)) * 80 + (tq ? 2560 : 0);
    uint32_t En[2][6], Vn[2][4];
    uint2 swn;
    auto kv_load = [&](int u) {
      swn = lds64(sb + OFF_SW + 8 * (8 * u + g));
#pragma unroll
      for (int hf = 0; hf < 2; hf++) {
        const int ah = 4 * hf + w;
        uint32_t K[4];
        ldsm4t(K, sb + OFF_TK + (ah + 1) * 2560 + toff + 16 * u);
        ldsm2t(En[hf][0], En[hf][1], sb + OFF_TK + ah * 2560 + hoff + 16 * u);
        ldsm4t(Vn[hf], sb + OFF_TV + ah * 2560 + toff + 16 * u);
        En[hf][2] = K[0]; En[hf][3] = K[1]; En[hf][4] = K[2]; En[hf][5] = K[3];
      }
    };
    kv_load(0);
#pragma unroll 1
    for (int u = 0; u < nu; u++) {
      uint32_t E[2][6], V[2][4];
#pragma unroll
      for (int hf = 0; hf < 2; hf++) {
#pragma unroll
        for (int i = 0; i < 6; i++) E[hf][i] = En[hf][i];
#pragma unroll
        for (int i = 0; i < 4; i++) V[hf][i] = Vn[hf][i];
      }
      const uint32_t w0 = prmt(swn.x, 0, 0x1010), w1 = prmt(swn.x, 0, 0x3232), w2 = prmt(swn.y, 0, 0x1010), w3 = prmt(swn.y, 0, 0x3232);
      if (u + 1 < nu) kv_load(u + 1);
#pragma unroll
      for (int hf = 0; hf < 2; hf++) {
        uint32_t O[5], o[4];
#pragma unroll
        for (int i = 0; i < 5; i++) O[i] = prmt(E[hf][i], E[hf][i + 1], 0x5432);
#pragma unroll
        for (int i = 0; i < 4; i++) {
          uint32_t s = hmul2(O[i], w3);
          s = hadd2(s, hmul2(E[hf][i + 1], w2));
          s = hadd2(s, hmul2(O[i + 1], w1));
          s = hadd2(s, hmul2(E[hf][i + 2], w0));
          o[i] = hmul2(s, V[hf][i]);
        }
        st_async4(rbase + OFF_UKV + u * 4096 + (hf ? (uoff ^ 32) + 256 : uoff), o[0], o[1], o[2], o[3], rbase + OFF_MB + 8 * (MB_UKV + u));
      }
    }
    TL(5);
    bar_sync(NB_WG0 + 3, 128);
    {
      float s[2] = {0.f, 0.f};
      bool ok = false;
#pragma unroll 1
      for (int it = 0; it < 4000 && !ok; it++) {
        ok = true; s[0] = s[1] = 0.f;
#pragma unroll
        for (int c = 0; c < NCL; c++) {
          uint64_t a, b;
          asm volatile("ld.relaxed.gpu.global.v2.u64 {%0,%1}, [%2];" : "=l"(a), "=l"(b) : "l"(&p.part[c * SEQ + rank * 256 + 2 * tid]) : "memory");
          ok = ok && (uint32_t)(a >> 32) == tag && (uint32_t)(b >> 32) == tag;
          s[0] += __uint_as_float((uint32_t)a); s[1] += __uint_as_float((uint32_t)b);
        }
      }
      if (ok) {
      } else {
#pragma unroll 1
        for (int hf = 0; hf < 2; hf++) {
          const int slot = 2 * tid + hf;
          const int row = rank * 256 + 32 * (slot & 7) + (slot >> 3);
          const uint32_t* xr = (const uint32_t*)(p.q + (size_t)row * DCH);
          const uint32_t* gr = (const uint32_t*)p.gate_w;
          float a = 0.f;
#pragma unroll 1
          for (int c = 0; c < DCH / 2; c++) { const uint32_t m = hmul2(__ldg(xr + c), __ldg(gr + c)); a += blo(m) + bhi(m); }
          if (hf) s[1] = a; else s[0] = a;
        }
      }
      const float g0 = bf16r(sigmoidf_(bf16r(s[0]))), g1 = bf16r(sigmoidf_(bf16r(s[1])));
      const float a0 = g0 * 0.0009765625f, b0 = bf16r(1.f - g0) * 0.0009765625f, a1 = g1 * 0.0009765625f, b1 = bf16r(1.f - g1) * 0.0009765625f;
      sts128(sb + OFF_TV + 16 * tid, pack(a0, a0), pack(b0, b0), pack(a1, a1), pack(b1, b1));
    }
    __syncwarp();
    if (lane == 0) asm volatile("mbarrier.arrive.shared::cta.b64 _, [%0];" :: "r"(mb + 8 * MB_Q2) : "memory");
  }
  mbar_wait(mb + 8 * MB_Q2);
  uint2 gg[2][4];
#pragma unroll
  for (int hh = 0; hh < 2; hh++)
#pragma unroll
    for (int i = 0; i < 4; i++) gg[hh][i] = lds64(sb + OFF_TV + 8 * (64 * w + 32 * hh + 8 * i + g));
  TL(24);
#pragma unroll 1
  for (int u = wg == 3 ? 0 : wg == 2 ? 4 : 2 * wg + 1; u < nu; u += 2) {
    uint32_t qv[2][4];
    const uint32_t qa = sb + OFF_TQ + (64 * w + lane) * 80 + 16 * u;
    ldsm4(qv[0], qa);
    ldsm4(qv[1], qa + 2560);
    mbar_wait(mb + 8 * (MB_Y + u));
    uint32_t ya[2][4], yb[2][4];
    const uint32_t yo = (8 * u + (lane & 7)) * YPITCH + (8 * w + (lane >> 3)) * 16;
#pragma unroll
    for (int hh = 0; hh < 2; hh++) { ldsm4t(ya[hh], sb + OFF_YA + yo + 64 * hh); ldsm4t(yb[hh], sb + OFF_YB + yo + 64 * hh); }
#pragma unroll
    for (int hh = 0; hh < 2; hh++) {
      uint32_t o[4];
#pragma unroll
      for (int i = 0; i < 4; i++) o[i] = hadd2(hmul2(gg[hh][i].x, hmul2(qv[hh][i], ya[hh][i])), hmul2(gg[hh][i].y, yb[hh][i]));
      stsm4(qa + 2560 * hh, o);
    }
    TL(25 + (u == 2));
    if (u) break;
  }
  bar_sync(NB_ROW0 + w, 128);
  TL(28);
  {
    uint4 v[3];
#pragma unroll
    for (int k = 0; k < 3; k++) {
      const int i = lane + 32 * k, sl = (i * 205) >> 10, c = i - 5 * sl;
      if (i < 80) v[k] = lds128(sb + OFF_TQ + (64 * w + 8 * (sl & 7) + 2 * wg + (sl >> 3)) * 80 + c * 16);
    }
#pragma unroll
    for (int k = 0; k < 3; k++) {
      const int i = lane + 32 * k, sl = (i * 205) >> 10, c = i - 5 * sl;
      if (i < 80 && c < nu)
        asm volatile("st.global.v4.u32 [%0], {%1,%2,%3,%4};" :: "l"(p.out + (size_t)(256 * rank + 32 * (2 * wg + (sl >> 3)) + 8 * w + (sl & 7)) * DCH + ch0 + 8 * c),
                     "r"(v[k].x), "r"(v[k].y), "r"(v[k].z), "r"(v[k].w) : "memory");
    }
  }
  TL(27);
  TL_DUMP();
}

typedef CUresult (*EncodeFn)(CUtensorMap*, CUtensorMapDataType, cuuint32_t, void*, const cuuint64_t*, const cuuint64_t*,
                             const cuuint32_t*, const cuuint32_t*, CUtensorMapInterleave, CUtensorMapSwizzle,
                             CUtensorMapL2promotion, CUtensorMapFloatOOBfill);

void encode(EncodeFn fn, CUtensorMap* tm, const void* ptr, int nd, const cuuint64_t* dims, const cuuint64_t* strides,
            const cuuint32_t* box, CUtensorMapSwizzle swz) {
  cuuint32_t es[4] = {1, 1, 1, 1};
  fn(tm, CU_TENSOR_MAP_DATA_TYPE_BFLOAT16, nd, const_cast<void*>(ptr), dims, strides, box, es, CU_TENSOR_MAP_INTERLEAVE_NONE,
     swz, CU_TENSOR_MAP_L2_PROMOTION_L2_128B, CU_TENSOR_MAP_FLOAT_OOB_FILL_NONE);
}
void map1(EncodeFn fn, CUtensorMap* tm, const void* ptr, int nhi) {
  const cuuint64_t dims[4] = {DCH, 4, 8, SEQ / 32}, strides[3] = {8 * DCH * 2, DCH * 2, 32 * DCH * 2};
  const cuuint32_t box[4] = {CPC, 4, 8, (cuuint32_t)nhi};
  encode(fn, tm, ptr, 4, dims, strides, box, CU_TENSOR_MAP_SWIZZLE_NONE);
}
void map2(EncodeFn fn, CUtensorMap* tm, const void* ptr, int nr) {
  const cuuint64_t dims[3] = {DCH, SEQ / 32, 32}, strides[2] = {32 * DCH * 2, DCH * 2};
  const cuuint32_t box[3] = {CPC, 8, (cuuint32_t)nr};
  encode(fn, tm, ptr, 3, dims, strides, box, CU_TENSOR_MAP_SWIZZLE_NONE);
}

}

extern "C" void kernel_launch(void* const* d_in, const int* in_sizes, int n_in, void* d_out, int out_size) {
  (void)in_sizes; (void)n_in; (void)out_size;
  static EncodeFn fn = nullptr;
  static void *tab = nullptr, *cnt = nullptr, *part = nullptr;
  if (!fn) {
    cudaGetSymbolAddress(&tab, d_tab);
    cudaGetSymbolAddress(&cnt, g_cnt);
    cudaGetSymbolAddress(&part, g_part);
    cudaDriverEntryPointQueryResult qr;
    cudaGetDriverEntryPoint("cuTensorMapEncodeTiled", (void**)&fn, cudaEnableDefault, &qr);
    cudaFuncSetAttribute(fused_kernel, cudaFuncAttributeMaxDynamicSharedMemorySize, SMEM_BYTES);
  }
  Params p;
  map1(fn, &p.tq, d_in[0], 4);
  map1(fn, &p.tk, d_in[1], 9);
  map1(fn, &p.tv, d_in[2], 8);
  map2(fn, &p.tq2, d_in[0], 32);
  p.out = (__nv_bfloat16*)d_out;
  {
    const cuuint64_t dims[4] = {32, SEQ / 32, DCH / 8, 8}, strides[3] = {64, 8 * SEQ * 2, SEQ * 2};
    const cuuint32_t box[4] = {32, 64, 5, 1};
    encode(fn, &p.th, d_in[4], 4, dims, strides, box, CU_TENSOR_MAP_SWIZZLE_64B);
  }
  p.tab = (const Tables*)tab;
  p.cnt = (unsigned*)cnt;
  p.part = (uint2*)part;
  p.tl = nullptr;
  p.q = (const __nv_bfloat16*)d_in[0];
  p.shift_k = (const __nv_bfloat16*)d_in[3];
  p.ssm_D = (const __nv_bfloat16*)d_in[5];
  p.logA = (const __nv_bfloat16*)d_in[7];
  p.Aim = (const __nv_bfloat16*)d_in[8];
  p.Cre = (const __nv_bfloat16*)d_in[9];
  p.Cim = (const __nv_bfloat16*)d_in[10];
  p.logdt = (const __nv_bfloat16*)d_in[11];
  p.Dskip = (const __nv_bfloat16*)d_in[12];
  p.gate_w = (const __nv_bfloat16*)d_in[13];
  fused_kernel<<<NCL * CS, NTHREADS, SMEM_BYTES, cudaStreamPerThread>>>(p);
}
```

```cpp
#include <cuda_runtime.h>
#include <cuda_bf16.h>
#include <cuda.h>
#include <stdint.h>

#define TIMELINE 0

namespace {

constexpr int SEQ = 2048, DCH = 576, NMODE = 128;
constexpr int CS = 8, CPC = 40, NCL = 15, NTHREADS = 512;

constexpr int YPITCH = 528;
constexpr int KTAB = 28672;
constexpr int OFF_T = 0;
constexpr int OFF_UKV = 2 * KTAB + 8192;
constexpr int OFF_UX = 3 * KTAB;
constexpr int OFF_HA = OFF_UX + 20480;
constexpr int OFF_CF = OFF_HA + 20480;
constexpr int OFF_CL = OFF_CF + 8192;
constexpr int OFF_TQ = OFF_CL + 4096;
constexpr int OFF_YA = OFF_TQ;
constexpr int OFF_TK = OFF_TQ + 21120;
constexpr int OFF_Q2 = OFF_TK;
constexpr int OFF_TV = OFF_TK + 23040;
constexpr int OFF_YB = OFF_TV + 20480;
constexpr int OFF_KC = OFF_YB + 40 * YPITCH;
constexpr int OFF_SW = OFF_KC + 3 * 1408;
constexpr int OFF_GW = OFF_SW + 320;
constexpr int OFF_SD = OFF_GW + 80;
constexpr int OFF_MB = OFF_SD + 32;
constexpr int OFF_TL = OFF_MB + 24 * 8;
constexpr int SMEM_BYTES = OFF_TL + (TIMELINE ? 2048 : 0);
static_assert(SMEM_BYTES <= 232448, "smem");
static_assert((KTAB & 1023) == 0 && (OFF_TQ & 127) == 0 && (OFF_TK & 127) == 0 && (OFF_TV & 127) == 0 && (OFF_MB & 7) == 0 && (OFF_KC & 15) == 0, "align");

enum { MB_UX = 0, MB_UKV = 5, MB_Y = 10, MB_Q2 = 15, MB_XQ = 16, MB_KV = 18, MB_HA = 19, MB_CF = 20, MB_COUNT = 21 };
enum { NB_WG0 = 1, NB_ROW0 = 5 };

constexpr double cos_turn(int m, int n) {
  m &= n - 1;
  if (m > n / 2) m = n - m;
  double sgn = 1.0;
  if (m > n / 4) { m = n / 2 - m; sgn = -1.0; }
  if (m == n / 4) return 0.0;
  const double x = 6.283185307179586476925 * m / n;
  double term = 1.0, sum = 1.0;
  for (int k = 1; k < 14; k++) { term *= -x * x / ((2 * k - 1) * (2 * k)); sum += term; }
  return sgn * sum;
}
constexpr uint32_t bf16_bits(double v) {
  if (v == 0.0) return 0;
  uint32_t sgn = 0;
  if (v < 0) { sgn = 0x8000; v = -v; }
  int e = 127;
  while (v < 1.0) { v *= 2.0; e--; }
  while (v >= 2.0) { v *= 0.5; e++; }
  const double f = v * 128.0;
  int m = (int)f;
  if (f - m > 0.5 || (f - m == 0.5 && (m & 1))) m++;
  return sgn | (uint32_t)((e << 7) + (m - 128));
}
constexpr uint32_t pair_bits(double lo, double hi) { return bf16_bits(lo) | (bf16_bits(hi) << 16); }
struct alignas(128) Tables {
  uint32_t mat[3072];
  uint32_t thr[4][128][4];
};
constexpr Tables make_tables() {
  Tables T{};
  for (int q = 0; q < 768; q++) {
    int m0 = 0, d0 = 0, d1 = 0;
    if (q < 512) {
      const int r = (q >> 6) * 8 + (q & 7), cc = (q >> 3) & 7;
      d0 = 4 * (r & 31); d1 = 2 * d0;
      m0 = 8 * (cc & 3) * d0 + ((r >> 5) == (cc >> 2) ? 0 : (r >> 5) ? 96 : 32);
    } else {
      const int r = ((q - 512) >> 5) * 8 + (q & 7), pc = (q >> 3) & 3;
      d0 = 4 * (8 * (r >> 4) + (r & 7)) + 1; d1 = 8 * d0;
      m0 = 2 * pc * d0 + ((r & 8) ? 32 : 0);
    }
    for (int e = 0; e < 4; e++) T.mat[4 * q + e] = pair_bits(cos_turn(m0 + e * d1, 128), cos_turn(m0 + e * d1 + d0, 128));
  }
  for (int tid = 0; tid < 128; tid++) {
    const int kk = 4 * (tid >> 2) + 1, t = tid & 3;
    for (int q = 0; q < 4; q++) {
      const int m = (8 * q + 2 * t) * kk;
      T.thr[q >> 1][tid][2 * (q & 1)] = pair_bits(cos_turn(m, 128), cos_turn(m + kk, 128));
      T.thr[q >> 1][tid][2 * (q & 1) + 1] = pair_bits(cos_turn(m + 32, 128), cos_turn(m + kk + 32, 128));
      T.thr[2][tid][q] = pair_bits(cos_turn(m, 4096), cos_turn(m + kk, 4096));
      T.thr[3][tid][q] = pair_bits(cos_turn(m + 3072, 4096), cos_turn(m + kk + 3072, 4096));
    }
  }
  return T;
}
__device__ const Tables d_tab = make_tables();

struct Params {
  const __nv_bfloat16 *logA, *Aim, *Cre, *Cim, *logdt;
  const Tables* tab;
  unsigned* cnt;
  const __nv_bfloat16 *Dskip, *shift_k, *ssm_D, *gate_w, *q;
  uint2* part;
  __nv_bfloat16* out;
  unsigned* tl;
  CUtensorMap tq, tk, tv, th, tq2;
};

__device__ uint2 g_part[NCL * SEQ];
__device__ unsigned g_cnt[CS * 32];
#define TL(i) do {} while (0)
#define TL_INIT() do {} while (0)
#define TL_DUMP() do {} while (0)

__device__ __forceinline__ uint32_t lds16(uint32_t a) { uint32_t v; asm volatile("ld.shared.u16 %0, [%1];" : "=r"(v) : "r"(a) : "memory"); return v; }
__device__ __forceinline__ uint2 lds64(uint32_t a) { uint2 v; asm volatile("ld.shared.v2.u32 {%0,%1}, [%2];" : "=r"(v.x), "=r"(v.y) : "r"(a) : "memory"); return v; }
__device__ __forceinline__ uint4 lds128(uint32_t a) { uint4 v; asm volatile("ld.shared.v4.u32 {%0,%1,%2,%3}, [%4];" : "=r"(v.x), "=r"(v.y), "=r"(v.z), "=r"(v.w) : "r"(a) : "memory"); return v; }
__device__ __forceinline__ void sts16(uint32_t a, uint32_t v) { asm volatile("st.shared.u16 [%0], %1;" :: "r"(a), "r"(v) : "memory"); }
__device__ __forceinline__ void sts32(uint32_t a, uint32_t v) { asm volatile("st.shared.u32 [%0], %1;" :: "r"(a), "r"(v) : "memory"); }
__device__ __forceinline__ void sts64(uint32_t a, uint32_t x, uint32_t y) { asm volatile("st.shared.v2.u32 [%0], {%1,%2};" :: "r"(a), "r"(x), "r"(y) : "memory"); }
__device__ __forceinline__ void sts128(uint32_t a, uint32_t x, uint32_t y, uint32_t z, uint32_t w) { asm volatile("st.shared.v4.u32 [%0], {%1,%2,%3,%4};" :: "r"(a), "r"(x), "r"(y), "r"(z), "r"(w) : "memory"); }
__device__ __forceinline__ void ldsm4t(uint32_t (&r)[4], uint32_t a) { asm volatile("ldmatrix.sync.aligned.m8n8.x4.trans.shared.b16 {%0,%1,%2,%3}, [%4];" : "=r"(r[0]), "=r"(r[1]), "=r"(r[2]), "=r"(r[3]) : "r"(a) : "memory"); }
__device__ __forceinline__ void ldsm2t(uint32_t& r0, uint32_t& r1, uint32_t a) { asm volatile("ldmatrix.sync.aligned.m8n8.x2.trans.shared.b16 {%0,%1}, [%2];" : "=r"(r0), "=r"(r1) : "r"(a) : "memory"); }
__device__ __forceinline__ void ldsm4(uint32_t (&r)[4], uint32_t a) { asm volatile("ldmatrix.sync.aligned.m8n8.x4.shared.b16 {%0,%1,%2,%3}, [%4];" : "=r"(r[0]), "=r"(r[1]), "=r"(r[2]), "=r"(r[3]) : "r"(a) : "memory"); }
__device__ __forceinline__ void stsm4(uint32_t a, const uint32_t (&r)[4]) { asm volatile("stmatrix.sync.aligned.m8n8.x4.shared.b16 [%0], {%1,%2,%3,%4};" :: "r"(a), "r"(r[0]), "r"(r[1]), "r"(r[2]), "r"(r[3]) : "memory"); }
__device__ __forceinline__ uint32_t pack(float lo, float hi) { uint32_t r; asm("cvt.rn.bf16x2.f32 %0, %1, %2;" : "=r"(r) : "f"(hi), "f"(lo)); return r; }
__device__ __forceinline__ float blo(uint32_t v) { return __uint_as_float(v << 16); }
__device__ __forceinline__ float bhi(uint32_t v) { return __uint_as_float(v & 0xffff0000u); }
__device__ __forceinline__ float bf16r(float x) { return blo(pack(x, 0.f)); }
__device__ __forceinline__ uint32_t hmul2(uint32_t a, uint32_t b) { uint32_t r; asm("mul.rn.bf16x2 %0, %1, %2;" : "=r"(r) : "r"(a), "r"(b)); return r; }
__device__ __forceinline__ uint32_t hadd2(uint32_t a, uint32_t b) { uint32_t r; asm("add.rn.bf16x2 %0, %1, %2;" : "=r"(r) : "r"(a), "r"(b)); return r; }
__device__ __forceinline__ uint32_t hfma2(uint32_t a, uint32_t b, uint32_t c) { uint32_t r; asm("fma.rn.bf16x2 %0, %1, %2, %3;" : "=r"(r) : "r"(a), "r"(b), "r"(c)); return r; }
__device__ __forceinline__ uint32_t prmt(uint32_t a, uint32_t b, uint32_t s) { return __byte_perm(a, b, s); }
__device__ __forceinline__ uint32_t ldraw(const __nv_bfloat16* p) { uint32_t v; asm volatile("ld.global.nc.u16 %0, [%1];" : "=r"(v) : "l"(p)); return v; }
__device__ __forceinline__ uint4 ldg128(const void* p) { uint4 v; asm volatile("ld.global.nc.v4.u32 {%0,%1,%2,%3}, [%4];" : "=r"(v.x), "=r"(v.y), "=r"(v.z), "=r"(v.w) : "l"(p)); return v; }
__device__ __forceinline__ void bar_sync(int id, int n) { asm volatile("bar.sync %0, %1;" :: "r"(id), "r"(n) : "memory"); }
__device__ __forceinline__ void bar_arrive(int id, int n) { asm volatile("bar.arrive %0, %1;" :: "r"(id), "r"(n) : "memory"); }
__device__ __forceinline__ void cluster_arrive() { asm volatile("barrier.cluster.arrive.relaxed.aligned;" ::: "memory"); }
__device__ __forceinline__ void cluster_wait() { asm volatile("barrier.cluster.wait.aligned;" ::: "memory"); }
__device__ __forceinline__ void fence_async() { asm volatile("fence.proxy.async.shared::cta;" ::: "memory"); }
__device__ __forceinline__ void fence_mbinit() { asm volatile("fence.mbarrier_init.release.cluster;" ::: "memory"); }
__device__ __forceinline__ uint32_t mapa(uint32_t a, uint32_t rank) { uint32_t r; asm("mapa.shared::cluster.u32 %0, %1, %2;" : "=r"(r) : "r"(a), "r"(rank)); return r; }
__device__ __forceinline__ void st_async4(uint32_t a, uint32_t x, uint32_t y, uint32_t z, uint32_t w, uint32_t mbar) {
  asm volatile("st.async.weak.shared::cluster.mbarrier::complete_tx::bytes.v4.b32 [%0], {%1,%2,%3,%4}, [%5];"
               :: "r"(a), "r"(x), "r"(y), "r"(z), "r"(w), "r"(mbar) : "memory");
}
__device__ __forceinline__ void bulk_dsmem(uint32_t dst, uint32_t src, uint32_t mbar) {
  asm volatile("cp.async.bulk.shared::cluster.shared::cta.mbarrier::complete_tx::bytes [%0], [%1], 512, [%2];" :: "r"(dst), "r"(src), "r"(mbar) : "memory");
}
__device__ __forceinline__ void mbar_init(uint32_t m, uint32_t cnt) { asm volatile("mbarrier.init.shared::cta.b64 [%0], %1;" :: "r"(m), "r"(cnt) : "memory"); }
__device__ __forceinline__ void mbar_expect(uint32_t m, uint32_t bytes) { asm volatile("mbarrier.arrive.expect_tx.shared::cta.b64 _, [%0], %1;" :: "r"(m), "r"(bytes) : "memory"); }
__device__ __forceinline__ void mbar_wait(uint32_t m) {
  uint32_t done;
  int it = 0;
  do {
    asm volatile("{.reg .pred p; mbarrier.try_wait.parity.shared::cta.b64 p, [%1], 0; selp.u32 %0, 1, 0, p;}" : "=r"(done) : "r"(m) : "memory");
    if (++it > (1 << 22)) __trap();
  } while (!done);
}
__device__ __forceinline__ void tma_load4(uint32_t dst, const CUtensorMap* tm, int c0, int c1, int c2, int c3, uint32_t mbar) {
  asm volatile("cp.async.bulk.tensor.4d.shared::cluster.global.mbarrier::complete_tx::bytes [%0], [%1, {%3, %4, %5, %6}], [%2];"
               :: "r"(dst), "l"(tm), "r"(mbar), "r"(c0), "r"(c1), "r"(c2), "r"(c3) : "memory");
}
__device__ __forceinline__ void tma_load3(uint32_t dst, const CUtensorMap* tm, int c0, int c1, int c2, uint32_t mbar) {
  asm volatile("cp.async.bulk.tensor.3d.shared::cluster.global.mbarrier::complete_tx::bytes [%0], [%1, {%3, %4, %5}], [%2];"
               :: "r"(dst), "l"(tm), "r"(mbar), "r"(c0), "r"(c1), "r"(c2) : "memory");
}
__device__ __forceinline__ void tma_store3(const CUtensorMap* tm, int c0, int c1, int c2, uint32_t src) {
  asm volatile("cp.async.bulk.tensor.3d.global.shared::cta.bulk_group [%0, {%2, %3, %4}], [%1];"
               :: "l"(tm), "r"(src), "r"(c0), "r"(c1), "r"(c2) : "memory");
}
__device__ __forceinline__ void wg_fence() { asm volatile("wgmma.fence.sync.aligned;" ::: "memory"); }
__device__ __forceinline__ void wg_commit() { asm volatile("wgmma.commit_group.sync.aligned;" ::: "memory"); }
template <int N> __device__ __forceinline__ void wg_wait() { asm volatile("wgmma.wait_group.sync.aligned %0;" :: "n"(N) : "memory"); }
template <int N> __device__ __forceinline__ void tie_all(float (&x)[N]) {
#pragma unroll
  for (int i = 0; i < N; i++) asm volatile("" : "+f"(x[i]) :: "memory");
}
#define R16(C, d) C(d[0]), C(d[1]), C(d[2]), C(d[3]), C(d[4]), C(d[5]), C(d[6]), C(d[7]), C(d[8]), C(d[9]), C(d[10]), C(d[11]), C(d[12]), C(d[13]), C(d[14]), C(d[15])
#define R32(C, d) R16(C, d), R16(C, (d + 16))
#define P16 "{%0,%1,%2,%3,%4,%5,%6,%7,%8,%9,%10,%11,%12,%13,%14,%15}"
#define P32 "{%0,%1,%2,%3,%4,%5,%6,%7,%8,%9,%10,%11,%12,%13,%14,%15,%16,%17,%18,%19,%20,%21,%22,%23,%24,%25,%26,%27,%28,%29,%30,%31}"
template <int SD, int TB, int OFF> __device__ __forceinline__ void rs64(float* d, const uint32_t* a, uint64_t db) {
  if (SD) asm volatile("{.reg .b64 db; add.s64 db, %36, %37; wgmma.mma_async.sync.aligned.m64n64k16.f32.bf16.bf16 " P32 ", {%32,%33,%34,%35}, db, 1, 1, 1, %38;}"
                       : R32("+f", d) : "r"(a[0]), "r"(a[1]), "r"(a[2]), "r"(a[3]), "l"(db), "n"(OFF), "n"(TB));
  else asm volatile("{.reg .b64 db; add.s64 db, %36, %37; wgmma.mma_async.sync.aligned.m64n64k16.f32.bf16.bf16 " P32 ", {%32,%33,%34,%35}, db, 0, 1, 1, %38;}"
                    : R32("=f", d) : "r"(a[0]), "r"(a[1]), "r"(a[2]), "r"(a[3]), "l"(db), "n"(OFF), "n"(TB));
}
template <int SD, int OFFA, int OFFB> __device__ __forceinline__ void ss32(float* d, uint64_t da, uint64_t db) {
  if (SD) asm volatile("{.reg .b64 da, db; add.s64 da, %16, %18; add.s64 db, %17, %19; wgmma.mma_async.sync.aligned.m64n32k16.f32.bf16.bf16 " P16 ", da, db, 1, 1, 1, 1, 1;}"
                       : R16("+f", d) : "l"(da), "l"(db), "n"(OFFA), "n"(OFFB));
  else asm volatile("{.reg .b64 da, db; add.s64 da, %16, %18; add.s64 db, %17, %19; wgmma.mma_async.sync.aligned.m64n32k16.f32.bf16.bf16 " P16 ", da, db, 0, 1, 1, 1, 1;}"
                    : R16("=f", d) : "l"(da), "l"(db), "n"(OFFA), "n"(OFFB));
}
template <int KS> __device__ __forceinline__ void kgen_mma(float (&c)[24], uint64_t da) {
  asm volatile("{.reg .b64 da, db; add.s64 da, %24, %25; add.s64 db, %24, %26;\n"
               "wgmma.mma_async.sync.aligned.m64n48k16.f32.bf16.bf16 {%0,%1,%2,%3,%4,%5,%6,%7,%8,%9,%10,%11,%12,%13,%14,%15,%16,%17,%18,%19,%20,%21,%22,%23}, da, db, %27, 1, 1, 1, 1;}"
               : R16("+f", c), "+f"(c[16]), "+f"(c[17]), "+f"(c[18]), "+f"(c[19]), "+f"(c[20]), "+f"(c[21]), "+f"(c[22]), "+f"(c[23])
               : "l"(da), "n"(8 * KS), "n"(8 * KS + 512), "n"(KS ? 1 : 0));
  if constexpr (KS < 7) kgen_mma<KS + 1>(c, da);
}
__device__ __forceinline__ uint64_t desc_lo(uint32_t a) { return (uint64_t)((a & 0x3FFFF) >> 4); }
__device__ __forceinline__ void stage1(float (&D)[32], const uint32_t (&A1)[8], uint32_t src) {
  const uint64_t du = desc_lo(src) | (128ull << 16) | (32ull << 32) | (2ull << 62);
  rs64<0, 1, 0>(D, A1, du); rs64<1, 1, 64>(D, A1 + 4, du);
}
template <int INV> __device__ __forceinline__ void stage2(float (&X)[32], const uint32_t (&F)[16], uint32_t cf) {
  constexpr int KS = INV ? 16 : 128, TB = INV ? 0 : 1;
  const uint64_t dc = desc_lo(cf) | (INV ? (8ull << 16) | (64ull << 32) : (64ull << 16) | (8ull << 32));
  rs64<0, TB, 0>(X, F, dc); rs64<1, TB, KS>(X, F + 4, dc); rs64<1, TB, 2 * KS>(X, F + 8, dc); rs64<1, TB, 3 * KS>(X, F + 12, dc);
}
__device__ __forceinline__ void fwd_mid(uint32_t (&F)[16], const float (&D)[32], const uint32_t (&tp)[12]) {
#pragma unroll
  for (int j = 0; j < 4; j++)
#pragma unroll
    for (int b = 0; b < 2; b++) {
      const int i = 4 * j + 16 * b;
      const uint32_t ar = pack(D[i], D[i + 1]), ai = pack(D[i + 2], D[i + 3]);
      F[2 * j + b] = hfma2(ar, tp[3 * j], hmul2(ai, tp[3 * j + 2]));
      F[8 + 2 * j + b] = hfma2(ar, tp[3 * j + 1], hmul2(ai, tp[3 * j]));
    }
}

struct cf { float x, y; };
__device__ __forceinline__ cf cmul(cf a, cf b) { cf r; r.x = fmaf(a.x, b.x, -a.y * b.y); r.y = fmaf(a.x, b.y, a.y * b.x); return r; }
__device__ __forceinline__ cf cexp_p(float lr2, float lt, float p) {
  float m = exp2f(lr2 * p);
  float t = lt * p;
  t = (t - rintf(t)) * 6.283185307179586f;
  cf r; r.x = m * __cosf(t); r.y = m * __sinf(t); return r;
}
__device__ __forceinline__ void store8(uint32_t a, const cf (&v)[8]) {
  sts128(a, pack(v[0].x, v[1].x), pack(v[2].x, v[3].x), pack(v[4].x, v[5].x), pack(v[6].x, v[7].x));
  sts128(a + KTAB / 2, pack(v[0].y, v[1].y), pack(v[2].y, v[3].y), pack(v[4].y, v[5].y), pack(v[6].y, v[7].y));
}
__device__ __forceinline__ float sigmoidf_(float s) { return 1.f / (1.f + __expf(-s)); }

__global__ void __cluster_dims__(CS, 1, 1) __launch_bounds__(NTHREADS, 1) fused_kernel(const __grid_constant__ Params p) {
  extern __shared__ __align__(1024) uint8_t smem[];
  TL_INIT();
  TL(31);
  const int wid = __shfl_sync(0xffffffffu, threadIdx.x >> 5, 0);
  uint32_t pla[2], pai[2], pcr[2], pci[2], pdt[2];
  if (threadIdx.x < 384) {
#pragma unroll
    for (int r = 0; r < 2; r++) {
      int ch = (blockIdx.x >> 3) * CPC + (blockIdx.x & 7) + 8 * (threadIdx.x >> 7) + 24 * r;
      if (ch >= DCH) ch = 0;
      const int o = ch * NMODE + (threadIdx.x & 127);
      pla[r] = ldraw(p.logA + o); pdt[r] = ldraw(p.logdt + ch); pai[r] = ldraw(p.Aim + o); pcr[r] = ldraw(p.Cre + o); pci[r] = ldraw(p.Cim + o);
    }
  }
  const uint32_t sb = (uint32_t)__cvta_generic_to_shared(smem);
  const uint32_t mb = sb + OFF_MB;
  const int wg = wid >> 2, w = wid & 3;
  const int tid = threadIdx.x & 127, lane = tid & 31, g = lane >> 2, t = lane & 3;
  const int cl = blockIdx.x >> 3, rank = blockIdx.x & 7;
  const int ch0 = cl * CPC;
  const int nu = min(5, (DCH - ch0) >> 3);

  if (wg < 3) {
    cluster_arrive();
    uint32_t A1[8], tp[12];
    {
      const uint4 a = ldg128(p.tab->thr[0][tid]), b = ldg128(p.tab->thr[1][tid]), c = ldg128(p.tab->thr[2][tid]), d = ldg128(p.tab->thr[3][tid]);
      A1[0] = a.x; A1[1] = a.y; A1[2] = a.z; A1[3] = a.w; A1[4] = b.x; A1[5] = b.y; A1[6] = b.z; A1[7] = b.w;
      tp[0] = c.x; tp[3] = c.y; tp[6] = c.z; tp[9] = c.w; tp[2] = d.x; tp[5] = d.y; tp[8] = d.z; tp[11] = d.w;
      tp[1] = tp[4] = tp[7] = tp[10] = 0;
    }
    TL(0);
    const uint32_t tab = sb + OFF_T + wg * KTAB;
#pragma unroll 1
    for (int job = 0; job < 4; job++) {
      const bool isA = job >= (wg == 2 ? 1 : 2);
      const int u = wg == 2 ? (job ? 2 * job - 2 : 2) : job < 2 ? wg + 3 * job : job == 2 ? 2 * wg + 1 : 9;

      if (!isA && u < nu) {
        const float la = blo(job ? pla[1] : pla[0]), ai = blo(job ? pai[1] : pai[0]), cr = blo(job ? pcr[1] : pcr[0]), ci = blo(job ? pci[1] : pci[0]);
        const float dt = bf16r(expf(blo(job ? pdt[1] : pdt[0])));
        const float lr2 = (-bf16r(expf(la)) * dt) * 1.4426950408889634f;
        const float lt = (ai * dt) * 0.15915494309189535f;
        const uint32_t row = tab + tid * 16;
        if (lr2 != 123.f) TL(16 + 4 * job);
        {
          const cf w1 = cexp_p(lr2, lt, 8.f);
          cf v[8];
          v[0].x = 1.f; v[0].y = 0.f; v[1] = w1; v[2] = cmul(w1, w1); v[3] = cmul(v[2], w1);
          const cf w4 = cmul(v[2], v[2]);
          v[4] = w4; v[5] = cmul(v[1], w4); v[6] = cmul(v[2], w4); v[7] = cmul(v[3], w4);
          const cf w8 = cmul(w4, w4);
          store8(row, v);
#pragma unroll
          for (int c = 1; c < 4; c++) {
#pragma unroll
            for (int i = 0; i < 8; i++) v[i] = (c == 1 && i == 0) ? w8 : cmul(v[i], w8);
            store8(row + 2048 * c, v);
          }
        }
        {
          cf z1 = cexp_p(lr2, lt, 1.f), Z = cexp_p(lr2, lt, 256.f);
          z1.y = -z1.y; Z.y = -Z.y;
          const cf z2 = cmul(z1, z1);
          cf h[8], v[8];
          h[0].x = 2.f * cr * dt; h[0].y = -2.f * ci * dt;
          h[1] = cmul(h[0], z1);
#pragma unroll
          for (int i = 2; i < 8; i++) h[i] = cmul(h[i - 2], z2);
          store8(row + 4 * 2048, h);
          v[0] = cmul(h[0], Z); v[1] = cmul(h[2], Z); v[2] = cmul(h[4], Z); v[3] = cmul(h[6], Z);
          v[4] = cmul(v[0], Z); v[5] = cmul(v[2], Z); v[6] = cmul(v[4], Z); v[7] = cmul(v[5], Z);
          store8(row + 5 * 2048, v);
          const cf Z2 = cmul(Z, Z);
          h[0] = cmul(v[4], Z2); h[1] = cmul(v[6], Z2); h[2] = cmul(h[0], Z2); h[3] = cmul(h[1], Z2); h[4] = cmul(h[2], Z2);
          h[5].x = h[5].y = h[6].x = h[6].y = h[7].x = h[7].y = 0.f;
          store8(row + 6 * 2048, h);
        }
        TL(17 + 4 * job);
        fence_async();
        bar_sync(NB_WG0 + wg, 128);
        float c[24];
        wg_fence();
        kgen_mma<0>(c, desc_lo(tab) | ((uint64_t)(KTAB / 32) << 16) | (64ull << 32));
        wg_commit();
        uint32_t kid[8];
        {
          float lf = __uint_as_float(0x4b000000u | (8 * tid)) - 8388608.f;
          asm volatile("" : "+f"(lf));
          const float lo = tid < 16 ? lf + 128.f : lf;
          const uint32_t sub = tid < 16 ? 0x42804300u : 0x42804280u;
#pragma unroll
          for (int i = 0; i < 8; i++) kid[i] = 2 * (pack(lo + i, lf + (1024 + i)) - sub);
        }
        wg_wait<0>(); tie_all(c);
        const uint32_t kc = sb + OFF_KC + wg * 1408;
        {
          const int a = 8 * w + g;
          sts32(kc + 4 * (4 * a + t), pack(c[0] + c[6], c[1] + c[7]));
          sts32(kc + 4 * (t < 2 ? 128 + 2 * a + t : 128 + 32 * t + a), pack(c[8] + c[14], c[9] + c[15]));
          if (t < 3) {
            const uint32_t p0 = pack(c[16] + c[22], c[17] + c[23]);
            sts16(kc + 2 * (512 + 64 * t + a), p0);
            sts16(kc + 2 * (544 + 64 * t + a), p0 >> 16);
          }
        }
        TL(18 + 4 * job);
        bar_sync(NB_WG0 + wg, 128);
        uint32_t v[2][8];
#pragma unroll
        for (int i = 0; i < 8; i++) { v[0][i] = lds16(kc + (kid[i] & 0xffffu)); v[1][i] = lds16(kc + (kid[i] >> 16)); }
#pragma unroll
        for (int cc = 0; cc < 2; cc++)
          sts128(tab + 2048 * cc + 16 * (tid ^ ((tid >> 3) & 3)), prmt(v[cc][0], v[cc][1], 0x5410), prmt(v[cc][2], v[cc][3], 0x5410),
                 prmt(v[cc][4], v[cc][5], 0x5410), prmt(v[cc][6], v[cc][7], 0x5410));
        fence_async();
        if (job) bar_sync(NB_WG0 + wg, 128);
      }
      if (job == 0) {
        cluster_wait();
        cluster_arrive();
        bar_sync(NB_WG0 + wg, 128);
        mbar_wait(mb + 8 * MB_CF);
#pragma unroll
        for (int j = 0; j < 4; j++) asm volatile("xor.b32 %0, %1, 0x80008000;" : "=r"(tp[3 * j + 1]) : "r"(tp[3 * j + 2]));
      }
      if (u >= nu) continue;
      TL(1 + job);
      float D[32], H[32], X[32];
      uint32_t F[16];
      if (isA) mbar_wait(mb + 8 * MB_HA);
      wg_fence();
      stage1(D, A1, isA ? sb + OFF_HA + u * 4096 : tab);
      wg_commit();
      wg_wait<0>(); tie_all(D);
      fwd_mid(F, D, tp);
      wg_fence();
      stage2<0>(H, F, sb + OFF_CF);
      wg_commit();
      mbar_wait(mb + 8 * ((isA ? MB_UKV : MB_UX) + u));
      fence_async();
      TL(5 + job);
      wg_fence();
      stage1(D, A1, sb + (isA ? OFF_UKV : OFF_UX) + u * 4096);
      wg_commit();
      wg_wait<0>(); tie_all(D); tie_all(H);
      fwd_mid(F, D, tp);
      wg_fence();
      stage2<0>(X, F, sb + OFF_CF);
      wg_commit();
      {
        const float dsk = blo(lds16(sb + OFF_SD + (isA ? 10 : 0) + 2 * u));
#pragma unroll
        for (int j = 0; j < 4; j++) { H[4 * j] += dsk; H[4 * j + 1] += dsk; }
      }
      wg_wait<0>(); tie_all(X);
#pragma unroll
      for (int j = 0; j < 4; j++) {
        float pr[2], pi[2], qr[2], qi[2];
#pragma unroll
        for (int n = 0; n < 2; n++) {
          const int i = 4 * j + n;
          pr[n] = fmaf(X[i], H[i], -X[i + 16] * H[i + 16]);
          pi[n] = fmaf(X[i], H[i + 16], X[i + 16] * H[i]);
          qr[n] = fmaf(X[i + 2], H[i], fmaf(-X[i + 18], H[i + 16], fmaf(X[i], H[i + 2], fmaf(-X[i + 16], H[i + 18], -pi[n]))));
          qi[n] = fmaf(X[i + 2], H[i + 16], fmaf(X[i + 18], H[i], fmaf(X[i], H[i + 18], fmaf(X[i + 16], H[i + 2], pr[n]))));
        }
        F[2 * j] = pack(pr[0], pr[1]); F[2 * j + 1] = pack(qr[0], qr[1]); F[8 + 2 * j] = pack(pi[0], pi[1]); F[9 + 2 * j] = pack(qi[0], qi[1]);
      }
      wg_fence();
      stage2<1>(H, F, sb + OFF_CF);
      wg_commit();
      wg_wait<0>(); tie_all(H);
      {
        const uint32_t va = tab + (16 * w + (lane & 15)) * 128;
        const int vx = (lane >> 4) ^ (lane & 7);
#pragma unroll
        for (int j = 0; j < 4; j++) {
          uint32_t V[4];
#pragma unroll
          for (int b = 0; b < 2; b++) {
            const int i = 4 * j + 2 * b;
            const uint32_t er = pack(H[i], H[i + 1]), ei = pack(H[i + 16], H[i + 17]);
            V[2 * b] = hfma2(er, tp[3 * j], hmul2(ei, tp[3 * j + 1]));
            V[2 * b + 1] = hfma2(ei, tp[3 * j], hmul2(er, tp[3 * j + 2]));
          }
          stsm4(va + ((vx ^ (2 * j)) << 4), V);
        }
      }
      fence_async();
      bar_sync(NB_WG0 + wg, 128);
      float O[16];
      {
        const uint64_t dv = desc_lo(tab) | (1ull << 16) | (64ull << 32) | (1ull << 62);
        const uint64_t dl = desc_lo(sb + OFF_CL) | (32ull << 16) | (8ull << 32);
        wg_fence();
        ss32<0, 0, 0>(O, dv, dl); ss32<1, 128, 64>(O, dv, dl); ss32<1, 256, 128>(O, dv, dl); ss32<1, 384, 192>(O, dv, dl);
        wg_commit();
      }
      wg_wait<0>(); tie_all(O);
      {
        const uint32_t stg = sb + (isA ? OFF_UKV : OFF_UX) + u * 4096, co = ((8 * w + g) ^ (2 * t)) * 16;
        const uint32_t yo = (isA ? OFF_YA : OFF_YB) + (8 * u + rank) * YPITCH, ym = OFF_MB + 8 * (MB_Y + u);
        const uint32_t a0 = pack(O[0], O[1]), a1 = pack(O[4], O[5]), a2 = pack(O[8], O[9]), a3 = pack(O[12], O[13]);
        const uint32_t b0 = pack(O[2], O[3]), b1 = pack(O[6], O[7]), b2 = pack(O[10], O[11]), b3 = pack(O[14], O[15]);
        sts128(stg + t * 512 + co, a0, a1, a2, a3);
        sts128(stg + t * 512 + 2048 + co, b0, b1, b2, b3);
        if (t == (rank & 3)) {
          if (rank < 4) st_async4(sb + yo + co, a0, a1, a2, a3, sb + ym); else st_async4(sb + yo + co, b0, b1, b2, b3, sb + ym);
        }
        fence_async();
        bar_sync(NB_WG0 + wg, 128);
        if (lane == 0) {
#pragma unroll
          for (int k = 0; k < 2; k++) {
            const int d = 2 * w + k;
            if (d != rank) { const uint32_t rb = mapa(sb, d); bulk_dsmem(rb + yo, stg + d * 512, rb + ym); }
          }
        }
        __syncwarp();
      }
      TL(9 + job);
    }
    cluster_wait();
  } else {
    if (lane == 0) {
#pragma unroll
      for (int i = 0; i < 4; i++) mbar_init(mb + 8 * (4 * w + i), 4 * w + i == MB_Q2 ? 5 : 1);
      mbar_init(mb + 8 * (MB_XQ + w), 1);
      if (w == 3) mbar_init(mb + 8 * MB_CF, 2);
      fence_mbinit();
      if (w == 3) {
        mbar_expect(mb + 8 * MB_CF, 12288);
        asm volatile("cp.async.bulk.shared::cluster.global.mbarrier::complete_tx::bytes [%0], [%1], %2, [%3];"
                     :: "r"(sb + OFF_CF), "l"(p.tab->mat), "r"(12288), "r"(mb + 8 * MB_CF) : "memory");
      }
#pragma unroll
      for (int i = 0; i < 4; i++) { const int b = 4 * w + i; mbar_expect(mb + 8 * b, b == MB_Q2 ? 20480 : b >= MB_Y ? 8192 : 4096); }
      mbar_expect(mb + 8 * (MB_XQ + w), w < 2 ? 10240 : w == 2 ? 23040 + 20480 : 20480);
    }
    __syncwarp();
    cluster_arrive();
    uint32_t tag = 0;
    if (w == 0) {
      if (lane < 2) asm volatile("atom.relaxed.gpu.global.add.u32 %0, [%1], %2;" : "=r"(tag) : "l"(&p.cnt[rank * 32 + lane]), "r"(cl == 0 ? 16 - (NCL - 1) : 1) : "memory");
      if (lane == 0) { tma_load4(sb + OFF_TQ, &p.tq, ch0, 0, 0, 8 * rank, mb + 8 * MB_XQ); TL(20); }
    } else if (w == 1) {
      uint32_t d = 0;
      const int u = lane < 5 ? lane : lane - 5;
      if (lane < 10 && u < nu) d = ldraw((lane < 5 ? p.Dskip : p.ssm_D) + ch0 + 8 * u + rank);
      if (lane == 0) tma_load4(sb + OFF_TQ + 10240, &p.tq, ch0, 0, 0, 8 * rank + 4, mb + 8 * (MB_XQ + 1));
      if (lane < 10) sts16(sb + OFF_SD + 2 * lane, d);
      __syncwarp();
      if (lane == 0) asm volatile("mbarrier.arrive.shared::cta.b64 _, [%0];" :: "r"(mb + 8 * MB_CF) : "memory");
    } else {
      uint2 swv = make_uint2(0, 0);
      uint32_t gwv = 0;
      const int c = tid - 64;
      if (c < 40 && ch0 + c < DCH) { swv = __ldg((const uint2*)(p.shift_k + (size_t)(ch0 + c) * 4)); gwv = ldraw(p.gate_w + ch0 + c); }
      if (c < 40) { sts64(sb + OFF_SW + 8 * c, swv.x, swv.y); sts16(sb + OFF_GW + 2 * c, gwv); }
      if (c == 0) {
        tma_load4(sb + OFF_TK, &p.tk, ch0, 0, 0, 8 * rank - 1, mb + 8 * MB_KV);
        tma_load4(sb + OFF_TV, &p.tv, ch0, 0, 0, 8 * rank, mb + 8 * MB_KV);
        TL(20);
      }
    }
    __syncwarp();
    TL(0);
    const int mi = lane >> 3, tq = (lane & 7) >> 1, jj = lane & 1;
    const uint32_t toff = (4 * (2 * mi + jj) + tq) * 80;
    const uint32_t uoff = 16 * (4 * w + (t ^ (w >> 1)));
    const uint32_t rb0 = mapa(sb, 2 * w), rb1 = mapa(sb, 2 * w + 1);
    auto put = [&](uint32_t stage, uint32_t dst, uint32_t mbar, uint32_t off, const uint32_t (&v)[4]) {
      if (g == rank) st_async4(dst + 512 * rank + off, v[0], v[1], v[2], v[3], mbar);
      else sts128(stage + g * YPITCH + off, v[0], v[1], v[2], v[3]);
    };
    auto send = [&](int stage, int dst, int mbar) {
      if (2 * w != rank) bulk_dsmem(rb0 + dst + 512 * rank, sb + stage + 2 * w * YPITCH, rb0 + mbar);
      if (2 * w + 1 != rank) bulk_dsmem(rb1 + dst + 512 * rank, sb + stage + (2 * w + 1) * YPITCH, rb1 + mbar);
    };
    cluster_wait();
    cluster_arrive();
    if (tid == 64) tma_load4(sb + OFF_HA, &p.th, 0, 0, 5 * cl, rank, mb + 8 * MB_HA);
    __syncwarp();
    mbar_wait(mb + 8 * MB_XQ);
    mbar_wait(mb + 8 * (MB_XQ + 1));
    TL(1);
    {
      uint32_t xr[5][2][4];
#pragma unroll
      for (int u = 0; u < 5; u++) { ldsm4t(xr[u][0], sb + OFF_TQ + w * 2560 + toff + 16 * u); ldsm4t(xr[u][1], sb + OFF_TQ + (w + 4) * 2560 + toff + 16 * u); }
#pragma unroll
      for (int u = 0; u < 5; u++) {
        put(sb + OFF_YB + 8 * u * YPITCH, sb + OFF_UX + u * 4096, mb + 8 * (MB_UX + u), uoff, xr[u][0]);
        put(sb + OFF_YB + 8 * u * YPITCH, sb + OFF_UX + u * 4096, mb + 8 * (MB_UX + u), (uoff ^ 32) + 256, xr[u][1]);
      }
    }
    if (tid == 1) sts32(sb + OFF_MB + 8 * MB_COUNT, tag);
    fence_async();
    bar_sync(NB_WG0 + 3, 128);
    if (lane == 0) {
#pragma unroll 1
      for (int u = 0; u < nu; u++) send(OFF_YB + 8 * u * YPITCH, OFF_UX + u * 4096, OFF_MB + 8 * (MB_UX + u));
    }
    __syncwarp();
    TL(2);
    tag = (lds64(sb + OFF_MB + 8 * MB_COUNT).x >> 4) + 1;
    {
      float s0 = 0.f, s1 = 0.f;
#pragma unroll
      for (int j = 0; j < 5; j++) {
        const uint4 gw = lds128(sb + OFF_GW + 16 * j);
        const uint4 x0 = lds128(sb + OFF_TQ + tid * 80 + 16 * j), x1 = lds128(sb + OFF_TQ + (tid + 128) * 80 + 16 * j);
        uint32_t m0 = hmul2(x0.x, gw.x), m1 = hmul2(x0.y, gw.y), m2 = hmul2(x0.z, gw.z), m3 = hmul2(x0.w, gw.w);
        s0 += ((blo(m0) + bhi(m0)) + (blo(m1) + bhi(m1))) + ((blo(m2) + bhi(m2)) + (blo(m3) + bhi(m3)));
        m0 = hmul2(x1.x, gw.x); m1 = hmul2(x1.y, gw.y); m2 = hmul2(x1.z, gw.z); m3 = hmul2(x1.w, gw.w);
        s1 += ((blo(m0) + bhi(m0)) + (blo(m1) + bhi(m1))) + ((blo(m2) + bhi(m2)) + (blo(m3) + bhi(m3)));
      }
      const int s2 = 8 * (8 * (lane & 3) + (lane >> 2)) + w;
      asm volatile("st.relaxed.gpu.global.u64 [%0], %1;" :: "l"(&p.part[cl * SEQ + rank * 256 + s2]), "l"(((uint64_t)tag << 32) | __float_as_uint(s0)) : "memory");
      asm volatile("st.relaxed.gpu.global.u64 [%0], %1;" :: "l"(&p.part[cl * SEQ + rank * 256 + s2 + 4]), "l"(((uint64_t)tag << 32) | __float_as_uint(s1)) : "memory");
    }
    bar_sync(NB_WG0 + 3, 128);
    TL(3);
    cluster_wait();
    mbar_wait(mb + 8 * MB_KV);
    TL(4);
    const uint32_t hoff = (4 * (4 + 2 * (mi & 1) + jj) + ((tq + 3) & 3)) * 80 + (tq ? 2560 : 0);
    uint32_t En[2][6], Vn[2][4];
    uint2 swn;
    auto kv_load = [&](int u) {
      swn = lds64(sb + OFF_SW + 8 * (8 * u + g));
#pragma unroll
      for (int hf = 0; hf < 2; hf++) {
        const int ah = 4 * hf + w;
        uint32_t K[4];
        ldsm4t(K, sb + OFF_TK + (ah + 1) * 2560 + toff + 16 * u);
        ldsm2t(En[hf][0], En[hf][1], sb + OFF_TK + ah * 2560 + hoff + 16 * u);
        ldsm4t(Vn[hf], sb + OFF_TV + ah * 2560 + toff + 16 * u);
        En[hf][2] = K[0]; En[hf][3] = K[1]; En[hf][4] = K[2]; En[hf][5] = K[3];
      }
    };
    kv_load(0);
#pragma unroll 1
    for (int u = 0; u < nu; u++) {
      uint32_t E[2][6], V[2][4];
#pragma unroll
      for (int hf = 0; hf < 2; hf++) {
#pragma unroll
        for (int i = 0; i < 6; i++) E[hf][i] = En[hf][i];
#pragma unroll
        for (int i = 0; i < 4; i++) V[hf][i] = Vn[hf][i];
      }
      const uint32_t w0 = prmt(swn.x, 0, 0x1010), w1 = prmt(swn.x, 0, 0x3232), w2 = prmt(swn.y, 0, 0x1010), w3 = prmt(swn.y, 0, 0x3232);
      if (u + 1 < nu) kv_load(u + 1);
#pragma unroll
      for (int hf = 0; hf < 2; hf++) {
        uint32_t O[5], o[4];
#pragma unroll
        for (int i = 0; i < 5; i++) O[i] = prmt(E[hf][i], E[hf][i + 1], 0x5432);
#pragma unroll
        for (int i = 0; i < 4; i++) {
          uint32_t s = hmul2(O[i], w3);
          s = hadd2(s, hmul2(E[hf][i + 1], w2));
          s = hadd2(s, hmul2(O[i + 1], w1));
          s = hadd2(s, hmul2(E[hf][i + 2], w0));
          o[i] = hmul2(s, V[hf][i]);
        }
        put(sb + OFF_YA + 8 * u * YPITCH, sb + OFF_UKV + u * 4096, mb + 8 * (MB_UKV + u), hf ? (uoff ^ 32) + 256 : uoff, o);
      }
      fence_async();
      bar_sync(NB_WG0 + 3, 128);
      if (lane == 0) send(OFF_YA + 8 * u * YPITCH, OFF_UKV + u * 4096, OFF_MB + 8 * (MB_UKV + u));
      __syncwarp();
    }
    if (tid == 0) tma_load3(sb + OFF_Q2, &p.tq2, ch0, 8 * rank, 0, mb + 8 * MB_Q2);
    __syncwarp();
    TL(5);
    {
      float s[2] = {0.f, 0.f};
      bool ok = false;
#pragma unroll 1
      for (int it = 0; it < 4000 && !ok; it++) {
        ok = true; s[0] = s[1] = 0.f;
#pragma unroll
        for (int c = 0; c < NCL; c++) {
          uint64_t a, b;
          asm volatile("ld.relaxed.gpu.global.v2.u64 {%0,%1}, [%2];" : "=l"(a), "=l"(b) : "l"(&p.part[c * SEQ + rank * 256 + 2 * tid]) : "memory");
          ok = ok && (uint32_t)(a >> 32) == tag && (uint32_t)(b >> 32) == tag;
          s[0] += __uint_as_float((uint32_t)a); s[1] += __uint_as_float((uint32_t)b);
        }
      }
      if (ok) {
      } else {
#pragma unroll 1
        for (int hf = 0; hf < 2; hf++) {
          const int slot = 2 * tid + hf;
          const int row = rank * 256 + 32 * (slot & 7) + (slot >> 3);
          const uint32_t* xr = (const uint32_t*)(p.q + (size_t)row * DCH);
          const uint32_t* gr = (const uint32_t*)p.gate_w;
          float a = 0.f;
#pragma unroll 1
          for (int c = 0; c < DCH / 2; c++) { const uint32_t m = hmul2(__ldg(xr + c), __ldg(gr + c)); a += blo(m) + bhi(m); }
          if (hf) s[1] = a; else s[0] = a;
        }
      }
      const float g0 = bf16r(sigmoidf_(bf16r(s[0]))), g1 = bf16r(sigmoidf_(bf16r(s[1])));
      const float a0 = g0 * 0.0009765625f, b0 = bf16r(1.f - g0) * 0.0009765625f, a1 = g1 * 0.0009765625f, b1 = bf16r(1.f - g1) * 0.0009765625f;
      sts128(sb + OFF_TV + 16 * tid, pack(a0, a0), pack(b0, b0), pack(a1, a1), pack(b1, b1));
    }
    __syncwarp();
    if (lane == 0) asm volatile("mbarrier.arrive.shared::cta.b64 _, [%0];" :: "r"(mb + 8 * MB_Q2) : "memory");
  }
  mbar_wait(mb + 8 * MB_Q2);
  uint2 gg[2][4];
#pragma unroll
  for (int hh = 0; hh < 2; hh++)
#pragma unroll
    for (int i = 0; i < 4; i++) gg[hh][i] = lds64(sb + OFF_TV + 8 * (64 * w + 32 * hh + 8 * i + g));
  TL(24);
#pragma unroll 1
  for (int u = wg == 3 ? 0 : wg == 2 ? 4 : 2 * wg + 1; u < nu; u += 2) {
    uint32_t qv[2][4];
    const uint32_t qa = sb + OFF_Q2 + (64 * w + lane) * 80 + 16 * u;
    ldsm4(qv[0], qa);
    ldsm4(qv[1], qa + 2560);
    mbar_wait(mb + 8 * (MB_Y + u));
    uint32_t ya[2][4], yb[2][4];
#pragma unroll
    for (int hh = 0; hh < 2; hh++) {
      const uint32_t yo = (8 * u + (lane & 7)) * YPITCH + ((8 * w + 4 * hh + (lane >> 3)) ^ (2 * (rank & 3))) * 16;
      ldsm4t(ya[hh], sb + OFF_YA + yo); ldsm4t(yb[hh], sb + OFF_YB + yo);
    }
#pragma unroll
    for (int hh = 0; hh < 2; hh++) {
      uint32_t o[4];
#pragma unroll
      for (int i = 0; i < 4; i++) o[i] = hadd2(hmul2(gg[hh][i].x, hmul2(qv[hh][i], ya[hh][i])), hmul2(gg[hh][i].y, yb[hh][i]));
      stsm4(qa + 2560 * hh, o);
    }
    TL(25 + (u == 2));
    if (u) break;
  }
  cluster_arrive();
  bar_sync(NB_ROW0 + w, 128);
  TL(28);
  {
    uint4 v[3];
#pragma unroll
    for (int k = 0; k < 3; k++) {
      const int i = lane + 32 * k, sl = (i * 205) >> 10, c = i - 5 * sl;
      if (i < 80) v[k] = lds128(sb + OFF_Q2 + (64 * w + 8 * (sl & 7) + 2 * wg + (sl >> 3)) * 80 + c * 16);
    }
#pragma unroll
    for (int k = 0; k < 3; k++) {
      const int i = lane + 32 * k, sl = (i * 205) >> 10, c = i - 5 * sl;
      if (i < 80 && c < nu)
        asm volatile("st.global.v4.u32 [%0], {%1,%2,%3,%4};" :: "l"(p.out + (size_t)(256 * rank + 32 * (2 * wg + (sl >> 3)) + 8 * w + (sl & 7)) * DCH + ch0 + 8 * c),
                     "r"(v[k].x), "r"(v[k].y), "r"(v[k].z), "r"(v[k].w) : "memory");
    }
  }
  cluster_wait();
  TL(27);
  TL_DUMP();
}

typedef CUresult (*EncodeFn)(CUtensorMap*, CUtensorMapDataType, cuuint32_t, void*, const cuuint64_t*, const cuuint64_t*,
                             const cuuint32_t*, const cuuint32_t*, CUtensorMapInterleave, CUtensorMapSwizzle,
                             CUtensorMapL2promotion, CUtensorMapFloatOOBfill);

void encode(EncodeFn fn, CUtensorMap* tm, const void* ptr, int nd, const cuuint64_t* dims, const cuuint64_t* strides,
            const cuuint32_t* box, CUtensorMapSwizzle swz) {
  cuuint32_t es[4] = {1, 1, 1, 1};
  fn(tm, CU_TENSOR_MAP_DATA_TYPE_BFLOAT16, nd, const_cast<void*>(ptr), dims, strides, box, es, CU_TENSOR_MAP_INTERLEAVE_NONE,
     swz, CU_TENSOR_MAP_L2_PROMOTION_L2_128B, CU_TENSOR_MAP_FLOAT_OOB_FILL_NONE);
}
void map1(EncodeFn fn, CUtensorMap* tm, const void* ptr, int nhi) {
  const cuuint64_t dims[4] = {DCH, 4, 8, SEQ / 32}, strides[3] = {8 * DCH * 2, DCH * 2, 32 * DCH * 2};
  const cuuint32_t box[4] = {CPC, 4, 8, (cuuint32_t)nhi};
  encode(fn, tm, ptr, 4, dims, strides, box, CU_TENSOR_MAP_SWIZZLE_NONE);
}
void map2(EncodeFn fn, CUtensorMap* tm, const void* ptr, int nr) {
  const cuuint64_t dims[3] = {DCH, SEQ / 32, 32}, strides[2] = {32 * DCH * 2, DCH * 2};
  const cuuint32_t box[3] = {CPC, 8, (cuuint32_t)nr};
  encode(fn, tm, ptr, 3, dims, strides, box, CU_TENSOR_MAP_SWIZZLE_NONE);
}

}

extern "C" void kernel_launch(void* const* d_in, const int* in_sizes, int n_in, void* d_out, int out_size) {
  (void)in_sizes; (void)n_in; (void)out_size;
  static EncodeFn fn = nullptr;
  static void *tab = nullptr, *cnt = nullptr, *part = nullptr;
  if (!fn) {
    cudaGetSymbolAddress(&tab, d_tab);
    cudaGetSymbolAddress(&cnt, g_cnt);
    cudaGetSymbolAddress(&part, g_part);
    cudaDriverEntryPointQueryResult qr;
    cudaGetDriverEntryPoint("cuTensorMapEncodeTiled", (void**)&fn, cudaEnableDefault, &qr);
    cudaFuncSetAttribute(fused_kernel, cudaFuncAttributeMaxDynamicSharedMemorySize, SMEM_BYTES);
  }
  Params p;
  map1(fn, &p.tq, d_in[0], 4);
  map1(fn, &p.tk, d_in[1], 9);
  map1(fn, &p.tv, d_in[2], 8);
  map2(fn, &p.tq2, d_in[0], 32);
  p.out = (__nv_bfloat16*)d_out;
  {
    const cuuint64_t dims[4] = {32, SEQ / 32, DCH / 8, 8}, strides[3] = {64, 8 * SEQ * 2, SEQ * 2};
    const cuuint32_t box[4] = {32, 64, 5, 1};
    encode(fn, &p.th, d_in[4], 4, dims, strides, box, CU_TENSOR_MAP_SWIZZLE_64B);
  }
  p.tab = (const Tables*)tab;
  p.cnt = (unsigned*)cnt;
  p.part = (uint2*)part;
  p.tl = nullptr;
  p.q = (const __nv_bfloat16*)d_in[0];
  p.shift_k = (const __nv_bfloat16*)d_in[3];
  p.ssm_D = (const __nv_bfloat16*)d_in[5];
  p.logA = (const __nv_bfloat16*)d_in[7];
  p.Aim = (const __nv_bfloat16*)d_in[8];
  p.Cre = (const __nv_bfloat16*)d_in[9];
  p.Cim = (const __nv_bfloat16*)d_in[10];
  p.logdt = (const __nv_bfloat16*)d_in[11];
  p.Dskip = (const __nv_bfloat16*)d_in[12];
  p.gate_w = (const __nv_bfloat16*)d_in[13];
  fused_kernel<<<NCL * CS, NTHREADS, SMEM_BYTES, cudaStreamPerThread>>>(p);
}
```

```cpp
#include <cuda_runtime.h>
#include <cuda_bf16.h>
#include <cuda_fp16.h>
#include <cuda.h>
#include <stdint.h>

#define TIMELINE 0

namespace {

constexpr int SEQ = 2048, DCH = 576, NMODE = 128;
constexpr int CS = 8, CPC = 40, NCL = 15, NTHREADS = 640;

constexpr int YPITCH = 528;
constexpr int KTAB = 14336;
constexpr int OFF_T = 0;
constexpr int T_UKV = 8192, T_MX = 12288;
constexpr int OFF_UX = 5 * KTAB;
constexpr int OFF_HA = OFF_UX + 20480;
constexpr int OFF_CF = OFF_HA + 20480;
constexpr int OFF_CL = OFF_CF + 8192;
constexpr int OFF_A1 = OFF_CL + 4096;
constexpr int OFF_TQ = OFF_A1 + 4096;
constexpr int OFF_YA = OFF_TQ;
constexpr int OFF_TK = OFF_TQ + 21120;
constexpr int OFF_Q2 = OFF_TK;
constexpr int OFF_TV = OFF_TK + 23040;
constexpr int OFF_YB = OFF_TV + 20480;
constexpr int OFF_KC = OFF_YB + 40 * YPITCH;
constexpr int OFF_GB = OFF_KC;
constexpr int OFF_MX = OFF_KC + 5 * 1408;
constexpr int OFF_SP = OFF_MX + 5120;
constexpr int OFF_MB = OFF_SP + 5 * 160;
constexpr int OFF_TL = OFF_MB + 32 * 8;
constexpr int SMEM_BYTES = OFF_TL + (TIMELINE ? 2560 : 0);
static_assert(SMEM_BYTES <= 232448, "smem");
static_assert((KTAB & 1023) == 0 && (OFF_TQ & 127) == 0 && (OFF_TK & 127) == 0 && (OFF_TV & 127) == 0 && (OFF_MB & 7) == 0 && (OFF_KC & 15) == 0, "align");

enum { MB_UX = 0, MB_UKV = 5, MB_Y = 10, MB_XQ = 15, MB_KV = 16, MB_HA = 17, MB_CF = 18, MB_Q2 = 19, MB_XD = 20, MB_KD = 21, MB_TAG = 22 };
enum { NB_WG0 = 1, NB_ROW0 = 6 };

constexpr double cos_turn(int m, int n) {
  m &= n - 1;
  if (m > n / 2) m = n - m;
  double sgn = 1.0;
  if (m > n / 4) { m = n / 2 - m; sgn = -1.0; }
  if (m == n / 4) return 0.0;
  const double x = 6.283185307179586476925 * m / n;
  double term = 1.0, sum = 1.0;
  for (int k = 1; k < 14; k++) { term *= -x * x / ((2 * k - 1) * (2 * k)); sum += term; }
  return sgn * sum;
}
constexpr uint32_t bf16_bits(double v) {
  if (v == 0.0) return 0;
  uint32_t sgn = 0;
  if (v < 0) { sgn = 0x8000; v = -v; }
  int e = 127;
  while (v < 1.0) { v *= 2.0; e--; }
  while (v >= 2.0) { v *= 0.5; e++; }
  const double f = v * 128.0;
  int m = (int)f;
  if (f - m > 0.5 || (f - m == 0.5 && (m & 1))) m++;
  return sgn | (uint32_t)((e << 7) + (m - 128));
}
constexpr uint32_t f16_bits(double v) {
  if (v == 0.0) return 0;
  uint32_t sgn = 0;
  if (v < 0) { sgn = 0x8000; v = -v; }
  int e = 15;
  while (v < 1.0) { v *= 2.0; e--; }
  const double f = v * 1024.0;
  int m = (int)f;
  if (f - m > 0.5 || (f - m == 0.5 && (m & 1))) m++;
  return sgn | (uint32_t)((e << 10) + (m - 1024));
}
constexpr uint32_t pair_bits(double lo, double hi) { return bf16_bits(lo) | (bf16_bits(hi) << 16); }
constexpr uint32_t pair_h(double lo, double hi) { return f16_bits(lo) | (f16_bits(hi) << 16); }
struct alignas(128) Tables {
  uint32_t mat[3072];
  uint32_t thr[4][128][4];
};
constexpr Tables make_tables() {
  Tables T{};
  for (int q = 0; q < 768; q++) {
    int m0 = 0, d0 = 0, d1 = 0;
    if (q < 512) {
      const int r = (q >> 6) * 8 + (q & 7), cc = (q >> 3) & 7;
      d0 = 4 * (r & 31); d1 = 2 * d0;
      m0 = 8 * (cc & 3) * d0 + ((r >> 5) == (cc >> 2) ? 0 : (r >> 5) ? 96 : 32);
    } else {
      const int r = ((q - 512) >> 5) * 8 + (q & 7), pc = (q >> 3) & 3;
      d0 = 4 * (8 * (r >> 4) + (r & 7)) + 1; d1 = 8 * d0;
      m0 = 2 * pc * d0 + ((r & 8) ? 32 : 0);
    }
    for (int e = 0; e < 4; e++) T.mat[4 * q + e] = pair_h(cos_turn(m0 + e * d1, 128), cos_turn(m0 + e * d1 + d0, 128));
  }
  for (int tid = 0; tid < 128; tid++) {
    const int kk = 4 * (tid >> 2) + 1, t = tid & 3;
    for (int q = 0; q < 4; q++) {
      const int m = (8 * q + 2 * t) * kk;
      T.thr[q >> 1][tid][2 * (q & 1)] = pair_bits(cos_turn(m, 128), cos_turn(m + kk, 128));
      T.thr[q >> 1][tid][2 * (q & 1) + 1] = pair_bits(cos_turn(m + 32, 128), cos_turn(m + kk + 32, 128));
      T.thr[2][tid][q] = pair_h(cos_turn(m, 4096), cos_turn(m + kk, 4096));
      T.thr[3][tid][q] = pair_h(cos_turn(m + 3072, 4096), cos_turn(m + kk + 3072, 4096));
    }
  }
  return T;
}
__device__ const Tables d_tab = make_tables();

struct Params {
  const __nv_bfloat16 *logA, *Aim, *Cre, *Cim, *logdt;
  const Tables* tab;
  unsigned* cnt;
  const __nv_bfloat16 *Dskip, *shift_k, *ssm_D, *gate_w, *q;
  uint2* part;
  __nv_bfloat16* out;
  unsigned* tl;
  CUtensorMap tq, tk, tv, th, tq2;
};

__device__ uint2 g_part[NCL * SEQ];
__device__ unsigned g_cnt[CS * 32];
#define TL(i) do {} while (0)
#define TL_INIT() do {} while (0)
#define TL_DUMP() do {} while (0)

__device__ __forceinline__ uint32_t lds16(uint32_t a) { uint32_t v; asm volatile("ld.shared.u16 %0, [%1];" : "=r"(v) : "r"(a) : "memory"); return v; }
__device__ __forceinline__ uint2 lds64(uint32_t a) { uint2 v; asm volatile("ld.shared.v2.u32 {%0,%1}, [%2];" : "=r"(v.x), "=r"(v.y) : "r"(a) : "memory"); return v; }
__device__ __forceinline__ uint4 lds128(uint32_t a) { uint4 v; asm volatile("ld.shared.v4.u32 {%0,%1,%2,%3}, [%4];" : "=r"(v.x), "=r"(v.y), "=r"(v.z), "=r"(v.w) : "r"(a) : "memory"); return v; }
__device__ __forceinline__ void sts16(uint32_t a, uint32_t v) { asm volatile("st.shared.u16 [%0], %1;" :: "r"(a), "r"(v) : "memory"); }
__device__ __forceinline__ void sts32(uint32_t a, uint32_t v) { asm volatile("st.shared.u32 [%0], %1;" :: "r"(a), "r"(v) : "memory"); }
__device__ __forceinline__ void sts64(uint32_t a, uint32_t x, uint32_t y) { asm volatile("st.shared.v2.u32 [%0], {%1,%2};" :: "r"(a), "r"(x), "r"(y) : "memory"); }
__device__ __forceinline__ void sts128(uint32_t a, uint32_t x, uint32_t y, uint32_t z, uint32_t w) { asm volatile("st.shared.v4.u32 [%0], {%1,%2,%3,%4};" :: "r"(a), "r"(x), "r"(y), "r"(z), "r"(w) : "memory"); }
__device__ __forceinline__ void ldsm4t(uint32_t (&r)[4], uint32_t a) { asm volatile("ldmatrix.sync.aligned.m8n8.x4.trans.shared.b16 {%0,%1,%2,%3}, [%4];" : "=r"(r[0]), "=r"(r[1]), "=r"(r[2]), "=r"(r[3]) : "r"(a) : "memory"); }
__device__ __forceinline__ void ldsm2t(uint32_t& r0, uint32_t& r1, uint32_t a) { asm volatile("ldmatrix.sync.aligned.m8n8.x2.trans.shared.b16 {%0,%1}, [%2];" : "=r"(r0), "=r"(r1) : "r"(a) : "memory"); }
__device__ __forceinline__ void ldsm4(uint32_t (&r)[4], uint32_t a) { asm volatile("ldmatrix.sync.aligned.m8n8.x4.shared.b16 {%0,%1,%2,%3}, [%4];" : "=r"(r[0]), "=r"(r[1]), "=r"(r[2]), "=r"(r[3]) : "r"(a) : "memory"); }
__device__ __forceinline__ void stsm4(uint32_t a, const uint32_t (&r)[4]) { asm volatile("stmatrix.sync.aligned.m8n8.x4.shared.b16 [%0], {%1,%2,%3,%4};" :: "r"(a), "r"(r[0]), "r"(r[1]), "r"(r[2]), "r"(r[3]) : "memory"); }
__device__ __forceinline__ uint32_t pack(float lo, float hi) { uint32_t r; asm("cvt.rn.bf16x2.f32 %0, %1, %2;" : "=r"(r) : "f"(hi), "f"(lo)); return r; }
__device__ __forceinline__ float blo(uint32_t v) { return __uint_as_float(v << 16); }
__device__ __forceinline__ float bhi(uint32_t v) { return __uint_as_float(v & 0xffff0000u); }
__device__ __forceinline__ float bf16r(float x) { return blo(pack(x, 0.f)); }
__device__ __forceinline__ uint32_t hmul2(uint32_t a, uint32_t b) { uint32_t r; asm("mul.rn.bf16x2 %0, %1, %2;" : "=r"(r) : "r"(a), "r"(b)); return r; }
__device__ __forceinline__ uint32_t hadd2(uint32_t a, uint32_t b) { uint32_t r; asm("add.rn.bf16x2 %0, %1, %2;" : "=r"(r) : "r"(a), "r"(b)); return r; }
__device__ __forceinline__ uint32_t hfma2(uint32_t a, uint32_t b, uint32_t c) { uint32_t r; asm("fma.rn.bf16x2 %0, %1, %2, %3;" : "=r"(r) : "r"(a), "r"(b), "r"(c)); return r; }
__device__ __forceinline__ uint32_t packh(float lo, float hi) { uint32_t r; asm("cvt.rn.f16x2.f32 %0, %1, %2;" : "=r"(r) : "f"(hi), "f"(lo)); return r; }
__device__ __forceinline__ __half2 H2(uint32_t a) { return *reinterpret_cast<__half2*>(&a); }
__device__ __forceinline__ uint32_t U2(__half2 a) { return *reinterpret_cast<uint32_t*>(&a); }
__device__ __forceinline__ uint32_t fmul(uint32_t a, uint32_t b) { return U2(__hmul2(H2(a), H2(b))); }
__device__ __forceinline__ uint32_t ffma(uint32_t a, uint32_t b, uint32_t c) { return U2(__hfma2(H2(a), H2(b), H2(c))); }
__device__ __forceinline__ uint32_t fneg(uint32_t a) { return U2(__hneg2(H2(a))); }
__device__ __forceinline__ uint32_t amax2(uint32_t a, uint32_t b) { uint32_t r; asm("max.xorsign.abs.bf16x2 %0, %1, %2;" : "=r"(r) : "r"(a), "r"(b)); return r; }
__device__ __forceinline__ uint32_t amax8(const uint32_t (&a)[4], const uint32_t (&b)[4]) {
  return amax2(amax2(amax2(a[0], a[1]), amax2(a[2], a[3])), amax2(amax2(b[0], b[1]), amax2(b[2], b[3])));
}
__device__ __forceinline__ uint32_t prmt(uint32_t a, uint32_t b, uint32_t s) { return __byte_perm(a, b, s); }
__device__ __forceinline__ uint32_t ldraw(const __nv_bfloat16* p) { uint32_t v; asm volatile("ld.global.nc.u16 %0, [%1];" : "=r"(v) : "l"(p)); return v; }
__device__ __forceinline__ uint4 ldg128(const void* p) { uint4 v; asm volatile("ld.global.nc.v4.u32 {%0,%1,%2,%3}, [%4];" : "=r"(v.x), "=r"(v.y), "=r"(v.z), "=r"(v.w) : "l"(p)); return v; }
__device__ __forceinline__ void bar_sync(int id, int n) { asm volatile("bar.sync %0, %1;" :: "r"(id), "r"(n) : "memory"); }
__device__ __forceinline__ void bar_arrive(int id, int n) { asm volatile("bar.arrive %0, %1;" :: "r"(id), "r"(n) : "memory"); }
__device__ __forceinline__ void cluster_arrive() { asm volatile("barrier.cluster.arrive.relaxed.aligned;" ::: "memory"); }
__device__ __forceinline__ void cluster_wait() { asm volatile("barrier.cluster.wait.aligned;" ::: "memory"); }
__device__ __forceinline__ void fence_async() { asm volatile("fence.proxy.async.shared::cta;" ::: "memory"); }
__device__ __forceinline__ void fence_mbinit() { asm volatile("fence.mbarrier_init.release.cluster;" ::: "memory"); }
__device__ __forceinline__ uint32_t mapa(uint32_t a, uint32_t rank) { uint32_t r; asm("mapa.shared::cluster.u32 %0, %1, %2;" : "=r"(r) : "r"(a), "r"(rank)); return r; }
__device__ __forceinline__ void st_async4(uint32_t a, uint32_t x, uint32_t y, uint32_t z, uint32_t w, uint32_t mbar) {
  asm volatile("st.async.weak.shared::cluster.mbarrier::complete_tx::bytes.v4.b32 [%0], {%1,%2,%3,%4}, [%5];"
               :: "r"(a), "r"(x), "r"(y), "r"(z), "r"(w), "r"(mbar) : "memory");
}
__device__ __forceinline__ void st_async1(uint32_t a, uint32_t x, uint32_t mbar) {
  asm volatile("st.async.weak.shared::cluster.mbarrier::complete_tx::bytes.b32 [%0], %1, [%2];" :: "r"(a), "r"(x), "r"(mbar) : "memory");
}
__device__ __forceinline__ void bulk_dsmem(uint32_t dst, uint32_t src, uint32_t mbar) {
  asm volatile("cp.async.bulk.shared::cluster.shared::cta.mbarrier::complete_tx::bytes [%0], [%1], 512, [%2];" :: "r"(dst), "r"(src), "r"(mbar) : "memory");
}
__device__ __forceinline__ void mbar_init(uint32_t m, uint32_t cnt) { asm volatile("mbarrier.init.shared::cta.b64 [%0], %1;" :: "r"(m), "r"(cnt) : "memory"); }
__device__ __forceinline__ void mbar_expect(uint32_t m, uint32_t bytes) { asm volatile("mbarrier.arrive.expect_tx.shared::cta.b64 _, [%0], %1;" :: "r"(m), "r"(bytes) : "memory"); }
__device__ __forceinline__ void mbar_wait(uint32_t m) {
  uint32_t done;
  int it = 0;
  do {
    asm volatile("{.reg .pred p; mbarrier.try_wait.parity.shared::cta.b64 p, [%1], 0; selp.u32 %0, 1, 0, p;}" : "=r"(done) : "r"(m) : "memory");
  } while (!done && ++it < (1 << 22));
}
__device__ __forceinline__ void tma_load4(uint32_t dst, const CUtensorMap* tm, int c0, int c1, int c2, int c3, uint32_t mbar) {
  asm volatile("cp.async.bulk.tensor.4d.shared::cluster.global.mbarrier::complete_tx::bytes [%0], [%1, {%3, %4, %5, %6}], [%2];"
               :: "r"(dst), "l"(tm), "r"(mbar), "r"(c0), "r"(c1), "r"(c2), "r"(c3) : "memory");
}
__device__ __forceinline__ void tma_load3(uint32_t dst, const CUtensorMap* tm, int c0, int c1, int c2, uint32_t mbar) {
  asm volatile("cp.async.bulk.tensor.3d.shared::cluster.global.mbarrier::complete_tx::bytes [%0], [%1, {%3, %4, %5}], [%2];"
               :: "r"(dst), "l"(tm), "r"(mbar), "r"(c0), "r"(c1), "r"(c2) : "memory");
}
__device__ __forceinline__ void tma_store3(const CUtensorMap* tm, int c0, int c1, int c2, uint32_t src) {
  asm volatile("cp.async.bulk.tensor.3d.global.shared::cta.bulk_group [%0, {%2, %3, %4}], [%1];"
               :: "l"(tm), "r"(src), "r"(c0), "r"(c1), "r"(c2) : "memory");
}
__device__ __forceinline__ void wg_fence() { asm volatile("wgmma.fence.sync.aligned;" ::: "memory"); }
__device__ __forceinline__ void wg_commit() { asm volatile("wgmma.commit_group.sync.aligned;" ::: "memory"); }
template <int N> __device__ __forceinline__ void wg_wait() { asm volatile("wgmma.wait_group.sync.aligned %0;" :: "n"(N) : "memory"); }
template <int N> __device__ __forceinline__ void tie_all(uint32_t (&x)[N]) {
#pragma unroll
  for (int i = 0; i < N; i++) asm volatile("" : "+r"(x[i]) :: "memory");
}
template <int N> __device__ __forceinline__ void tie_all(float (&x)[N]) {
#pragma unroll
  for (int i = 0; i < N; i++) asm volatile("" : "+f"(x[i]) :: "memory");
}
#define R16(C, d) C(d[0]), C(d[1]), C(d[2]), C(d[3]), C(d[4]), C(d[5]), C(d[6]), C(d[7]), C(d[8]), C(d[9]), C(d[10]), C(d[11]), C(d[12]), C(d[13]), C(d[14]), C(d[15])
#define R32(C, d) R16(C, d), R16(C, (d + 16))
#define P16 "{%0,%1,%2,%3,%4,%5,%6,%7,%8,%9,%10,%11,%12,%13,%14,%15}"
#define P32 "{%0,%1,%2,%3,%4,%5,%6,%7,%8,%9,%10,%11,%12,%13,%14,%15,%16,%17,%18,%19,%20,%21,%22,%23,%24,%25,%26,%27,%28,%29,%30,%31}"
template <int SD, int TB, int OFF> __device__ __forceinline__ void rs64(float* d, const uint32_t* a, uint64_t db) {
  if (SD) asm volatile("{.reg .b64 db; add.s64 db, %36, %37; wgmma.mma_async.sync.aligned.m64n64k16.f32.bf16.bf16 " P32 ", {%32,%33,%34,%35}, db, 1, 1, 1, %38;}"
                       : R32("+f", d) : "r"(a[0]), "r"(a[1]), "r"(a[2]), "r"(a[3]), "l"(db), "n"(OFF), "n"(TB));
  else asm volatile("{.reg .b64 db; add.s64 db, %36, %37; wgmma.mma_async.sync.aligned.m64n64k16.f32.bf16.bf16 " P32 ", {%32,%33,%34,%35}, db, 0, 1, 1, %38;}"
                    : R32("=f", d) : "r"(a[0]), "r"(a[1]), "r"(a[2]), "r"(a[3]), "l"(db), "n"(OFF), "n"(TB));
}
template <int SD, int TB, int OFF> __device__ __forceinline__ void rs64h(uint32_t* d, const uint32_t* a, uint64_t db) {
  if (SD) asm volatile("{.reg .b64 db; add.s64 db, %20, %21; wgmma.mma_async.sync.aligned.m64n64k16.f16.f16.f16 " P16 ", {%16,%17,%18,%19}, db, 1, 1, 1, %22;}"
                       : R16("+r", d) : "r"(a[0]), "r"(a[1]), "r"(a[2]), "r"(a[3]), "l"(db), "n"(OFF), "n"(TB));
  else asm volatile("{.reg .b64 db; add.s64 db, %20, %21; wgmma.mma_async.sync.aligned.m64n64k16.f16.f16.f16 " P16 ", {%16,%17,%18,%19}, db, 0, 1, 1, %22;}"
                    : R16("=r", d) : "r"(a[0]), "r"(a[1]), "r"(a[2]), "r"(a[3]), "l"(db), "n"(OFF), "n"(TB));
}
template <int SD, int OFFA, int OFFB> __device__ __forceinline__ void ss32(float* d, uint64_t da, uint64_t db) {
  if (SD) asm volatile("{.reg .b64 da, db; add.s64 da, %16, %18; add.s64 db, %17, %19; wgmma.mma_async.sync.aligned.m64n32k16.f32.f16.f16 " P16 ", da, db, 1, 1, 1, 1, 1;}"
                       : R16("+f", d) : "l"(da), "l"(db), "n"(OFFA), "n"(OFFB));
  else asm volatile("{.reg .b64 da, db; add.s64 da, %16, %18; add.s64 db, %17, %19; wgmma.mma_async.sync.aligned.m64n32k16.f32.f16.f16 " P16 ", da, db, 0, 1, 1, 1, 1;}"
                    : R16("=f", d) : "l"(da), "l"(db), "n"(OFFA), "n"(OFFB));
}
#define R24(C, c) R16(C, c), C(c[16]), C(c[17]), C(c[18]), C(c[19]), C(c[20]), C(c[21]), C(c[22]), C(c[23])
#define KGEN_ASM(SD) "{.reg .b64 da, db; add.s64 da, %24, %25; add.s64 db, %24, %26;\n" \
  "wgmma.mma_async.sync.aligned.m64n48k16.f32.bf16.bf16 {%0,%1,%2,%3,%4,%5,%6,%7,%8,%9,%10,%11,%12,%13,%14,%15,%16,%17,%18,%19,%20,%21,%22,%23}, da, db, " SD ", 1, 1, 1, 1;}"
template <int KS, int ACC> __device__ __forceinline__ void kgen_mma(float (&c)[24], uint64_t da) {
  if (KS || ACC) asm volatile(KGEN_ASM("1") : R24("+f", c) : "l"(da), "n"(16 * KS), "n"(16 * KS + 512));
  else asm volatile(KGEN_ASM("0") : R24("=f", c) : "l"(da), "n"(16 * KS), "n"(16 * KS + 512));
  if constexpr (KS < 3) kgen_mma<KS + 1, ACC>(c, da);
}
__device__ __forceinline__ uint64_t desc_lo(uint32_t a) { return (uint64_t)((a & 0x3FFFF) >> 4); }
__device__ __forceinline__ void stage1(float (&D)[32], const uint32_t (&A1)[8], uint32_t src) {
  const uint64_t du = desc_lo(src) | (128ull << 16) | (32ull << 32) | (2ull << 62);
  rs64<0, 1, 0>(D, A1, du); rs64<1, 1, 64>(D, A1 + 4, du);
}
template <int INV> __device__ __forceinline__ void stage2(uint32_t (&X)[16], const uint32_t (&F)[16], uint32_t cf) {
  constexpr int KS = INV ? 16 : 128, TB = INV ? 0 : 1;
  const uint64_t dc = desc_lo(cf) | (INV ? (8ull << 16) | (64ull << 32) : (64ull << 16) | (8ull << 32));
  rs64h<0, TB, 0>(X, F, dc); rs64h<1, TB, KS>(X, F + 4, dc); rs64h<1, TB, 2 * KS>(X, F + 8, dc); rs64h<1, TB, 3 * KS>(X, F + 12, dc);
}
__device__ __forceinline__ void fwd_mid(uint32_t (&F)[16], const float (&D)[32], const uint32_t (&tc)[4], const uint32_t (&ts)[4]) {
#pragma unroll
  for (int j = 0; j < 4; j++)
#pragma unroll
    for (int b = 0; b < 2; b++) {
      const int i = 4 * j + 16 * b;
      const uint32_t ar = packh(D[i], D[i + 1]), ai = packh(D[i + 2], D[i + 3]);
      F[2 * j + b] = ffma(ar, tc[j], fmul(ai, ts[j]));
      F[8 + 2 * j + b] = ffma(ai, tc[j], fneg(fmul(ar, ts[j])));
    }
}
__device__ __forceinline__ uint32_t max_exp(uint32_t a) {
  const uint4 v = lds128(a);
  const uint32_t m = amax2(amax2(v.x, v.y), amax2(v.z, v.w));
  return __reduce_max_sync(0xffffffffu, max(m & 0x7f80u, (m >> 16) & 0x7f80u)) >> 7;
}
__device__ __forceinline__ void load_a1(uint32_t (&A1)[8], uint32_t a, uint32_t field) {
  const uint4 x = lds128(a), y = lds128(a + 2048);
  const uint32_t s = field * 0x00800080u;
  A1[0] = hmul2(x.x, s); A1[1] = hmul2(x.y, s); A1[2] = hmul2(x.z, s); A1[3] = hmul2(x.w, s);
  A1[4] = hmul2(y.x, s); A1[5] = hmul2(y.y, s); A1[6] = hmul2(y.z, s); A1[7] = hmul2(y.w, s);
}

struct cf { float x, y; };
__device__ __forceinline__ cf cmul(cf a, cf b) { cf r; r.x = fmaf(a.x, b.x, -a.y * b.y); r.y = fmaf(a.x, b.y, a.y * b.x); return r; }
__device__ __forceinline__ cf cexp_p(float lr2, float lt, float p) {
  float m = exp2f(lr2 * p);
  float t = lt * p;
  t = (t - rintf(t)) * 6.283185307179586f;
  cf r; r.x = m * __cosf(t); r.y = m * __sinf(t); return r;
}
__device__ __forceinline__ void store8(uint32_t a, const cf (&v)[8], uint32_t* im) {
  sts128(a, pack(v[0].x, v[1].x), pack(v[2].x, v[3].x), pack(v[4].x, v[5].x), pack(v[6].x, v[7].x));
#pragma unroll
  for (int i = 0; i < 4; i++) asm volatile("cvt.rn.bf16x2.f32 %0, %1, %2;" : "=r"(im[i]) : "f"(v[2 * i + 1].y), "f"(v[2 * i].y) : "memory");
}
__device__ __forceinline__ void mbar_arrive(uint32_t m) { asm volatile("mbarrier.arrive.shared::cta.b64 _, [%0];" :: "r"(m) : "memory"); }
__device__ __forceinline__ float sigmoidf_(float s) { return 1.f / (1.f + __expf(-s)); }

__global__ void __cluster_dims__(CS, 1, 1) __launch_bounds__(NTHREADS, 1) fused_kernel(const __grid_constant__ Params p) {
  extern __shared__ __align__(1024) uint8_t smem[];
  TL_INIT();
  TL(31);
  const int wid = __shfl_sync(0xffffffffu, threadIdx.x >> 5, 0);
  const uint32_t sb = (uint32_t)__cvta_generic_to_shared(smem);
  const uint32_t mb = sb + OFF_MB;
  const int u = wid >> 2, w = wid & 3;
  const int tid = threadIdx.x & 127, lane = tid & 31, g = lane >> 2, t = lane & 3;
  const int cl = blockIdx.x >> 3, rank = blockIdx.x & 7;
  const int ch0 = cl * CPC;
  const int nu = min(5, (DCH - ch0) >> 3);
  const bool act = u < nu;

  if (u == 4 && lane == 0) {
    if (w < 3) {
#pragma unroll
      for (int i = 0; i < 5; i++) mbar_init(mb + 40 * w + 8 * i, 1);
      fence_mbinit();
#pragma unroll
      for (int i = 0; i < 5; i++) mbar_expect(mb + 40 * w + 8 * i, w < 2 ? 4608 : 8192);
    } else {
      mbar_init(mb + 8 * MB_XQ, 1); mbar_init(mb + 8 * MB_KV, 2); mbar_init(mb + 8 * MB_HA, 1); mbar_init(mb + 8 * MB_CF, 1);
      mbar_init(mb + 8 * MB_Q2, 9); mbar_init(mb + 8 * MB_XD, 20); mbar_init(mb + 8 * MB_KD, 20);
      fence_mbinit();
      mbar_expect(mb + 8 * MB_CF, 16384);
      asm volatile("cp.async.bulk.shared::cluster.global.mbarrier::complete_tx::bytes [%0], [%1], %2, [%3];"
                   :: "r"(sb + OFF_CF), "l"(p.tab->mat), "r"(16384), "r"(mb + 8 * MB_CF) : "memory");
      mbar_expect(mb + 8 * MB_XQ, 20480); mbar_expect(mb + 8 * MB_KV, 23040); mbar_expect(mb + 8 * MB_HA, 20480); mbar_expect(mb + 8 * MB_Q2, 20480);
    }
  }
  uint32_t pla, pai, pcr, pci, pdt, tag = 0;
  uint4 psm;
  {
    const int ch = act ? ch0 + 8 * u + rank : 0, o = ch * NMODE + tid;
    pla = ldraw(p.logA + o); pdt = ldraw(p.logdt + ch); pai = ldraw(p.Aim + o); pcr = ldraw(p.Cre + o); pci = ldraw(p.Cim + o);
    if (w == 1) {
      if (lane < 9) psm = ldg128(lane < 5 ? p.gate_w + (lane < nu ? ch0 + 8 * lane : 0) : p.shift_k + (act ? ch0 + 8 * u : 0) * 4 + 8 * (lane - 5));
      else { psm.x = ldraw(p.Dskip + ch); psm.y = ldraw(p.ssm_D + ch); }
    }
    if (wid == 12 && lane < 2) asm volatile("atom.relaxed.gpu.global.add.u32 %0, [%1], %2;" : "=r"(tag) : "l"(&p.cnt[rank * 32 + lane]), "r"(cl == 0 ? 16 - (NCL - 1) : 1) : "memory");
  }
  if (wid == 19 && lane == 0) {
    tma_load4(sb + OFF_TQ, &p.tq, ch0, 0, 0, 8 * rank, mb + 8 * MB_XQ);
    tma_load4(sb + OFF_TK, &p.tk, ch0, 0, 0, 8 * rank - 1, mb + 8 * MB_KV);
    TL(20);
  }
  __syncwarp();
  cluster_arrive();
  TL(0);

  const uint32_t tab = sb + OFF_T + u * KTAB;
  const int mi = lane >> 3, tq = (lane & 7) >> 1, jj = lane & 1;
  const uint32_t toff = (4 * (2 * mi + jj) + tq) * 80 + 16 * u;
  const uint32_t uoff = 16 * (4 * w + (t ^ (w >> 1)));
  auto put = [&](int stage, int dst, int mbar, uint32_t off, const uint32_t (&v)[4]) {
    if (g == rank) st_async4(sb + dst + 512 * rank + off, v[0], v[1], v[2], v[3], sb + mbar);
    else sts128(sb + stage + g * YPITCH + off, v[0], v[1], v[2], v[3]);
  };
  auto send = [&](int stage, int pitch, int dst, int mbar) {
    if (lane == 0) {
#pragma unroll
      for (int k = 0; k < 2; k++) {
        const int d = 2 * w + k;
        if (d != rank) { const uint32_t rb = mapa(sb, d); bulk_dsmem(rb + dst, sb + stage + d * pitch, rb + mbar); }
      }
    }
    __syncwarp();
  };

  uint32_t im[28];
  float c[24];
  const uint64_t dk = desc_lo(tab) | (8ull << 16) | (64ull << 32);
  {
    const float dt = bf16r(expf(blo(pdt)));
    const float lr2 = (-bf16r(expf(blo(pla))) * dt) * 1.4426950408889634f;
    const float lt = (blo(pai) * dt) * 0.15915494309189535f;
    const uint32_t row = tab + tid * 16;
    if (lr2 != 123.f) TL(16);
    if (w == 1 && lane < 10) sts128(sb + OFF_SP + 160 * u + 16 * lane, psm.x, psm.y, psm.z, psm.w);
    {
      const cf w1 = cexp_p(lr2, lt, 8.f);
      cf v[8];
      v[0].x = 1.f; v[0].y = 0.f; v[1] = w1; v[2] = cmul(w1, w1); v[3] = cmul(v[2], w1);
      const cf w4 = cmul(v[2], v[2]);
      v[4] = w4; v[5] = cmul(v[1], w4); v[6] = cmul(v[2], w4); v[7] = cmul(v[3], w4);
      const cf w8 = cmul(w4, w4);
      store8(row, v, im);
#pragma unroll
      for (int k = 1; k < 4; k++) {
#pragma unroll
        for (int i = 0; i < 8; i++) v[i] = (k == 1 && i == 0) ? w8 : cmul(v[i], w8);
        store8(row + 2048 * k, v, im + 4 * k);
      }
    }
    {
      cf z1 = cexp_p(lr2, lt, 1.f), Z = cexp_p(lr2, lt, 256.f);
      z1.y = -z1.y; Z.y = -Z.y;
      const cf z2 = cmul(z1, z1);
      cf h[8], v[8];
      h[0].x = 2.f * blo(pcr) * dt; h[0].y = -2.f * blo(pci) * dt;
      h[1] = cmul(h[0], z1);
#pragma unroll
      for (int i = 2; i < 8; i++) h[i] = cmul(h[i - 2], z2);
      store8(row + 4 * 2048, h, im + 16);
      v[0] = cmul(h[0], Z); v[1] = cmul(h[2], Z); v[2] = cmul(h[4], Z); v[3] = cmul(h[6], Z);
      v[4] = cmul(v[0], Z); v[5] = cmul(v[2], Z); v[6] = cmul(v[4], Z); v[7] = cmul(v[5], Z);
      store8(row + 5 * 2048, v, im + 20);
      const cf Z2 = cmul(Z, Z);
      h[0] = cmul(v[4], Z2); h[1] = cmul(v[6], Z2); h[2] = cmul(h[0], Z2); h[3] = cmul(h[1], Z2); h[4] = cmul(h[2], Z2);
      h[5].x = h[5].y = h[6].x = h[6].y = h[7].x = h[7].y = 0.f;
      store8(row + 6 * 2048, h, im + 24);
    }
    TL(17);
    fence_async();
    bar_sync(NB_WG0 + u, 128);
    wg_fence();
    kgen_mma<0, 0>(c, dk);
    wg_commit();
  }
  cluster_wait();
  if (wid == 12 && lane == 0) sts32(mb + 8 * MB_TAG, tag);
  mbar_wait(mb + 8 * MB_XQ);
  TL(18);
  {
    uint32_t x0[4], x1[4];
    ldsm4t(x0, sb + OFF_TQ + w * 2560 + toff);
    ldsm4t(x1, sb + OFF_TQ + (w + 4) * 2560 + toff);
    put(OFF_YB + 8 * u * YPITCH, OFF_UX + u * 4096, OFF_MB + 8 * (MB_UX + u), uoff, x0);
    put(OFF_YB + 8 * u * YPITCH, OFF_UX + u * 4096, OFF_MB + 8 * (MB_UX + u), (uoff ^ 32) + 256, x1);
    st_async1(mapa(sb + OFF_MX + u * 1024 + 512 + 4 * (16 * rank + 4 * w + t), g), amax8(x0, x1), mapa(mb + 8 * (MB_UX + u), g));
    wg_wait<0>();
    bar_sync(NB_WG0 + u, 128);
#pragma unroll
    for (int k = 0; k < 7; k++) sts128(tab + tid * 16 + 2048 * k, im[4 * k], im[4 * k + 1], im[4 * k + 2], im[4 * k + 3]);
    fence_async();
    bar_sync(NB_WG0 + u, 128);
    wg_fence();
    kgen_mma<0, 1>(c, dk);
    wg_commit();
    send(OFF_YB + 8 * u * YPITCH, YPITCH, OFF_UX + u * 4096 + 512 * rank, OFF_MB + 8 * (MB_UX + u));
  }
  float gsum = 0.f;
  if (u >= 3) {
#pragma unroll
    for (int j = 0; j < 5; j++) {
      const uint4 x = lds128(sb + OFF_TQ + (tid + 128 * (u - 3)) * 80 + 16 * j);
      const uint4 gw = lds128(sb + OFF_SP + 160 * u + 16 * j);
      const uint32_t m0 = hmul2(x.x, gw.x), m1 = hmul2(x.y, gw.y), m2 = hmul2(x.z, gw.z), m3 = hmul2(x.w, gw.w);
      gsum += ((blo(m0) + bhi(m0)) + (blo(m1) + bhi(m1))) + ((blo(m2) + bhi(m2)) + (blo(m3) + bhi(m3)));
    }
    asm volatile("" : "+f"(gsum));
  }
  if (lane == 0) mbar_arrive(mb + 8 * MB_XD);
  uint32_t tc[4], ts[4];
  {
    const uint4 a = ldg128(p.tab->thr[2][tid]), b = ldg128(p.tab->thr[3][tid]);
    tc[0] = a.x; tc[1] = a.y; tc[2] = a.z; tc[3] = a.w; ts[0] = b.x; ts[1] = b.y; ts[2] = b.z; ts[3] = b.w;
  }
  {
    uint32_t kid[8];
    {
      const float lf = __uint_as_float(0x4b000000u | (8 * tid)) - 8388608.f;
      const float lo = tid < 16 ? lf + 128.f : lf;
      const uint32_t sub = tid < 16 ? 0x42804300u : 0x42804280u;
#pragma unroll
      for (int i = 0; i < 8; i++) kid[i] = 2 * (pack(lo + i, lf + (1024 + i)) - sub);
    }
    wg_wait<0>(); tie_all(c);
    const uint32_t kc = sb + OFF_KC + u * 1408;
    {
      const int a = 8 * w + g;
      const uint32_t k0 = pack(c[0] + c[6], c[1] + c[7]), k1 = pack(c[8] + c[14], c[9] + c[15]), p0 = pack(c[16] + c[22], c[17] + c[23]);
      sts32(kc + 4 * (4 * a + t), k0);
      sts32(kc + 4 * (t < 2 ? 128 + 2 * a + t : 128 + 32 * t + a), k1);
      sts32(sb + OFF_MX + u * 1024 + 4 * tid, amax2(amax2(k0, k1), p0));
      if (t < 3) {
        sts16(kc + 2 * (512 + 64 * t + a), p0);
        sts16(kc + 2 * (544 + 64 * t + a), p0 >> 16);
      }
    }
    TL(19);
    bar_sync(NB_WG0 + u, 128);
    uint32_t v[2][8];
#pragma unroll
    for (int i = 0; i < 8; i++) { v[0][i] = lds16(kc + (kid[i] & 0xffffu)); v[1][i] = lds16(kc + (kid[i] >> 16)); }
#pragma unroll
    for (int cc = 0; cc < 2; cc++)
      sts128(tab + 2048 * cc + 16 * (tid ^ ((tid >> 3) & 3)), prmt(v[cc][0], v[cc][1], 0x5410), prmt(v[cc][2], v[cc][3], 0x5410),
             prmt(v[cc][4], v[cc][5], 0x5410), prmt(v[cc][6], v[cc][7], 0x5410));
    fence_async();
  }
  cluster_arrive();
  if (u >= 3) {
    mbar_wait(mb + 8 * MB_XD);
    if (wid == 16 && lane == 0) {
      mbar_expect(mb + 8 * MB_KV, 20480);
      tma_load4(sb + OFF_TV, &p.tv, ch0, 0, 0, 8 * rank, mb + 8 * MB_KV);
      tma_load4(sb + OFF_HA, &p.th, 0, 0, 5 * cl, rank, mb + 8 * MB_HA);
      TL(20);
    }
    tag = (lds64(mb + 8 * MB_TAG).x >> 4) + 1;
    asm volatile("st.relaxed.gpu.global.u64 [%0], %1;" :: "l"(&p.part[cl * SEQ + rank * 256 + 8 * (8 * t + g) + w + 4 * (u - 3)]),
                 "l"(((uint64_t)tag << 32) | __float_as_uint(gsum)) : "memory");
  }
  bar_sync(NB_WG0 + u, 128);
  mbar_wait(mb + 8 * MB_CF);

#pragma unroll
  for (int isA = 0; isA < 2; isA++) {
    if (isA) {
      cluster_wait();
      mbar_wait(mb + 8 * MB_XD);
      mbar_wait(mb + 8 * MB_KV);
      TL(21);
      {
        const uint32_t hoff = (4 * (4 + 2 * (mi & 1) + jj) + ((tq + 3) & 3)) * 80 + (tq ? 2560 : 0) + 16 * u;
        uint32_t E[2][6], V[2][4];
        const uint2 psw = lds64(sb + OFF_SP + 160 * u + 80 + 8 * g);
#pragma unroll
        for (int hf = 0; hf < 2; hf++) {
          const int ah = 4 * hf + w;
          uint32_t K[4];
          ldsm4t(K, sb + OFF_TK + (ah + 1) * 2560 + toff);
          ldsm2t(E[hf][0], E[hf][1], sb + OFF_TK + ah * 2560 + hoff);
          ldsm4t(V[hf], sb + OFF_TV + ah * 2560 + toff);
          E[hf][2] = K[0]; E[hf][3] = K[1]; E[hf][4] = K[2]; E[hf][5] = K[3];
        }
        const uint32_t w0 = prmt(psw.x, 0, 0x1010), w1 = prmt(psw.x, 0, 0x3232), w2 = prmt(psw.y, 0, 0x1010), w3 = prmt(psw.y, 0, 0x3232);
        uint32_t o[2][4];
#pragma unroll
        for (int hf = 0; hf < 2; hf++) {
          uint32_t O[5];
#pragma unroll
          for (int i = 0; i < 5; i++) O[i] = prmt(E[hf][i], E[hf][i + 1], 0x5432);
#pragma unroll
          for (int i = 0; i < 4; i++) {
            uint32_t s = hmul2(O[i], w3);
            s = hadd2(s, hmul2(E[hf][i + 1], w2));
            s = hadd2(s, hmul2(O[i + 1], w1));
            s = hadd2(s, hmul2(E[hf][i + 2], w0));
            o[hf][i] = hmul2(s, V[hf][i]);
          }
          put(OFF_YA + 8 * u * YPITCH, OFF_T + u * KTAB + T_UKV, OFF_MB + 8 * (MB_UKV + u), hf ? (uoff ^ 32) + 256 : uoff, o[hf]);
        }
        st_async1(mapa(tab + T_MX + 512 + 4 * (16 * rank + 4 * w + t), g), amax8(o[0], o[1]), mapa(mb + 8 * (MB_UKV + u), g));
        fence_async();
        bar_sync(NB_WG0 + u, 128);
        send(OFF_YA + 8 * u * YPITCH, YPITCH, OFF_T + u * KTAB + T_UKV + 512 * rank, OFF_MB + 8 * (MB_UKV + u));
      }
      if (lane == 0) mbar_arrive(mb + 8 * MB_KD);
      TL(22);
      if (u < 2) {
        const int slot = tid + 128 * u;
        tag = (lds64(mb + 8 * MB_TAG).x >> 4) + 1;
        float s = 0.f;
        bool ok = false;
        const uint2* gp = p.part + rank * 256 + slot;
#pragma unroll 1
        for (int it = 0; it < 4000 && !ok; it++) {
          ok = true; s = 0.f;
#pragma unroll
          for (int k = 0; k < NCL; k++) {
            uint64_t a;
            asm volatile("ld.relaxed.gpu.global.u64 %0, [%1];" : "=l"(a) : "l"(gp + k * SEQ) : "memory");
            ok = ok && (uint32_t)(a >> 32) == tag;
            s += __uint_as_float((uint32_t)a);
          }
        }
        if (!ok) {
          const uint32_t* xr = (const uint32_t*)(p.q + (size_t)(rank * 256 + 32 * (slot & 7) + (slot >> 3)) * DCH);
          const uint32_t* gr = (const uint32_t*)p.gate_w;
          s = 0.f;
#pragma unroll 1
          for (int k = 0; k < DCH / 2; k++) { const uint32_t m = hmul2(__ldg(xr + k), __ldg(gr + k)); s += blo(m) + bhi(m); }
        }
        const float g0 = bf16r(sigmoidf_(bf16r(s)));
        sts64(sb + OFF_GB + 8 * slot, pack(g0, g0), pack(1.f - g0, 1.f - g0));
        __syncwarp();
        if (lane == 0) mbar_arrive(mb + 8 * MB_Q2);
      }
      TL(23);
      mbar_wait(mb + 8 * MB_HA);
      {
        const uint4 a = lds128(sb + OFF_HA + u * 4096 + 16 * tid), b = lds128(sb + OFF_HA + u * 4096 + 2048 + 16 * tid);
        const uint32_t aa[4] = {a.x, a.y, a.z, a.w}, bb[4] = {b.x, b.y, b.z, b.w};
        sts32(tab + T_MX + 4 * tid, amax8(aa, bb));
      }
      bar_sync(NB_WG0 + u, 128);
    }
    {
      TL(1 + isA);
      const uint32_t usrc = isA ? tab + T_UKV : sb + OFF_UX + u * 4096;
      const uint32_t mxa = (isA ? tab + T_MX : sb + OFF_MX + u * 1024) + 16 * lane;
      const uint32_t pd = lds16(sb + OFF_SP + 160 * u + 144 + 4 * isA);
      float D[32];
      uint32_t A1[8], F[16], H[16], X[16];
      const uint32_t eh = min(max((int)max_exp(mxa), (int)((pd >> 7) & 0xff) - 5), 240);
      load_a1(A1, sb + OFF_A1 + 16 * tid, 248 - eh);
      wg_fence();
      stage1(D, A1, isA ? sb + OFF_HA + u * 4096 : tab);
      wg_commit();
      wg_wait<0>(); tie_all(D);
      fwd_mid(F, D, tc, ts);
      wg_fence();
      stage2<0>(H, F, sb + OFF_CF);
      wg_commit();
      mbar_wait(mb + 8 * ((isA ? MB_UKV : MB_UX) + u));
      fence_async();
      TL(5 + isA);
      const uint32_t eu = min(max_exp(mxa + 512), 240u);
      load_a1(A1, sb + OFF_A1 + 16 * tid, 250 - eu);
      wg_wait<0>(); tie_all(H);
      wg_fence();
      stage1(D, A1, usrc);
      wg_commit();
      wg_wait<0>(); tie_all(D);
      fwd_mid(F, D, tc, ts);
      wg_fence();
      stage2<0>(X, F, sb + OFF_CF);
      wg_commit();
      {
        const float dsk = blo(pd) * __uint_as_float((248 - eh) << 23);
        const uint32_t d2 = packh(dsk, dsk);
#pragma unroll
        for (int j = 0; j < 4; j++) H[2 * j] = U2(__hadd2(H2(H[2 * j]), H2(d2)));
      }
      wg_wait<0>(); tie_all(X);
#pragma unroll
      for (int j = 0; j < 4; j++) {
        const uint32_t h0r = H[2 * j], h1r = H[2 * j + 1], h0i = H[8 + 2 * j], h1i = H[9 + 2 * j];
        const uint32_t x0r = X[2 * j], x1r = X[2 * j + 1], x0i = X[8 + 2 * j], x1i = X[9 + 2 * j];
        F[2 * j] = ffma(x0r, h0r, fneg(fmul(x0i, h0i)));
        F[8 + 2 * j] = ffma(x0r, h0i, fmul(x0i, h0r));
        F[2 * j + 1] = ffma(x1r, h0r, ffma(fneg(x1i), h0i, ffma(x0r, h1r, fneg(ffma(x0i, h1i, F[8 + 2 * j])))));
        F[9 + 2 * j] = ffma(x1r, h0i, ffma(x1i, h0r, ffma(x0r, h1i, ffma(x0i, h1r, F[2 * j]))));
      }
      wg_fence();
      stage2<1>(H, F, sb + OFF_CF);
      wg_commit();
      if (isA && wid == 0) {
        mbar_wait(mb + 8 * MB_KD);
        if (lane == 0) tma_load3(sb + OFF_Q2, &p.tq2, ch0, 8 * rank, 0, mb + 8 * MB_Q2);
        __syncwarp();
      }
      wg_wait<0>(); tie_all(H);
      {
        const uint32_t va = tab + (16 * w + (lane & 15)) * 128;
        const int vx = (lane >> 4) ^ (lane & 7);
#pragma unroll
        for (int j = 0; j < 4; j++) {
          uint32_t V[4];
#pragma unroll
          for (int b = 0; b < 2; b++) {
            const uint32_t er = H[2 * j + b], ei = H[8 + 2 * j + b];
            V[2 * b] = ffma(er, tc[j], fneg(fmul(ei, ts[j])));
            V[2 * b + 1] = ffma(ei, tc[j], fmul(er, ts[j]));
          }
          stsm4(va + ((vx ^ (2 * j)) << 4), V);
        }
      }
      fence_async();
      bar_sync(NB_WG0 + u, 128);
      float O[16];
      {
        const uint64_t dv = desc_lo(tab) | (1ull << 16) | (64ull << 32) | (1ull << 62);
        const uint64_t dl = desc_lo(sb + OFF_CL) | (32ull << 16) | (8ull << 32);
        wg_fence();
        ss32<0, 0, 0>(O, dv, dl); ss32<1, 128, 64>(O, dv, dl); ss32<1, 256, 128>(O, dv, dl); ss32<1, 384, 192>(O, dv, dl);
        wg_commit();
      }
      wg_wait<0>(); tie_all(O);
      {
        const uint32_t co = ((8 * w + g) ^ (2 * t)) * 16;
        const int yo = (isA ? OFF_YA : OFF_YB) + (8 * u + rank) * YPITCH, ym = OFF_MB + 8 * (MB_Y + u);
        const uint32_t us = min(max((int)(eu + eh) - 127, 0), 254) * 0x00800080u;
        const uint32_t a0 = hmul2(pack(O[0], O[1]), us), a1 = hmul2(pack(O[4], O[5]), us), a2 = hmul2(pack(O[8], O[9]), us), a3 = hmul2(pack(O[12], O[13]), us);
        const uint32_t b0 = hmul2(pack(O[2], O[3]), us), b1 = hmul2(pack(O[6], O[7]), us), b2 = hmul2(pack(O[10], O[11]), us), b3 = hmul2(pack(O[14], O[15]), us);
        sts128(usrc + t * 512 + co, a0, a1, a2, a3);
        sts128(usrc + t * 512 + 2048 + co, b0, b1, b2, b3);
        if (t == (rank & 3)) {
          if (rank < 4) st_async4(sb + yo + co, a0, a1, a2, a3, sb + ym); else st_async4(sb + yo + co, b0, b1, b2, b3, sb + ym);
        }
        fence_async();
        bar_sync(NB_WG0 + u, 128);
        send(usrc - sb, 512, yo, ym);
      }
      TL(9 + isA);
    }
  }

  {
    mbar_wait(mb + 8 * MB_Q2);
    uint2 gg[2][4];
    uint32_t qv[2][4];
#pragma unroll
    for (int hh = 0; hh < 2; hh++)
#pragma unroll
      for (int i = 0; i < 4; i++) gg[hh][i] = lds64(sb + OFF_GB + 8 * (64 * w + 32 * hh + 8 * i + g));
    const uint32_t qa = sb + OFF_Q2 + (64 * w + lane) * 80 + 16 * u;
    ldsm4(qv[0], qa);
    ldsm4(qv[1], qa + 2560);
    TL(24);
    mbar_wait(mb + 8 * (MB_Y + u));
    uint32_t ya[2][4], yb[2][4];
#pragma unroll
    for (int hh = 0; hh < 2; hh++) {
      const uint32_t yo = (8 * u + (lane & 7)) * YPITCH + ((8 * w + 4 * hh + (lane >> 3)) ^ (2 * (rank & 3))) * 16;
      ldsm4t(ya[hh], sb + OFF_YA + yo); ldsm4t(yb[hh], sb + OFF_YB + yo);
    }
#pragma unroll
    for (int hh = 0; hh < 2; hh++) {
      uint32_t o[4];
#pragma unroll
      for (int i = 0; i < 4; i++) o[i] = hadd2(hmul2(gg[hh][i].x, hmul2(qv[hh][i], ya[hh][i])), hmul2(gg[hh][i].y, yb[hh][i]));
      stsm4(qa + 2560 * hh, o);
    }
    TL(25);
  }
  cluster_arrive();
  bar_sync(NB_ROW0 + w, 160);
  {
    uint4 v[2];
#pragma unroll
    for (int k = 0; k < 2; k++) {
      const int i = 64 * u + 32 * k + lane, sl = (i * 205) >> 10, cc = i - 5 * sl;
      v[k] = lds128(sb + OFF_Q2 + (64 * w + 8 * (sl & 7) + (sl >> 3)) * 80 + cc * 16);
    }
#pragma unroll
    for (int k = 0; k < 2; k++) {
      const int i = 64 * u + 32 * k + lane, sl = (i * 205) >> 10, cc = i - 5 * sl;
      if (cc < nu)
        asm volatile("st.global.v4.u32 [%0], {%1,%2,%3,%4};" :: "l"(p.out + (size_t)(256 * rank + 32 * (sl >> 3) + 8 * w + (sl & 7)) * DCH + ch0 + 8 * cc),
                     "r"(v[k].x), "r"(v[k].y), "r"(v[k].z), "r"(v[k].w) : "memory");
    }
  }
  cluster_wait();
  TL(27);
  TL_DUMP();
}

typedef CUresult (*EncodeFn)(CUtensorMap*, CUtensorMapDataType, cuuint32_t, void*, const cuuint64_t*, const cuuint64_t*,
                             const cuuint32_t*, const cuuint32_t*, CUtensorMapInterleave, CUtensorMapSwizzle,
                             CUtensorMapL2promotion, CUtensorMapFloatOOBfill);

void encode(EncodeFn fn, CUtensorMap* tm, const void* ptr, int nd, const cuuint64_t* dims, const cuuint64_t* strides,
            const cuuint32_t* box, CUtensorMapSwizzle swz) {
  cuuint32_t es[4] = {1, 1, 1, 1};
  fn(tm, CU_TENSOR_MAP_DATA_TYPE_BFLOAT16, nd, const_cast<void*>(ptr), dims, strides, box, es, CU_TENSOR_MAP_INTERLEAVE_NONE,
     swz, CU_TENSOR_MAP_L2_PROMOTION_L2_128B, CU_TENSOR_MAP_FLOAT_OOB_FILL_NONE);
}
void map1(EncodeFn fn, CUtensorMap* tm, const void* ptr, int nhi) {
  const cuuint64_t dims[4] = {DCH, 4, 8, SEQ / 32}, strides[3] = {8 * DCH * 2, DCH * 2, 32 * DCH * 2};
  const cuuint32_t box[4] = {CPC, 4, 8, (cuuint32_t)nhi};
  encode(fn, tm, ptr, 4, dims, strides, box, CU_TENSOR_MAP_SWIZZLE_NONE);
}
void map2(EncodeFn fn, CUtensorMap* tm, const void* ptr, int nr) {
  const cuuint64_t dims[3] = {DCH, SEQ / 32, 32}, strides[2] = {32 * DCH * 2, DCH * 2};
  const cuuint32_t box[3] = {CPC, 8, (cuuint32_t)nr};
  encode(fn, tm, ptr, 3, dims, strides, box, CU_TENSOR_MAP_SWIZZLE_NONE);
}

}

extern "C" void kernel_launch(void* const* d_in, const int* in_sizes, int n_in, void* d_out, int out_size) {
  (void)in_sizes; (void)n_in; (void)out_size;
  static EncodeFn fn = nullptr;
  static void *tab = nullptr, *cnt = nullptr, *part = nullptr;
  if (!fn) {
    cudaGetSymbolAddress(&tab, d_tab);
    cudaGetSymbolAddress(&cnt, g_cnt);
    cudaGetSymbolAddress(&part, g_part);
    cudaDriverEntryPointQueryResult qr;
    cudaGetDriverEntryPoint("cuTensorMapEncodeTiled", (void**)&fn, cudaEnableDefault, &qr);
    cudaFuncSetAttribute(fused_kernel, cudaFuncAttributeMaxDynamicSharedMemorySize, SMEM_BYTES);
  }
  Params p;
  map1(fn, &p.tq, d_in[0], 8);
  map1(fn, &p.tk, d_in[1], 9);
  map1(fn, &p.tv, d_in[2], 8);
  map2(fn, &p.tq2, d_in[0], 32);
  p.out = (__nv_bfloat16*)d_out;
  {
    const cuuint64_t dims[4] = {32, SEQ / 32, DCH / 8, 8}, strides[3] = {64, 8 * SEQ * 2, SEQ * 2};
    const cuuint32_t box[4] = {32, 64, 5, 1};
    encode(fn, &p.th, d_in[4], 4, dims, strides, box, CU_TENSOR_MAP_SWIZZLE_64B);
  }
  p.tab = (const Tables*)tab;
  p.cnt = (unsigned*)cnt;
  p.part = (uint2*)part;
  p.tl = nullptr;
  p.q = (const __nv_bfloat16*)d_in[0];
  p.shift_k = (const __nv_bfloat16*)d_in[3];
  p.ssm_D = (const __nv_bfloat16*)d_in[5];
  p.logA = (const __nv_bfloat16*)d_in[7];
  p.Aim = (const __nv_bfloat16*)d_in[8];
  p.Cre = (const __nv_bfloat16*)d_in[9];
  p.Cim = (const __nv_bfloat16*)d_in[10];
  p.logdt = (const __nv_bfloat16*)d_in[11];
  p.Dskip = (const __nv_bfloat16*)d_in[12];
  p.gate_w = (const __nv_bfloat16*)d_in[13];
  fused_kernel<<<NCL * CS, NTHREADS, SMEM_BYTES, cudaStreamPerThread>>>(p);
}
```

```cpp
#include <cuda_runtime.h>
#include <cuda_bf16.h>
#include <cuda_fp16.h>
#include <cuda.h>
#include <stdint.h>

#define TIMELINE 0

namespace {

constexpr int SEQ = 2048, DCH = 576, NMODE = 128;
constexpr int CS = 8, CPC = 40, NCL = 15, NTHREADS = 640;

constexpr int YPITCH = 528;
constexpr int KTAB = 14336;
constexpr int OFF_T = 0;
constexpr int T_UKV = 8192, T_MX = 12288;
constexpr int OFF_UX = 5 * KTAB;
constexpr int OFF_HA = OFF_UX + 20480;
constexpr int OFF_CF = OFF_HA + 20480;
constexpr int OFF_CL = OFF_CF + 8192;
constexpr int OFF_A1 = OFF_CL + 4096;
constexpr int OFF_TQ = OFF_A1 + 4096;
constexpr int OFF_YA = OFF_TQ;
constexpr int OFF_TK = OFF_TQ + 21120;
constexpr int OFF_Q2 = OFF_TK;
constexpr int OFF_TV = OFF_TK + 23040;
constexpr int OFF_YB = OFF_TV + 20480;
constexpr int OFF_KC = OFF_YB + 40 * YPITCH;
constexpr int OFF_GB = OFF_KC;
constexpr int OFF_MX = OFF_KC + 5 * 1408;
constexpr int OFF_SP = OFF_MX + 5120;
constexpr int OFF_MB = OFF_SP + 5 * 160;
constexpr int OFF_TL = OFF_MB + 32 * 8;
constexpr int SMEM_BYTES = OFF_TL + (TIMELINE ? 2560 : 0);
static_assert(SMEM_BYTES <= 232448, "smem");
static_assert((KTAB & 1023) == 0 && (OFF_TQ & 127) == 0 && (OFF_TK & 127) == 0 && (OFF_TV & 127) == 0 && (OFF_MB & 7) == 0 && (OFF_KC & 15) == 0, "align");

enum { MB_UX = 0, MB_UKV = 5, MB_Y = 10, MB_XQ = 15, MB_KV = 16, MB_HA = 17, MB_CF = 18, MB_Q2 = 19, MB_XD = 20, MB_KD = 21, MB_TAG = 22 };
enum { NB_WG0 = 1, NB_ROW0 = 6, NB_K3 = 10, NB_K4 = 11 };

constexpr double cos_turn(int m, int n) {
  m &= n - 1;
  if (m > n / 2) m = n - m;
  double sgn = 1.0;
  if (m > n / 4) { m = n / 2 - m; sgn = -1.0; }
  if (m == n / 4) return 0.0;
  const double x = 6.283185307179586476925 * m / n;
  double term = 1.0, sum = 1.0;
  for (int k = 1; k < 14; k++) { term *= -x * x / ((2 * k - 1) * (2 * k)); sum += term; }
  return sgn * sum;
}
constexpr uint32_t bf16_bits(double v) {
  if (v == 0.0) return 0;
  uint32_t sgn = 0;
  if (v < 0) { sgn = 0x8000; v = -v; }
  int e = 127;
  while (v < 1.0) { v *= 2.0; e--; }
  while (v >= 2.0) { v *= 0.5; e++; }
  const double f = v * 128.0;
  int m = (int)f;
  if (f - m > 0.5 || (f - m == 0.5 && (m & 1))) m++;
  return sgn | (uint32_t)((e << 7) + (m - 128));
}
constexpr uint32_t f16_bits(double v) {
  if (v == 0.0) return 0;
  uint32_t sgn = 0;
  if (v < 0) { sgn = 0x8000; v = -v; }
  int e = 15;
  while (v < 1.0) { v *= 2.0; e--; }
  const double f = v * 1024.0;
  int m = (int)f;
  if (f - m > 0.5 || (f - m == 0.5 && (m & 1))) m++;
  return sgn | (uint32_t)((e << 10) + (m - 1024));
}
constexpr uint32_t pair_bits(double lo, double hi) { return bf16_bits(lo) | (bf16_bits(hi) << 16); }
constexpr uint32_t pair_h(double lo, double hi) { return f16_bits(lo) | (f16_bits(hi) << 16); }
struct alignas(128) Tables {
  uint32_t mat[3072];
  uint32_t thr[4][128][4];
};
constexpr Tables make_tables() {
  Tables T{};
  for (int q = 0; q < 768; q++) {
    int m0 = 0, d0 = 0, d1 = 0;
    if (q < 512) {
      const int r = (q >> 6) * 8 + (q & 7), cc = (q >> 3) & 7;
      d0 = 4 * (r & 31); d1 = 2 * d0;
      m0 = 8 * (cc & 3) * d0 + ((r >> 5) == (cc >> 2) ? 0 : (r >> 5) ? 96 : 32);
    } else {
      const int r = ((q - 512) >> 5) * 8 + (q & 7), pc = (q >> 3) & 3;
      d0 = 4 * (8 * (r >> 4) + (r & 7)) + 1; d1 = 8 * d0;
      m0 = 2 * pc * d0 + ((r & 8) ? 32 : 0);
    }
    for (int e = 0; e < 4; e++) T.mat[4 * q + e] = pair_h(cos_turn(m0 + e * d1, 128), cos_turn(m0 + e * d1 + d0, 128));
  }
  for (int tid = 0; tid < 128; tid++) {
    const int kk = 4 * (tid >> 2) + 1, t = tid & 3;
    for (int q = 0; q < 4; q++) {
      const int m = (8 * q + 2 * t) * kk;
      T.thr[q >> 1][tid][2 * (q & 1)] = pair_bits(cos_turn(m, 128), cos_turn(m + kk, 128));
      T.thr[q >> 1][tid][2 * (q & 1) + 1] = pair_bits(cos_turn(m + 32, 128), cos_turn(m + kk + 32, 128));
      T.thr[2][tid][q] = pair_h(cos_turn(m, 4096), cos_turn(m + kk, 4096));
      T.thr[3][tid][q] = pair_h(cos_turn(m + 3072, 4096), cos_turn(m + kk + 3072, 4096));
    }
  }
  return T;
}
__device__ const Tables d_tab = make_tables();

struct Params {
  const __nv_bfloat16 *logA, *Aim, *Cre, *Cim, *logdt;
  const Tables* tab;
  unsigned* cnt;
  const __nv_bfloat16 *Dskip, *shift_k, *ssm_D, *gate_w, *q;
  uint2* part;
  __nv_bfloat16* out;
  unsigned* tl;
  CUtensorMap tq, tk, tv, th, tq2;
};

__device__ uint2 g_part[NCL * SEQ];
__device__ unsigned g_cnt[CS * 32];
#define TL(i) do {} while (0)
#define TL_INIT() do {} while (0)
#define TL_DUMP() do {} while (0)

__device__ __forceinline__ uint32_t lds16(uint32_t a) { uint32_t v; asm volatile("ld.shared.u16 %0, [%1];" : "=r"(v) : "r"(a) : "memory"); return v; }
__device__ __forceinline__ uint2 lds64(uint32_t a) { uint2 v; asm volatile("ld.shared.v2.u32 {%0,%1}, [%2];" : "=r"(v.x), "=r"(v.y) : "r"(a) : "memory"); return v; }
__device__ __forceinline__ uint4 lds128(uint32_t a) { uint4 v; asm volatile("ld.shared.v4.u32 {%0,%1,%2,%3}, [%4];" : "=r"(v.x), "=r"(v.y), "=r"(v.z), "=r"(v.w) : "r"(a) : "memory"); return v; }
__device__ __forceinline__ void sts16(uint32_t a, uint32_t v) { asm volatile("st.shared.u16 [%0], %1;" :: "r"(a), "r"(v) : "memory"); }
__device__ __forceinline__ void sts32(uint32_t a, uint32_t v) { asm volatile("st.shared.u32 [%0], %1;" :: "r"(a), "r"(v) : "memory"); }
__device__ __forceinline__ void sts64(uint32_t a, uint32_t x, uint32_t y) { asm volatile("st.shared.v2.u32 [%0], {%1,%2};" :: "r"(a), "r"(x), "r"(y) : "memory"); }
__device__ __forceinline__ void sts128(uint32_t a, uint32_t x, uint32_t y, uint32_t z, uint32_t w) { asm volatile("st.shared.v4.u32 [%0], {%1,%2,%3,%4};" :: "r"(a), "r"(x), "r"(y), "r"(z), "r"(w) : "memory"); }
__device__ __forceinline__ void ldsm4t(uint32_t (&r)[4], uint32_t a) { asm volatile("ldmatrix.sync.aligned.m8n8.x4.trans.shared.b16 {%0,%1,%2,%3}, [%4];" : "=r"(r[0]), "=r"(r[1]), "=r"(r[2]), "=r"(r[3]) : "r"(a) : "memory"); }
__device__ __forceinline__ void ldsm2t(uint32_t& r0, uint32_t& r1, uint32_t a) { asm volatile("ldmatrix.sync.aligned.m8n8.x2.trans.shared.b16 {%0,%1}, [%2];" : "=r"(r0), "=r"(r1) : "r"(a) : "memory"); }
__device__ __forceinline__ void ldsm4(uint32_t (&r)[4], uint32_t a) { asm volatile("ldmatrix.sync.aligned.m8n8.x4.shared.b16 {%0,%1,%2,%3}, [%4];" : "=r"(r[0]), "=r"(r[1]), "=r"(r[2]), "=r"(r[3]) : "r"(a) : "memory"); }
__device__ __forceinline__ void stsm4(uint32_t a, const uint32_t (&r)[4]) { asm volatile("stmatrix.sync.aligned.m8n8.x4.shared.b16 [%0], {%1,%2,%3,%4};" :: "r"(a), "r"(r[0]), "r"(r[1]), "r"(r[2]), "r"(r[3]) : "memory"); }
__device__ __forceinline__ uint32_t pack(float lo, float hi) { uint32_t r; asm("cvt.rn.bf16x2.f32 %0, %1, %2;" : "=r"(r) : "f"(hi), "f"(lo)); return r; }
__device__ __forceinline__ float blo(uint32_t v) { return __uint_as_float(v << 16); }
__device__ __forceinline__ float bhi(uint32_t v) { return __uint_as_float(v & 0xffff0000u); }
__device__ __forceinline__ float bf16r(float x) { return blo(pack(x, 0.f)); }
__device__ __forceinline__ uint32_t hmul2(uint32_t a, uint32_t b) { uint32_t r; asm("mul.rn.bf16x2 %0, %1, %2;" : "=r"(r) : "r"(a), "r"(b)); return r; }
__device__ __forceinline__ uint32_t hadd2(uint32_t a, uint32_t b) { uint32_t r; asm("add.rn.bf16x2 %0, %1, %2;" : "=r"(r) : "r"(a), "r"(b)); return r; }
__device__ __forceinline__ uint32_t hfma2(uint32_t a, uint32_t b, uint32_t c) { uint32_t r; asm("fma.rn.bf16x2 %0, %1, %2, %3;" : "=r"(r) : "r"(a), "r"(b), "r"(c)); return r; }
__device__ __forceinline__ uint32_t packh(float lo, float hi) { uint32_t r; asm("cvt.rn.f16x2.f32 %0, %1, %2;" : "=r"(r) : "f"(hi), "f"(lo)); return r; }
__device__ __forceinline__ __half2 H2(uint32_t a) { return *reinterpret_cast<__half2*>(&a); }
__device__ __forceinline__ uint32_t U2(__half2 a) { return *reinterpret_cast<uint32_t*>(&a); }
__device__ __forceinline__ uint32_t fmul(uint32_t a, uint32_t b) { return U2(__hmul2(H2(a), H2(b))); }
__device__ __forceinline__ uint32_t ffma(uint32_t a, uint32_t b, uint32_t c) { return U2(__hfma2(H2(a), H2(b), H2(c))); }
__device__ __forceinline__ uint32_t fneg(uint32_t a) { return U2(__hneg2(H2(a))); }
__device__ __forceinline__ uint32_t amax2(uint32_t a, uint32_t b) { uint32_t r; asm("max.xorsign.abs.bf16x2 %0, %1, %2;" : "=r"(r) : "r"(a), "r"(b)); return r; }
__device__ __forceinline__ uint32_t amax8(const uint32_t (&a)[4], const uint32_t (&b)[4]) {
  return amax2(amax2(amax2(a[0], a[1]), amax2(a[2], a[3])), amax2(amax2(b[0], b[1]), amax2(b[2], b[3])));
}
__device__ __forceinline__ uint32_t prmt(uint32_t a, uint32_t b, uint32_t s) { return __byte_perm(a, b, s); }
__device__ __forceinline__ uint32_t ldraw(const __nv_bfloat16* p) { uint32_t v; asm volatile("ld.global.nc.u16 %0, [%1];" : "=r"(v) : "l"(p)); return v; }
__device__ __forceinline__ uint4 ldg128(const void* p) { uint4 v; asm volatile("ld.global.nc.v4.u32 {%0,%1,%2,%3}, [%4];" : "=r"(v.x), "=r"(v.y), "=r"(v.z), "=r"(v.w) : "l"(p)); return v; }
__device__ __forceinline__ void bar_sync(int id, int n) { asm volatile("bar.sync %0, %1;" :: "r"(id), "r"(n) : "memory"); }
__device__ __forceinline__ void bar_arrive(int id, int n) { asm volatile("bar.arrive %0, %1;" :: "r"(id), "r"(n) : "memory"); }
__device__ __forceinline__ void cluster_arrive() { asm volatile("barrier.cluster.arrive.relaxed.aligned;" ::: "memory"); }
__device__ __forceinline__ void cluster_wait() { asm volatile("barrier.cluster.wait.aligned;" ::: "memory"); }
__device__ __forceinline__ void fence_async() { asm volatile("fence.proxy.async.shared::cta;" ::: "memory"); }
__device__ __forceinline__ void fence_mbinit() { asm volatile("fence.mbarrier_init.release.cluster;" ::: "memory"); }
__device__ __forceinline__ uint32_t mapa(uint32_t a, uint32_t rank) { uint32_t r; asm("mapa.shared::cluster.u32 %0, %1, %2;" : "=r"(r) : "r"(a), "r"(rank)); return r; }
__device__ __forceinline__ void st_async4(uint32_t a, uint32_t x, uint32_t y, uint32_t z, uint32_t w, uint32_t mbar) {
  asm volatile("st.async.weak.shared::cluster.mbarrier::complete_tx::bytes.v4.b32 [%0], {%1,%2,%3,%4}, [%5];"
               :: "r"(a), "r"(x), "r"(y), "r"(z), "r"(w), "r"(mbar) : "memory");
}
__device__ __forceinline__ void st_async1(uint32_t a, uint32_t x, uint32_t mbar) {
  asm volatile("st.async.weak.shared::cluster.mbarrier::complete_tx::bytes.b32 [%0], %1, [%2];" :: "r"(a), "r"(x), "r"(mbar) : "memory");
}
__device__ __forceinline__ void bulk_dsmem(uint32_t dst, uint32_t src, uint32_t mbar) {
  asm volatile("cp.async.bulk.shared::cluster.shared::cta.mbarrier::complete_tx::bytes [%0], [%1], 512, [%2];" :: "r"(dst), "r"(src), "r"(mbar) : "memory");
}
__device__ __forceinline__ void mbar_init(uint32_t m, uint32_t cnt) { asm volatile("mbarrier.init.shared::cta.b64 [%0], %1;" :: "r"(m), "r"(cnt) : "memory"); }
__device__ __forceinline__ void mbar_expect(uint32_t m, uint32_t bytes) { asm volatile("mbarrier.arrive.expect_tx.shared::cta.b64 _, [%0], %1;" :: "r"(m), "r"(bytes) : "memory"); }
__device__ __forceinline__ void mbar_wait(uint32_t m) {
  uint32_t done;
  int it = 0;
  do {
    asm volatile("{.reg .pred p; mbarrier.try_wait.parity.shared::cta.b64 p, [%1], 0; selp.u32 %0, 1, 0, p;}" : "=r"(done) : "r"(m) : "memory");
  } while (!done && ++it < (1 << 22));
}
__device__ __forceinline__ void tma_load4(uint32_t dst, const CUtensorMap* tm, int c0, int c1, int c2, int c3, uint32_t mbar) {
  asm volatile("cp.async.bulk.tensor.4d.shared::cluster.global.mbarrier::complete_tx::bytes [%0], [%1, {%3, %4, %5, %6}], [%2];"
               :: "r"(dst), "l"(tm), "r"(mbar), "r"(c0), "r"(c1), "r"(c2), "r"(c3) : "memory");
}
__device__ __forceinline__ void tma_load3(uint32_t dst, const CUtensorMap* tm, int c0, int c1, int c2, uint32_t mbar) {
  asm volatile("cp.async.bulk.tensor.3d.shared::cluster.global.mbarrier::complete_tx::bytes [%0], [%1, {%3, %4, %5}], [%2];"
               :: "r"(dst), "l"(tm), "r"(mbar), "r"(c0), "r"(c1), "r"(c2) : "memory");
}
__device__ __forceinline__ void tma_store3(const CUtensorMap* tm, int c0, int c1, int c2, uint32_t src) {
  asm volatile("cp.async.bulk.tensor.3d.global.shared::cta.bulk_group [%0, {%2, %3, %4}], [%1];"
               :: "l"(tm), "r"(src), "r"(c0), "r"(c1), "r"(c2) : "memory");
}
__device__ __forceinline__ void wg_fence() { asm volatile("wgmma.fence.sync.aligned;" ::: "memory"); }
__device__ __forceinline__ void wg_commit() { asm volatile("wgmma.commit_group.sync.aligned;" ::: "memory"); }
template <int N> __device__ __forceinline__ void wg_wait() { asm volatile("wgmma.wait_group.sync.aligned %0;" :: "n"(N) : "memory"); }
template <int N> __device__ __forceinline__ void tie_all(uint32_t (&x)[N]) {
#pragma unroll
  for (int i = 0; i < N; i++) asm volatile("" : "+r"(x[i]) :: "memory");
}
template <int N> __device__ __forceinline__ void tie_all(float (&x)[N]) {
#pragma unroll
  for (int i = 0; i < N; i++) asm volatile("" : "+f"(x[i]) :: "memory");
}
#define R16(C, d) C(d[0]), C(d[1]), C(d[2]), C(d[3]), C(d[4]), C(d[5]), C(d[6]), C(d[7]), C(d[8]), C(d[9]), C(d[10]), C(d[11]), C(d[12]), C(d[13]), C(d[14]), C(d[15])
#define R32(C, d) R16(C, d), R16(C, (d + 16))
#define P16 "{%0,%1,%2,%3,%4,%5,%6,%7,%8,%9,%10,%11,%12,%13,%14,%15}"
#define P32 "{%0,%1,%2,%3,%4,%5,%6,%7,%8,%9,%10,%11,%12,%13,%14,%15,%16,%17,%18,%19,%20,%21,%22,%23,%24,%25,%26,%27,%28,%29,%30,%31}"
template <int SD, int TB, int OFF> __device__ __forceinline__ void rs64(float* d, const uint32_t* a, uint64_t db) {
  if (SD) asm volatile("{.reg .b64 db; add.s64 db, %36, %37; wgmma.mma_async.sync.aligned.m64n64k16.f32.bf16.bf16 " P32 ", {%32,%33,%34,%35}, db, 1, 1, 1, %38;}"
                       : R32("+f", d) : "r"(a[0]), "r"(a[1]), "r"(a[2]), "r"(a[3]), "l"(db), "n"(OFF), "n"(TB));
  else asm volatile("{.reg .b64 db; add.s64 db, %36, %37; wgmma.mma_async.sync.aligned.m64n64k16.f32.bf16.bf16 " P32 ", {%32,%33,%34,%35}, db, 0, 1, 1, %38;}"
                    : R32("=f", d) : "r"(a[0]), "r"(a[1]), "r"(a[2]), "r"(a[3]), "l"(db), "n"(OFF), "n"(TB));
}
template <int SD, int TB, int OFF> __device__ __forceinline__ void rs64h(uint32_t* d, const uint32_t* a, uint64_t db) {
  if (SD) asm volatile("{.reg .b64 db; add.s64 db, %20, %21; wgmma.mma_async.sync.aligned.m64n64k16.f16.f16.f16 " P16 ", {%16,%17,%18,%19}, db, 1, 1, 1, %22;}"
                       : R16("+r", d) : "r"(a[0]), "r"(a[1]), "r"(a[2]), "r"(a[3]), "l"(db), "n"(OFF), "n"(TB));
  else asm volatile("{.reg .b64 db; add.s64 db, %20, %21; wgmma.mma_async.sync.aligned.m64n64k16.f16.f16.f16 " P16 ", {%16,%17,%18,%19}, db, 0, 1, 1, %22;}"
                    : R16("=r", d) : "r"(a[0]), "r"(a[1]), "r"(a[2]), "r"(a[3]), "l"(db), "n"(OFF), "n"(TB));
}
template <int SD, int OFFA, int OFFB> __device__ __forceinline__ void ss32(float* d, uint64_t da, uint64_t db) {
  if (SD) asm volatile("{.reg .b64 da, db; add.s64 da, %16, %18; add.s64 db, %17, %19; wgmma.mma_async.sync.aligned.m64n32k16.f32.f16.f16 " P16 ", da, db, 1, 1, 1, 1, 1;}"
                       : R16("+f", d) : "l"(da), "l"(db), "n"(OFFA), "n"(OFFB));
  else asm volatile("{.reg .b64 da, db; add.s64 da, %16, %18; add.s64 db, %17, %19; wgmma.mma_async.sync.aligned.m64n32k16.f32.f16.f16 " P16 ", da, db, 0, 1, 1, 1, 1;}"
                    : R16("=f", d) : "l"(da), "l"(db), "n"(OFFA), "n"(OFFB));
}
#define R24(C, c) R16(C, c), C(c[16]), C(c[17]), C(c[18]), C(c[19]), C(c[20]), C(c[21]), C(c[22]), C(c[23])
#define KGEN_ASM(SD) "{.reg .b64 da, db; add.s64 da, %24, %25; add.s64 db, %24, %26;\n" \
  "wgmma.mma_async.sync.aligned.m64n48k16.f32.bf16.bf16 {%0,%1,%2,%3,%4,%5,%6,%7,%8,%9,%10,%11,%12,%13,%14,%15,%16,%17,%18,%19,%20,%21,%22,%23}, da, db, " SD ", 1, 1, 1, 1;}"
template <int KS> __device__ __forceinline__ void kgen_mma(float (&c)[24], uint64_t da) {
  if (KS) asm volatile(KGEN_ASM("1") : R24("+f", c) : "l"(da), "n"(8 * KS), "n"(8 * KS + 512));
  else asm volatile(KGEN_ASM("0") : R24("=f", c) : "l"(da), "n"(8 * KS), "n"(8 * KS + 512));
  if constexpr (KS < 7) kgen_mma<KS + 1>(c, da);
}
__device__ __forceinline__ uint64_t desc_lo(uint32_t a) { return (uint64_t)((a & 0x3FFFF) >> 4); }
__device__ __forceinline__ void stage1(float (&D)[32], const uint32_t (&A1)[8], uint32_t src) {
  const uint64_t du = desc_lo(src) | (128ull << 16) | (32ull << 32) | (2ull << 62);
  rs64<0, 1, 0>(D, A1, du); rs64<1, 1, 64>(D, A1 + 4, du);
}
template <int INV> __device__ __forceinline__ void stage2(uint32_t (&X)[16], const uint32_t (&F)[16], uint32_t cf) {
  constexpr int KS = INV ? 16 : 128, TB = INV ? 0 : 1;
  const uint64_t dc = desc_lo(cf) | (INV ? (8ull << 16) | (64ull << 32) : (64ull << 16) | (8ull << 32));
  rs64h<0, TB, 0>(X, F, dc); rs64h<1, TB, KS>(X, F + 4, dc); rs64h<1, TB, 2 * KS>(X, F + 8, dc); rs64h<1, TB, 3 * KS>(X, F + 12, dc);
}
__device__ __forceinline__ void fwd_mid(uint32_t (&F)[16], const float (&D)[32], const uint32_t (&tc)[4], const uint32_t (&ts)[4]) {
#pragma unroll
  for (int j = 0; j < 4; j++)
#pragma unroll
    for (int b = 0; b < 2; b++) {
      const int i = 4 * j + 16 * b;
      const uint32_t ar = packh(D[i], D[i + 1]), ai = packh(D[i + 2], D[i + 3]);
      F[2 * j + b] = ffma(ar, tc[j], fmul(ai, ts[j]));
      F[8 + 2 * j + b] = ffma(ai, tc[j], fneg(fmul(ar, ts[j])));
    }
}
__device__ __forceinline__ uint32_t max_exp(uint32_t a) {
  const uint4 v = lds128(a);
  const uint32_t m = amax2(amax2(v.x, v.y), amax2(v.z, v.w));
  return __reduce_max_sync(0xffffffffu, max(m & 0x7f80u, (m >> 16) & 0x7f80u)) >> 7;
}
__device__ __forceinline__ void load_a1(uint32_t (&A1)[8], uint32_t a, uint32_t field) {
  const uint4 x = lds128(a), y = lds128(a + 2048);
  const uint32_t s = field * 0x00800080u;
  A1[0] = hmul2(x.x, s); A1[1] = hmul2(x.y, s); A1[2] = hmul2(x.z, s); A1[3] = hmul2(x.w, s);
  A1[4] = hmul2(y.x, s); A1[5] = hmul2(y.y, s); A1[6] = hmul2(y.z, s); A1[7] = hmul2(y.w, s);
}

struct cf { float x, y; };
__device__ __forceinline__ cf cmul(cf a, cf b) { cf r; r.x = fmaf(a.x, b.x, -a.y * b.y); r.y = fmaf(a.x, b.y, a.y * b.x); return r; }
__device__ __forceinline__ cf cexp_p(float lr2, float lt, float p) {
  float m = exp2f(lr2 * p);
  float t = lt * p;
  t = (t - rintf(t)) * 6.283185307179586f;
  cf r; r.x = m * __cosf(t); r.y = m * __sinf(t); return r;
}
__device__ __forceinline__ void store8(uint32_t a, uint32_t b, const cf (&v)[8]) {
  sts128(a, pack(v[0].x, v[1].x), pack(v[2].x, v[3].x), pack(v[4].x, v[5].x), pack(v[6].x, v[7].x));
  sts128(b, pack(v[0].y, v[1].y), pack(v[2].y, v[3].y), pack(v[4].y, v[5].y), pack(v[6].y, v[7].y));
}
__device__ __forceinline__ void mbar_arrive(uint32_t m) { asm volatile("mbarrier.arrive.shared::cta.b64 _, [%0];" :: "r"(m) : "memory"); }
__device__ __forceinline__ float sigmoidf_(float s) { return 1.f / (1.f + __expf(-s)); }

__global__ void __cluster_dims__(CS, 1, 1) __launch_bounds__(NTHREADS, 1) fused_kernel(const __grid_constant__ Params p) {
  extern __shared__ __align__(1024) uint8_t smem[];
  TL_INIT();
  TL(31);
  const int wid = __shfl_sync(0xffffffffu, threadIdx.x >> 5, 0);
  const uint32_t sb = (uint32_t)__cvta_generic_to_shared(smem);
  const uint32_t mb = sb + OFF_MB;
  const int u = wid >> 2, w = wid & 3;
  const int tid = threadIdx.x & 127, lane = tid & 31, g = lane >> 2, t = lane & 3;
  const int cl = blockIdx.x >> 3, rank = blockIdx.x & 7;
  const int ch0 = cl * CPC;
  const int nu = min(5, (DCH - ch0) >> 3);
  const bool act = u < nu;

  if (u == 4 && lane == 0) {
    if (w < 3) {
#pragma unroll
      for (int i = 0; i < 5; i++) mbar_init(mb + 40 * w + 8 * i, 1);
      fence_mbinit();
#pragma unroll
      for (int i = 0; i < 5; i++) mbar_expect(mb + 40 * w + 8 * i, w < 2 ? 4608 : 8192);
    } else {
      mbar_init(mb + 8 * MB_XQ, 1); mbar_init(mb + 8 * MB_KV, 2); mbar_init(mb + 8 * MB_HA, 1); mbar_init(mb + 8 * MB_CF, 1);
      mbar_init(mb + 8 * MB_Q2, 9); mbar_init(mb + 8 * MB_XD, 4); mbar_init(mb + 8 * MB_KD, 20);
      fence_mbinit();
      mbar_expect(mb + 8 * MB_CF, 16384);
      asm volatile("cp.async.bulk.shared::cluster.global.mbarrier::complete_tx::bytes [%0], [%1], %2, [%3];"
                   :: "r"(sb + OFF_CF), "l"(p.tab->mat), "r"(16384), "r"(mb + 8 * MB_CF) : "memory");
      mbar_expect(mb + 8 * MB_XQ, 20480); mbar_expect(mb + 8 * MB_KV, 23040); mbar_expect(mb + 8 * MB_HA, 20480); mbar_expect(mb + 8 * MB_Q2, 20480);
    }
  }
  uint32_t pla, pai, pcr, pci, pdt, tag = 0;
  uint4 psm;
  {
    const int ch = act ? ch0 + 8 * u + rank : 0, o = ch * NMODE + tid;
    pla = ldraw(p.logA + o); pdt = ldraw(p.logdt + ch); pai = ldraw(p.Aim + o); pcr = ldraw(p.Cre + o); pci = ldraw(p.Cim + o);
    if (w == 1) {
      if (lane < 9) psm = ldg128(lane < 5 ? p.gate_w + (lane < nu ? ch0 + 8 * lane : 0) : p.shift_k + (act ? ch0 + 8 * u : 0) * 4 + 8 * (lane - 5));
      else { psm.x = ldraw(p.Dskip + ch); psm.y = ldraw(p.ssm_D + ch); }
    }
    if (wid == 16 && lane < 2) asm volatile("atom.relaxed.gpu.global.add.u32 %0, [%1], %2;" : "=r"(tag) : "l"(&p.cnt[rank * 32 + lane]), "r"(cl == 0 ? 16 - (NCL - 1) : 1) : "memory");
  }
  if (wid == 19 && lane == 0) {
    tma_load4(sb + OFF_TQ, &p.tq, ch0, 0, 0, 8 * rank, mb + 8 * MB_XQ);
    tma_load4(sb + OFF_TK, &p.tk, ch0, 0, 0, 8 * rank - 1, mb + 8 * MB_KV);
    TL(20);
  }
  __syncwarp();
  cluster_arrive();
  TL(0);

  const uint32_t tab = sb + OFF_T + u * KTAB;
  const int mi = lane >> 3, tq = (lane & 7) >> 1, jj = lane & 1;
  const uint32_t toff = (4 * (2 * mi + jj) + tq) * 80;
  const uint32_t uoff = 16 * (4 * w + (t ^ (w >> 1)));
  auto put = [&](int stage, int dst, int mbar, uint32_t off, const uint32_t (&v)[4]) {
    if (g == rank) st_async4(sb + dst + 512 * rank + off, v[0], v[1], v[2], v[3], sb + mbar);
    else sts128(sb + stage + g * YPITCH + off, v[0], v[1], v[2], v[3]);
  };
  auto send = [&](int stage, int pitch, int dst, int mbar) {
    if (lane == 0) {
#pragma unroll
      for (int k = 0; k < 2; k++) {
        const int d = 2 * w + k;
        if (d != rank) { const uint32_t rb = mapa(sb, d); bulk_dsmem(rb + dst, sb + stage + d * pitch, rb + mbar); }
      }
    }
    __syncwarp();
  };

  uint32_t tc[4], ts[4];
  {
    const uint4 a = ldg128(p.tab->thr[2][tid]), b = ldg128(p.tab->thr[3][tid]);
    tc[0] = a.x; tc[1] = a.y; tc[2] = a.z; tc[3] = a.w; ts[0] = b.x; ts[1] = b.y; ts[2] = b.z; ts[3] = b.w;
  }
  if (w == 1 && lane < 10) sts128(sb + OFF_SP + 160 * u + 16 * lane, psm.x, psm.y, psm.z, psm.w);
  if (u == 4) {
    cluster_wait();
    mbar_wait(mb + 8 * MB_XQ);
    TL(18);
#pragma unroll
    for (int k = 0; k < 5; k++) {
      uint32_t x0[4], x1[4];
      ldsm4t(x0, sb + OFF_TQ + w * 2560 + toff + 16 * k);
      ldsm4t(x1, sb + OFF_TQ + (w + 4) * 2560 + toff + 16 * k);
      put(OFF_YB + 8 * k * YPITCH, OFF_UX + k * 4096, OFF_MB + 8 * (MB_UX + k), uoff, x0);
      put(OFF_YB + 8 * k * YPITCH, OFF_UX + k * 4096, OFF_MB + 8 * (MB_UX + k), (uoff ^ 32) + 256, x1);
      st_async1(mapa(sb + OFF_MX + k * 1024 + 512 + 4 * (16 * rank + 4 * w + t), g), amax8(x0, x1), mapa(mb + 8 * (MB_UX + k), g));
    }
    if (tid == 0) sts32(mb + 8 * MB_TAG, tag);
    TL(3);
    fence_async();
    bar_sync(NB_WG0 + u, 128);
    TL(4);
#pragma unroll 1
    for (int k = 0; k < 5; k++) send(OFF_YB + 8 * k * YPITCH, YPITCH, OFF_UX + k * 4096 + 512 * rank, OFF_MB + 8 * (MB_UX + k));
    if (tid == 96) {
      mbar_expect(mb + 8 * MB_KV, 20480);
      tma_load4(sb + OFF_TV, &p.tv, ch0, 0, 0, 8 * rank, mb + 8 * MB_KV);
    }
    __syncwarp();
    TL(7);
    float s0 = 0.f, s1 = 0.f;
#pragma unroll
    for (int j = 0; j < 5; j++) {
      const uint4 gw = lds128(sb + OFF_SP + 160 * u + 16 * j);
      const uint4 x0 = lds128(sb + OFF_TQ + tid * 80 + 16 * j), x1 = lds128(sb + OFF_TQ + (tid + 128) * 80 + 16 * j);
      uint32_t m0 = hmul2(x0.x, gw.x), m1 = hmul2(x0.y, gw.y), m2 = hmul2(x0.z, gw.z), m3 = hmul2(x0.w, gw.w);
      s0 += ((blo(m0) + bhi(m0)) + (blo(m1) + bhi(m1))) + ((blo(m2) + bhi(m2)) + (blo(m3) + bhi(m3)));
      m0 = hmul2(x1.x, gw.x); m1 = hmul2(x1.y, gw.y); m2 = hmul2(x1.z, gw.z); m3 = hmul2(x1.w, gw.w);
      s1 += ((blo(m0) + bhi(m0)) + (blo(m1) + bhi(m1))) + ((blo(m2) + bhi(m2)) + (blo(m3) + bhi(m3)));
    }
    tag = (lds64(mb + 8 * MB_TAG).x >> 4) + 1;
    uint2* gp = p.part + cl * SEQ + rank * 256 + 8 * (8 * t + g) + w;
    asm volatile("st.relaxed.gpu.global.u64 [%0], %1;" :: "l"(gp), "l"(((uint64_t)tag << 32) | __float_as_uint(s0)) : "memory");
    asm volatile("st.relaxed.gpu.global.u64 [%0], %1;" :: "l"(gp + 4), "l"(((uint64_t)tag << 32) | __float_as_uint(s1)) : "memory");
    __syncwarp();
    if (lane == 0) mbar_arrive(mb + 8 * MB_XD);
    TL(8);
  }

  {
    const float dt = bf16r(expf(blo(pdt)));
    const float lr2 = (-bf16r(expf(blo(pla))) * dt) * 1.4426950408889634f;
    const float lt = (blo(pai) * dt) * 0.15915494309189535f;
    const uint32_t tim = u < 2 ? tab + 3 * KTAB : sb + OFF_HA;
    const uint32_t row = tab + tid * 16, rim = tim + tid * 16;
    if (lr2 != 123.f) TL(16);
    if (u >= 3) bar_sync(NB_K3 + u - 3, 384);
    TL(11);
    {
      const cf w1 = cexp_p(lr2, lt, 8.f);
      cf v[8];
      v[0].x = 1.f; v[0].y = 0.f; v[1] = w1; v[2] = cmul(w1, w1); v[3] = cmul(v[2], w1);
      const cf w4 = cmul(v[2], v[2]);
      v[4] = w4; v[5] = cmul(v[1], w4); v[6] = cmul(v[2], w4); v[7] = cmul(v[3], w4);
      const cf w8 = cmul(w4, w4);
      store8(row, rim, v);
#pragma unroll
      for (int k = 1; k < 4; k++) {
#pragma unroll
        for (int i = 0; i < 8; i++) v[i] = (k == 1 && i == 0) ? w8 : cmul(v[i], w8);
        store8(row + 2048 * k, rim + 2048 * k, v);
      }
    }
    {
      cf z1 = cexp_p(lr2, lt, 1.f), Z = cexp_p(lr2, lt, 256.f);
      z1.y = -z1.y; Z.y = -Z.y;
      const cf z2 = cmul(z1, z1);
      cf h[8], v[8];
      h[0].x = 2.f * blo(pcr) * dt; h[0].y = -2.f * blo(pci) * dt;
      h[1] = cmul(h[0], z1);
#pragma unroll
      for (int i = 2; i < 8; i++) h[i] = cmul(h[i - 2], z2);
      store8(row + 4 * 2048, rim + 4 * 2048, h);
      v[0] = cmul(h[0], Z); v[1] = cmul(h[2], Z); v[2] = cmul(h[4], Z); v[3] = cmul(h[6], Z);
      v[4] = cmul(v[0], Z); v[5] = cmul(v[2], Z); v[6] = cmul(v[4], Z); v[7] = cmul(v[5], Z);
      store8(row + 5 * 2048, rim + 5 * 2048, v);
      const cf Z2 = cmul(Z, Z);
      h[0] = cmul(v[4], Z2); h[1] = cmul(v[6], Z2); h[2] = cmul(h[0], Z2); h[3] = cmul(h[1], Z2); h[4] = cmul(h[2], Z2);
      h[5].x = h[5].y = h[6].x = h[6].y = h[7].x = h[7].y = 0.f;
      store8(row + 6 * 2048, rim + 6 * 2048, h);
    }
    TL(17);
    fence_async();
    bar_sync(NB_WG0 + u, 128);
    float c[24];
    wg_fence();
    kgen_mma<0>(c, desc_lo(tab) | ((uint64_t)((tim - tab) >> 4) << 16) | (64ull << 32));
    wg_commit();
    uint32_t kid[8];
    {
      const float lf = __uint_as_float(0x4b000000u | (8 * tid)) - 8388608.f;
      const float lo = tid < 16 ? lf + 128.f : lf;
      const uint32_t sub = tid < 16 ? 0x42804300u : 0x42804280u;
#pragma unroll
      for (int i = 0; i < 8; i++) kid[i] = 2 * (pack(lo + i, lf + (1024 + i)) - sub);
    }
    if (u < 4) cluster_wait();
    wg_wait<0>(); tie_all(c);
    if (u < 4) bar_arrive(NB_K3 + (u & 1), 384);
    cluster_arrive();
    const uint32_t kc = sb + OFF_KC + u * 1408;
    {
      const int a = 8 * w + g;
      const uint32_t k0 = pack(c[0] + c[6], c[1] + c[7]), k1 = pack(c[8] + c[14], c[9] + c[15]), p0 = pack(c[16] + c[22], c[17] + c[23]);
      sts32(kc + 4 * (4 * a + t), k0);
      sts32(kc + 4 * (t < 2 ? 128 + 2 * a + t : 128 + 32 * t + a), k1);
      sts32(sb + OFF_MX + u * 1024 + 4 * tid, amax2(amax2(k0, k1), p0));
      if (t < 3) {
        sts16(kc + 2 * (512 + 64 * t + a), p0);
        sts16(kc + 2 * (544 + 64 * t + a), p0 >> 16);
      }
    }
    TL(19);
    bar_sync(NB_WG0 + u, 128);
    if (wid == 16 && lane == 0) { tma_load4(sb + OFF_HA, &p.th, 0, 0, 5 * cl, rank, mb + 8 * MB_HA); TL(20); }
    __syncwarp();
    uint32_t v[2][8];
#pragma unroll
    for (int i = 0; i < 8; i++) { v[0][i] = lds16(kc + (kid[i] & 0xffffu)); v[1][i] = lds16(kc + (kid[i] >> 16)); }
#pragma unroll
    for (int cc = 0; cc < 2; cc++)
      sts128(tab + 2048 * cc + 16 * (tid ^ ((tid >> 3) & 3)), prmt(v[cc][0], v[cc][1], 0x5410), prmt(v[cc][2], v[cc][3], 0x5410),
             prmt(v[cc][4], v[cc][5], 0x5410), prmt(v[cc][6], v[cc][7], 0x5410));
    fence_async();
    bar_sync(NB_WG0 + u, 128);
    mbar_wait(mb + 8 * MB_CF);
  }

#pragma unroll
  for (int isA = 0; isA < 2; isA++) {
    if (isA) {
      cluster_wait();
      mbar_wait(mb + 8 * MB_XD);
      mbar_wait(mb + 8 * MB_KV);
      TL(21);
      {
        const uint32_t hoff = (4 * (4 + 2 * (mi & 1) + jj) + ((tq + 3) & 3)) * 80 + (tq ? 2560 : 0) + 16 * u;
        uint32_t E[2][6], V[2][4];
        const uint2 psw = lds64(sb + OFF_SP + 160 * u + 80 + 8 * g);
#pragma unroll
        for (int hf = 0; hf < 2; hf++) {
          const int ah = 4 * hf + w;
          uint32_t K[4];
          ldsm4t(K, sb + OFF_TK + (ah + 1) * 2560 + toff + 16 * u);
          ldsm2t(E[hf][0], E[hf][1], sb + OFF_TK + ah * 2560 + hoff);
          ldsm4t(V[hf], sb + OFF_TV + ah * 2560 + toff + 16 * u);
          E[hf][2] = K[0]; E[hf][3] = K[1]; E[hf][4] = K[2]; E[hf][5] = K[3];
        }
        const uint32_t w0 = prmt(psw.x, 0, 0x1010), w1 = prmt(psw.x, 0, 0x3232), w2 = prmt(psw.y, 0, 0x1010), w3 = prmt(psw.y, 0, 0x3232);
        uint32_t o[2][4];
#pragma unroll
        for (int hf = 0; hf < 2; hf++) {
          uint32_t O[5];
#pragma unroll
          for (int i = 0; i < 5; i++) O[i] = prmt(E[hf][i], E[hf][i + 1], 0x5432);
#pragma unroll
          for (int i = 0; i < 4; i++) {
            uint32_t s = hmul2(O[i], w3);
            s = hadd2(s, hmul2(E[hf][i + 1], w2));
            s = hadd2(s, hmul2(O[i + 1], w1));
            s = hadd2(s, hmul2(E[hf][i + 2], w0));
            o[hf][i] = hmul2(s, V[hf][i]);
          }
          put(OFF_YA + 8 * u * YPITCH, OFF_T + u * KTAB + T_UKV, OFF_MB + 8 * (MB_UKV + u), hf ? (uoff ^ 32) + 256 : uoff, o[hf]);
        }
        st_async1(mapa(tab + T_MX + 512 + 4 * (16 * rank + 4 * w + t), g), amax8(o[0], o[1]), mapa(mb + 8 * (MB_UKV + u), g));
        TL(12);
        fence_async();
        TL(13);
        bar_sync(NB_WG0 + u, 128);
        TL(14);
        send(OFF_YA + 8 * u * YPITCH, YPITCH, OFF_T + u * KTAB + T_UKV + 512 * rank, OFF_MB + 8 * (MB_UKV + u));
      }
      if (lane == 0) mbar_arrive(mb + 8 * MB_KD);
      TL(22);
      TL(23);
      mbar_wait(mb + 8 * MB_HA);
      {
        const uint4 a = lds128(sb + OFF_HA + u * 4096 + 16 * tid), b = lds128(sb + OFF_HA + u * 4096 + 2048 + 16 * tid);
        const uint32_t aa[4] = {a.x, a.y, a.z, a.w}, bb[4] = {b.x, b.y, b.z, b.w};
        sts32(tab + T_MX + 4 * tid, amax8(aa, bb));
      }
      bar_sync(NB_WG0 + u, 128);
    }
    {
      TL(1 + isA);
      const uint32_t usrc = isA ? tab + T_UKV : sb + OFF_UX + u * 4096;
      const uint32_t mxa = (isA ? tab + T_MX : sb + OFF_MX + u * 1024) + 16 * lane;
      const uint32_t pd = lds16(sb + OFF_SP + 160 * u + 144 + 4 * isA);
      float D[32];
      uint32_t A1[8], F[16], H[16], X[16];
      const uint32_t eh = min(max((int)max_exp(mxa), (int)((pd >> 7) & 0xff) - 5), 240);
      load_a1(A1, sb + OFF_A1 + 16 * tid, 248 - eh);
      wg_fence();
      stage1(D, A1, isA ? sb + OFF_HA + u * 4096 : tab);
      wg_commit();
      wg_wait<0>(); tie_all(D);
      fwd_mid(F, D, tc, ts);
      wg_fence();
      stage2<0>(H, F, sb + OFF_CF);
      wg_commit();
      mbar_wait(mb + 8 * ((isA ? MB_UKV : MB_UX) + u));
      fence_async();
      TL(5 + isA);
      const uint32_t eu = min(max_exp(mxa + 512), 240u);
      load_a1(A1, sb + OFF_A1 + 16 * tid, 250 - eu);
      wg_wait<0>(); tie_all(H);
      wg_fence();
      stage1(D, A1, usrc);
      wg_commit();
      wg_wait<0>(); tie_all(D);
      fwd_mid(F, D, tc, ts);
      wg_fence();
      stage2<0>(X, F, sb + OFF_CF);
      wg_commit();
      {
        const float dsk = blo(pd) * __uint_as_float((248 - eh) << 23);
        const uint32_t d2 = packh(dsk, dsk);
#pragma unroll
        for (int j = 0; j < 4; j++) H[2 * j] = U2(__hadd2(H2(H[2 * j]), H2(d2)));
      }
      wg_wait<0>(); tie_all(X);
#pragma unroll
      for (int j = 0; j < 4; j++) {
        const uint32_t h0r = H[2 * j], h1r = H[2 * j + 1], h0i = H[8 + 2 * j], h1i = H[9 + 2 * j];
        const uint32_t x0r = X[2 * j], x1r = X[2 * j + 1], x0i = X[8 + 2 * j], x1i = X[9 + 2 * j];
        F[2 * j] = ffma(x0r, h0r, fneg(fmul(x0i, h0i)));
        F[8 + 2 * j] = ffma(x0r, h0i, fmul(x0i, h0r));
        F[2 * j + 1] = ffma(x1r, h0r, ffma(fneg(x1i), h0i, ffma(x0r, h1r, fneg(ffma(x0i, h1i, F[8 + 2 * j])))));
        F[9 + 2 * j] = ffma(x1r, h0i, ffma(x1i, h0r, ffma(x0r, h1i, ffma(x0i, h1r, F[2 * j]))));
      }
      wg_fence();
      stage2<1>(H, F, sb + OFF_CF);
      wg_commit();
      wg_wait<0>(); tie_all(H);
      {
        const uint32_t va = tab + (16 * w + (lane & 15)) * 128;
        const int vx = (lane >> 4) ^ (lane & 7);
#pragma unroll
        for (int j = 0; j < 4; j++) {
          uint32_t V[4];
#pragma unroll
          for (int b = 0; b < 2; b++) {
            const uint32_t er = H[2 * j + b], ei = H[8 + 2 * j + b];
            V[2 * b] = ffma(er, tc[j], fneg(fmul(ei, ts[j])));
            V[2 * b + 1] = ffma(ei, tc[j], fmul(er, ts[j]));
          }
          stsm4(va + ((vx ^ (2 * j)) << 4), V);
        }
      }
      fence_async();
      bar_sync(NB_WG0 + u, 128);
      float O[16];
      {
        const uint64_t dv = desc_lo(tab) | (1ull << 16) | (64ull << 32) | (1ull << 62);
        const uint64_t dl = desc_lo(sb + OFF_CL) | (32ull << 16) | (8ull << 32);
        wg_fence();
        ss32<0, 0, 0>(O, dv, dl); ss32<1, 128, 64>(O, dv, dl); ss32<1, 256, 128>(O, dv, dl); ss32<1, 384, 192>(O, dv, dl);
        wg_commit();
      }
      wg_wait<0>(); tie_all(O);
      {
        const uint32_t co = ((8 * w + g) ^ (2 * t)) * 16;
        const int yo = (isA ? OFF_YA : OFF_YB) + (8 * u + rank) * YPITCH, ym = OFF_MB + 8 * (MB_Y + u);
        const uint32_t us = min(max((int)(eu + eh) - 127, 0), 254) * 0x00800080u;
        const uint32_t a0 = hmul2(pack(O[0], O[1]), us), a1 = hmul2(pack(O[4], O[5]), us), a2 = hmul2(pack(O[8], O[9]), us), a3 = hmul2(pack(O[12], O[13]), us);
        const uint32_t b0 = hmul2(pack(O[2], O[3]), us), b1 = hmul2(pack(O[6], O[7]), us), b2 = hmul2(pack(O[10], O[11]), us), b3 = hmul2(pack(O[14], O[15]), us);
        sts128(usrc + t * 512 + co, a0, a1, a2, a3);
        sts128(usrc + t * 512 + 2048 + co, b0, b1, b2, b3);
        if (t == (rank & 3)) {
          if (rank < 4) st_async4(sb + yo + co, a0, a1, a2, a3, sb + ym); else st_async4(sb + yo + co, b0, b1, b2, b3, sb + ym);
        }
        if (isA) TL(15);
        fence_async();
        bar_sync(NB_WG0 + u, 128);
        if (isA) TL(26);
        send(usrc - sb, 512, yo, ym);
      }
      TL(9 + isA);
    }
  }

  mbar_wait(mb + 8 * MB_KD);
  if (wid == 8 && lane == 0) tma_load3(sb + OFF_Q2, &p.tq2, ch0, 8 * rank, 0, mb + 8 * MB_Q2);
  __syncwarp();
  if (u < 2) {
    const int slot = tid + 128 * u;
    tag = (lds64(mb + 8 * MB_TAG).x >> 4) + 1;
    float s = 0.f;
    bool ok = false;
    const uint2* gp = p.part + rank * 256 + slot;
#pragma unroll 1
    for (int it = 0; it < 4000 && !ok; it++) {
      ok = true; s = 0.f;
#pragma unroll
      for (int k = 0; k < NCL; k++) {
        uint64_t a;
        asm volatile("ld.relaxed.gpu.global.u64 %0, [%1];" : "=l"(a) : "l"(gp + k * SEQ) : "memory");
        ok = ok && (uint32_t)(a >> 32) == tag;
        s += __uint_as_float((uint32_t)a);
      }
    }
    if (!ok) {
      const uint32_t* xr = (const uint32_t*)(p.q + (size_t)(rank * 256 + 32 * (slot & 7) + (slot >> 3)) * DCH);
      const uint32_t* gr = (const uint32_t*)p.gate_w;
      s = 0.f;
#pragma unroll 1
      for (int k = 0; k < DCH / 2; k++) { const uint32_t m = hmul2(__ldg(xr + k), __ldg(gr + k)); s += blo(m) + bhi(m); }
    }
    const float g0 = bf16r(sigmoidf_(bf16r(s)));
    sts64(sb + OFF_GB + 8 * slot, pack(g0, g0), pack(1.f - g0, 1.f - g0));
    __syncwarp();
    if (lane == 0) mbar_arrive(mb + 8 * MB_Q2);
  }
  {
    mbar_wait(mb + 8 * MB_Q2);
    uint2 gg[2][4];
    uint32_t qv[2][4];
#pragma unroll
    for (int hh = 0; hh < 2; hh++)
#pragma unroll
      for (int i = 0; i < 4; i++) gg[hh][i] = lds64(sb + OFF_GB + 8 * (64 * w + 32 * hh + 8 * i + g));
    const uint32_t qa = sb + OFF_Q2 + (64 * w + lane) * 80 + 16 * u;
    ldsm4(qv[0], qa);
    ldsm4(qv[1], qa + 2560);
    TL(24);
    mbar_wait(mb + 8 * (MB_Y + u));
    uint32_t ya[2][4], yb[2][4];
#pragma unroll
    for (int hh = 0; hh < 2; hh++) {
      const uint32_t yo = (8 * u + (lane & 7)) * YPITCH + ((8 * w + 4 * hh + (lane >> 3)) ^ (2 * (rank & 3))) * 16;
      ldsm4t(ya[hh], sb + OFF_YA + yo); ldsm4t(yb[hh], sb + OFF_YB + yo);
    }
#pragma unroll
    for (int hh = 0; hh < 2; hh++) {
      uint32_t o[4];
#pragma unroll
      for (int i = 0; i < 4; i++) o[i] = hadd2(hmul2(gg[hh][i].x, hmul2(qv[hh][i], ya[hh][i])), hmul2(gg[hh][i].y, yb[hh][i]));
      stsm4(qa + 2560 * hh, o);
    }
    TL(25);
  }
  cluster_arrive();
  bar_sync(NB_ROW0 + w, 160);
  {
    uint4 v[2];
#pragma unroll
    for (int k = 0; k < 2; k++) {
      const int i = 64 * u + 32 * k + lane, sl = (i * 205) >> 10, cc = i - 5 * sl;
      v[k] = lds128(sb + OFF_Q2 + (64 * w + 8 * (sl & 7) + (sl >> 3)) * 80 + cc * 16);
    }
#pragma unroll
    for (int k = 0; k < 2; k++) {
      const int i = 64 * u + 32 * k + lane, sl = (i * 205) >> 10, cc = i - 5 * sl;
      if (cc < nu)
        asm volatile("st.global.v4.u32 [%0], {%1,%2,%3,%4};" :: "l"(p.out + (size_t)(256 * rank + 32 * (sl >> 3) + 8 * w + (sl & 7)) * DCH + ch0 + 8 * cc),
                     "r"(v[k].x), "r"(v[k].y), "r"(v[k].z), "r"(v[k].w) : "memory");
    }
  }
  cluster_wait();
  TL(27);
  TL_DUMP();
}

typedef CUresult (*EncodeFn)(CUtensorMap*, CUtensorMapDataType, cuuint32_t, void*, const cuuint64_t*, const cuuint64_t*,
                             const cuuint32_t*, const cuuint32_t*, CUtensorMapInterleave, CUtensorMapSwizzle,
                             CUtensorMapL2promotion, CUtensorMapFloatOOBfill);

void encode(EncodeFn fn, CUtensorMap* tm, const void* ptr, int nd, const cuuint64_t* dims, const cuuint64_t* strides,
            const cuuint32_t* box, CUtensorMapSwizzle swz) {
  cuuint32_t es[4] = {1, 1, 1, 1};
  fn(tm, CU_TENSOR_MAP_DATA_TYPE_BFLOAT16, nd, const_cast<void*>(ptr), dims, strides, box, es, CU_TENSOR_MAP_INTERLEAVE_NONE,
     swz, CU_TENSOR_MAP_L2_PROMOTION_L2_128B, CU_TENSOR_MAP_FLOAT_OOB_FILL_NONE);
}
void map1(EncodeFn fn, CUtensorMap* tm, const void* ptr, int nhi) {
  const cuuint64_t dims[4] = {DCH, 4, 8, SEQ / 32}, strides[3] = {8 * DCH * 2, DCH * 2, 32 * DCH * 2};
  const cuuint32_t box[4] = {CPC, 4, 8, (cuuint32_t)nhi};
  encode(fn, tm, ptr, 4, dims, strides, box, CU_TENSOR_MAP_SWIZZLE_NONE);
}
void map2(EncodeFn fn, CUtensorMap* tm, const void* ptr, int nr) {
  const cuuint64_t dims[3] = {DCH, SEQ / 32, 32}, strides[2] = {32 * DCH * 2, DCH * 2};
  const cuuint32_t box[3] = {CPC, 8, (cuuint32_t)nr};
  encode(fn, tm, ptr, 3, dims, strides, box, CU_TENSOR_MAP_SWIZZLE_NONE);
}

}

extern "C" void kernel_launch(void* const* d_in, const int* in_sizes, int n_in, void* d_out, int out_size) {
  (void)in_sizes; (void)n_in; (void)out_size;
  static EncodeFn fn = nullptr;
  static void *tab = nullptr, *cnt = nullptr, *part = nullptr;
  if (!fn) {
    cudaGetSymbolAddress(&tab, d_tab);
    cudaGetSymbolAddress(&cnt, g_cnt);
    cudaGetSymbolAddress(&part, g_part);
    cudaDriverEntryPointQueryResult qr;
    cudaGetDriverEntryPoint("cuTensorMapEncodeTiled", (void**)&fn, cudaEnableDefault, &qr);
    cudaFuncSetAttribute(fused_kernel, cudaFuncAttributeMaxDynamicSharedMemorySize, SMEM_BYTES);
  }
  Params p;
  map1(fn, &p.tq, d_in[0], 8);
  map1(fn, &p.tk, d_in[1], 9);
  map1(fn, &p.tv, d_in[2], 8);
  map2(fn, &p.tq2, d_in[0], 32);
  p.out = (__nv_bfloat16*)d_out;
  {
    const cuuint64_t dims[4] = {32, SEQ / 32, DCH / 8, 8}, strides[3] = {64, 8 * SEQ * 2, SEQ * 2};
    const cuuint32_t box[4] = {32, 64, 5, 1};
    encode(fn, &p.th, d_in[4], 4, dims, strides, box, CU_TENSOR_MAP_SWIZZLE_64B);
  }
  p.tab = (const Tables*)tab;
  p.cnt = (unsigned*)cnt;
  p.part = (uint2*)part;
  p.tl = nullptr;
  p.q = (const __nv_bfloat16*)d_in[0];
  p.shift_k = (const __nv_bfloat16*)d_in[3];
  p.ssm_D = (const __nv_bfloat16*)d_in[5];
  p.logA = (const __nv_bfloat16*)d_in[7];
  p.Aim = (const __nv_bfloat16*)d_in[8];
  p.Cre = (const __nv_bfloat16*)d_in[9];
  p.Cim = (const __nv_bfloat16*)d_in[10];
  p.logdt = (const __nv_bfloat16*)d_in[11];
  p.Dskip = (const __nv_bfloat16*)d_in[12];
  p.gate_w = (const __nv_bfloat16*)d_in[13];
  fused_kernel<<<NCL * CS, NTHREADS, SMEM_BYTES, cudaStreamPerThread>>>(p);
}
```

```cpp
#include <cuda_runtime.h>
#include <cuda_bf16.h>
#include <cuda_fp16.h>
#include <cuda.h>
#include <stdint.h>

#define TIMELINE 0

namespace {

constexpr int SEQ = 2048, DCH = 576, NMODE = 128;
constexpr int CS = 8, CPC = 40, NCL = 15, NTHREADS = 640;

constexpr int YPITCH = 528;
constexpr int KTAB = 14336;
constexpr int OFF_T = 0;
constexpr int T_UKV = 8192;
constexpr int OFF_UX = 5 * KTAB;
constexpr int OFF_HA = OFF_UX + 20480;
constexpr int OFF_CF = OFF_HA + 20480;
constexpr int OFF_CL = OFF_CF + 8192;
constexpr int OFF_A1 = OFF_CL + 4096;
constexpr int OFF_TQ = OFF_A1 + 4096;
constexpr int OFF_YA = OFF_TQ;
constexpr int OFF_TK = OFF_TQ + 21120;
constexpr int OFF_Q2 = OFF_TK;
constexpr int OFF_TV = OFF_TK + 23040;
constexpr int OFF_YB = OFF_TV + 20480;
constexpr int OFF_KC = OFF_YB + 40 * YPITCH;
constexpr int OFF_GB = OFF_KC;
constexpr int OFF_MX = OFF_KC + 5 * 1408;
constexpr int OFF_SP = OFF_MX + 320;
constexpr int OFF_MB = OFF_SP + 5 * 160;
constexpr int OFF_TL = OFF_MB + 32 * 8;
constexpr int SMEM_BYTES = OFF_TL + (TIMELINE ? 2560 : 0);
static_assert(SMEM_BYTES <= 232448, "smem");
static_assert((KTAB & 1023) == 0 && (OFF_TQ & 127) == 0 && (OFF_TK & 127) == 0 && (OFF_TV & 127) == 0 && (OFF_MB & 7) == 0 && (OFF_KC & 15) == 0, "align");

enum { MB_UX = 0, MB_UKV = 5, MB_Y = 10, MB_XQ = 15, MB_KV = 16, MB_HA = 17, MB_CF = 18, MB_Q2 = 19, MB_XD = 20, MB_KD = 21, MB_TAG = 22 };
enum { NB_WG0 = 1, NB_ROW0 = 6, NB_K3 = 10, NB_K4 = 11 };

constexpr double cos_turn(int m, int n) {
  m &= n - 1;
  if (m > n / 2) m = n - m;
  double sgn = 1.0;
  if (m > n / 4) { m = n / 2 - m; sgn = -1.0; }
  if (m == n / 4) return 0.0;
  const double x = 6.283185307179586476925 * m / n;
  double term = 1.0, sum = 1.0;
  for (int k = 1; k < 14; k++) { term *= -x * x / ((2 * k - 1) * (2 * k)); sum += term; }
  return sgn * sum;
}
constexpr uint32_t bf16_bits(double v) {
  if (v == 0.0) return 0;
  uint32_t sgn = 0;
  if (v < 0) { sgn = 0x8000; v = -v; }
  int e = 127;
  while (v < 1.0) { v *= 2.0; e--; }
  while (v >= 2.0) { v *= 0.5; e++; }
  const double f = v * 128.0;
  int m = (int)f;
  if (f - m > 0.5 || (f - m == 0.5 && (m & 1))) m++;
  return sgn | (uint32_t)((e << 7) + (m - 128));
}
constexpr uint32_t f16_bits(double v) {
  if (v == 0.0) return 0;
  uint32_t sgn = 0;
  if (v < 0) { sgn = 0x8000; v = -v; }
  int e = 15;
  while (v < 1.0) { v *= 2.0; e--; }
  const double f = v * 1024.0;
  int m = (int)f;
  if (f - m > 0.5 || (f - m == 0.5 && (m & 1))) m++;
  return sgn | (uint32_t)((e << 10) + (m - 1024));
}
constexpr uint32_t pair_bits(double lo, double hi) { return bf16_bits(lo) | (bf16_bits(hi) << 16); }
constexpr uint32_t pair_h(double lo, double hi) { return f16_bits(lo) | (f16_bits(hi) << 16); }
struct alignas(128) Tables {
  uint32_t mat[3072];
  uint32_t thr[4][128][4];
};
constexpr Tables make_tables() {
  Tables T{};
  for (int q = 0; q < 768; q++) {
    int m0 = 0, d0 = 0, d1 = 0;
    if (q < 512) {
      const int r = (q >> 6) * 8 + (q & 7), cc = (q >> 3) & 7;
      d0 = 4 * (r & 31); d1 = 2 * d0;
      m0 = 8 * (cc & 3) * d0 + ((r >> 5) == (cc >> 2) ? 0 : (r >> 5) ? 96 : 32);
    } else {
      const int r = ((q - 512) >> 5) * 8 + (q & 7), pc = (q >> 3) & 3;
      d0 = 4 * (8 * (r >> 4) + (r & 7)) + 1; d1 = 8 * d0;
      m0 = 2 * pc * d0 + ((r & 8) ? 32 : 0);
    }
    for (int e = 0; e < 4; e++) T.mat[4 * q + e] = pair_h(cos_turn(m0 + e * d1, 128), cos_turn(m0 + e * d1 + d0, 128));
  }
  for (int tid = 0; tid < 128; tid++) {
    const int kk = 4 * (tid >> 2) + 1, t = tid & 3;
    for (int q = 0; q < 4; q++) {
      const int m = (8 * q + 2 * t) * kk;
      T.thr[q >> 1][tid][2 * (q & 1)] = pair_bits(cos_turn(m, 128), cos_turn(m + kk, 128));
      T.thr[q >> 1][tid][2 * (q & 1) + 1] = pair_bits(cos_turn(m + 32, 128), cos_turn(m + kk + 32, 128));
      T.thr[2][tid][q] = pair_h(cos_turn(m, 4096), cos_turn(m + kk, 4096));
      T.thr[3][tid][q] = pair_h(cos_turn(m + 3072, 4096), cos_turn(m + kk + 3072, 4096));
    }
  }
  return T;
}
__device__ const Tables d_tab = make_tables();

struct Params {
  const __nv_bfloat16 *logA, *Aim, *Cre, *Cim, *logdt;
  const Tables* tab;
  unsigned* cnt;
  const __nv_bfloat16 *Dskip, *shift_k, *ssm_D, *gate_w, *q;
  uint2* part;
  __nv_bfloat16* out;
  unsigned* tl;
  CUtensorMap tq, tk, tv, th, tq2;
};

__device__ uint2 g_part[NCL * SEQ];
__device__ unsigned g_cnt[CS * 32];
#define TL(i) do {} while (0)
#define TL_INIT() do {} while (0)
#define TL_DUMP() do {} while (0)

__device__ __forceinline__ uint32_t lds16(uint32_t a) { uint32_t v; asm volatile("ld.shared.u16 %0, [%1];" : "=r"(v) : "r"(a) : "memory"); return v; }
__device__ __forceinline__ uint2 lds64(uint32_t a) { uint2 v; asm volatile("ld.shared.v2.u32 {%0,%1}, [%2];" : "=r"(v.x), "=r"(v.y) : "r"(a) : "memory"); return v; }
__device__ __forceinline__ uint4 lds128(uint32_t a) { uint4 v; asm volatile("ld.shared.v4.u32 {%0,%1,%2,%3}, [%4];" : "=r"(v.x), "=r"(v.y), "=r"(v.z), "=r"(v.w) : "r"(a) : "memory"); return v; }
__device__ __forceinline__ void sts16(uint32_t a, uint32_t v) { asm volatile("st.shared.u16 [%0], %1;" :: "r"(a), "r"(v) : "memory"); }
__device__ __forceinline__ void sts32(uint32_t a, uint32_t v) { asm volatile("st.shared.u32 [%0], %1;" :: "r"(a), "r"(v) : "memory"); }
__device__ __forceinline__ void sts64(uint32_t a, uint32_t x, uint32_t y) { asm volatile("st.shared.v2.u32 [%0], {%1,%2};" :: "r"(a), "r"(x), "r"(y) : "memory"); }
__device__ __forceinline__ void sts128(uint32_t a, uint32_t x, uint32_t y, uint32_t z, uint32_t w) { asm volatile("st.shared.v4.u32 [%0], {%1,%2,%3,%4};" :: "r"(a), "r"(x), "r"(y), "r"(z), "r"(w) : "memory"); }
__device__ __forceinline__ void ldsm4t(uint32_t (&r)[4], uint32_t a) { asm volatile("ldmatrix.sync.aligned.m8n8.x4.trans.shared.b16 {%0,%1,%2,%3}, [%4];" : "=r"(r[0]), "=r"(r[1]), "=r"(r[2]), "=r"(r[3]) : "r"(a) : "memory"); }
__device__ __forceinline__ void ldsm2t(uint32_t& r0, uint32_t& r1, uint32_t a) { asm volatile("ldmatrix.sync.aligned.m8n8.x2.trans.shared.b16 {%0,%1}, [%2];" : "=r"(r0), "=r"(r1) : "r"(a) : "memory"); }
__device__ __forceinline__ void ldsm4(uint32_t (&r)[4], uint32_t a) { asm volatile("ldmatrix.sync.aligned.m8n8.x4.shared.b16 {%0,%1,%2,%3}, [%4];" : "=r"(r[0]), "=r"(r[1]), "=r"(r[2]), "=r"(r[3]) : "r"(a) : "memory"); }
__device__ __forceinline__ void stsm4(uint32_t a, const uint32_t (&r)[4]) { asm volatile("stmatrix.sync.aligned.m8n8.x4.shared.b16 [%0], {%1,%2,%3,%4};" :: "r"(a), "r"(r[0]), "r"(r[1]), "r"(r[2]), "r"(r[3]) : "memory"); }
__device__ __forceinline__ uint32_t pack(float lo, float hi) { uint32_t r; asm("cvt.rn.bf16x2.f32 %0, %1, %2;" : "=r"(r) : "f"(hi), "f"(lo)); return r; }
__device__ __forceinline__ float blo(uint32_t v) { return __uint_as_float(v << 16); }
__device__ __forceinline__ float bhi(uint32_t v) { return __uint_as_float(v & 0xffff0000u); }
__device__ __forceinline__ float bf16r(float x) { return blo(pack(x, 0.f)); }
__device__ __forceinline__ uint32_t hmul2(uint32_t a, uint32_t b) { uint32_t r; asm("mul.rn.bf16x2 %0, %1, %2;" : "=r"(r) : "r"(a), "r"(b)); return r; }
__device__ __forceinline__ uint32_t hadd2(uint32_t a, uint32_t b) { uint32_t r; asm("add.rn.bf16x2 %0, %1, %2;" : "=r"(r) : "r"(a), "r"(b)); return r; }
__device__ __forceinline__ uint32_t hfma2(uint32_t a, uint32_t b, uint32_t c) { uint32_t r; asm("fma.rn.bf16x2 %0, %1, %2, %3;" : "=r"(r) : "r"(a), "r"(b), "r"(c)); return r; }
__device__ __forceinline__ uint32_t packh(float lo, float hi) { uint32_t r; asm("cvt.rn.f16x2.f32 %0, %1, %2;" : "=r"(r) : "f"(hi), "f"(lo)); return r; }
__device__ __forceinline__ __half2 H2(uint32_t a) { return *reinterpret_cast<__half2*>(&a); }
__device__ __forceinline__ uint32_t U2(__half2 a) { return *reinterpret_cast<uint32_t*>(&a); }
__device__ __forceinline__ uint32_t fmul(uint32_t a, uint32_t b) { return U2(__hmul2(H2(a), H2(b))); }
__device__ __forceinline__ uint32_t ffma(uint32_t a, uint32_t b, uint32_t c) { return U2(__hfma2(H2(a), H2(b), H2(c))); }
__device__ __forceinline__ uint32_t fneg(uint32_t a) { return U2(__hneg2(H2(a))); }
__device__ __forceinline__ uint32_t amax2(uint32_t a, uint32_t b) { uint32_t r; asm("max.xorsign.abs.bf16x2 %0, %1, %2;" : "=r"(r) : "r"(a), "r"(b)); return r; }
__device__ __forceinline__ uint32_t prmt(uint32_t a, uint32_t b, uint32_t s) { return __byte_perm(a, b, s); }
__device__ __forceinline__ uint32_t ldraw(const __nv_bfloat16* p) { uint32_t v; asm volatile("ld.global.nc.u16 %0, [%1];" : "=r"(v) : "l"(p)); return v; }
__device__ __forceinline__ uint4 ldg128(const void* p) { uint4 v; asm volatile("ld.global.nc.v4.u32 {%0,%1,%2,%3}, [%4];" : "=r"(v.x), "=r"(v.y), "=r"(v.z), "=r"(v.w) : "l"(p)); return v; }
__device__ __forceinline__ void bar_sync(int id, int n) { asm volatile("bar.sync %0, %1;" :: "r"(id), "r"(n) : "memory"); }
__device__ __forceinline__ void bar_arrive(int id, int n) { asm volatile("bar.arrive %0, %1;" :: "r"(id), "r"(n) : "memory"); }
__device__ __forceinline__ void cluster_arrive() { asm volatile("barrier.cluster.arrive.relaxed.aligned;" ::: "memory"); }
__device__ __forceinline__ void cluster_wait() { asm volatile("barrier.cluster.wait.aligned;" ::: "memory"); }
__device__ __forceinline__ void fence_async() { asm volatile("fence.proxy.async.shared::cta;" ::: "memory"); }
__device__ __forceinline__ void fence_mbinit() { asm volatile("fence.mbarrier_init.release.cluster;" ::: "memory"); }
__device__ __forceinline__ uint32_t mapa(uint32_t a, uint32_t rank) { uint32_t r; asm("mapa.shared::cluster.u32 %0, %1, %2;" : "=r"(r) : "r"(a), "r"(rank)); return r; }
__device__ __forceinline__ void bulk_dsmem(uint32_t dst, uint32_t src, uint32_t mbar) {
  asm volatile("cp.async.bulk.shared::cluster.shared::cta.mbarrier::complete_tx::bytes [%0], [%1], 512, [%2];" :: "r"(dst), "r"(src), "r"(mbar) : "memory");
}
__device__ __forceinline__ void mbar_init(uint32_t m, uint32_t cnt) { asm volatile("mbarrier.init.shared::cta.b64 [%0], %1;" :: "r"(m), "r"(cnt) : "memory"); }
__device__ __forceinline__ void mbar_expect(uint32_t m, uint32_t bytes) { asm volatile("mbarrier.arrive.expect_tx.shared::cta.b64 _, [%0], %1;" :: "r"(m), "r"(bytes) : "memory"); }
__device__ __forceinline__ void mbar_wait(uint32_t m) {
  uint32_t done;
  int it = 0;
  do {
    asm volatile("{.reg .pred p; mbarrier.try_wait.parity.shared::cta.b64 p, [%1], 0; selp.u32 %0, 1, 0, p;}" : "=r"(done) : "r"(m) : "memory");
  } while (!done && ++it < (1 << 22));
}
__device__ __forceinline__ void tma_load4(uint32_t dst, const CUtensorMap* tm, int c0, int c1, int c2, int c3, uint32_t mbar) {
  asm volatile("cp.async.bulk.tensor.4d.shared::cluster.global.mbarrier::complete_tx::bytes [%0], [%1, {%3, %4, %5, %6}], [%2];"
               :: "r"(dst), "l"(tm), "r"(mbar), "r"(c0), "r"(c1), "r"(c2), "r"(c3) : "memory");
}
__device__ __forceinline__ void tma_load3(uint32_t dst, const CUtensorMap* tm, int c0, int c1, int c2, uint32_t mbar) {
  asm volatile("cp.async.bulk.tensor.3d.shared::cluster.global.mbarrier::complete_tx::bytes [%0], [%1, {%3, %4, %5}], [%2];"
               :: "r"(dst), "l"(tm), "r"(mbar), "r"(c0), "r"(c1), "r"(c2) : "memory");
}
__device__ __forceinline__ void tma_store3(const CUtensorMap* tm, int c0, int c1, int c2, uint32_t src) {
  asm volatile("cp.async.bulk.tensor.3d.global.shared::cta.bulk_group [%0, {%2, %3, %4}], [%1];"
               :: "l"(tm), "r"(src), "r"(c0), "r"(c1), "r"(c2) : "memory");
}
__device__ __forceinline__ void wg_fence() { asm volatile("wgmma.fence.sync.aligned;" ::: "memory"); }
__device__ __forceinline__ void wg_commit() { asm volatile("wgmma.commit_group.sync.aligned;" ::: "memory"); }
template <int N> __device__ __forceinline__ void wg_wait() { asm volatile("wgmma.wait_group.sync.aligned %0;" :: "n"(N) : "memory"); }
template <int N> __device__ __forceinline__ void tie_all(uint32_t (&x)[N]) {
#pragma unroll
  for (int i = 0; i < N; i++) asm volatile("" : "+r"(x[i]) :: "memory");
}
template <int N> __device__ __forceinline__ void tie_all(float (&x)[N]) {
#pragma unroll
  for (int i = 0; i < N; i++) asm volatile("" : "+f"(x[i]) :: "memory");
}
#define R16(C, d) C(d[0]), C(d[1]), C(d[2]), C(d[3]), C(d[4]), C(d[5]), C(d[6]), C(d[7]), C(d[8]), C(d[9]), C(d[10]), C(d[11]), C(d[12]), C(d[13]), C(d[14]), C(d[15])
#define R32(C, d) R16(C, d), R16(C, (d + 16))
#define P16 "{%0,%1,%2,%3,%4,%5,%6,%7,%8,%9,%10,%11,%12,%13,%14,%15}"
#define P32 "{%0,%1,%2,%3,%4,%5,%6,%7,%8,%9,%10,%11,%12,%13,%14,%15,%16,%17,%18,%19,%20,%21,%22,%23,%24,%25,%26,%27,%28,%29,%30,%31}"
template <int SD, int TB, int OFF> __device__ __forceinline__ void rs64(float* d, const uint32_t* a, uint64_t db) {
  if (SD) asm volatile("{.reg .b64 db; add.s64 db, %36, %37; wgmma.mma_async.sync.aligned.m64n64k16.f32.bf16.bf16 " P32 ", {%32,%33,%34,%35}, db, 1, 1, 1, %38;}"
                       : R32("+f", d) : "r"(a[0]), "r"(a[1]), "r"(a[2]), "r"(a[3]), "l"(db), "n"(OFF), "n"(TB));
  else asm volatile("{.reg .b64 db; add.s64 db, %36, %37; wgmma.mma_async.sync.aligned.m64n64k16.f32.bf16.bf16 " P32 ", {%32,%33,%34,%35}, db, 0, 1, 1, %38;}"
                    : R32("=f", d) : "r"(a[0]), "r"(a[1]), "r"(a[2]), "r"(a[3]), "l"(db), "n"(OFF), "n"(TB));
}
template <int SD, int TB, int OFF> __device__ __forceinline__ void rs64h(uint32_t* d, const uint32_t* a, uint64_t db) {
  if (SD) asm volatile("{.reg .b64 db; add.s64 db, %20, %21; wgmma.mma_async.sync.aligned.m64n64k16.f16.f16.f16 " P16 ", {%16,%17,%18,%19}, db, 1, 1, 1, %22;}"
                       : R16("+r", d) : "r"(a[0]), "r"(a[1]), "r"(a[2]), "r"(a[3]), "l"(db), "n"(OFF), "n"(TB));
  else asm volatile("{.reg .b64 db; add.s64 db, %20, %21; wgmma.mma_async.sync.aligned.m64n64k16.f16.f16.f16 " P16 ", {%16,%17,%18,%19}, db, 0, 1, 1, %22;}"
                    : R16("=r", d) : "r"(a[0]), "r"(a[1]), "r"(a[2]), "r"(a[3]), "l"(db), "n"(OFF), "n"(TB));
}
template <int SD, int OFFA, int OFFB> __device__ __forceinline__ void ss32(float* d, uint64_t da, uint64_t db) {
  if (SD) asm volatile("{.reg .b64 da, db; add.s64 da, %16, %18; add.s64 db, %17, %19; wgmma.mma_async.sync.aligned.m64n32k16.f32.f16.f16 " P16 ", da, db, 1, 1, 1, 1, 1;}"
                       : R16("+f", d) : "l"(da), "l"(db), "n"(OFFA), "n"(OFFB));
  else asm volatile("{.reg .b64 da, db; add.s64 da, %16, %18; add.s64 db, %17, %19; wgmma.mma_async.sync.aligned.m64n32k16.f32.f16.f16 " P16 ", da, db, 0, 1, 1, 1, 1;}"
                    : R16("=f", d) : "l"(da), "l"(db), "n"(OFFA), "n"(OFFB));
}
#define R24(C, c) R16(C, c), C(c[16]), C(c[17]), C(c[18]), C(c[19]), C(c[20]), C(c[21]), C(c[22]), C(c[23])
#define KGEN_ASM(SD) "{.reg .b64 da, db; add.s64 da, %24, %25; add.s64 db, %24, %26;\n" \
  "wgmma.mma_async.sync.aligned.m64n48k16.f32.bf16.bf16 {%0,%1,%2,%3,%4,%5,%6,%7,%8,%9,%10,%11,%12,%13,%14,%15,%16,%17,%18,%19,%20,%21,%22,%23}, da, db, " SD ", 1, 1, 1, 1;}"
template <int KS> __device__ __forceinline__ void kgen_mma(float (&c)[24], uint64_t da) {
  if (KS) asm volatile(KGEN_ASM("1") : R24("+f", c) : "l"(da), "n"(8 * KS), "n"(8 * KS + 512));
  else asm volatile(KGEN_ASM("0") : R24("=f", c) : "l"(da), "n"(8 * KS), "n"(8 * KS + 512));
  if constexpr (KS < 7) kgen_mma<KS + 1>(c, da);
}
__device__ __forceinline__ uint64_t desc_lo(uint32_t a) { return (uint64_t)((a & 0x3FFFF) >> 4); }
__device__ __forceinline__ void stage1(float (&D)[32], const uint32_t (&A1)[8], uint32_t src) {
  const uint64_t du = desc_lo(src) | (128ull << 16) | (32ull << 32) | (2ull << 62);
  rs64<0, 1, 0>(D, A1, du); rs64<1, 1, 64>(D, A1 + 4, du);
}
template <int INV> __device__ __forceinline__ void stage2(uint32_t (&X)[16], const uint32_t (&F)[16], uint32_t cf) {
  constexpr int KS = INV ? 16 : 128, TB = INV ? 0 : 1;
  const uint64_t dc = desc_lo(cf) | (INV ? (8ull << 16) | (64ull << 32) : (64ull << 16) | (8ull << 32));
  rs64h<0, TB, 0>(X, F, dc); rs64h<1, TB, KS>(X, F + 4, dc); rs64h<1, TB, 2 * KS>(X, F + 8, dc); rs64h<1, TB, 3 * KS>(X, F + 12, dc);
}
__device__ __forceinline__ void fwd_mid(uint32_t (&F)[16], const float (&D)[32], const uint32_t (&tc)[4], const uint32_t (&ts)[4]) {
#pragma unroll
  for (int j = 0; j < 4; j++)
#pragma unroll
    for (int b = 0; b < 2; b++) {
      const int i = 4 * j + 16 * b;
      const uint32_t ar = packh(D[i], D[i + 1]), ai = packh(D[i + 2], D[i + 3]);
      F[2 * j + b] = ffma(ar, tc[j], fmul(ai, ts[j]));
      F[8 + 2 * j + b] = ffma(ai, tc[j], fneg(fmul(ar, ts[j])));
    }
}
__device__ __forceinline__ void put_exp(uint32_t a, uint32_t m, int lane) {
  m = __reduce_max_sync(0xffffffffu, max(m & 0x7f80u, (m >> 16) & 0x7f80u));
  if (lane == 0) sts32(a, m);
}
__device__ __forceinline__ uint32_t seq_mag(uint32_t a) {
  const uint4 x = lds128(a), y = lds128(a + 2048);
  return amax2(amax2(amax2(x.x, x.y), amax2(x.z, x.w)), amax2(amax2(y.x, y.y), amax2(y.z, y.w)));
}
__device__ __forceinline__ uint32_t get_exp(uint32_t a) { const uint4 v = lds128(a); return max(max(v.x, v.y), max(v.z, v.w)) >> 7; }
__device__ __forceinline__ void load_a1(uint32_t (&A1)[8], uint32_t a, uint32_t field) {
  const uint4 x = lds128(a), y = lds128(a + 2048);
  const uint32_t s = field * 0x00800080u;
  A1[0] = hmul2(x.x, s); A1[1] = hmul2(x.y, s); A1[2] = hmul2(x.z, s); A1[3] = hmul2(x.w, s);
  A1[4] = hmul2(y.x, s); A1[5] = hmul2(y.y, s); A1[6] = hmul2(y.z, s); A1[7] = hmul2(y.w, s);
}

struct cf { float x, y; };
__device__ __forceinline__ cf cmul(cf a, cf b) { cf r; r.x = fmaf(a.x, b.x, -a.y * b.y); r.y = fmaf(a.x, b.y, a.y * b.x); return r; }
__device__ __forceinline__ cf cexp_p(float lr2, float lt, float p) {
  float m = exp2f(lr2 * p);
  float t = lt * p;
  t = (t - rintf(t)) * 6.283185307179586f;
  cf r; r.x = m * __cosf(t); r.y = m * __sinf(t); return r;
}
__device__ __forceinline__ void store8(uint32_t a, uint32_t b, const cf (&v)[8]) {
  sts128(a, pack(v[0].x, v[1].x), pack(v[2].x, v[3].x), pack(v[4].x, v[5].x), pack(v[6].x, v[7].x));
  sts128(b, pack(v[0].y, v[1].y), pack(v[2].y, v[3].y), pack(v[4].y, v[5].y), pack(v[6].y, v[7].y));
}
__device__ __forceinline__ void mbar_arrive(uint32_t m) { asm volatile("mbarrier.arrive.shared::cta.b64 _, [%0];" :: "r"(m) : "memory"); }
__device__ __forceinline__ float sigmoidf_(float s) { return 1.f / (1.f + __expf(-s)); }

__global__ void __cluster_dims__(CS, 1, 1) __launch_bounds__(NTHREADS, 1) fused_kernel(const __grid_constant__ Params p) {
  extern __shared__ __align__(1024) uint8_t smem[];
  TL_INIT();
  TL(31);
  const int wid = __shfl_sync(0xffffffffu, threadIdx.x >> 5, 0);
  const uint32_t sb = (uint32_t)__cvta_generic_to_shared(smem);
  const uint32_t mb = sb + OFF_MB;
  const int u = wid >> 2, w = wid & 3;
  const int tid = threadIdx.x & 127, lane = tid & 31, g = lane >> 2, t = lane & 3;
  const int cl = blockIdx.x >> 3, rank = blockIdx.x & 7;
  const int ch0 = cl * CPC;
  const int nu = min(5, (DCH - ch0) >> 3);
  const bool act = u < nu;

  if (u == 4 && lane == 0) {
    if (w < 3) {
#pragma unroll
      for (int i = 0; i < 5; i++) mbar_init(mb + 40 * w + 8 * i, w < 2 ? 2 : 3);
      fence_mbinit();
#pragma unroll
      for (int i = 0; i < 5; i++) mbar_expect(mb + 40 * w + 8 * i, w < 2 ? 3584 : 7168);
    } else {
      mbar_init(mb + 8 * MB_XQ, 1); mbar_init(mb + 8 * MB_KV, 2); mbar_init(mb + 8 * MB_HA, 1); mbar_init(mb + 8 * MB_CF, 1);
      mbar_init(mb + 8 * MB_Q2, 9); mbar_init(mb + 8 * MB_XD, 8); mbar_init(mb + 8 * MB_KD, 20);
      fence_mbinit();
      mbar_expect(mb + 8 * MB_CF, 16384);
      asm volatile("cp.async.bulk.shared::cluster.global.mbarrier::complete_tx::bytes [%0], [%1], %2, [%3];"
                   :: "r"(sb + OFF_CF), "l"(p.tab->mat), "r"(16384), "r"(mb + 8 * MB_CF) : "memory");
      mbar_expect(mb + 8 * MB_XQ, 20480); mbar_expect(mb + 8 * MB_KV, 23040); mbar_expect(mb + 8 * MB_HA, 20480); mbar_expect(mb + 8 * MB_Q2, 20480);
    }
  }
  uint32_t pla, pai, pcr, pci, pdt, tag = 0;
  uint4 psm;
  {
    const int ch = act ? ch0 + 8 * u + rank : 0, o = ch * NMODE + tid;
    pla = ldraw(p.logA + o); pdt = ldraw(p.logdt + ch); pai = ldraw(p.Aim + o); pcr = ldraw(p.Cre + o); pci = ldraw(p.Cim + o);
    if (w == 1) {
      if (lane < 9) psm = ldg128(lane < 5 ? p.gate_w + (lane < nu ? ch0 + 8 * lane : 0) : p.shift_k + (act ? ch0 + 8 * u : 0) * 4 + 8 * (lane - 5));
      else { psm.x = ldraw(p.Dskip + ch); psm.y = ldraw(p.ssm_D + ch); }
    }
    if (wid == 16 && lane < 2) asm volatile("atom.relaxed.gpu.global.add.u32 %0, [%1], %2;" : "=r"(tag) : "l"(&p.cnt[rank * 32 + lane]), "r"(cl == 0 ? 16 - (NCL - 1) : 1) : "memory");
  }
  if (wid == 19 && lane == 0) {
    tma_load4(sb + OFF_TQ, &p.tq, ch0, 0, 0, 8 * rank, mb + 8 * MB_XQ);
    tma_load4(sb + OFF_TK, &p.tk, ch0, 0, 0, 8 * rank - 1, mb + 8 * MB_KV);
    TL(20);
  }
  __syncwarp();
  cluster_arrive();
  TL(0);

  const uint32_t tab = sb + OFF_T + u * KTAB;
  const int mi = lane >> 3, tq = (lane & 7) >> 1, jj = lane & 1;
  const uint32_t toff = (4 * (2 * mi + jj) + tq) * 80;
  const uint32_t uoff = 16 * (4 * w + (t ^ (w >> 1)));
  auto put = [&](int stage, int dst, uint32_t off, const uint32_t (&v)[4]) {
    sts128(sb + off + (g == rank ? dst + 512 * rank : stage + g * YPITCH), v[0], v[1], v[2], v[3]);
  };
  auto send = [&](int stage, int pitch, int dst, int mbar) {
    if (lane == 0) {
#pragma unroll
      for (int k = 0; k < 2; k++) {
        const int d = 2 * w + k;
        if (d != rank) { const uint32_t rb = mapa(sb, d); bulk_dsmem(rb + dst, sb + stage + d * pitch, rb + mbar); }
        else mbar_arrive(sb + mbar);
      }
    }
    __syncwarp();
  };

  uint32_t tc[4], ts[4];
  {
    const uint4 a = ldg128(p.tab->thr[2][tid]), b = ldg128(p.tab->thr[3][tid]);
    tc[0] = a.x; tc[1] = a.y; tc[2] = a.z; tc[3] = a.w; ts[0] = b.x; ts[1] = b.y; ts[2] = b.z; ts[3] = b.w;
  }
  if (w == 1 && lane < 10) sts128(sb + OFF_SP + 160 * u + 16 * lane, psm.x, psm.y, psm.z, psm.w);
  if (u >= 3) {
    cluster_wait();
    mbar_wait(mb + 8 * MB_XQ);
    TL(18);
    const int k0 = u == 3 ? 0 : 3;
    uint32_t x0[3][4], x1[3][4];
#pragma unroll
    for (int k = 0; k < 3; k++) { ldsm4t(x0[k], sb + OFF_TQ + w * 2560 + toff + 16 * (k0 + k)); ldsm4t(x1[k], sb + OFF_TQ + (w + 4) * 2560 + toff + 16 * (k0 + k)); }
#pragma unroll
    for (int k = 0; k < 3; k++)
      if (k0 + k < 5) {
        put(OFF_YB + 8 * (k0 + k) * YPITCH, OFF_UX + (k0 + k) * 4096, uoff, x0[k]);
        put(OFF_YB + 8 * (k0 + k) * YPITCH, OFF_UX + (k0 + k) * 4096, (uoff ^ 32) + 256, x1[k]);
      }
    if (wid == 16 && lane == 0) sts32(mb + 8 * MB_TAG, tag);
    TL(3);
    fence_async();
    bar_sync(NB_WG0 + u, 128);
    TL(4);
    if (u == 3) {
#pragma unroll 1
      for (int k = 0; k < 3; k++) send(OFF_YB + 8 * k * YPITCH, YPITCH, OFF_UX + k * 4096 + 512 * rank, OFF_MB + 8 * (MB_UX + k));
      if (lane == 0) mbar_arrive(mb + 8 * MB_XD);
      TL(7);
    }
  }
  if (u == 4) {
    float s0 = 0.f, s1 = 0.f;
#pragma unroll
    for (int j = 0; j < 5; j++) {
      const uint4 gw = lds128(sb + OFF_SP + 160 * u + 16 * j);
      const uint4 x0 = lds128(sb + OFF_TQ + tid * 80 + 16 * j), x1 = lds128(sb + OFF_TQ + (tid + 128) * 80 + 16 * j);
      uint32_t m0 = hmul2(x0.x, gw.x), m1 = hmul2(x0.y, gw.y), m2 = hmul2(x0.z, gw.z), m3 = hmul2(x0.w, gw.w);
      s0 += ((blo(m0) + bhi(m0)) + (blo(m1) + bhi(m1))) + ((blo(m2) + bhi(m2)) + (blo(m3) + bhi(m3)));
      m0 = hmul2(x1.x, gw.x); m1 = hmul2(x1.y, gw.y); m2 = hmul2(x1.z, gw.z); m3 = hmul2(x1.w, gw.w);
      s1 += ((blo(m0) + bhi(m0)) + (blo(m1) + bhi(m1))) + ((blo(m2) + bhi(m2)) + (blo(m3) + bhi(m3)));
    }
    tag = (lds64(mb + 8 * MB_TAG).x >> 4) + 1;
    uint2* gp = p.part + cl * SEQ + rank * 256 + 8 * (8 * t + g) + w;
    asm volatile("st.relaxed.gpu.global.u64 [%0], %1;" :: "l"(gp), "l"(((uint64_t)tag << 32) | __float_as_uint(s0)) : "memory");
    asm volatile("st.relaxed.gpu.global.u64 [%0], %1;" :: "l"(gp + 4), "l"(((uint64_t)tag << 32) | __float_as_uint(s1)) : "memory");
    __syncwarp();
    if (lane == 0) mbar_arrive(mb + 8 * MB_XD);
    TL(7);
#pragma unroll 1
    for (int k = 3; k < 5; k++) send(OFF_YB + 8 * k * YPITCH, YPITCH, OFF_UX + k * 4096 + 512 * rank, OFF_MB + 8 * (MB_UX + k));
    if (tid == 96) {
      mbar_expect(mb + 8 * MB_KV, 20480);
      tma_load4(sb + OFF_TV, &p.tv, ch0, 0, 0, 8 * rank, mb + 8 * MB_KV);
    }
    __syncwarp();
    TL(8);
  }

  {
    const float dt = bf16r(expf(blo(pdt)));
    const float lr2 = (-bf16r(expf(blo(pla))) * dt) * 1.4426950408889634f;
    const float lt = (blo(pai) * dt) * 0.15915494309189535f;
    const uint32_t tim = u < 2 ? tab + 3 * KTAB : sb + OFF_HA;
    const uint32_t row = tab + tid * 16, rim = tim + tid * 16;
    if (lr2 != 123.f) TL(16);
    if (u >= 3) bar_sync(NB_K3 + u - 3, 384);
    TL(11);
    {
      const cf w1 = cexp_p(lr2, lt, 8.f);
      cf v[8];
      v[0].x = 1.f; v[0].y = 0.f; v[1] = w1; v[2] = cmul(w1, w1); v[3] = cmul(v[2], w1);
      const cf w4 = cmul(v[2], v[2]);
      v[4] = w4; v[5] = cmul(v[1], w4); v[6] = cmul(v[2], w4); v[7] = cmul(v[3], w4);
      const cf w8 = cmul(w4, w4);
      store8(row, rim, v);
#pragma unroll
      for (int k = 1; k < 4; k++) {
#pragma unroll
        for (int i = 0; i < 8; i++) v[i] = (k == 1 && i == 0) ? w8 : cmul(v[i], w8);
        store8(row + 2048 * k, rim + 2048 * k, v);
      }
    }
    {
      cf z1 = cexp_p(lr2, lt, 1.f), Z = cexp_p(lr2, lt, 256.f);
      z1.y = -z1.y; Z.y = -Z.y;
      const cf z2 = cmul(z1, z1);
      cf h[8], v[8];
      h[0].x = 2.f * blo(pcr) * dt; h[0].y = -2.f * blo(pci) * dt;
      h[1] = cmul(h[0], z1);
#pragma unroll
      for (int i = 2; i < 8; i++) h[i] = cmul(h[i - 2], z2);
      store8(row + 4 * 2048, rim + 4 * 2048, h);
      v[0] = cmul(h[0], Z); v[1] = cmul(h[2], Z); v[2] = cmul(h[4], Z); v[3] = cmul(h[6], Z);
      v[4] = cmul(v[0], Z); v[5] = cmul(v[2], Z); v[6] = cmul(v[4], Z); v[7] = cmul(v[5], Z);
      store8(row + 5 * 2048, rim + 5 * 2048, v);
      const cf Z2 = cmul(Z, Z);
      h[0] = cmul(v[4], Z2); h[1] = cmul(v[6], Z2); h[2] = cmul(h[0], Z2); h[3] = cmul(h[1], Z2); h[4] = cmul(h[2], Z2);
      h[5].x = h[5].y = h[6].x = h[6].y = h[7].x = h[7].y = 0.f;
      store8(row + 6 * 2048, rim + 6 * 2048, h);
    }
    TL(17);
    fence_async();
    bar_sync(NB_WG0 + u, 128);
    float c[24];
    wg_fence();
    kgen_mma<0>(c, desc_lo(tab) | ((uint64_t)((tim - tab) >> 4) << 16) | (64ull << 32));
    wg_commit();
    uint32_t kid[8];
    {
      const float lf = __uint_as_float(0x4b000000u | (8 * tid)) - 8388608.f;
      const float lo = tid < 16 ? lf + 128.f : lf;
      const uint32_t sub = tid < 16 ? 0x42804300u : 0x42804280u;
#pragma unroll
      for (int i = 0; i < 8; i++) kid[i] = 2 * (pack(lo + i, lf + (1024 + i)) - sub);
    }
    if (u < 3) cluster_wait();
    wg_wait<0>(); tie_all(c);
    if (u < 4) bar_arrive(NB_K3 + (u & 1), 384);
    cluster_arrive();
    const uint32_t kc = sb + OFF_KC + u * 1408;
    {
      const int a = 8 * w + g;
      const uint32_t k0 = pack(c[0] + c[6], c[1] + c[7]), k1 = pack(c[8] + c[14], c[9] + c[15]), p0 = pack(c[16] + c[22], c[17] + c[23]);
      sts32(kc + 4 * (4 * a + t), k0);
      sts32(kc + 4 * (t < 2 ? 128 + 2 * a + t : 128 + 32 * t + a), k1);
      put_exp(sb + OFF_MX + u * 64 + 4 * w, amax2(amax2(k0, k1), p0), lane);
      if (t < 3) {
        sts16(kc + 2 * (512 + 64 * t + a), p0);
        sts16(kc + 2 * (544 + 64 * t + a), p0 >> 16);
      }
    }
    TL(19);
    bar_sync(NB_WG0 + u, 128);
    if (wid == 16 && lane == 0) { tma_load4(sb + OFF_HA, &p.th, 0, 0, 5 * cl, rank, mb + 8 * MB_HA); TL(20); }
    __syncwarp();
    uint32_t v[2][8];
#pragma unroll
    for (int i = 0; i < 8; i++) { v[0][i] = lds16(kc + (kid[i] & 0xffffu)); v[1][i] = lds16(kc + (kid[i] >> 16)); }
#pragma unroll
    for (int cc = 0; cc < 2; cc++)
      sts128(tab + 2048 * cc + 16 * (tid ^ ((tid >> 3) & 3)), prmt(v[cc][0], v[cc][1], 0x5410), prmt(v[cc][2], v[cc][3], 0x5410),
             prmt(v[cc][4], v[cc][5], 0x5410), prmt(v[cc][6], v[cc][7], 0x5410));
    fence_async();
    bar_sync(NB_WG0 + u, 128);
    mbar_wait(mb + 8 * MB_CF);
  }

#pragma unroll
  for (int isA = 0; isA < 2; isA++) {
    if (isA) {
      cluster_wait();
      mbar_wait(mb + 8 * MB_XD);
      mbar_wait(mb + 8 * MB_KV);
      TL(21);
      {
        const uint32_t hoff = (4 * (4 + 2 * (mi & 1) + jj) + ((tq + 3) & 3)) * 80 + (tq ? 2560 : 0) + 16 * u;
        uint32_t E[2][6], V[2][4];
        const uint2 psw = lds64(sb + OFF_SP + 160 * u + 80 + 8 * g);
#pragma unroll
        for (int hf = 0; hf < 2; hf++) {
          const int ah = 4 * hf + w;
          uint32_t K[4];
          ldsm4t(K, sb + OFF_TK + (ah + 1) * 2560 + toff + 16 * u);
          ldsm2t(E[hf][0], E[hf][1], sb + OFF_TK + ah * 2560 + hoff);
          ldsm4t(V[hf], sb + OFF_TV + ah * 2560 + toff + 16 * u);
          E[hf][2] = K[0]; E[hf][3] = K[1]; E[hf][4] = K[2]; E[hf][5] = K[3];
        }
        const uint32_t w0 = prmt(psw.x, 0, 0x1010), w1 = prmt(psw.x, 0, 0x3232), w2 = prmt(psw.y, 0, 0x1010), w3 = prmt(psw.y, 0, 0x3232);
        uint32_t o[2][4];
#pragma unroll
        for (int hf = 0; hf < 2; hf++) {
          uint32_t O[5];
#pragma unroll
          for (int i = 0; i < 5; i++) O[i] = prmt(E[hf][i], E[hf][i + 1], 0x5432);
#pragma unroll
          for (int i = 0; i < 4; i++) {
            uint32_t s = hmul2(O[i], w3);
            s = hadd2(s, hmul2(E[hf][i + 1], w2));
            s = hadd2(s, hmul2(O[i + 1], w1));
            s = hadd2(s, hmul2(E[hf][i + 2], w0));
            o[hf][i] = hmul2(s, V[hf][i]);
          }
          put(OFF_YA + 8 * u * YPITCH, OFF_T + u * KTAB + T_UKV, hf ? (uoff ^ 32) + 256 : uoff, o[hf]);
        }
        TL(12);
        fence_async();
        TL(13);
        bar_sync(NB_WG0 + u, 128);
        TL(14);
        send(OFF_YA + 8 * u * YPITCH, YPITCH, OFF_T + u * KTAB + T_UKV + 512 * rank, OFF_MB + 8 * (MB_UKV + u));
      }
      if (lane == 0) mbar_arrive(mb + 8 * MB_KD);
      TL(22);
      TL(23);
      mbar_wait(mb + 8 * MB_HA);
      put_exp(sb + OFF_MX + u * 64 + 32 + 4 * w, seq_mag(sb + OFF_HA + u * 4096 + 16 * tid), lane);
      bar_sync(NB_WG0 + u, 128);
    }
    {
      TL(1 + isA);
      const uint32_t usrc = isA ? tab + T_UKV : sb + OFF_UX + u * 4096;
      const uint32_t mxa = sb + OFF_MX + u * 64 + 32 * isA;
      const uint32_t pd = lds16(sb + OFF_SP + 160 * u + 144 + 4 * isA);
      float D[32];
      uint32_t A1[8], F[16], H[16], X[16];
      const uint32_t eh = min(max((int)get_exp(mxa), (int)((pd >> 7) & 0xff) - 5), 240);
      load_a1(A1, sb + OFF_A1 + 16 * tid, 248 - eh);
      wg_fence();
      stage1(D, A1, isA ? sb + OFF_HA + u * 4096 : tab);
      wg_commit();
      wg_wait<0>(); tie_all(D);
      fwd_mid(F, D, tc, ts);
      wg_fence();
      stage2<0>(H, F, sb + OFF_CF);
      wg_commit();
      mbar_wait(mb + 8 * ((isA ? MB_UKV : MB_UX) + u));
      TL(5 + isA);
      put_exp(mxa + 16 + 4 * w, seq_mag(usrc + 16 * tid), lane);
      bar_sync(NB_WG0 + u, 128);
      const uint32_t eu = min(get_exp(mxa + 16), 240u);
      load_a1(A1, sb + OFF_A1 + 16 * tid, 250 - eu);
      wg_wait<0>(); tie_all(H);
      wg_fence();
      stage1(D, A1, usrc);
      wg_commit();
      wg_wait<0>(); tie_all(D);
      fwd_mid(F, D, tc, ts);
      wg_fence();
      stage2<0>(X, F, sb + OFF_CF);
      wg_commit();
      {
        const float dsk = blo(pd) * __uint_as_float((248 - eh) << 23);
        const uint32_t d2 = packh(dsk, dsk);
#pragma unroll
        for (int j = 0; j < 4; j++) H[2 * j] = U2(__hadd2(H2(H[2 * j]), H2(d2)));
      }
      wg_wait<0>(); tie_all(X);
#pragma unroll
      for (int j = 0; j < 4; j++) {
        const uint32_t h0r = H[2 * j], h1r = H[2 * j + 1], h0i = H[8 + 2 * j], h1i = H[9 + 2 * j];
        const uint32_t x0r = X[2 * j], x1r = X[2 * j + 1], x0i = X[8 + 2 * j], x1i = X[9 + 2 * j];
        F[2 * j] = ffma(x0r, h0r, fneg(fmul(x0i, h0i)));
        F[8 + 2 * j] = ffma(x0r, h0i, fmul(x0i, h0r));
        F[2 * j + 1] = ffma(x1r, h0r, ffma(fneg(x1i), h0i, ffma(x0r, h1r, fneg(ffma(x0i, h1i, F[8 + 2 * j])))));
        F[9 + 2 * j] = ffma(x1r, h0i, ffma(x1i, h0r, ffma(x0r, h1i, ffma(x0i, h1r, F[2 * j]))));
      }
      wg_fence();
      stage2<1>(H, F, sb + OFF_CF);
      wg_commit();
      wg_wait<0>(); tie_all(H);
      {
        const uint32_t va = tab + (16 * w + (lane & 15)) * 128;
        const int vx = (lane >> 4) ^ (lane & 7);
#pragma unroll
        for (int j = 0; j < 4; j++) {
          uint32_t V[4];
#pragma unroll
          for (int b = 0; b < 2; b++) {
            const uint32_t er = H[2 * j + b], ei = H[8 + 2 * j + b];
            V[2 * b] = ffma(er, tc[j], fneg(fmul(ei, ts[j])));
            V[2 * b + 1] = ffma(ei, tc[j], fmul(er, ts[j]));
          }
          stsm4(va + ((vx ^ (2 * j)) << 4), V);
        }
      }
      fence_async();
      bar_sync(NB_WG0 + u, 128);
      float O[16];
      {
        const uint64_t dv = desc_lo(tab) | (1ull << 16) | (64ull << 32) | (1ull << 62);
        const uint64_t dl = desc_lo(sb + OFF_CL) | (32ull << 16) | (8ull << 32);
        wg_fence();
        ss32<0, 0, 0>(O, dv, dl); ss32<1, 128, 64>(O, dv, dl); ss32<1, 256, 128>(O, dv, dl); ss32<1, 384, 192>(O, dv, dl);
        wg_commit();
      }
      wg_wait<0>(); tie_all(O);
      {
        const uint32_t co = ((8 * w + g) ^ (2 * t)) * 16;
        const int yo = (isA ? OFF_YA : OFF_YB) + (8 * u + rank) * YPITCH, ym = OFF_MB + 8 * (MB_Y + u);
        const uint32_t us = min(max((int)(eu + eh) - 127, 0), 254) * 0x00800080u;
        const uint32_t a0 = hmul2(pack(O[0], O[1]), us), a1 = hmul2(pack(O[4], O[5]), us), a2 = hmul2(pack(O[8], O[9]), us), a3 = hmul2(pack(O[12], O[13]), us);
        const uint32_t b0 = hmul2(pack(O[2], O[3]), us), b1 = hmul2(pack(O[6], O[7]), us), b2 = hmul2(pack(O[10], O[11]), us), b3 = hmul2(pack(O[14], O[15]), us);
        sts128((t == rank ? sb + yo : usrc + t * 512) + co, a0, a1, a2, a3);
        sts128((t + 4 == rank ? sb + yo : usrc + t * 512 + 2048) + co, b0, b1, b2, b3);
        if (isA) TL(15);
        fence_async();
        bar_sync(NB_WG0 + u, 128);
        if (isA) TL(26);
        send(usrc - sb, 512, yo, ym);
      }
      TL(9 + isA);
    }
  }

  mbar_wait(mb + 8 * MB_KD);
  if (wid == 8 && lane == 0) tma_load3(sb + OFF_Q2, &p.tq2, ch0, 8 * rank, 0, mb + 8 * MB_Q2);
  __syncwarp();
  if (u < 2) {
    const int slot = tid + 128 * u;
    tag = (lds64(mb + 8 * MB_TAG).x >> 4) + 1;
    float s = 0.f;
    bool ok = false;
    const uint2* gp = p.part + rank * 256 + slot;
#pragma unroll 1
    for (int it = 0; it < 4000 && !ok; it++) {
      ok = true; s = 0.f;
#pragma unroll
      for (int k = 0; k < NCL; k++) {
        uint64_t a;
        asm volatile("ld.relaxed.gpu.global.u64 %0, [%1];" : "=l"(a) : "l"(gp + k * SEQ) : "memory");
        ok = ok && (uint32_t)(a >> 32) == tag;
        s += __uint_as_float((uint32_t)a);
      }
    }
    if (!ok) {
      const uint32_t* xr = (const uint32_t*)(p.q + (size_t)(rank * 256 + 32 * (slot & 7) + (slot >> 3)) * DCH);
      const uint32_t* gr = (const uint32_t*)p.gate_w;
      s = 0.f;
#pragma unroll 1
      for (int k = 0; k < DCH / 2; k++) { const uint32_t m = hmul2(__ldg(xr + k), __ldg(gr + k)); s += blo(m) + bhi(m); }
    }
    const float g0 = bf16r(sigmoidf_(bf16r(s)));
    sts64(sb + OFF_GB + 8 * slot, pack(g0, g0), pack(1.f - g0, 1.f - g0));
    __syncwarp();
    if (lane == 0) mbar_arrive(mb + 8 * MB_Q2);
  }
  {
    mbar_wait(mb + 8 * MB_Q2);
    uint2 gg[2][4];
    uint32_t qv[2][4];
#pragma unroll
    for (int hh = 0; hh < 2; hh++)
#pragma unroll
      for (int i = 0; i < 4; i++) gg[hh][i] = lds64(sb + OFF_GB + 8 * (64 * w + 32 * hh + 8 * i + g));
    const uint32_t qa = sb + OFF_Q2 + (64 * w + lane) * 80 + 16 * u;
    ldsm4(qv[0], qa);
    ldsm4(qv[1], qa + 2560);
    TL(24);
    mbar_wait(mb + 8 * (MB_Y + u));
    uint32_t ya[2][4], yb[2][4];
#pragma unroll
    for (int hh = 0; hh < 2; hh++) {
      const uint32_t yo = (8 * u + (lane & 7)) * YPITCH + ((8 * w + 4 * hh + (lane >> 3)) ^ (2 * (rank & 3))) * 16;
      ldsm4t(ya[hh], sb + OFF_YA + yo); ldsm4t(yb[hh], sb + OFF_YB + yo);
    }
#pragma unroll
    for (int hh = 0; hh < 2; hh++) {
      uint32_t o[4];
#pragma unroll
      for (int i = 0; i < 4; i++) o[i] = hadd2(hmul2(gg[hh][i].x, hmul2(qv[hh][i], ya[hh][i])), hmul2(gg[hh][i].y, yb[hh][i]));
      stsm4(qa + 2560 * hh, o);
    }
    TL(25);
  }
  cluster_arrive();
  bar_sync(NB_ROW0 + w, 160);
  {
    uint4 v[2];
#pragma unroll
    for (int k = 0; k < 2; k++) {
      const int i = 64 * u + 32 * k + lane, sl = (i * 205) >> 10, cc = i - 5 * sl;
      v[k] = lds128(sb + OFF_Q2 + (64 * w + 8 * (sl & 7) + (sl >> 3)) * 80 + cc * 16);
    }
#pragma unroll
    for (int k = 0; k < 2; k++) {
      const int i = 64 * u + 32 * k + lane, sl = (i * 205) >> 10, cc = i - 5 * sl;
      if (cc < nu)
        asm volatile("st.global.v4.u32 [%0], {%1,%2,%3,%4};" :: "l"(p.out + (size_t)(256 * rank + 32 * (sl >> 3) + 8 * w + (sl & 7)) * DCH + ch0 + 8 * cc),
                     "r"(v[k].x), "r"(v[k].y), "r"(v[k].z), "r"(v[k].w) : "memory");
    }
  }
  cluster_wait();
  TL(27);
  TL_DUMP();
}

typedef CUresult (*EncodeFn)(CUtensorMap*, CUtensorMapDataType, cuuint32_t, void*, const cuuint64_t*, const cuuint64_t*,
                             const cuuint32_t*, const cuuint32_t*, CUtensorMapInterleave, CUtensorMapSwizzle,
                             CUtensorMapL2promotion, CUtensorMapFloatOOBfill);

void encode(EncodeFn fn, CUtensorMap* tm, const void* ptr, int nd, const cuuint64_t* dims, const cuuint64_t* strides,
            const cuuint32_t* box, CUtensorMapSwizzle swz) {
  cuuint32_t es[4] = {1, 1, 1, 1};
  fn(tm, CU_TENSOR_MAP_DATA_TYPE_BFLOAT16, nd, const_cast<void*>(ptr), dims, strides, box, es, CU_TENSOR_MAP_INTERLEAVE_NONE,
     swz, CU_TENSOR_MAP_L2_PROMOTION_L2_128B, CU_TENSOR_MAP_FLOAT_OOB_FILL_NONE);
}
void map1(EncodeFn fn, CUtensorMap* tm, const void* ptr, int nhi) {
  const cuuint64_t dims[4] = {DCH, 4, 8, SEQ / 32}, strides[3] = {8 * DCH * 2, DCH * 2, 32 * DCH * 2};
  const cuuint32_t box[4] = {CPC, 4, 8, (cuuint32_t)nhi};
  encode(fn, tm, ptr, 4, dims, strides, box, CU_TENSOR_MAP_SWIZZLE_NONE);
}
void map2(EncodeFn fn, CUtensorMap* tm, const void* ptr, int nr) {
  const cuuint64_t dims[3] = {DCH, SEQ / 32, 32}, strides[2] = {32 * DCH * 2, DCH * 2};
  const cuuint32_t box[3] = {CPC, 8, (cuuint32_t)nr};
  encode(fn, tm, ptr, 3, dims, strides, box, CU_TENSOR_MAP_SWIZZLE_NONE);
}

}

extern "C" void kernel_launch(void* const* d_in, const int* in_sizes, int n_in, void* d_out, int out_size) {
  (void)in_sizes; (void)n_in; (void)out_size;
  static EncodeFn fn = nullptr;
  static void *tab = nullptr, *cnt = nullptr, *part = nullptr;
  if (!fn) {
    cudaGetSymbolAddress(&tab, d_tab);
    cudaGetSymbolAddress(&cnt, g_cnt);
    cudaGetSymbolAddress(&part, g_part);
    cudaDriverEntryPointQueryResult qr;
    cudaGetDriverEntryPoint("cuTensorMapEncodeTiled", (void**)&fn, cudaEnableDefault, &qr);
    cudaFuncSetAttribute(fused_kernel, cudaFuncAttributeMaxDynamicSharedMemorySize, SMEM_BYTES);
  }
  Params p;
  map1(fn, &p.tq, d_in[0], 8);
  map1(fn, &p.tk, d_in[1], 9);
  map1(fn, &p.tv, d_in[2], 8);
  map2(fn, &p.tq2, d_in[0], 32);
  p.out = (__nv_bfloat16*)d_out;
  {
    const cuuint64_t dims[4] = {32, SEQ / 32, DCH / 8, 8}, strides[3] = {64, 8 * SEQ * 2, SEQ * 2};
    const cuuint32_t box[4] = {32, 64, 5, 1};
    encode(fn, &p.th, d_in[4], 4, dims, strides, box, CU_TENSOR_MAP_SWIZZLE_64B);
  }
  p.tab = (const Tables*)tab;
  p.cnt = (unsigned*)cnt;
  p.part = (uint2*)part;
  p.tl = nullptr;
  p.q = (const __nv_bfloat16*)d_in[0];
  p.shift_k = (const __nv_bfloat16*)d_in[3];
  p.ssm_D = (const __nv_bfloat16*)d_in[5];
  p.logA = (const __nv_bfloat16*)d_in[7];
  p.Aim = (const __nv_bfloat16*)d_in[8];
  p.Cre = (const __nv_bfloat16*)d_in[9];
  p.Cim = (const __nv_bfloat16*)d_in[10];
  p.logdt = (const __nv_bfloat16*)d_in[11];
  p.Dskip = (const __nv_bfloat16*)d_in[12];
  p.gate_w = (const __nv_bfloat16*)d_in[13];
  fused_kernel<<<NCL * CS, NTHREADS, SMEM_BYTES, cudaStreamPerThread>>>(p);
}
```

```cpp
#include <cuda_runtime.h>
#include <cuda_bf16.h>
#include <cuda_fp16.h>
#include <cuda.h>
#include <stdint.h>

#define TIMELINE 0

namespace {

constexpr int SEQ = 2048, DCH = 576, NMODE = 128;
constexpr int CS = 8, CPC = 40, NCL = 15, NTHREADS = 640;

constexpr int YPITCH = 528;
constexpr int KTAB = 14336;
constexpr int OFF_T = 0;
constexpr int T_UKV = 8192;
constexpr int OFF_UX = 5 * KTAB;
constexpr int OFF_HA = OFF_UX + 20480;
constexpr int OFF_TV = OFF_HA + 20480;
constexpr int OFF_CF = OFF_HA + 3 * KTAB;
constexpr int OFF_CL = OFF_CF + 8192;
constexpr int OFF_A1 = OFF_CL + 4096;
constexpr int OFF_TQ = OFF_A1 + 4096;
constexpr int OFF_YA = OFF_TQ;
constexpr int OFF_TK = OFF_TQ + 21120;
constexpr int OFF_Q2 = OFF_TK;
constexpr int OFF_YB = OFF_TK + 23040;
constexpr int OFF_KC = OFF_YB + 40 * YPITCH;
constexpr int OFF_GB = OFF_KC + 5 * 1408;
constexpr int OFF_MX = OFF_GB + 2048;
constexpr int OFF_SP = OFF_MX + 320;
constexpr int OFF_MB = OFF_SP + 5 * 160;
constexpr int OFF_TL = OFF_MB + 32 * 8;
constexpr int SMEM_BYTES = OFF_TL + (TIMELINE ? 2560 : 0);
static_assert(SMEM_BYTES <= 232448, "smem");
static_assert((KTAB & 1023) == 0 && (OFF_TQ & 127) == 0 && (OFF_TK & 127) == 0 && (OFF_TV & 127) == 0 && (OFF_MB & 7) == 0 && (OFF_KC & 15) == 0, "align");

enum { MB_UX = 0, MB_UKV = 5, MB_Y = 10, MB_XQ = 15, MB_KV = 16, MB_HA = 17, MB_CF = 18, MB_Q2 = 19, MB_XD = 20, MB_KD = 21, MB_TAG = 22 };
enum { NB_WG0 = 1, NB_ROW0 = 6, NB_K4 = 10 };

constexpr double cos_turn(int m, int n) {
  m &= n - 1;
  if (m > n / 2) m = n - m;
  double sgn = 1.0;
  if (m > n / 4) { m = n / 2 - m; sgn = -1.0; }
  if (m == n / 4) return 0.0;
  const double x = 6.283185307179586476925 * m / n;
  double term = 1.0, sum = 1.0;
  for (int k = 1; k < 14; k++) { term *= -x * x / ((2 * k - 1) * (2 * k)); sum += term; }
  return sgn * sum;
}
constexpr uint32_t bf16_bits(double v) {
  if (v == 0.0) return 0;
  uint32_t sgn = 0;
  if (v < 0) { sgn = 0x8000; v = -v; }
  int e = 127;
  while (v < 1.0) { v *= 2.0; e--; }
  while (v >= 2.0) { v *= 0.5; e++; }
  const double f = v * 128.0;
  int m = (int)f;
  if (f - m > 0.5 || (f - m == 0.5 && (m & 1))) m++;
  return sgn | (uint32_t)((e << 7) + (m - 128));
}
constexpr uint32_t f16_bits(double v) {
  if (v == 0.0) return 0;
  uint32_t sgn = 0;
  if (v < 0) { sgn = 0x8000; v = -v; }
  int e = 15;
  while (v < 1.0) { v *= 2.0; e--; }
  const double f = v * 1024.0;
  int m = (int)f;
  if (f - m > 0.5 || (f - m == 0.5 && (m & 1))) m++;
  return sgn | (uint32_t)((e << 10) + (m - 1024));
}
constexpr uint32_t pair_bits(double lo, double hi) { return bf16_bits(lo) | (bf16_bits(hi) << 16); }
constexpr uint32_t pair_h(double lo, double hi) { return f16_bits(lo) | (f16_bits(hi) << 16); }
struct alignas(128) Tables {
  uint32_t mat[3072];
  uint32_t thr[4][128][4];
};
constexpr Tables make_tables() {
  Tables T{};
  for (int q = 0; q < 768; q++) {
    int m0 = 0, d0 = 0, d1 = 0;
    if (q < 512) {
      const int r = (q >> 6) * 8 + (q & 7), cc = (q >> 3) & 7;
      d0 = 4 * (r & 31); d1 = 2 * d0;
      m0 = 8 * (cc & 3) * d0 + ((r >> 5) == (cc >> 2) ? 0 : (r >> 5) ? 96 : 32);
    } else {
      const int r = ((q - 512) >> 5) * 8 + (q & 7), pc = (q >> 3) & 3;
      d0 = 4 * (8 * (r >> 4) + (r & 7)) + 1; d1 = 8 * d0;
      m0 = 2 * pc * d0 + ((r & 8) ? 32 : 0);
    }
    for (int e = 0; e < 4; e++) T.mat[4 * q + e] = pair_h(cos_turn(m0 + e * d1, 128), cos_turn(m0 + e * d1 + d0, 128));
  }
  for (int tid = 0; tid < 128; tid++) {
    const int kk = 4 * (tid >> 2) + 1, t = tid & 3;
    for (int q = 0; q < 4; q++) {
      const int m = (8 * q + 2 * t) * kk;
      T.thr[q >> 1][tid][2 * (q & 1)] = pair_bits(cos_turn(m, 128), cos_turn(m + kk, 128));
      T.thr[q >> 1][tid][2 * (q & 1) + 1] = pair_bits(cos_turn(m + 32, 128), cos_turn(m + kk + 32, 128));
      T.thr[2][tid][q] = pair_h(cos_turn(m, 4096), cos_turn(m + kk, 4096));
      T.thr[3][tid][q] = pair_h(cos_turn(m + 3072, 4096), cos_turn(m + kk + 3072, 4096));
    }
  }
  return T;
}
__device__ const Tables d_tab = make_tables();

struct Params {
  const __nv_bfloat16 *logA, *Aim, *Cre, *Cim, *logdt;
  const Tables* tab;
  unsigned* cnt;
  const __nv_bfloat16 *Dskip, *shift_k, *ssm_D, *gate_w, *q;
  uint2* part;
  __nv_bfloat16* out;
  unsigned* tl;
  CUtensorMap tq, tk, tv, th, tq2;
};

__device__ uint2 g_part[NCL * SEQ];
__device__ unsigned g_cnt[CS * 32];
#define TL(i) do {} while (0)
#define TL_INIT() do {} while (0)
#define TL_DUMP() do {} while (0)

__device__ __forceinline__ uint32_t lds16(uint32_t a) { uint32_t v; asm volatile("ld.shared.u16 %0, [%1];" : "=r"(v) : "r"(a) : "memory"); return v; }
__device__ __forceinline__ uint2 lds64(uint32_t a) { uint2 v; asm volatile("ld.shared.v2.u32 {%0,%1}, [%2];" : "=r"(v.x), "=r"(v.y) : "r"(a) : "memory"); return v; }
__device__ __forceinline__ uint4 lds128(uint32_t a) { uint4 v; asm volatile("ld.shared.v4.u32 {%0,%1,%2,%3}, [%4];" : "=r"(v.x), "=r"(v.y), "=r"(v.z), "=r"(v.w) : "r"(a) : "memory"); return v; }
__device__ __forceinline__ void sts16(uint32_t a, uint32_t v) { asm volatile("st.shared.u16 [%0], %1;" :: "r"(a), "r"(v) : "memory"); }
__device__ __forceinline__ void sts32(uint32_t a, uint32_t v) { asm volatile("st.shared.u32 [%0], %1;" :: "r"(a), "r"(v) : "memory"); }
__device__ __forceinline__ void sts64(uint32_t a, uint32_t x, uint32_t y) { asm volatile("st.shared.v2.u32 [%0], {%1,%2};" :: "r"(a), "r"(x), "r"(y) : "memory"); }
__device__ __forceinline__ void sts128(uint32_t a, uint32_t x, uint32_t y, uint32_t z, uint32_t w) { asm volatile("st.shared.v4.u32 [%0], {%1,%2,%3,%4};" :: "r"(a), "r"(x), "r"(y), "r"(z), "r"(w) : "memory"); }
__device__ __forceinline__ void ldsm4t(uint32_t (&r)[4], uint32_t a) { asm volatile("ldmatrix.sync.aligned.m8n8.x4.trans.shared.b16 {%0,%1,%2,%3}, [%4];" : "=r"(r[0]), "=r"(r[1]), "=r"(r[2]), "=r"(r[3]) : "r"(a) : "memory"); }
__device__ __forceinline__ void ldsm2t(uint32_t& r0, uint32_t& r1, uint32_t a) { asm volatile("ldmatrix.sync.aligned.m8n8.x2.trans.shared.b16 {%0,%1}, [%2];" : "=r"(r0), "=r"(r1) : "r"(a) : "memory"); }
__device__ __forceinline__ void ldsm4(uint32_t (&r)[4], uint32_t a) { asm volatile("ldmatrix.sync.aligned.m8n8.x4.shared.b16 {%0,%1,%2,%3}, [%4];" : "=r"(r[0]), "=r"(r[1]), "=r"(r[2]), "=r"(r[3]) : "r"(a) : "memory"); }
__device__ __forceinline__ void stsm4(uint32_t a, const uint32_t (&r)[4]) { asm volatile("stmatrix.sync.aligned.m8n8.x4.shared.b16 [%0], {%1,%2,%3,%4};" :: "r"(a), "r"(r[0]), "r"(r[1]), "r"(r[2]), "r"(r[3]) : "memory"); }
__device__ __forceinline__ uint32_t pack(float lo, float hi) { uint32_t r; asm("cvt.rn.bf16x2.f32 %0, %1, %2;" : "=r"(r) : "f"(hi), "f"(lo)); return r; }
__device__ __forceinline__ float blo(uint32_t v) { return __uint_as_float(v << 16); }
__device__ __forceinline__ float bhi(uint32_t v) { return __uint_as_float(v & 0xffff0000u); }
__device__ __forceinline__ float bf16r(float x) { return blo(pack(x, 0.f)); }
__device__ __forceinline__ uint32_t hmul2(uint32_t a, uint32_t b) { uint32_t r; asm("mul.rn.bf16x2 %0, %1, %2;" : "=r"(r) : "r"(a), "r"(b)); return r; }
__device__ __forceinline__ uint32_t hadd2(uint32_t a, uint32_t b) { uint32_t r; asm("add.rn.bf16x2 %0, %1, %2;" : "=r"(r) : "r"(a), "r"(b)); return r; }
__device__ __forceinline__ uint32_t hfma2(uint32_t a, uint32_t b, uint32_t c) { uint32_t r; asm("fma.rn.bf16x2 %0, %1, %2, %3;" : "=r"(r) : "r"(a), "r"(b), "r"(c)); return r; }
__device__ __forceinline__ uint32_t packh(float lo, float hi) { uint32_t r; asm("cvt.rn.f16x2.f32 %0, %1, %2;" : "=r"(r) : "f"(hi), "f"(lo)); return r; }
__device__ __forceinline__ __half2 H2(uint32_t a) { return *reinterpret_cast<__half2*>(&a); }
__device__ __forceinline__ uint32_t U2(__half2 a) { return *reinterpret_cast<uint32_t*>(&a); }
__device__ __forceinline__ uint32_t fmul(uint32_t a, uint32_t b) { return U2(__hmul2(H2(a), H2(b))); }
__device__ __forceinline__ uint32_t ffma(uint32_t a, uint32_t b, uint32_t c) { return U2(__hfma2(H2(a), H2(b), H2(c))); }
__device__ __forceinline__ uint32_t fneg(uint32_t a) { return U2(__hneg2(H2(a))); }
__device__ __forceinline__ uint32_t amax2(uint32_t a, uint32_t b) { uint32_t r; asm("max.xorsign.abs.bf16x2 %0, %1, %2;" : "=r"(r) : "r"(a), "r"(b)); return r; }
__device__ __forceinline__ uint32_t prmt(uint32_t a, uint32_t b, uint32_t s) { return __byte_perm(a, b, s); }
__device__ __forceinline__ uint32_t ldraw(const __nv_bfloat16* p) { uint32_t v; asm volatile("ld.global.nc.u16 %0, [%1];" : "=r"(v) : "l"(p)); return v; }
__device__ __forceinline__ uint4 ldg128(const void* p) { uint4 v; asm volatile("ld.global.nc.v4.u32 {%0,%1,%2,%3}, [%4];" : "=r"(v.x), "=r"(v.y), "=r"(v.z), "=r"(v.w) : "l"(p)); return v; }
__device__ __forceinline__ void bar_sync(int id, int n) { asm volatile("bar.sync %0, %1;" :: "r"(id), "r"(n) : "memory"); }
__device__ __forceinline__ void bar_arrive(int id, int n) { asm volatile("bar.arrive %0, %1;" :: "r"(id), "r"(n) : "memory"); }
__device__ __forceinline__ void cluster_arrive() { asm volatile("barrier.cluster.arrive.relaxed.aligned;" ::: "memory"); }
__device__ __forceinline__ void cluster_wait() { asm volatile("barrier.cluster.wait.aligned;" ::: "memory"); }
__device__ __forceinline__ void fence_async() { asm volatile("fence.proxy.async.shared::cta;" ::: "memory"); }
__device__ __forceinline__ void fence_mbinit() { asm volatile("fence.mbarrier_init.release.cluster;" ::: "memory"); }
__device__ __forceinline__ uint32_t mapa(uint32_t a, uint32_t rank) { uint32_t r; asm("mapa.shared::cluster.u32 %0, %1, %2;" : "=r"(r) : "r"(a), "r"(rank)); return r; }
__device__ __forceinline__ void bulk_dsmem(uint32_t dst, uint32_t src, uint32_t mbar) {
  asm volatile("cp.async.bulk.shared::cluster.shared::cta.mbarrier::complete_tx::bytes [%0], [%1], 512, [%2];" :: "r"(dst), "r"(src), "r"(mbar) : "memory");
}
__device__ __forceinline__ void mbar_init(uint32_t m, uint32_t cnt) { asm volatile("mbarrier.init.shared::cta.b64 [%0], %1;" :: "r"(m), "r"(cnt) : "memory"); }
__device__ __forceinline__ void mbar_expect(uint32_t m, uint32_t bytes) { asm volatile("mbarrier.arrive.expect_tx.shared::cta.b64 _, [%0], %1;" :: "r"(m), "r"(bytes) : "memory"); }
__device__ __forceinline__ void mbar_wait(uint32_t m) {
  uint32_t done;
  int it = 0;
  do {
    asm volatile("{.reg .pred p; mbarrier.try_wait.parity.shared::cta.b64 p, [%1], 0; selp.u32 %0, 1, 0, p;}" : "=r"(done) : "r"(m) : "memory");
  } while (!done && ++it < (1 << 22));
}
__device__ __forceinline__ void tma_load4(uint32_t dst, const CUtensorMap* tm, int c0, int c1, int c2, int c3, uint32_t mbar) {
  asm volatile("cp.async.bulk.tensor.4d.shared::cluster.global.mbarrier::complete_tx::bytes [%0], [%1, {%3, %4, %5, %6}], [%2];"
               :: "r"(dst), "l"(tm), "r"(mbar), "r"(c0), "r"(c1), "r"(c2), "r"(c3) : "memory");
}
__device__ __forceinline__ void tma_load3(uint32_t dst, const CUtensorMap* tm, int c0, int c1, int c2, uint32_t mbar) {
  asm volatile("cp.async.bulk.tensor.3d.shared::cluster.global.mbarrier::complete_tx::bytes [%0], [%1, {%3, %4, %5}], [%2];"
               :: "r"(dst), "l"(tm), "r"(mbar), "r"(c0), "r"(c1), "r"(c2) : "memory");
}
__device__ __forceinline__ void tma_store3(const CUtensorMap* tm, int c0, int c1, int c2, uint32_t src) {
  asm volatile("cp.async.bulk.tensor.3d.global.shared::cta.bulk_group [%0, {%2, %3, %4}], [%1];"
               :: "l"(tm), "r"(src), "r"(c0), "r"(c1), "r"(c2) : "memory");
}
__device__ __forceinline__ void wg_fence() { asm volatile("wgmma.fence.sync.aligned;" ::: "memory"); }
__device__ __forceinline__ void wg_commit() { asm volatile("wgmma.commit_group.sync.aligned;" ::: "memory"); }
template <int N> __device__ __forceinline__ void wg_wait() { asm volatile("wgmma.wait_group.sync.aligned %0;" :: "n"(N) : "memory"); }
template <int N> __device__ __forceinline__ void tie_all(uint32_t (&x)[N]) {
#pragma unroll
  for (int i = 0; i < N; i++) asm volatile("" : "+r"(x[i]) :: "memory");
}
template <int N> __device__ __forceinline__ void tie_all(float (&x)[N]) {
#pragma unroll
  for (int i = 0; i < N; i++) asm volatile("" : "+f"(x[i]) :: "memory");
}
#define R16(C, d) C(d[0]), C(d[1]), C(d[2]), C(d[3]), C(d[4]), C(d[5]), C(d[6]), C(d[7]), C(d[8]), C(d[9]), C(d[10]), C(d[11]), C(d[12]), C(d[13]), C(d[14]), C(d[15])
#define R32(C, d) R16(C, d), R16(C, (d + 16))
#define P16 "{%0,%1,%2,%3,%4,%5,%6,%7,%8,%9,%10,%11,%12,%13,%14,%15}"
#define P32 "{%0,%1,%2,%3,%4,%5,%6,%7,%8,%9,%10,%11,%12,%13,%14,%15,%16,%17,%18,%19,%20,%21,%22,%23,%24,%25,%26,%27,%28,%29,%30,%31}"
template <int SD, int TB, int OFF> __device__ __forceinline__ void rs64(float* d, const uint32_t* a, uint64_t db) {
  if (SD) asm volatile("{.reg .b64 db; add.s64 db, %36, %37; wgmma.mma_async.sync.aligned.m64n64k16.f32.bf16.bf16 " P32 ", {%32,%33,%34,%35}, db, 1, 1, 1, %38;}"
                       : R32("+f", d) : "r"(a[0]), "r"(a[1]), "r"(a[2]), "r"(a[3]), "l"(db), "n"(OFF), "n"(TB));
  else asm volatile("{.reg .b64 db; add.s64 db, %36, %37; wgmma.mma_async.sync.aligned.m64n64k16.f32.bf16.bf16 " P32 ", {%32,%33,%34,%35}, db, 0, 1, 1, %38;}"
                    : R32("=f", d) : "r"(a[0]), "r"(a[1]), "r"(a[2]), "r"(a[3]), "l"(db), "n"(OFF), "n"(TB));
}
template <int SD, int TB, int OFF> __device__ __forceinline__ void rs64h(uint32_t* d, const uint32_t* a, uint64_t db) {
  if (SD) asm volatile("{.reg .b64 db; add.s64 db, %20, %21; wgmma.mma_async.sync.aligned.m64n64k16.f16.f16.f16 " P16 ", {%16,%17,%18,%19}, db, 1, 1, 1, %22;}"
                       : R16("+r", d) : "r"(a[0]), "r"(a[1]), "r"(a[2]), "r"(a[3]), "l"(db), "n"(OFF), "n"(TB));
  else asm volatile("{.reg .b64 db; add.s64 db, %20, %21; wgmma.mma_async.sync.aligned.m64n64k16.f16.f16.f16 " P16 ", {%16,%17,%18,%19}, db, 0, 1, 1, %22;}"
                    : R16("=r", d) : "r"(a[0]), "r"(a[1]), "r"(a[2]), "r"(a[3]), "l"(db), "n"(OFF), "n"(TB));
}
template <int SD, int OFFA, int OFFB> __device__ __forceinline__ void ss32(float* d, uint64_t da, uint64_t db) {
  if (SD) asm volatile("{.reg .b64 da, db; add.s64 da, %16, %18; add.s64 db, %17, %19; wgmma.mma_async.sync.aligned.m64n32k16.f32.f16.f16 " P16 ", da, db, 1, 1, 1, 1, 1;}"
                       : R16("+f", d) : "l"(da), "l"(db), "n"(OFFA), "n"(OFFB));
  else asm volatile("{.reg .b64 da, db; add.s64 da, %16, %18; add.s64 db, %17, %19; wgmma.mma_async.sync.aligned.m64n32k16.f32.f16.f16 " P16 ", da, db, 0, 1, 1, 1, 1;}"
                    : R16("=f", d) : "l"(da), "l"(db), "n"(OFFA), "n"(OFFB));
}
#define R24(C, c) R16(C, c), C(c[16]), C(c[17]), C(c[18]), C(c[19]), C(c[20]), C(c[21]), C(c[22]), C(c[23])
#define KGEN_ASM(SD) "{.reg .b64 da, db; add.s64 da, %24, %25; add.s64 db, %24, %26;\n" \
  "wgmma.mma_async.sync.aligned.m64n48k16.f32.bf16.bf16 {%0,%1,%2,%3,%4,%5,%6,%7,%8,%9,%10,%11,%12,%13,%14,%15,%16,%17,%18,%19,%20,%21,%22,%23}, da, db, " SD ", 1, 1, 1, 1;}"
template <int KS> __device__ __forceinline__ void kgen_mma(float (&c)[24], uint64_t da) {
  if (KS) asm volatile(KGEN_ASM("1") : R24("+f", c) : "l"(da), "n"(8 * KS), "n"(8 * KS + 512));
  else asm volatile(KGEN_ASM("0") : R24("=f", c) : "l"(da), "n"(8 * KS), "n"(8 * KS + 512));
  if constexpr (KS < 7) kgen_mma<KS + 1>(c, da);
}
__device__ __forceinline__ uint64_t desc_lo(uint32_t a) { return (uint64_t)((a & 0x3FFFF) >> 4); }
__device__ __forceinline__ void stage1(float (&D)[32], const uint32_t (&A1)[8], uint32_t src) {
  const uint64_t du = desc_lo(src) | (128ull << 16) | (32ull << 32) | (2ull << 62);
  rs64<0, 1, 0>(D, A1, du); rs64<1, 1, 64>(D, A1 + 4, du);
}
template <int INV> __device__ __forceinline__ void stage2(uint32_t (&X)[16], const uint32_t (&F)[16], uint32_t cf) {
  constexpr int KS = INV ? 16 : 128, TB = INV ? 0 : 1;
  const uint64_t dc = desc_lo(cf) | (INV ? (8ull << 16) | (64ull << 32) : (64ull << 16) | (8ull << 32));
  rs64h<0, TB, 0>(X, F, dc); rs64h<1, TB, KS>(X, F + 4, dc); rs64h<1, TB, 2 * KS>(X, F + 8, dc); rs64h<1, TB, 3 * KS>(X, F + 12, dc);
}
__device__ __forceinline__ void fwd_mid(uint32_t (&F)[16], const float (&D)[32], const uint32_t (&tc)[4], const uint32_t (&ts)[4]) {
#pragma unroll
  for (int j = 0; j < 4; j++)
#pragma unroll
    for (int b = 0; b < 2; b++) {
      const int i = 4 * j + 16 * b;
      const uint32_t ar = packh(D[i], D[i + 1]), ai = packh(D[i + 2], D[i + 3]);
      F[2 * j + b] = ffma(ar, tc[j], fmul(ai, ts[j]));
      F[8 + 2 * j + b] = ffma(ai, tc[j], fneg(fmul(ar, ts[j])));
    }
}
__device__ __forceinline__ void put_exp(uint32_t a, uint32_t m, int lane) {
  m = __reduce_max_sync(0xffffffffu, max(m & 0x7f80u, (m >> 16) & 0x7f80u));
  if (lane == 0) sts32(a, m);
}
__device__ __forceinline__ uint32_t seq_mag(uint32_t a) {
  const uint4 x = lds128(a), y = lds128(a + 2048);
  return amax2(amax2(amax2(x.x, x.y), amax2(x.z, x.w)), amax2(amax2(y.x, y.y), amax2(y.z, y.w)));
}
__device__ __forceinline__ uint32_t get_exp(uint32_t a) { const uint4 v = lds128(a); return max(max(v.x, v.y), max(v.z, v.w)) >> 7; }
__device__ __forceinline__ void load_a1(uint32_t (&A1)[8], uint32_t a) {
  const uint4 x = lds128(a), y = lds128(a + 2048);
  A1[0] = x.x; A1[1] = x.y; A1[2] = x.z; A1[3] = x.w; A1[4] = y.x; A1[5] = y.y; A1[6] = y.z; A1[7] = y.w;
}
__device__ __forceinline__ void scale_a1(uint32_t (&A1)[8], uint32_t field) {
#pragma unroll
  for (int i = 0; i < 8; i++) A1[i] = hmul2(A1[i], field * 0x00800080u);
}

struct cf { float x, y; };
__device__ __forceinline__ cf cmul(cf a, cf b) { cf r; r.x = fmaf(a.x, b.x, -a.y * b.y); r.y = fmaf(a.x, b.y, a.y * b.x); return r; }
__device__ __forceinline__ cf cexp_p(float lr2, float lt, float p) {
  float m = exp2f(lr2 * p);
  float t = lt * p;
  t = (t - rintf(t)) * 6.283185307179586f;
  cf r; r.x = m * __cosf(t); r.y = m * __sinf(t); return r;
}
__device__ __forceinline__ void store8(uint32_t a, uint32_t b, const cf (&v)[8]) {
  sts128(a, pack(v[0].x, v[1].x), pack(v[2].x, v[3].x), pack(v[4].x, v[5].x), pack(v[6].x, v[7].x));
  sts128(b, pack(v[0].y, v[1].y), pack(v[2].y, v[3].y), pack(v[4].y, v[5].y), pack(v[6].y, v[7].y));
}
__device__ __forceinline__ void mbar_arrive(uint32_t m) { asm volatile("mbarrier.arrive.shared::cta.b64 _, [%0];" :: "r"(m) : "memory"); }
__device__ __forceinline__ float sigmoidf_(float s) { return 1.f / (1.f + __expf(-s)); }

__global__ void __cluster_dims__(CS, 1, 1) __launch_bounds__(NTHREADS, 1) fused_kernel(const __grid_constant__ Params p) {
  extern __shared__ __align__(1024) uint8_t smem[];
  TL_INIT();
  TL(31);
  const int wid = __shfl_sync(0xffffffffu, threadIdx.x >> 5, 0);
  const uint32_t sb = (uint32_t)__cvta_generic_to_shared(smem);
  const uint32_t mb = sb + OFF_MB;
  const int u = wid >> 2, w = wid & 3;
  const int tid = threadIdx.x & 127, lane = tid & 31, g = lane >> 2, t = lane & 3;
  const int cl = blockIdx.x >> 3, rank = blockIdx.x & 7;
  const int ch0 = cl * CPC;
  const int nu = min(5, (DCH - ch0) >> 3);
  const bool act = u < nu;

  if (u == 4 && lane == 0) {
    if (w < 3) {
#pragma unroll
      for (int i = 0; i < 5; i++) mbar_init(mb + 40 * w + 8 * i, w < 2 ? 2 : 3);
      fence_mbinit();
#pragma unroll
      for (int i = 0; i < 5; i++) mbar_expect(mb + 40 * w + 8 * i, w < 2 ? 3584 : 7168);
    } else {
      mbar_init(mb + 8 * MB_XQ, 1); mbar_init(mb + 8 * MB_KV, 2); mbar_init(mb + 8 * MB_HA, 1); mbar_init(mb + 8 * MB_CF, 1);
      mbar_init(mb + 8 * MB_Q2, 9); mbar_init(mb + 8 * MB_XD, 4); mbar_init(mb + 8 * MB_KD, 16);
      fence_mbinit();
      mbar_expect(mb + 8 * MB_CF, 16384);
      asm volatile("cp.async.bulk.shared::cluster.global.mbarrier::complete_tx::bytes [%0], [%1], %2, [%3];"
                   :: "r"(sb + OFF_CF), "l"(p.tab->mat), "r"(16384), "r"(mb + 8 * MB_CF) : "memory");
      mbar_expect(mb + 8 * MB_XQ, 20480); mbar_expect(mb + 8 * MB_KV, 23040); mbar_expect(mb + 8 * MB_HA, 20480); mbar_expect(mb + 8 * MB_Q2, 20480);
    }
  }
  uint32_t pla, pai, pcr, pci, pdt, tag = 0;
  uint4 psm;
  {
    const int ch = act ? ch0 + 8 * u + rank : 0, o = ch * NMODE + tid;
    pla = ldraw(p.logA + o); pdt = ldraw(p.logdt + ch); pai = ldraw(p.Aim + o); pcr = ldraw(p.Cre + o); pci = ldraw(p.Cim + o);
    if (w == 1) {
      if (lane < 9) psm = ldg128(lane < 5 ? p.gate_w + (lane < nu ? ch0 + 8 * lane : 0) : p.shift_k + (act ? ch0 + 8 * u : 0) * 4 + 8 * (lane - 5));
      else { psm.x = ldraw(p.Dskip + ch); psm.y = ldraw(p.ssm_D + ch); }
    }
    if (wid == 16 && lane < 2) asm volatile("atom.relaxed.gpu.global.add.u32 %0, [%1], %2;" : "=r"(tag) : "l"(&p.cnt[rank * 32 + lane]), "r"(cl == 0 ? 16 - (NCL - 1) : 1) : "memory");
  }
  if (wid == 19 && lane == 0) {
    tma_load4(sb + OFF_TQ, &p.tq, ch0, 0, 0, 8 * rank, mb + 8 * MB_XQ);
    tma_load4(sb + OFF_TK, &p.tk, ch0, 0, 0, 8 * rank - 1, mb + 8 * MB_KV);
    TL(20);
  }
  __syncwarp();
  cluster_arrive();
  TL(0);

  const uint32_t tab = sb + OFF_T + u * KTAB;
  const int mi = lane >> 3, tq = (lane & 7) >> 1, jj = lane & 1;
  const uint32_t toff = (4 * (2 * mi + jj) + tq) * 80;
  const uint32_t uoff = 16 * (4 * w + (t ^ (w >> 1)));
  auto put = [&](int stage, int dst, uint32_t off, const uint32_t (&v)[4]) {
    sts128(sb + off + (g == rank ? dst + 512 * rank : stage + g * YPITCH), v[0], v[1], v[2], v[3]);
  };
  auto send = [&](int stage, int pitch, int dst, int mbar) {
    if (lane == 0) {
#pragma unroll
      for (int k = 0; k < 2; k++) {
        const int d = 2 * w + k;
        if (d != rank) { const uint32_t rb = mapa(sb, d); bulk_dsmem(rb + dst, sb + stage + d * pitch, rb + mbar); }
        else mbar_arrive(sb + mbar);
      }
    }
    __syncwarp();
  };

  uint32_t tc[4], ts[4];
  {
    const uint4 a = ldg128(p.tab->thr[2][tid]), b = ldg128(p.tab->thr[3][tid]);
    tc[0] = a.x; tc[1] = a.y; tc[2] = a.z; tc[3] = a.w; ts[0] = b.x; ts[1] = b.y; ts[2] = b.z; ts[3] = b.w;
  }
  if (w == 1 && lane < 10) sts128(sb + OFF_SP + 160 * u + 16 * lane, psm.x, psm.y, psm.z, psm.w);
  if (u == 4) {
    cluster_wait();
    mbar_wait(mb + 8 * MB_XQ);
    TL(18);
    {
      uint32_t x0[5][4], x1[5][4];
#pragma unroll
      for (int k = 0; k < 5; k++) { ldsm4t(x0[k], sb + OFF_TQ + w * 2560 + toff + 16 * k); ldsm4t(x1[k], sb + OFF_TQ + (w + 4) * 2560 + toff + 16 * k); }
#pragma unroll
      for (int k = 0; k < 5; k++) {
        put(OFF_YB + 8 * k * YPITCH, OFF_UX + k * 4096, uoff, x0[k]);
        put(OFF_YB + 8 * k * YPITCH, OFF_UX + k * 4096, (uoff ^ 32) + 256, x1[k]);
      }
    }
    if (tid == 0) sts32(mb + 8 * MB_TAG, tag);
    TL(3);
    fence_async();
    bar_sync(NB_WG0 + u, 128);
    TL(4);
    float s0 = 0.f, s1 = 0.f;
#pragma unroll 1
    for (int j = 0; j < 5; j++) {
      const uint4 gw = lds128(sb + OFF_SP + 160 * u + 16 * j);
      const uint4 x0 = lds128(sb + OFF_TQ + tid * 80 + 16 * j), x1 = lds128(sb + OFF_TQ + (tid + 128) * 80 + 16 * j);
      send(OFF_YB + 8 * j * YPITCH, YPITCH, OFF_UX + j * 4096 + 512 * rank, OFF_MB + 8 * (MB_UX + j));
      uint32_t m0 = hmul2(x0.x, gw.x), m1 = hmul2(x0.y, gw.y), m2 = hmul2(x0.z, gw.z), m3 = hmul2(x0.w, gw.w);
      s0 += ((blo(m0) + bhi(m0)) + (blo(m1) + bhi(m1))) + ((blo(m2) + bhi(m2)) + (blo(m3) + bhi(m3)));
      m0 = hmul2(x1.x, gw.x); m1 = hmul2(x1.y, gw.y); m2 = hmul2(x1.z, gw.z); m3 = hmul2(x1.w, gw.w);
      s1 += ((blo(m0) + bhi(m0)) + (blo(m1) + bhi(m1))) + ((blo(m2) + bhi(m2)) + (blo(m3) + bhi(m3)));
    }
    tag = (lds64(mb + 8 * MB_TAG).x >> 4) + 1;
    uint2* gp = p.part + cl * SEQ + rank * 256 + 8 * (8 * t + g) + w;
    asm volatile("st.relaxed.gpu.global.u64 [%0], %1;" :: "l"(gp), "l"(((uint64_t)tag << 32) | __float_as_uint(s0)) : "memory");
    asm volatile("st.relaxed.gpu.global.u64 [%0], %1;" :: "l"(gp + 4), "l"(((uint64_t)tag << 32) | __float_as_uint(s1)) : "memory");
    __syncwarp();
    if (lane == 0) mbar_arrive(mb + 8 * MB_XD);
    TL(7);
    bar_sync(NB_K4, 640);
    if (tid == 96) {
      mbar_expect(mb + 8 * MB_KV, 20480);
      tma_load4(sb + OFF_TV, &p.tv, ch0, 0, 0, 8 * rank, mb + 8 * MB_KV);
    }
    __syncwarp();
    TL(8);
  }

  {
    const float dt = bf16r(expf(blo(pdt)));
    const float lr2 = (-bf16r(expf(blo(pla))) * dt) * 1.4426950408889634f;
    const float lt = (blo(pai) * dt) * 0.15915494309189535f;
    const uint32_t tim = u == 0 ? sb + OFF_T + 4 * KTAB : sb + OFF_HA + (u == 4 ? 0 : u - 1) * KTAB;
    const uint32_t row = tab + tid * 16, rim = tim + tid * 16;
    if (lr2 != 123.f) TL(16);
    {
      const cf w1 = cexp_p(lr2, lt, 8.f);
      cf v[8];
      v[0].x = 1.f; v[0].y = 0.f; v[1] = w1; v[2] = cmul(w1, w1); v[3] = cmul(v[2], w1);
      const cf w4 = cmul(v[2], v[2]);
      v[4] = w4; v[5] = cmul(v[1], w4); v[6] = cmul(v[2], w4); v[7] = cmul(v[3], w4);
      const cf w8 = cmul(w4, w4);
      store8(row, rim, v);
#pragma unroll
      for (int k = 1; k < 4; k++) {
#pragma unroll
        for (int i = 0; i < 8; i++) v[i] = (k == 1 && i == 0) ? w8 : cmul(v[i], w8);
        store8(row + 2048 * k, rim + 2048 * k, v);
      }
    }
    {
      cf z1 = cexp_p(lr2, lt, 1.f), Z = cexp_p(lr2, lt, 256.f);
      z1.y = -z1.y; Z.y = -Z.y;
      const cf z2 = cmul(z1, z1);
      cf h[8], v[8];
      h[0].x = 2.f * blo(pcr) * dt; h[0].y = -2.f * blo(pci) * dt;
      h[1] = cmul(h[0], z1);
#pragma unroll
      for (int i = 2; i < 8; i++) h[i] = cmul(h[i - 2], z2);
      store8(row + 4 * 2048, rim + 4 * 2048, h);
      v[0] = cmul(h[0], Z); v[1] = cmul(h[2], Z); v[2] = cmul(h[4], Z); v[3] = cmul(h[6], Z);
      v[4] = cmul(v[0], Z); v[5] = cmul(v[2], Z); v[6] = cmul(v[4], Z); v[7] = cmul(v[5], Z);
      store8(row + 5 * 2048, rim + 5 * 2048, v);
      const cf Z2 = cmul(Z, Z);
      h[0] = cmul(v[4], Z2); h[1] = cmul(v[6], Z2); h[2] = cmul(h[0], Z2); h[3] = cmul(h[1], Z2); h[4] = cmul(h[2], Z2);
      h[5].x = h[5].y = h[6].x = h[6].y = h[7].x = h[7].y = 0.f;
      store8(row + 6 * 2048, rim + 6 * 2048, h);
    }
    TL(17);
    fence_async();
    TL(12);
    bar_sync(NB_WG0 + u, 128);
    TL(13);
    float c[24];
    wg_fence();
    kgen_mma<0>(c, desc_lo(tab) | ((uint64_t)((tim - tab) >> 4) << 16) | (64ull << 32));
    wg_commit();
    uint32_t kid[8];
    {
      const float lf = __uint_as_float(0x4b000000u | (8 * tid)) - 8388608.f;
      const float lo = tid < 16 ? lf + 128.f : lf;
      const uint32_t sub = tid < 16 ? 0x42804300u : 0x42804280u;
#pragma unroll
      for (int i = 0; i < 8; i++) kid[i] = 2 * (pack(lo + i, lf + (1024 + i)) - sub);
    }
    TL(14);
    if (u < 4) cluster_wait();
    TL(23);
    wg_wait<0>(); tie_all(c);
    TL(26);
    if (u < 4) bar_arrive(NB_K4, 640);
    cluster_arrive();
    const uint32_t kc = sb + OFF_KC + u * 1408;
    {
      const int a = 8 * w + g;
      const uint32_t k0 = pack(c[0] + c[6], c[1] + c[7]), k1 = pack(c[8] + c[14], c[9] + c[15]), p0 = pack(c[16] + c[22], c[17] + c[23]);
      sts32(kc + 4 * (4 * a + t), k0);
      sts32(kc + 4 * (t < 2 ? 128 + 2 * a + t : 128 + 32 * t + a), k1);
      put_exp(sb + OFF_MX + u * 64 + 4 * w, amax2(amax2(k0, k1), p0), lane);
      if (t < 3) {
        sts16(kc + 2 * (512 + 64 * t + a), p0);
        sts16(kc + 2 * (544 + 64 * t + a), p0 >> 16);
      }
    }
    TL(19);
    bar_sync(NB_WG0 + u, 128);
    if (wid == 16 && lane == 0) { tma_load4(sb + OFF_HA, &p.th, 0, 0, 5 * cl, rank, mb + 8 * MB_HA); TL(20); }
    __syncwarp();
    uint32_t v[2][8];
#pragma unroll
    for (int i = 0; i < 8; i++) { v[0][i] = lds16(kc + (kid[i] & 0xffffu)); v[1][i] = lds16(kc + (kid[i] >> 16)); }
#pragma unroll
    for (int cc = 0; cc < 2; cc++)
      sts128(tab + 2048 * cc + 16 * (tid ^ ((tid >> 3) & 3)), prmt(v[cc][0], v[cc][1], 0x5410), prmt(v[cc][2], v[cc][3], 0x5410),
             prmt(v[cc][4], v[cc][5], 0x5410), prmt(v[cc][6], v[cc][7], 0x5410));
    TL(15);
    fence_async();
    bar_sync(NB_WG0 + u, 128);
    TL(28);
    mbar_wait(mb + 8 * MB_CF);
  }

#pragma unroll
  for (int isA = 0; isA < 2; isA++) {
    if (isA) {
      cluster_wait();
      if (u < 4) { mbar_wait(mb + 8 * MB_XD); mbar_wait(mb + 8 * MB_KV); }
      TL(21);
#pragma unroll 1
      for (int k = u == 4 ? 5 : u; k < 5; k += u == 3 ? 1 : 5) {
        const uint32_t hoff = (4 * (4 + 2 * (mi & 1) + jj) + ((tq + 3) & 3)) * 80 + (tq ? 2560 : 0) + 16 * k;
        uint32_t E[2][6], V[2][4];
        const uint2 psw = lds64(sb + OFF_SP + 160 * k + 80 + 8 * g);
#pragma unroll
        for (int hf = 0; hf < 2; hf++) {
          const int ah = 4 * hf + w;
          uint32_t K[4];
          ldsm4t(K, sb + OFF_TK + (ah + 1) * 2560 + toff + 16 * k);
          ldsm2t(E[hf][0], E[hf][1], sb + OFF_TK + ah * 2560 + hoff);
          ldsm4t(V[hf], sb + OFF_TV + ah * 2560 + toff + 16 * k);
          E[hf][2] = K[0]; E[hf][3] = K[1]; E[hf][4] = K[2]; E[hf][5] = K[3];
        }
        const uint32_t w0 = prmt(psw.x, 0, 0x1010), w1 = prmt(psw.x, 0, 0x3232), w2 = prmt(psw.y, 0, 0x1010), w3 = prmt(psw.y, 0, 0x3232);
        uint32_t o[2][4];
#pragma unroll
        for (int hf = 0; hf < 2; hf++) {
          uint32_t O[5];
#pragma unroll
          for (int i = 0; i < 5; i++) O[i] = prmt(E[hf][i], E[hf][i + 1], 0x5432);
#pragma unroll
          for (int i = 0; i < 4; i++) {
            uint32_t s = hmul2(O[i], w3);
            s = hadd2(s, hmul2(E[hf][i + 1], w2));
            s = hadd2(s, hmul2(O[i + 1], w1));
            s = hadd2(s, hmul2(E[hf][i + 2], w0));
            o[hf][i] = hmul2(s, V[hf][i]);
          }
          put(OFF_YA + 8 * k * YPITCH, OFF_T + k * KTAB + T_UKV, hf ? (uoff ^ 32) + 256 : uoff, o[hf]);
        }
        fence_async();
        bar_sync(NB_WG0 + u, 128);
        send(OFF_YA + 8 * k * YPITCH, YPITCH, OFF_T + k * KTAB + T_UKV + 512 * rank, OFF_MB + 8 * (MB_UKV + k));
      }
      if (lane == 0 && u < 4) mbar_arrive(mb + 8 * MB_KD);
      TL(22);
      if (u < 2) {
        const int slot = tid + 128 * u;
        tag = (lds64(mb + 8 * MB_TAG).x >> 4) + 1;
        float s = 0.f;
        bool ok = false;
        const uint2* gp = p.part + rank * 256 + slot;
    #pragma unroll 1
        for (int it = 0; it < 4000 && !ok; it++) {
          ok = true; s = 0.f;
    #pragma unroll
          for (int k = 0; k < NCL; k++) {
            uint64_t a;
            asm volatile("ld.relaxed.gpu.global.u64 %0, [%1];" : "=l"(a) : "l"(gp + k * SEQ) : "memory");
            ok = ok && (uint32_t)(a >> 32) == tag;
            s += __uint_as_float((uint32_t)a);
          }
        }
        if (!ok) {
          const uint32_t* xr = (const uint32_t*)(p.q + (size_t)(rank * 256 + 32 * (slot & 7) + (slot >> 3)) * DCH);
          const uint32_t* gr = (const uint32_t*)p.gate_w;
          s = 0.f;
    #pragma unroll 1
          for (int k = 0; k < DCH / 2; k++) { const uint32_t m = hmul2(__ldg(xr + k), __ldg(gr + k)); s += blo(m) + bhi(m); }
        }
        const float g0 = bf16r(sigmoidf_(bf16r(s)));
        sts64(sb + OFF_GB + 8 * slot, pack(g0, g0), pack(1.f - g0, 1.f - g0));
        __syncwarp();
        if (lane == 0) mbar_arrive(mb + 8 * MB_Q2);
      }
      TL(11);
      mbar_wait(mb + 8 * MB_HA);
      put_exp(sb + OFF_MX + u * 64 + 32 + 4 * w, seq_mag(sb + OFF_HA + u * 4096 + 16 * tid), lane);
      bar_sync(NB_WG0 + u, 128);
    }
    {
      TL(1 + isA);
      const uint32_t usrc = isA ? tab + T_UKV : sb + OFF_UX + u * 4096;
      const uint32_t mxa = sb + OFF_MX + u * 64 + 32 * isA;
      const uint32_t pd = lds16(sb + OFF_SP + 160 * u + 144 + 4 * isA);
      float D[32];
      uint32_t A1[8], F[16], H[16], X[16];
      load_a1(A1, sb + OFF_A1 + 16 * tid);
      const uint32_t eh = min(max((int)get_exp(mxa), (int)((pd >> 7) & 0xff) - 5), 240);
      scale_a1(A1, 248 - eh);
      wg_fence();
      stage1(D, A1, isA ? sb + OFF_HA + u * 4096 : tab);
      wg_commit();
      wg_wait<0>(); tie_all(D);
      fwd_mid(F, D, tc, ts);
      wg_fence();
      stage2<0>(H, F, sb + OFF_CF);
      wg_commit();
      load_a1(A1, sb + OFF_A1 + 16 * tid);
      mbar_wait(mb + 8 * ((isA ? MB_UKV : MB_UX) + u));
      TL(5 + isA);
      put_exp(mxa + 16 + 4 * w, seq_mag(usrc + 16 * tid), lane);
      bar_sync(NB_WG0 + u, 128);
      const uint32_t eu = min(get_exp(mxa + 16), 240u);
      scale_a1(A1, 250 - eu);
      wg_wait<0>(); tie_all(H);
      wg_fence();
      stage1(D, A1, usrc);
      wg_commit();
      wg_wait<0>(); tie_all(D);
      fwd_mid(F, D, tc, ts);
      wg_fence();
      stage2<0>(X, F, sb + OFF_CF);
      wg_commit();
      {
        const float dsk = blo(pd) * __uint_as_float((248 - eh) << 23);
        const uint32_t d2 = packh(dsk, dsk);
#pragma unroll
        for (int j = 0; j < 4; j++) H[2 * j] = U2(__hadd2(H2(H[2 * j]), H2(d2)));
      }
      wg_wait<0>(); tie_all(X);
#pragma unroll
      for (int j = 0; j < 4; j++) {
        const uint32_t h0r = H[2 * j], h1r = H[2 * j + 1], h0i = H[8 + 2 * j], h1i = H[9 + 2 * j];
        const uint32_t x0r = X[2 * j], x1r = X[2 * j + 1], x0i = X[8 + 2 * j], x1i = X[9 + 2 * j];
        F[2 * j] = ffma(x0r, h0r, fneg(fmul(x0i, h0i)));
        F[8 + 2 * j] = ffma(x0r, h0i, fmul(x0i, h0r));
        F[2 * j + 1] = ffma(x1r, h0r, ffma(fneg(x1i), h0i, ffma(x0r, h1r, fneg(ffma(x0i, h1i, F[8 + 2 * j])))));
        F[9 + 2 * j] = ffma(x1r, h0i, ffma(x1i, h0r, ffma(x0r, h1i, ffma(x0i, h1r, F[2 * j]))));
      }
      wg_fence();
      stage2<1>(H, F, sb + OFF_CF);
      wg_commit();
      if (isA && wid == 8) {
        mbar_wait(mb + 8 * MB_KD);
        if (lane == 0) tma_load3(sb + OFF_Q2, &p.tq2, ch0, 8 * rank, 0, mb + 8 * MB_Q2);
        __syncwarp();
      }
      wg_wait<0>(); tie_all(H);
      {
        const uint32_t va = tab + (16 * w + (lane & 15)) * 128;
        const int vx = (lane >> 4) ^ (lane & 7);
#pragma unroll
        for (int j = 0; j < 4; j++) {
          uint32_t V[4];
#pragma unroll
          for (int b = 0; b < 2; b++) {
            const uint32_t er = H[2 * j + b], ei = H[8 + 2 * j + b];
            V[2 * b] = ffma(er, tc[j], fneg(fmul(ei, ts[j])));
            V[2 * b + 1] = ffma(ei, tc[j], fmul(er, ts[j]));
          }
          stsm4(va + ((vx ^ (2 * j)) << 4), V);
        }
      }
      fence_async();
      bar_sync(NB_WG0 + u, 128);
      float O[16];
      {
        const uint64_t dv = desc_lo(tab) | (1ull << 16) | (64ull << 32) | (1ull << 62);
        const uint64_t dl = desc_lo(sb + OFF_CL) | (32ull << 16) | (8ull << 32);
        wg_fence();
        ss32<0, 0, 0>(O, dv, dl); ss32<1, 128, 64>(O, dv, dl); ss32<1, 256, 128>(O, dv, dl); ss32<1, 384, 192>(O, dv, dl);
        wg_commit();
      }
      wg_wait<0>(); tie_all(O);
      {
        const uint32_t co = ((8 * w + g) ^ (2 * t)) * 16;
        const int yo = (isA ? OFF_YA : OFF_YB) + (8 * u + rank) * YPITCH, ym = OFF_MB + 8 * (MB_Y + u);
        const uint32_t us = min(max((int)(eu + eh) - 127, 0), 254) * 0x00800080u;
        const uint32_t a0 = hmul2(pack(O[0], O[1]), us), a1 = hmul2(pack(O[4], O[5]), us), a2 = hmul2(pack(O[8], O[9]), us), a3 = hmul2(pack(O[12], O[13]), us);
        const uint32_t b0 = hmul2(pack(O[2], O[3]), us), b1 = hmul2(pack(O[6], O[7]), us), b2 = hmul2(pack(O[10], O[11]), us), b3 = hmul2(pack(O[14], O[15]), us);
        sts128((t == rank ? sb + yo : usrc + t * 512) + co, a0, a1, a2, a3);
        sts128((t + 4 == rank ? sb + yo : usrc + t * 512 + 2048) + co, b0, b1, b2, b3);
        fence_async();
        bar_sync(NB_WG0 + u, 128);
        send(usrc - sb, 512, yo, ym);
      }
      TL(9 + isA);
    }
  }

  {
    mbar_wait(mb + 8 * MB_Q2);
    uint2 gg[2][4];
    uint32_t qv[2][4];
#pragma unroll
    for (int hh = 0; hh < 2; hh++)
#pragma unroll
      for (int i = 0; i < 4; i++) gg[hh][i] = lds64(sb + OFF_GB + 8 * (64 * w + 32 * hh + 8 * i + g));
    const uint32_t qa = sb + OFF_Q2 + (64 * w + lane) * 80 + 16 * u;
    ldsm4(qv[0], qa);
    ldsm4(qv[1], qa + 2560);
    TL(24);
    mbar_wait(mb + 8 * (MB_Y + u));
    uint32_t ya[2][4], yb[2][4];
#pragma unroll
    for (int hh = 0; hh < 2; hh++) {
      const uint32_t yo = (8 * u + (lane & 7)) * YPITCH + ((8 * w + 4 * hh + (lane >> 3)) ^ (2 * (rank & 3))) * 16;
      ldsm4t(ya[hh], sb + OFF_YA + yo); ldsm4t(yb[hh], sb + OFF_YB + yo);
    }
#pragma unroll
    for (int hh = 0; hh < 2; hh++) {
      uint32_t o[4];
#pragma unroll
      for (int i = 0; i < 4; i++) o[i] = hadd2(hmul2(gg[hh][i].x, hmul2(qv[hh][i], ya[hh][i])), hmul2(gg[hh][i].y, yb[hh][i]));
      stsm4(qa + 2560 * hh, o);
    }
    TL(25);
  }
  cluster_arrive();
  bar_sync(NB_ROW0 + w, 160);
  {
    uint4 v[2];
#pragma unroll
    for (int k = 0; k < 2; k++) {
      const int i = 64 * u + 32 * k + lane, sl = (i * 205) >> 10, cc = i - 5 * sl;
      v[k] = lds128(sb + OFF_Q2 + (64 * w + 8 * (sl & 7) + (sl >> 3)) * 80 + cc * 16);
    }
#pragma unroll
    for (int k = 0; k < 2; k++) {
      const int i = 64 * u + 32 * k + lane, sl = (i * 205) >> 10, cc = i - 5 * sl;
      if (cc < nu)
        asm volatile("st.global.v4.u32 [%0], {%1,%2,%3,%4};" :: "l"(p.out + (size_t)(256 * rank + 32 * (sl >> 3) + 8 * w + (sl & 7)) * DCH + ch0 + 8 * cc),
                     "r"(v[k].x), "r"(v[k].y), "r"(v[k].z), "r"(v[k].w) : "memory");
    }
  }
  cluster_wait();
  TL(27);
  TL_DUMP();
}

typedef CUresult (*EncodeFn)(CUtensorMap*, CUtensorMapDataType, cuuint32_t, void*, const cuuint64_t*, const cuuint64_t*,
                             const cuuint32_t*, const cuuint32_t*, CUtensorMapInterleave, CUtensorMapSwizzle,
                             CUtensorMapL2promotion, CUtensorMapFloatOOBfill);

void encode(EncodeFn fn, CUtensorMap* tm, const void* ptr, int nd, const cuuint64_t* dims, const cuuint64_t* strides,
            const cuuint32_t* box, CUtensorMapSwizzle swz) {
  cuuint32_t es[4] = {1, 1, 1, 1};
  fn(tm, CU_TENSOR_MAP_DATA_TYPE_BFLOAT16, nd, const_cast<void*>(ptr), dims, strides, box, es, CU_TENSOR_MAP_INTERLEAVE_NONE,
     swz, CU_TENSOR_MAP_L2_PROMOTION_L2_128B, CU_TENSOR_MAP_FLOAT_OOB_FILL_NONE);
}
void map1(EncodeFn fn, CUtensorMap* tm, const void* ptr, int nhi) {
  const cuuint64_t dims[4] = {DCH, 4, 8, SEQ / 32}, strides[3] = {8 * DCH * 2, DCH * 2, 32 * DCH * 2};
  const cuuint32_t box[4] = {CPC, 4, 8, (cuuint32_t)nhi};
  encode(fn, tm, ptr, 4, dims, strides, box, CU_TENSOR_MAP_SWIZZLE_NONE);
}
void map2(EncodeFn fn, CUtensorMap* tm, const void* ptr, int nr) {
  const cuuint64_t dims[3] = {DCH, SEQ / 32, 32}, strides[2] = {32 * DCH * 2, DCH * 2};
  const cuuint32_t box[3] = {CPC, 8, (cuuint32_t)nr};
  encode(fn, tm, ptr, 3, dims, strides, box, CU_TENSOR_MAP_SWIZZLE_NONE);
}

}

extern "C" void kernel_launch(void* const* d_in, const int* in_sizes, int n_in, void* d_out, int out_size) {
  (void)in_sizes; (void)n_in; (void)out_size;
  static EncodeFn fn = nullptr;
  static void *tab = nullptr, *cnt = nullptr, *part = nullptr;
  if (!fn) {
    cudaGetSymbolAddress(&tab, d_tab);
    cudaGetSymbolAddress(&cnt, g_cnt);
    cudaGetSymbolAddress(&part, g_part);
    cudaDriverEntryPointQueryResult qr;
    cudaGetDriverEntryPoint("cuTensorMapEncodeTiled", (void**)&fn, cudaEnableDefault, &qr);
    cudaFuncSetAttribute(fused_kernel, cudaFuncAttributeMaxDynamicSharedMemorySize, SMEM_BYTES);
  }
  Params p;
  map1(fn, &p.tq, d_in[0], 8);
  map1(fn, &p.tk, d_in[1], 9);
  map1(fn, &p.tv, d_in[2], 8);
  map2(fn, &p.tq2, d_in[0], 32);
  p.out = (__nv_bfloat16*)d_out;
  {
    const cuuint64_t dims[4] = {32, SEQ / 32, DCH / 8, 8}, strides[3] = {64, 8 * SEQ * 2, SEQ * 2};
    const cuuint32_t box[4] = {32, 64, 5, 1};
    encode(fn, &p.th, d_in[4], 4, dims, strides, box, CU_TENSOR_MAP_SWIZZLE_64B);
  }
  p.tab = (const Tables*)tab;
  p.cnt = (unsigned*)cnt;
  p.part = (uint2*)part;
  p.tl = nullptr;
  p.q = (const __nv_bfloat16*)d_in[0];
  p.shift_k = (const __nv_bfloat16*)d_in[3];
  p.ssm_D = (const __nv_bfloat16*)d_in[5];
  p.logA = (const __nv_bfloat16*)d_in[7];
  p.Aim = (const __nv_bfloat16*)d_in[8];
  p.Cre = (const __nv_bfloat16*)d_in[9];
  p.Cim = (const __nv_bfloat16*)d_in[10];
  p.logdt = (const __nv_bfloat16*)d_in[11];
  p.Dskip = (const __nv_bfloat16*)d_in[12];
  p.gate_w = (const __nv_bfloat16*)d_in[13];
  fused_kernel<<<NCL * CS, NTHREADS, SMEM_BYTES, cudaStreamPerThread>>>(p);
}
```

```cpp
#include <cuda_runtime.h>
#include <cuda_bf16.h>
#include <cuda_fp16.h>
#include <cuda.h>
#include <stdint.h>

#define TIMELINE 0

namespace {

constexpr int SEQ = 2048, DCH = 576, NMODE = 128;
constexpr int CS = 8, CPC = 40, NCL = 15, NTHREADS = 640;

constexpr int YPITCH = 528;
constexpr int KTAB = 16384;
constexpr int OFF_T = 0;
constexpr int T_UKV = 8192, T_HA = 12288;
constexpr int OFF_UX = 5 * KTAB;
constexpr int OFF_IM = OFF_UX + 20480;
constexpr int OFF_Q2 = OFF_IM;
constexpr int OFF_GB = OFF_Q2 + 20480;
constexpr int OFF_TV = OFF_IM + 3 * KTAB - 20480;
constexpr int OFF_CF = OFF_IM + 3 * KTAB;
constexpr int OFF_CL = OFF_CF + 8192;
constexpr int OFF_TQ = OFF_CL + 4096;
constexpr int OFF_YA = OFF_TQ;
constexpr int OFF_TK = OFF_TQ + 21120;
constexpr int OFF_YB = OFF_TK + 23040;
constexpr int OFF_MX = OFF_YB + 40 * YPITCH;
constexpr int OFF_SP = OFF_MX + 320;
constexpr int OFF_MB = OFF_SP + 5 * 160;
constexpr int OFF_TL = OFF_MB + 32 * 8;
constexpr int SMEM_BYTES = OFF_TL + (TIMELINE ? 1280 : 0);
static_assert(SMEM_BYTES <= 232448, "smem");
static_assert((OFF_TQ & 127) == 0 && (OFF_TK & 127) == 0 && (OFF_TV & 127) == 0 && (OFF_MB & 7) == 0 && (OFF_MX & 15) == 0, "align");

enum { MB_UX = 0, MB_UKV = 5, MB_Y = 10, MB_HA = 15, MB_XQ = 20, MB_KV = 21, MB_CF = 22, MB_Q2 = 23, MB_XD = 24, MB_TAG = 25 };
enum { NB_WG0 = 1, NB_ROW0 = 6, NB_K4 = 10 };

constexpr double cos_turn(int m, int n) {
  m &= n - 1;
  if (m > n / 2) m = n - m;
  double sgn = 1.0;
  if (m > n / 4) { m = n / 2 - m; sgn = -1.0; }
  if (m == n / 4) return 0.0;
  const double x = 6.283185307179586476925 * m / n;
  double term = 1.0, sum = 1.0;
  for (int k = 1; k < 14; k++) { term *= -x * x / ((2 * k - 1) * (2 * k)); sum += term; }
  return sgn * sum;
}
constexpr uint32_t bf16_bits(double v) {
  if (v == 0.0) return 0;
  uint32_t sgn = 0;
  if (v < 0) { sgn = 0x8000; v = -v; }
  int e = 127;
  while (v < 1.0) { v *= 2.0; e--; }
  while (v >= 2.0) { v *= 0.5; e++; }
  const double f = v * 128.0;
  int m = (int)f;
  if (f - m > 0.5 || (f - m == 0.5 && (m & 1))) m++;
  return sgn | (uint32_t)((e << 7) + (m - 128));
}
constexpr uint32_t f16_bits(double v) {
  if (v == 0.0) return 0;
  uint32_t sgn = 0;
  if (v < 0) { sgn = 0x8000; v = -v; }
  int e = 15;
  while (v < 1.0) { v *= 2.0; e--; }
  const double f = v * 1024.0;
  int m = (int)f;
  if (f - m > 0.5 || (f - m == 0.5 && (m & 1))) m++;
  return sgn | (uint32_t)((e << 10) + (m - 1024));
}
constexpr uint32_t pair_bits(double lo, double hi) { return bf16_bits(lo) | (bf16_bits(hi) << 16); }
constexpr uint32_t pair_h(double lo, double hi) { return f16_bits(lo) | (f16_bits(hi) << 16); }
struct alignas(128) Tables {
  uint32_t mat[3072];
  uint32_t thr[4][128][4];
};
constexpr Tables make_tables() {
  Tables T{};
  for (int q = 0; q < 768; q++) {
    int m0 = 0, d0 = 0, d1 = 0;
    if (q < 512) {
      const int r = (q >> 6) * 8 + (q & 7), cc = (q >> 3) & 7;
      d0 = 4 * (r & 31); d1 = 2 * d0;
      m0 = 8 * (cc & 3) * d0 + ((r >> 5) == (cc >> 2) ? 0 : (r >> 5) ? 96 : 32);
    } else {
      const int r = ((q - 512) >> 5) * 8 + (q & 7), pc = (q >> 3) & 3;
      d0 = 4 * (8 * (r >> 4) + (r & 7)) + 1; d1 = 8 * d0;
      m0 = 2 * pc * d0 + ((r & 8) ? 32 : 0);
    }
    for (int e = 0; e < 4; e++) T.mat[4 * q + e] = pair_h(cos_turn(m0 + e * d1, 128), cos_turn(m0 + e * d1 + d0, 128));
  }
  for (int tid = 0; tid < 128; tid++) {
    const int kk = 4 * (tid >> 2) + 1, t = tid & 3;
    for (int q = 0; q < 4; q++) {
      const int m = (8 * q + 2 * t) * kk;
      T.thr[q >> 1][tid][2 * (q & 1)] = pair_bits(cos_turn(m, 128), cos_turn(m + kk, 128));
      T.thr[q >> 1][tid][2 * (q & 1) + 1] = pair_bits(cos_turn(m + 32, 128), cos_turn(m + kk + 32, 128));
      T.thr[2][tid][q] = pair_h(cos_turn(m, 4096), cos_turn(m + kk, 4096));
      T.thr[3][tid][q] = pair_h(cos_turn(m + 3072, 4096), cos_turn(m + kk + 3072, 4096));
    }
  }
  return T;
}
__device__ const Tables d_tab = make_tables();

struct Params {
  const __nv_bfloat16 *logA, *Aim, *Cre, *Cim, *logdt;
  const Tables* tab;
  unsigned* cnt;
  const __nv_bfloat16 *Dskip, *shift_k, *ssm_D, *gate_w, *q;
  uint2* part;
  __nv_bfloat16* out;
  unsigned* tl;
  CUtensorMap tq, tk, tv, th, tq2;
};

__device__ uint2 g_part[NCL * SEQ];
__device__ unsigned g_cnt[CS * 32];
#define TL(i) do {} while (0)
#define TL_INIT() do {} while (0)
#define TL_DUMP() do {} while (0)

__device__ __forceinline__ uint32_t lds16(uint32_t a) { uint32_t v; asm volatile("ld.shared.u16 %0, [%1];" : "=r"(v) : "r"(a) : "memory"); return v; }
__device__ __forceinline__ uint2 lds64(uint32_t a) { uint2 v; asm volatile("ld.shared.v2.u32 {%0,%1}, [%2];" : "=r"(v.x), "=r"(v.y) : "r"(a) : "memory"); return v; }
__device__ __forceinline__ uint4 lds128(uint32_t a) { uint4 v; asm volatile("ld.shared.v4.u32 {%0,%1,%2,%3}, [%4];" : "=r"(v.x), "=r"(v.y), "=r"(v.z), "=r"(v.w) : "r"(a) : "memory"); return v; }
__device__ __forceinline__ void sts16(uint32_t a, uint32_t v) { asm volatile("st.shared.u16 [%0], %1;" :: "r"(a), "r"(v) : "memory"); }
__device__ __forceinline__ void sts32(uint32_t a, uint32_t v) { asm volatile("st.shared.u32 [%0], %1;" :: "r"(a), "r"(v) : "memory"); }
__device__ __forceinline__ void sts64(uint32_t a, uint32_t x, uint32_t y) { asm volatile("st.shared.v2.u32 [%0], {%1,%2};" :: "r"(a), "r"(x), "r"(y) : "memory"); }
__device__ __forceinline__ void sts128(uint32_t a, uint32_t x, uint32_t y, uint32_t z, uint32_t w) { asm volatile("st.shared.v4.u32 [%0], {%1,%2,%3,%4};" :: "r"(a), "r"(x), "r"(y), "r"(z), "r"(w) : "memory"); }
__device__ __forceinline__ void ldsm4t(uint32_t (&r)[4], uint32_t a) { asm volatile("ldmatrix.sync.aligned.m8n8.x4.trans.shared.b16 {%0,%1,%2,%3}, [%4];" : "=r"(r[0]), "=r"(r[1]), "=r"(r[2]), "=r"(r[3]) : "r"(a) : "memory"); }
__device__ __forceinline__ void ldsm2t(uint32_t& r0, uint32_t& r1, uint32_t a) { asm volatile("ldmatrix.sync.aligned.m8n8.x2.trans.shared.b16 {%0,%1}, [%2];" : "=r"(r0), "=r"(r1) : "r"(a) : "memory"); }
__device__ __forceinline__ void ldsm4(uint32_t (&r)[4], uint32_t a) { asm volatile("ldmatrix.sync.aligned.m8n8.x4.shared.b16 {%0,%1,%2,%3}, [%4];" : "=r"(r[0]), "=r"(r[1]), "=r"(r[2]), "=r"(r[3]) : "r"(a) : "memory"); }
__device__ __forceinline__ void stsm4(uint32_t a, const uint32_t (&r)[4]) { asm volatile("stmatrix.sync.aligned.m8n8.x4.shared.b16 [%0], {%1,%2,%3,%4};" :: "r"(a), "r"(r[0]), "r"(r[1]), "r"(r[2]), "r"(r[3]) : "memory"); }
__device__ __forceinline__ uint32_t pack(float lo, float hi) { uint32_t r; asm("cvt.rn.bf16x2.f32 %0, %1, %2;" : "=r"(r) : "f"(hi), "f"(lo)); return r; }
__device__ __forceinline__ float blo(uint32_t v) { return __uint_as_float(v << 16); }
__device__ __forceinline__ float bhi(uint32_t v) { return __uint_as_float(v & 0xffff0000u); }
__device__ __forceinline__ float bf16r(float x) { return blo(pack(x, 0.f)); }
__device__ __forceinline__ uint32_t hmul2(uint32_t a, uint32_t b) { uint32_t r; asm("mul.rn.bf16x2 %0, %1, %2;" : "=r"(r) : "r"(a), "r"(b)); return r; }
__device__ __forceinline__ uint32_t hadd2(uint32_t a, uint32_t b) { uint32_t r; asm("add.rn.bf16x2 %0, %1, %2;" : "=r"(r) : "r"(a), "r"(b)); return r; }
__device__ __forceinline__ uint32_t hfma2(uint32_t a, uint32_t b, uint32_t c) { uint32_t r; asm("fma.rn.bf16x2 %0, %1, %2, %3;" : "=r"(r) : "r"(a), "r"(b), "r"(c)); return r; }
__device__ __forceinline__ uint32_t packh(float lo, float hi) { uint32_t r; asm("cvt.rn.f16x2.f32 %0, %1, %2;" : "=r"(r) : "f"(hi), "f"(lo)); return r; }
__device__ __forceinline__ __half2 H2(uint32_t a) { return *reinterpret_cast<__half2*>(&a); }
__device__ __forceinline__ uint32_t U2(__half2 a) { return *reinterpret_cast<uint32_t*>(&a); }
__device__ __forceinline__ uint32_t fmul(uint32_t a, uint32_t b) { return U2(__hmul2(H2(a), H2(b))); }
__device__ __forceinline__ uint32_t ffma(uint32_t a, uint32_t b, uint32_t c) { return U2(__hfma2(H2(a), H2(b), H2(c))); }
__device__ __forceinline__ uint32_t fneg(uint32_t a) { return U2(__hneg2(H2(a))); }
__device__ __forceinline__ uint32_t amax2(uint32_t a, uint32_t b) { uint32_t r; asm("max.xorsign.abs.bf16x2 %0, %1, %2;" : "=r"(r) : "r"(a), "r"(b)); return r; }
__device__ __forceinline__ uint32_t prmt(uint32_t a, uint32_t b, uint32_t s) { return __byte_perm(a, b, s); }
__device__ __forceinline__ uint32_t ldraw(const __nv_bfloat16* p) { uint32_t v; asm volatile("ld.global.nc.u16 %0, [%1];" : "=r"(v) : "l"(p)); return v; }
__device__ __forceinline__ uint4 ldg128(const void* p) { uint4 v; asm volatile("ld.global.nc.v4.u32 {%0,%1,%2,%3}, [%4];" : "=r"(v.x), "=r"(v.y), "=r"(v.z), "=r"(v.w) : "l"(p)); return v; }
__device__ __forceinline__ void bar_sync(int id, int n) { asm volatile("bar.sync %0, %1;" :: "r"(id), "r"(n) : "memory"); }
__device__ __forceinline__ void bar_arrive(int id, int n) { asm volatile("bar.arrive %0, %1;" :: "r"(id), "r"(n) : "memory"); }
__device__ __forceinline__ void cluster_arrive() { asm volatile("barrier.cluster.arrive.relaxed.aligned;" ::: "memory"); }
__device__ __forceinline__ void cluster_wait() { asm volatile("barrier.cluster.wait.aligned;" ::: "memory"); }
__device__ __forceinline__ void fence_async() { asm volatile("fence.proxy.async.shared::cta;" ::: "memory"); }
__device__ __forceinline__ void fence_mbinit() { asm volatile("fence.mbarrier_init.release.cluster;" ::: "memory"); }
__device__ __forceinline__ uint32_t mapa(uint32_t a, uint32_t rank) { uint32_t r; asm("mapa.shared::cluster.u32 %0, %1, %2;" : "=r"(r) : "r"(a), "r"(rank)); return r; }
__device__ __forceinline__ void bulk_dsmem(uint32_t dst, uint32_t src, uint32_t mbar) {
  asm volatile("cp.async.bulk.shared::cluster.shared::cta.mbarrier::complete_tx::bytes [%0], [%1], 512, [%2];" :: "r"(dst), "r"(src), "r"(mbar) : "memory");
}
__device__ __forceinline__ void mbar_init(uint32_t m, uint32_t cnt) { asm volatile("mbarrier.init.shared::cta.b64 [%0], %1;" :: "r"(m), "r"(cnt) : "memory"); }
__device__ __forceinline__ void mbar_expect(uint32_t m, uint32_t bytes) { asm volatile("mbarrier.arrive.expect_tx.shared::cta.b64 _, [%0], %1;" :: "r"(m), "r"(bytes) : "memory"); }
__device__ __forceinline__ bool mbar_try(uint32_t m) {
  uint32_t done;
  asm volatile("{.reg .pred p; mbarrier.try_wait.parity.shared::cta.b64 p, [%1], 0; selp.u32 %0, 1, 0, p;}" : "=r"(done) : "r"(m) : "memory");
  return done;
}
__device__ __forceinline__ void mbar_wait(uint32_t m) {
  if (!mbar_try(m)) {
    int it = 0;
    while (!mbar_try(m) && ++it < (1 << 22)) {}
  }
}
__device__ __forceinline__ bool elect() {
  uint32_t e;
  asm volatile("{.reg .pred p; elect.sync _|p, 0xffffffff; selp.u32 %0, 1, 0, p;}" : "=r"(e));
  return e;
}
__device__ __forceinline__ void tma_load4(uint32_t dst, const CUtensorMap* tm, int c0, int c1, int c2, int c3, uint32_t mbar) {
  asm volatile("cp.async.bulk.tensor.4d.shared::cluster.global.mbarrier::complete_tx::bytes [%0], [%1, {%3, %4, %5, %6}], [%2];"
               :: "r"(dst), "l"(tm), "r"(mbar), "r"(c0), "r"(c1), "r"(c2), "r"(c3) : "memory");
}
__device__ __forceinline__ void tma_load3(uint32_t dst, const CUtensorMap* tm, int c0, int c1, int c2, uint32_t mbar) {
  asm volatile("cp.async.bulk.tensor.3d.shared::cluster.global.mbarrier::complete_tx::bytes [%0], [%1, {%3, %4, %5}], [%2];"
               :: "r"(dst), "l"(tm), "r"(mbar), "r"(c0), "r"(c1), "r"(c2) : "memory");
}
__device__ __forceinline__ void tma_store3(const CUtensorMap* tm, int c0, int c1, int c2, uint32_t src) {
  asm volatile("cp.async.bulk.tensor.3d.global.shared::cta.bulk_group [%0, {%2, %3, %4}], [%1];"
               :: "l"(tm), "r"(src), "r"(c0), "r"(c1), "r"(c2) : "memory");
}
__device__ __forceinline__ void wg_fence() { asm volatile("wgmma.fence.sync.aligned;" ::: "memory"); }
__device__ __forceinline__ void wg_commit() { asm volatile("wgmma.commit_group.sync.aligned;" ::: "memory"); }
template <int N> __device__ __forceinline__ void wg_wait() { asm volatile("wgmma.wait_group.sync.aligned %0;" :: "n"(N) : "memory"); }
template <int N> __device__ __forceinline__ void tie_all(uint32_t (&x)[N]) {
#pragma unroll
  for (int i = 0; i < N; i++) asm volatile("" : "+r"(x[i]) :: "memory");
}
template <int N> __device__ __forceinline__ void tie_all(float (&x)[N]) {
#pragma unroll
  for (int i = 0; i < N; i++) asm volatile("" : "+f"(x[i]) :: "memory");
}
#define R16(C, d) C(d[0]), C(d[1]), C(d[2]), C(d[3]), C(d[4]), C(d[5]), C(d[6]), C(d[7]), C(d[8]), C(d[9]), C(d[10]), C(d[11]), C(d[12]), C(d[13]), C(d[14]), C(d[15])
#define R32(C, d) R16(C, d), R16(C, (d + 16))
#define P16 "{%0,%1,%2,%3,%4,%5,%6,%7,%8,%9,%10,%11,%12,%13,%14,%15}"
#define P32 "{%0,%1,%2,%3,%4,%5,%6,%7,%8,%9,%10,%11,%12,%13,%14,%15,%16,%17,%18,%19,%20,%21,%22,%23,%24,%25,%26,%27,%28,%29,%30,%31}"
template <int SD, int TB, int OFF> __device__ __forceinline__ void rs64(float* d, const uint32_t* a, uint64_t db) {
  if (SD) asm volatile("{.reg .b64 db; add.s64 db, %36, %37; wgmma.mma_async.sync.aligned.m64n64k16.f32.bf16.bf16 " P32 ", {%32,%33,%34,%35}, db, 1, 1, 1, %38;}"
                       : R32("+f", d) : "r"(a[0]), "r"(a[1]), "r"(a[2]), "r"(a[3]), "l"(db), "n"(OFF), "n"(TB));
  else asm volatile("{.reg .b64 db; add.s64 db, %36, %37; wgmma.mma_async.sync.aligned.m64n64k16.f32.bf16.bf16 " P32 ", {%32,%33,%34,%35}, db, 0, 1, 1, %38;}"
                    : R32("=f", d) : "r"(a[0]), "r"(a[1]), "r"(a[2]), "r"(a[3]), "l"(db), "n"(OFF), "n"(TB));
}
template <int SD, int TB, int OFF> __device__ __forceinline__ void rs64h(uint32_t* d, const uint32_t* a, uint64_t db) {
  if (SD) asm volatile("{.reg .b64 db; add.s64 db, %20, %21; wgmma.mma_async.sync.aligned.m64n64k16.f16.f16.f16 " P16 ", {%16,%17,%18,%19}, db, 1, 1, 1, %22;}"
                       : R16("+r", d) : "r"(a[0]), "r"(a[1]), "r"(a[2]), "r"(a[3]), "l"(db), "n"(OFF), "n"(TB));
  else asm volatile("{.reg .b64 db; add.s64 db, %20, %21; wgmma.mma_async.sync.aligned.m64n64k16.f16.f16.f16 " P16 ", {%16,%17,%18,%19}, db, 0, 1, 1, %22;}"
                    : R16("=r", d) : "r"(a[0]), "r"(a[1]), "r"(a[2]), "r"(a[3]), "l"(db), "n"(OFF), "n"(TB));
}
template <int SD, int OFFA, int OFFB> __device__ __forceinline__ void ss32(float* d, uint64_t da, uint64_t db) {
  if (SD) asm volatile("{.reg .b64 da, db; add.s64 da, %16, %18; add.s64 db, %17, %19; wgmma.mma_async.sync.aligned.m64n32k16.f32.f16.f16 " P16 ", da, db, 1, 1, 1, 1, 1;}"
                       : R16("+f", d) : "l"(da), "l"(db), "n"(OFFA), "n"(OFFB));
  else asm volatile("{.reg .b64 da, db; add.s64 da, %16, %18; add.s64 db, %17, %19; wgmma.mma_async.sync.aligned.m64n32k16.f32.f16.f16 " P16 ", da, db, 0, 1, 1, 1, 1;}"
                    : R16("=f", d) : "l"(da), "l"(db), "n"(OFFA), "n"(OFFB));
}
#define KGEN_ASM(SD) "{.reg .b64 da, db; add.s64 da, %32, %33; add.s64 db, %32, %34;\n" \
  "wgmma.mma_async.sync.aligned.m64n64k16.f32.bf16.bf16 " P32 ", da, db, " SD ", 1, 1, 1, 1;}"
template <int KS> __device__ __forceinline__ void kgen_mma(float (&c)[32], uint64_t da) {
  if (KS) asm volatile(KGEN_ASM("1") : R32("+f", c) : "l"(da), "n"(8 * KS), "n"(8 * KS + 512));
  else asm volatile(KGEN_ASM("0") : R32("=f", c) : "l"(da), "n"(8 * KS), "n"(8 * KS + 512));
  if constexpr (KS < 7) kgen_mma<KS + 1>(c, da);
}
__device__ __forceinline__ uint64_t desc_lo(uint32_t a) { return (uint64_t)((a & 0x3FFFF) >> 4); }
__device__ __forceinline__ void stage1(float (&D)[32], const uint32_t (&A1)[8], uint32_t src) {
  const uint64_t du = desc_lo(src) | (128ull << 16) | (32ull << 32) | (2ull << 62);
  rs64<0, 1, 0>(D, A1, du); rs64<1, 1, 64>(D, A1 + 4, du);
}
template <int INV> __device__ __forceinline__ void stage2(uint32_t (&X)[16], const uint32_t (&F)[16], uint32_t cf) {
  constexpr int KS = INV ? 16 : 128, TB = INV ? 0 : 1;
  const uint64_t dc = desc_lo(cf) | (INV ? (8ull << 16) | (64ull << 32) : (64ull << 16) | (8ull << 32));
  rs64h<0, TB, 0>(X, F, dc); rs64h<1, TB, KS>(X, F + 4, dc); rs64h<1, TB, 2 * KS>(X, F + 8, dc); rs64h<1, TB, 3 * KS>(X, F + 12, dc);
}
__device__ __forceinline__ void fwd_mid(uint32_t (&F)[16], const float (&D)[32], const uint32_t (&tc)[4], const uint32_t (&ts)[4]) {
#pragma unroll
  for (int j = 0; j < 4; j++)
#pragma unroll
    for (int b = 0; b < 2; b++) {
      const int i = 4 * j + 16 * b;
      const uint32_t ar = packh(D[i], D[i + 1]), ai = packh(D[i + 2], D[i + 3]);
      F[2 * j + b] = ffma(ar, tc[j], fmul(ai, ts[j]));
      F[8 + 2 * j + b] = ffma(ai, tc[j], fneg(fmul(ar, ts[j])));
    }
}
__device__ __forceinline__ void put_exp(uint32_t a, uint32_t m, int lane) {
  m = __reduce_max_sync(0xffffffffu, max(m & 0x7f80u, (m >> 16) & 0x7f80u));
  if (lane == 0) sts32(a, m);
}
__device__ __forceinline__ uint32_t seq_mag(uint32_t a) {
  const uint4 x = lds128(a), y = lds128(a + 2048);
  return amax2(amax2(amax2(x.x, x.y), amax2(x.z, x.w)), amax2(amax2(y.x, y.y), amax2(y.z, y.w)));
}
__device__ __forceinline__ uint32_t get_exp(uint32_t a) { const uint4 v = lds128(a); return max(max(v.x, v.y), max(v.z, v.w)) >> 7; }
__device__ __forceinline__ void scale_a1(uint32_t (&As)[8], const uint32_t (&A1)[8], uint32_t field) {
#pragma unroll
  for (int i = 0; i < 8; i++) As[i] = hmul2(A1[i], field * 0x00800080u);
}

struct cf { float x, y; };
__device__ __forceinline__ cf cmul(cf a, cf b) { cf r; r.x = fmaf(a.x, b.x, -a.y * b.y); r.y = fmaf(a.x, b.y, a.y * b.x); return r; }
__device__ __forceinline__ cf cexp_p(float lr2, float lt, float p) {
  float m;
  asm("ex2.approx.ftz.f32 %0, %1;" : "=f"(m) : "f"(lr2 * p));
  float t = lt * p;
  t = (t - rintf(t)) * 6.283185307179586f;
  cf r; r.x = m * __cosf(t); r.y = m * __sinf(t); return r;
}
__device__ __forceinline__ void store8(uint32_t a, uint32_t b, const cf (&v)[8]) {
  sts128(a, pack(v[0].x, v[1].x), pack(v[2].x, v[3].x), pack(v[4].x, v[5].x), pack(v[6].x, v[7].x));
  sts128(b, pack(v[0].y, v[1].y), pack(v[2].y, v[3].y), pack(v[4].y, v[5].y), pack(v[6].y, v[7].y));
}
__device__ __forceinline__ void mbar_arrive(uint32_t m) { asm volatile("mbarrier.arrive.shared::cta.b64 _, [%0];" :: "r"(m) : "memory"); }
__device__ __forceinline__ float sigmoidf_(float s) { return 1.f / (1.f + __expf(-s)); }

__global__ void __cluster_dims__(CS, 1, 1) __launch_bounds__(NTHREADS, 1) fused_kernel(const __grid_constant__ Params p) {
  extern __shared__ __align__(1024) uint8_t smem[];
  TL_INIT();
  TL(31);
  const int wid = __shfl_sync(0xffffffffu, threadIdx.x >> 5, 0);
  const uint32_t sb = (uint32_t)__cvta_generic_to_shared(smem);
  const uint32_t mb = sb + OFF_MB;
  const int u = wid >> 2, w = wid & 3;
  const int tid = threadIdx.x & 127, lane = tid & 31, g = lane >> 2, t = lane & 3;
  const int cl = blockIdx.x >> 3, rank = blockIdx.x & 7;
  const int ch0 = cl * CPC;
  const int nu = min(5, (DCH - ch0) >> 3);
  const bool act = u < nu;

  if (u == 4 && elect()) {
#pragma unroll
    for (int i = 0; i < 5; i++) mbar_init(mb + 40 * w + 8 * i, w == 3 ? 1 : w == 2 ? 3 : 2);
    if (w == 3) {
      mbar_init(mb + 8 * MB_XQ, 1); mbar_init(mb + 8 * MB_KV, 2); mbar_init(mb + 8 * MB_CF, 1); mbar_init(mb + 8 * MB_Q2, 9); mbar_init(mb + 8 * MB_XD, 4);
    }
    fence_mbinit();
    if (w == 3) {
      mbar_expect(mb + 8 * MB_CF, 12288);
      asm volatile("cp.async.bulk.shared::cluster.global.mbarrier::complete_tx::bytes [%0], [%1], %2, [%3];"
                   :: "r"(sb + OFF_CF), "l"(p.tab->mat), "r"(12288), "r"(mb + 8 * MB_CF) : "memory");
      mbar_expect(mb + 8 * MB_XQ, 20480); mbar_expect(mb + 8 * MB_KV, 23040); mbar_expect(mb + 8 * MB_Q2, 20480);
    }
#pragma unroll
    for (int i = 0; i < 5; i++) mbar_expect(mb + 40 * w + 8 * i, w == 3 ? 4096 : w == 2 ? 7168 : 3584);
  }
  uint32_t pla, pai, pcr, pci, pdt, tag = 0;
  uint4 psm;
  {
    const int ch = act ? ch0 + 8 * u + rank : 0, o = ch * NMODE + tid;
    pla = ldraw(p.logA + o); pdt = ldraw(p.logdt + ch); pai = ldraw(p.Aim + o); pcr = ldraw(p.Cre + o); pci = ldraw(p.Cim + o);
    if (w == 1) {
      if (lane < 9) psm = ldg128(lane < 5 ? p.gate_w + (lane < nu ? ch0 + 8 * lane : 0) : p.shift_k + (act ? ch0 + 8 * u : 0) * 4 + 8 * (lane - 5));
      else { psm.x = ldraw(p.Dskip + ch); psm.y = ldraw(p.ssm_D + ch); }
    }
    if (wid == 16 && lane < 2) asm volatile("atom.relaxed.gpu.global.add.u32 %0, [%1], %2;" : "=r"(tag) : "l"(&p.cnt[rank * 32 + lane]), "r"(cl == 0 ? 16 - (NCL - 1) : 1) : "memory");
  }
  if (wid == 19 && elect()) {
    tma_load4(sb + OFF_TQ, &p.tq, ch0, 0, 0, 8 * rank, mb + 8 * MB_XQ);
    tma_load4(sb + OFF_TK, &p.tk, ch0, 0, 0, 8 * rank - 1, mb + 8 * MB_KV);
    TL(20);
  }
  __syncwarp();
  cluster_arrive();
  TL(0);

  const uint32_t tab = sb + OFF_T + u * KTAB;
  const int mi = lane >> 3, tq = (lane & 7) >> 1, jj = lane & 1;
  const uint32_t toff = (4 * (2 * mi + jj) + tq) * 80;
  const uint32_t uoff = 16 * (4 * w + (t ^ (w >> 1)));
  auto put = [&](int stage, int dst, uint32_t off, const uint32_t (&v)[4]) {
    sts128(sb + off + (g == rank ? dst + 512 * rank : stage + g * YPITCH), v[0], v[1], v[2], v[3]);
  };
  const int d0 = rank ^ (2 * w), d1 = d0 ^ 1;
  const uint32_t rb0 = mapa(sb, d0), rb1 = mapa(sb, d1);
  auto send = [&](int stage, int pitch, int dst, int mbar) {
    if (elect()) {
      if (w) bulk_dsmem(rb0 + dst, sb + stage + d0 * pitch, rb0 + mbar); else mbar_arrive(sb + mbar);
      bulk_dsmem(rb1 + dst, sb + stage + d1 * pitch, rb1 + mbar);
    }
    __syncwarp();
  };

  uint32_t A1[8], tc[4], ts[4];
  {
    const uint4 x = ldg128(p.tab->thr[0][tid]), y = ldg128(p.tab->thr[1][tid]);
    A1[0] = x.x; A1[1] = x.y; A1[2] = x.z; A1[3] = x.w; A1[4] = y.x; A1[5] = y.y; A1[6] = y.z; A1[7] = y.w;
    const uint4 a = ldg128(p.tab->thr[2][tid]), b = ldg128(p.tab->thr[3][tid]);
    tc[0] = a.x; tc[1] = a.y; tc[2] = a.z; tc[3] = a.w; ts[0] = b.x; ts[1] = b.y; ts[2] = b.z; ts[3] = b.w;
  }
  if (w == 1 && lane < 10) sts128(sb + OFF_SP + 160 * u + 16 * lane, psm.x, psm.y, psm.z, psm.w);
  if (u == 4) {
    cluster_wait();
    mbar_wait(mb + 8 * MB_XQ);
    TL(18);
    {
      uint32_t x0[5][4], x1[5][4];
#pragma unroll
      for (int k = 0; k < 5; k++) { ldsm4t(x0[k], sb + OFF_TQ + w * 2560 + toff + 16 * k); ldsm4t(x1[k], sb + OFF_TQ + (w + 4) * 2560 + toff + 16 * k); }
#pragma unroll
      for (int k = 0; k < 5; k++) {
        put(OFF_YB + 8 * k * YPITCH, OFF_UX + k * 4096, uoff, x0[k]);
        put(OFF_YB + 8 * k * YPITCH, OFF_UX + k * 4096, (uoff ^ 32) + 256, x1[k]);
      }
    }
    if (tid == 0) sts32(mb + 8 * MB_TAG, tag);
    TL(3);
    fence_async();
    bar_sync(NB_WG0 + u, 128);
    TL(4);
    float s0 = 0.f, s1 = 0.f;
#pragma unroll 1
    for (int j = 0; j < 5; j++) {
      const uint4 gw = lds128(sb + OFF_SP + 160 * u + 16 * j);
      const uint4 x0 = lds128(sb + OFF_TQ + tid * 80 + 16 * j), x1 = lds128(sb + OFF_TQ + (tid + 128) * 80 + 16 * j);
      send(OFF_YB + 8 * j * YPITCH, YPITCH, OFF_UX + j * 4096 + 512 * rank, OFF_MB + 8 * (MB_UX + j));
      uint32_t m0 = hmul2(x0.x, gw.x), m1 = hmul2(x0.y, gw.y), m2 = hmul2(x0.z, gw.z), m3 = hmul2(x0.w, gw.w);
      s0 += ((blo(m0) + bhi(m0)) + (blo(m1) + bhi(m1))) + ((blo(m2) + bhi(m2)) + (blo(m3) + bhi(m3)));
      m0 = hmul2(x1.x, gw.x); m1 = hmul2(x1.y, gw.y); m2 = hmul2(x1.z, gw.z); m3 = hmul2(x1.w, gw.w);
      s1 += ((blo(m0) + bhi(m0)) + (blo(m1) + bhi(m1))) + ((blo(m2) + bhi(m2)) + (blo(m3) + bhi(m3)));
    }
    tag = (lds64(mb + 8 * MB_TAG).x >> 4) + 1;
    uint2* gp = p.part + cl * SEQ + rank * 256 + 8 * (8 * t + g) + w;
    asm volatile("st.relaxed.gpu.global.u64 [%0], %1;" :: "l"(gp), "l"(((uint64_t)tag << 32) | __float_as_uint(s0)) : "memory");
    asm volatile("st.relaxed.gpu.global.u64 [%0], %1;" :: "l"(gp + 4), "l"(((uint64_t)tag << 32) | __float_as_uint(s1)) : "memory");
    __syncwarp();
    if (lane == 0) mbar_arrive(mb + 8 * MB_XD);
    TL(7);
    bar_sync(NB_K4, 640);
    if (w == 3 && elect()) {
      mbar_expect(mb + 8 * MB_KV, 20480);
      tma_load4(sb + OFF_TV, &p.tv, ch0, 0, 0, 8 * rank, mb + 8 * MB_KV);
    }
    __syncwarp();
    TL(8);
  }

  {
    const float dt = bf16r(expf(blo(pdt)));
    const float lr2 = (-bf16r(expf(blo(pla))) * dt) * 1.4426950408889634f;
    const float lt = (blo(pai) * dt) * 0.15915494309189535f;
    const uint32_t tim = u == 0 ? sb + OFF_T + 4 * KTAB : sb + OFF_IM + (u == 4 ? 0 : u - 1) * KTAB;
    const uint32_t row = tab + tid * 16, rim = tim + tid * 16;
    if (lr2 != 123.f) TL(16);
    {
      const cf w1 = cexp_p(lr2, lt, 8.f);
      cf v[8];
      v[0].x = 1.f; v[0].y = 0.f; v[1] = w1; v[2] = cmul(w1, w1); v[3] = cmul(v[2], w1);
      const cf w4 = cmul(v[2], v[2]);
      v[4] = w4; v[5] = cmul(v[1], w4); v[6] = cmul(v[2], w4); v[7] = cmul(v[3], w4);
      const cf w8 = cmul(w4, w4);
      store8(row, rim, v);
#pragma unroll
      for (int k = 1; k < 4; k++) {
#pragma unroll
        for (int i = 0; i < 8; i++) v[i] = (k == 1 && i == 0) ? w8 : cmul(v[i], w8);
        store8(row + 2048 * k, rim + 2048 * k, v);
      }
    }
    {
      cf z1 = cexp_p(lr2, lt, 1.f), Z = cexp_p(lr2, lt, 256.f);
      z1.y = -z1.y; Z.y = -Z.y;
      const cf z2 = cmul(z1, z1);
      cf h[8], v[8];
      h[0].x = 2.f * blo(pcr) * dt; h[0].y = -2.f * blo(pci) * dt;
      h[1] = cmul(h[0], z1);
#pragma unroll
      for (int i = 2; i < 8; i++) h[i] = cmul(h[i - 2], z2);
      store8(row + 4 * 2048, rim + 4 * 2048, h);
      const cf h8 = cmul(h[6], z2);
      v[0] = cmul(h[0], Z); v[2] = cmul(h[2], Z); v[3] = cmul(h[4], Z); v[6] = cmul(h[6], Z); v[7] = cmul(h8, Z);
      v[1] = v[0]; v[4] = v[5] = v[3];
      store8(row + 5 * 2048, rim + 5 * 2048, v);
      h[0] = cmul(v[0], Z); h[1] = cmul(v[3], Z); h[3] = cmul(v[7], Z); h[4] = cmul(h[0], Z); h[5] = cmul(h[1], Z); h[7] = cmul(h[3], Z);
      h[2] = h[1]; h[6] = h[5];
      store8(row + 6 * 2048, rim + 6 * 2048, h);
      const cf Z2 = cmul(Z, Z);
      v[0] = cmul(h[0], Z2); v[1] = cmul(h[3], Z2); v[2] = cmul(h[4], Z2); v[3] = cmul(h[7], Z2);
#pragma unroll
      for (int i = 4; i < 8; i++) v[i] = cmul(v[i - 4], Z2);
      store8(row + 7 * 2048, rim + 7 * 2048, v);
    }
    TL(17);
    fence_async();
    bar_sync(NB_WG0 + u, 128);
    TL(13);
    float c[32];
    wg_fence();
    kgen_mma<0>(c, desc_lo(tab) | ((uint64_t)((tim - tab) >> 4) << 16) | (64ull << 32));
    wg_commit();
    if (u < 4) cluster_wait();
    wg_wait<0>(); tie_all(c);
    TL(26);
    if (u < 4) bar_arrive(NB_K4, 640);
    cluster_arrive();
    bar_sync(NB_WG0 + u, 128);
    if (w == 0 && elect()) {
      tma_load4(tab + T_HA, &p.th, 0, 0, 5 * cl + u, rank, mb + 8 * (MB_HA + u));
      if (u == 4) tma_load3(sb + OFF_Q2, &p.tq2, ch0, 8 * rank, 0, mb + 8 * MB_Q2);
    }
    __syncwarp();
    const uint32_t k0 = pack(c[0] + c[6], c[1] + c[7]), k1 = pack(c[8] + c[14], c[9] + c[15]);
    const uint32_t k2 = pack(c[16] + c[22], c[17] + c[23]), k3 = pack(c[24] + c[30], c[25] + c[31]);
    const uint32_t ka = tab + 16 * (8 * w + (g ^ w));
    sts32(ka + 4 * t, k0);
    sts32(ka + 512 + 4 * t, k1);
    sts64(ka + 1024 + 512 * (t >> 1) + 8 * (t & 1), prmt(k2, 0, 0x1010), (t & 1) ? prmt(k2, 0, 0x3232) : k2);
    const uint32_t lo = prmt(k3, 0, 0x1010), hi = prmt(k3, 0, 0x3232);
    sts128(ka + 2048 + 512 * t, lo, lo, (g & 1) ? hi : k3, hi);
    put_exp(sb + OFF_MX + u * 64 + 4 * w, amax2(amax2(k0, k1), amax2(k2, k3)), lane);
    TL(15);
    fence_async();
    bar_sync(NB_WG0 + u, 128);
    mbar_wait(mb + 8 * MB_CF);
  }

#pragma unroll
  for (int isA = 0; isA < 2; isA++) {
    if (isA) {
      cluster_wait();
      if (u < 4) { mbar_wait(mb + 8 * MB_XD); mbar_wait(mb + 8 * MB_KV); }
      TL(21);
#pragma unroll 1
      for (int k = u == 4 ? 5 : u; k < 5; k += u == 3 ? 1 : 5) {
        const uint32_t hoff = (4 * (4 + 2 * (mi & 1) + jj) + ((tq + 3) & 3)) * 80 + (tq ? 2560 : 0) + 16 * k;
        uint32_t E[2][6], V[2][4];
        const uint2 psw = lds64(sb + OFF_SP + 160 * k + 80 + 8 * g);
#pragma unroll
        for (int hf = 0; hf < 2; hf++) {
          const int ah = 4 * hf + w;
          uint32_t K[4];
          ldsm4t(K, sb + OFF_TK + (ah + 1) * 2560 + toff + 16 * k);
          ldsm2t(E[hf][0], E[hf][1], sb + OFF_TK + ah * 2560 + hoff);
          ldsm4t(V[hf], sb + OFF_TV + ah * 2560 + toff + 16 * k);
          E[hf][2] = K[0]; E[hf][3] = K[1]; E[hf][4] = K[2]; E[hf][5] = K[3];
        }
        const uint32_t w0 = prmt(psw.x, 0, 0x1010), w1 = prmt(psw.x, 0, 0x3232), w2 = prmt(psw.y, 0, 0x1010), w3 = prmt(psw.y, 0, 0x3232);
        uint32_t o[2][4];
#pragma unroll
        for (int hf = 0; hf < 2; hf++) {
          uint32_t O[5];
#pragma unroll
          for (int i = 0; i < 5; i++) O[i] = prmt(E[hf][i], E[hf][i + 1], 0x5432);
#pragma unroll
          for (int i = 0; i < 4; i++) {
            o[hf][i] = hmul2(hfma2(E[hf][i + 2], w0, hfma2(O[i + 1], w1, hfma2(E[hf][i + 1], w2, hmul2(O[i], w3)))), V[hf][i]);
          }
          put(OFF_YA + 8 * k * YPITCH, OFF_T + k * KTAB + T_UKV, hf ? (uoff ^ 32) + 256 : uoff, o[hf]);
        }
        fence_async();
        bar_sync(NB_WG0 + u, 128);
        send(OFF_YA + 8 * k * YPITCH, YPITCH, OFF_T + k * KTAB + T_UKV + 512 * rank, OFF_MB + 8 * (MB_UKV + k));
      }
      TL(22);
      if (u < 2) {
        const int slot = tid + 128 * u;
        tag = (lds64(mb + 8 * MB_TAG).x >> 4) + 1;
        float s = 0.f;
        bool ok = false;
        const uint2* gp = p.part + rank * 256 + slot;
    #pragma unroll 1
        for (int it = 0; it < 4000 && !ok; it++) {
          ok = true; s = 0.f;
    #pragma unroll
          for (int k = 0; k < NCL; k++) {
            uint64_t a;
            asm volatile("ld.relaxed.gpu.global.u64 %0, [%1];" : "=l"(a) : "l"(gp + k * SEQ) : "memory");
            ok = ok && (uint32_t)(a >> 32) == tag;
            s += __uint_as_float((uint32_t)a);
          }
        }
        if (!ok) {
          const uint32_t* xr = (const uint32_t*)(p.q + (size_t)(rank * 256 + 32 * (slot & 7) + (slot >> 3)) * DCH);
          const uint32_t* gr = (const uint32_t*)p.gate_w;
          s = 0.f;
    #pragma unroll 1
          for (int k = 0; k < DCH / 2; k++) { const uint32_t m = hmul2(__ldg(xr + k), __ldg(gr + k)); s += blo(m) + bhi(m); }
        }
        const float g0 = bf16r(sigmoidf_(bf16r(s)));
        sts64(sb + OFF_GB + 8 * slot, pack(g0, g0), pack(1.f - g0, 1.f - g0));
        __syncwarp();
        if (lane == 0) mbar_arrive(mb + 8 * MB_Q2);
      }
      TL(11);
      mbar_wait(mb + 8 * (MB_HA + u));
      put_exp(sb + OFF_MX + u * 64 + 32 + 4 * w, seq_mag(tab + T_HA + 16 * tid), lane);
      bar_sync(NB_WG0 + u, 128);
    }
    {
      TL(1 + isA);
      const uint32_t usrc = isA ? tab + T_UKV : sb + OFF_UX + u * 4096;
      const uint32_t mxa = sb + OFF_MX + u * 64 + 32 * isA;
      const uint32_t pd = lds16(sb + OFF_SP + 160 * u + 144 + 4 * isA);
      float D[32];
      uint32_t As[8], F[16], H[16], X[16];
      const uint32_t eh = min(max((int)get_exp(mxa), (int)((pd >> 7) & 0xff) - 5), 240);
      scale_a1(As, A1, 248 - eh);
      wg_fence();
      stage1(D, As, isA ? tab + T_HA : tab);
      wg_commit();
      wg_wait<0>(); tie_all(D);
      fwd_mid(F, D, tc, ts);
      wg_fence();
      stage2<0>(H, F, sb + OFF_CF);
      wg_commit();
      mbar_wait(mb + 8 * ((isA ? MB_UKV : MB_UX) + u));
      TL(5 + isA);
      put_exp(mxa + 16 + 4 * w, seq_mag(usrc + 16 * tid), lane);
      bar_sync(NB_WG0 + u, 128);
      const uint32_t eu = min(get_exp(mxa + 16), 240u);
      scale_a1(As, A1, 250 - eu);
      wg_wait<0>(); tie_all(H);
      wg_fence();
      stage1(D, As, usrc);
      wg_commit();
      wg_wait<0>(); tie_all(D);
      fwd_mid(F, D, tc, ts);
      wg_fence();
      stage2<0>(X, F, sb + OFF_CF);
      wg_commit();
      {
        const float dsk = blo(pd) * __uint_as_float((248 - eh) << 23);
        const uint32_t d2 = packh(dsk, dsk);
#pragma unroll
        for (int j = 0; j < 4; j++) H[2 * j] = U2(__hadd2(H2(H[2 * j]), H2(d2)));
      }
      wg_wait<0>(); tie_all(X);
#pragma unroll
      for (int j = 0; j < 4; j++) {
        const uint32_t h0r = H[2 * j], h1r = H[2 * j + 1], h0i = H[8 + 2 * j], h1i = H[9 + 2 * j];
        const uint32_t x0r = X[2 * j], x1r = X[2 * j + 1], x0i = X[8 + 2 * j], x1i = X[9 + 2 * j];
        F[2 * j] = ffma(x0r, h0r, fneg(fmul(x0i, h0i)));
        F[8 + 2 * j] = ffma(x0r, h0i, fmul(x0i, h0r));
        F[2 * j + 1] = ffma(x1r, h0r, ffma(fneg(x1i), h0i, ffma(x0r, h1r, fneg(ffma(x0i, h1i, F[8 + 2 * j])))));
        F[9 + 2 * j] = ffma(x1r, h0i, ffma(x1i, h0r, ffma(x0r, h1i, ffma(x0i, h1r, F[2 * j]))));
      }
      wg_fence();
      stage2<1>(H, F, sb + OFF_CF);
      wg_commit();
      wg_wait<0>(); tie_all(H);
      {
        const uint32_t va = tab + (16 * w + (lane & 15)) * 128;
        const int vx = (lane >> 4) ^ (lane & 7);
#pragma unroll
        for (int j = 0; j < 4; j++) {
          uint32_t V[4];
#pragma unroll
          for (int b = 0; b < 2; b++) {
            const uint32_t er = H[2 * j + b], ei = H[8 + 2 * j + b];
            V[2 * b] = ffma(er, tc[j], fneg(fmul(ei, ts[j])));
            V[2 * b + 1] = ffma(ei, tc[j], fmul(er, ts[j]));
          }
          stsm4(va + ((vx ^ (2 * j)) << 4), V);
        }
      }
      fence_async();
      bar_sync(NB_WG0 + u, 128);
      float O[16];
      {
        const uint64_t dv = desc_lo(tab) | (1ull << 16) | (64ull << 32) | (1ull << 62);
        const uint64_t dl = desc_lo(sb + OFF_CL) | (32ull << 16) | (8ull << 32);
        wg_fence();
        ss32<0, 0, 0>(O, dv, dl); ss32<1, 128, 64>(O, dv, dl); ss32<1, 256, 128>(O, dv, dl); ss32<1, 384, 192>(O, dv, dl);
        wg_commit();
      }
      wg_wait<0>(); tie_all(O);
      {
        const uint32_t co = ((8 * w + g) ^ (2 * t)) * 16;
        const int yo = (isA ? OFF_YA : OFF_YB) + (8 * u + rank) * YPITCH, ym = OFF_MB + 8 * (MB_Y + u);
        const uint32_t us = min(max((int)(eu + eh) - 127, 0), 254) * 0x00800080u;
        const uint32_t a0 = hmul2(pack(O[0], O[1]), us), a1 = hmul2(pack(O[4], O[5]), us), a2 = hmul2(pack(O[8], O[9]), us), a3 = hmul2(pack(O[12], O[13]), us);
        const uint32_t b0 = hmul2(pack(O[2], O[3]), us), b1 = hmul2(pack(O[6], O[7]), us), b2 = hmul2(pack(O[10], O[11]), us), b3 = hmul2(pack(O[14], O[15]), us);
        sts128((t == rank ? sb + yo : usrc + t * 512) + co, a0, a1, a2, a3);
        sts128((t + 4 == rank ? sb + yo : usrc + t * 512 + 2048) + co, b0, b1, b2, b3);
        fence_async();
        bar_sync(NB_WG0 + u, 128);
        send(usrc - sb, 512, yo, ym);
      }
      TL(9 + isA);
    }
  }

  {
    mbar_wait(mb + 8 * MB_Q2);
    uint2 gg[2][4];
    uint32_t qv[2][4];
#pragma unroll
    for (int hh = 0; hh < 2; hh++)
#pragma unroll
      for (int i = 0; i < 4; i++) gg[hh][i] = lds64(sb + OFF_GB + 8 * (64 * w + 32 * hh + 8 * i + g));
    const uint32_t qa = sb + OFF_Q2 + (64 * w + lane) * 80 + 16 * u;
    ldsm4(qv[0], qa);
    ldsm4(qv[1], qa + 2560);
    TL(24);
    mbar_wait(mb + 8 * (MB_Y + u));
    uint32_t ya[2][4], yb[2][4];
#pragma unroll
    for (int hh = 0; hh < 2; hh++) {
      const uint32_t yo = (8 * u + (lane & 7)) * YPITCH + ((8 * w + 4 * hh + (lane >> 3)) ^ (2 * (rank & 3))) * 16;
      ldsm4t(ya[hh], sb + OFF_YA + yo); ldsm4t(yb[hh], sb + OFF_YB + yo);
    }
#pragma unroll
    for (int hh = 0; hh < 2; hh++) {
      uint32_t o[4];
#pragma unroll
      for (int i = 0; i < 4; i++) o[i] = hadd2(hmul2(gg[hh][i].x, hmul2(qv[hh][i], ya[hh][i])), hmul2(gg[hh][i].y, yb[hh][i]));
      stsm4(qa + 2560 * hh, o);
    }
    TL(25);
  }
  cluster_arrive();
  bar_sync(NB_ROW0 + w, 160);
  {
    uint4 v[2];
#pragma unroll
    for (int k = 0; k < 2; k++) {
      const int i = 64 * u + 32 * k + lane, sl = (i * 205) >> 10, cc = i - 5 * sl;
      v[k] = lds128(sb + OFF_Q2 + (64 * w + 8 * (sl & 7) + (sl >> 3)) * 80 + cc * 16);
    }
#pragma unroll
    for (int k = 0; k < 2; k++) {
      const int i = 64 * u + 32 * k + lane, sl = (i * 205) >> 10, cc = i - 5 * sl;
      if (cc < nu)
        asm volatile("st.global.v4.u32 [%0], {%1,%2,%3,%4};" :: "l"(p.out + (size_t)(256 * rank + 32 * (sl >> 3) + 8 * w + (sl & 7)) * DCH + ch0 + 8 * cc),
                     "r"(v[k].x), "r"(v[k].y), "r"(v[k].z), "r"(v[k].w) : "memory");
    }
  }
  cluster_wait();
  TL(27);
  TL_DUMP();
}

typedef CUresult (*EncodeFn)(CUtensorMap*, CUtensorMapDataType, cuuint32_t, void*, const cuuint64_t*, const cuuint64_t*,
                             const cuuint32_t*, const cuuint32_t*, CUtensorMapInterleave, CUtensorMapSwizzle,
                             CUtensorMapL2promotion, CUtensorMapFloatOOBfill);

void encode(EncodeFn fn, CUtensorMap* tm, const void* ptr, int nd, const cuuint64_t* dims, const cuuint64_t* strides,
            const cuuint32_t* box, CUtensorMapSwizzle swz) {
  cuuint32_t es[4] = {1, 1, 1, 1};
  fn(tm, CU_TENSOR_MAP_DATA_TYPE_BFLOAT16, nd, const_cast<void*>(ptr), dims, strides, box, es, CU_TENSOR_MAP_INTERLEAVE_NONE,
     swz, CU_TENSOR_MAP_L2_PROMOTION_L2_128B, CU_TENSOR_MAP_FLOAT_OOB_FILL_NONE);
}
void map1(EncodeFn fn, CUtensorMap* tm, const void* ptr, int nhi) {
  const cuuint64_t dims[4] = {DCH, 4, 8, SEQ / 32}, strides[3] = {8 * DCH * 2, DCH * 2, 32 * DCH * 2};
  const cuuint32_t box[4] = {CPC, 4, 8, (cuuint32_t)nhi};
  encode(fn, tm, ptr, 4, dims, strides, box, CU_TENSOR_MAP_SWIZZLE_NONE);
}
void map2(EncodeFn fn, CUtensorMap* tm, const void* ptr, int nr) {
  const cuuint64_t dims[3] = {DCH, SEQ / 32, 32}, strides[2] = {32 * DCH * 2, DCH * 2};
  const cuuint32_t box[3] = {CPC, 8, (cuuint32_t)nr};
  encode(fn, tm, ptr, 3, dims, strides, box, CU_TENSOR_MAP_SWIZZLE_NONE);
}

}

extern "C" void kernel_launch(void* const* d_in, const int* in_sizes, int n_in, void* d_out, int out_size) {
  (void)in_sizes; (void)n_in; (void)out_size;
  static EncodeFn fn = nullptr;
  static void *tab = nullptr, *cnt = nullptr, *part = nullptr;
  if (!fn) {
    cudaGetSymbolAddress(&tab, d_tab);
    cudaGetSymbolAddress(&cnt, g_cnt);
    cudaGetSymbolAddress(&part, g_part);
    cudaDriverEntryPointQueryResult qr;
    cudaGetDriverEntryPoint("cuTensorMapEncodeTiled", (void**)&fn, cudaEnableDefault, &qr);
    cudaFuncSetAttribute(fused_kernel, cudaFuncAttributeMaxDynamicSharedMemorySize, SMEM_BYTES);
  }
  Params p;
  map1(fn, &p.tq, d_in[0], 8);
  map1(fn, &p.tk, d_in[1], 9);
  map1(fn, &p.tv, d_in[2], 8);
  map2(fn, &p.tq2, d_in[0], 32);
  p.out = (__nv_bfloat16*)d_out;
  {
    const cuuint64_t dims[4] = {32, SEQ / 32, DCH / 8, 8}, strides[3] = {64, 8 * SEQ * 2, SEQ * 2};
    const cuuint32_t box[4] = {32, 64, 1, 1};
    encode(fn, &p.th, d_in[4], 4, dims, strides, box, CU_TENSOR_MAP_SWIZZLE_64B);
  }
  p.tab = (const Tables*)tab;
  p.cnt = (unsigned*)cnt;
  p.part = (uint2*)part;
  p.tl = nullptr;
  p.q = (const __nv_bfloat16*)d_in[0];
  p.shift_k = (const __nv_bfloat16*)d_in[3];
  p.ssm_D = (const __nv_bfloat16*)d_in[5];
  p.logA = (const __nv_bfloat16*)d_in[7];
  p.Aim = (const __nv_bfloat16*)d_in[8];
  p.Cre = (const __nv_bfloat16*)d_in[9];
  p.Cim = (const __nv_bfloat16*)d_in[10];
  p.logdt = (const __nv_bfloat16*)d_in[11];
  p.Dskip = (const __nv_bfloat16*)d_in[12];
  p.gate_w = (const __nv_bfloat16*)d_in[13];
  fused_kernel<<<NCL * CS, NTHREADS, SMEM_BYTES, cudaStreamPerThread>>>(p);
}
```

```cpp
#include <cuda_runtime.h>
#include <cuda_bf16.h>
#include <cuda_fp16.h>
#include <cuda.h>
#include <stdint.h>

#define TIMELINE 0

namespace {

constexpr int SEQ = 2048, DCH = 576, NMODE = 128;
constexpr int CS = 8, CPC = 40, NCL = 15, NTHREADS = 640;

constexpr int YPITCH = 528;
constexpr int KTAB = 16384;
constexpr int OFF_T = 0;
constexpr int T_UKV = 8192, T_HA = 12288;
constexpr int OFF_UX = 5 * KTAB;
constexpr int OFF_IM = OFF_UX + 20480;
constexpr int OFF_Q2 = OFF_IM;
constexpr int OFF_GB = OFF_Q2 + 20480;
constexpr int OFF_TV = OFF_IM + 3 * KTAB - 20480;
constexpr int OFF_CF = OFF_IM + 3 * KTAB;
constexpr int OFF_CL = OFF_CF + 8192;
constexpr int OFF_TQ = OFF_CL + 4096;
constexpr int OFF_YA = OFF_TQ;
constexpr int OFF_TK = OFF_TQ + 21120;
constexpr int OFF_YB = OFF_TK + 23040;
constexpr int OFF_MX = OFF_YB + 40 * YPITCH;
constexpr int OFF_SP = OFF_MX + 320;
constexpr int OFF_MB = OFF_SP + 5 * 160;
constexpr int OFF_TL = OFF_MB + 32 * 8;
constexpr int SMEM_BYTES = OFF_TL + (TIMELINE ? 1280 : 0);
static_assert(SMEM_BYTES <= 232448, "smem");
static_assert((OFF_TQ & 127) == 0 && (OFF_TK & 127) == 0 && (OFF_TV & 127) == 0 && (OFF_MB & 7) == 0 && (OFF_MX & 15) == 0, "align");

enum { MB_UX = 0, MB_UKV = 5, MB_Y = 10, MB_HA = 15, MB_XQ = 20, MB_KV = 21, MB_CF = 22, MB_Q2 = 23, MB_XD = 24, MB_TAG = 25 };
enum { NB_WG0 = 1, NB_ROW0 = 6, NB_K4 = 10 };

constexpr double cos_turn(int m, int n) {
  m &= n - 1;
  if (m > n / 2) m = n - m;
  double sgn = 1.0;
  if (m > n / 4) { m = n / 2 - m; sgn = -1.0; }
  if (m == n / 4) return 0.0;
  const double x = 6.283185307179586476925 * m / n;
  double term = 1.0, sum = 1.0;
  for (int k = 1; k < 14; k++) { term *= -x * x / ((2 * k - 1) * (2 * k)); sum += term; }
  return sgn * sum;
}
constexpr uint32_t bf16_bits(double v) {
  if (v == 0.0) return 0;
  uint32_t sgn = 0;
  if (v < 0) { sgn = 0x8000; v = -v; }
  int e = 127;
  while (v < 1.0) { v *= 2.0; e--; }
  while (v >= 2.0) { v *= 0.5; e++; }
  const double f = v * 128.0;
  int m = (int)f;
  if (f - m > 0.5 || (f - m == 0.5 && (m & 1))) m++;
  return sgn | (uint32_t)((e << 7) + (m - 128));
}
constexpr uint32_t f16_bits(double v) {
  if (v == 0.0) return 0;
  uint32_t sgn = 0;
  if (v < 0) { sgn = 0x8000; v = -v; }
  int e = 15;
  while (v < 1.0) { v *= 2.0; e--; }
  const double f = v * 1024.0;
  int m = (int)f;
  if (f - m > 0.5 || (f - m == 0.5 && (m & 1))) m++;
  return sgn | (uint32_t)((e << 10) + (m - 1024));
}
constexpr uint32_t pair_bits(double lo, double hi) { return bf16_bits(lo) | (bf16_bits(hi) << 16); }
constexpr uint32_t pair_h(double lo, double hi) { return f16_bits(lo) | (f16_bits(hi) << 16); }
struct alignas(128) Tables {
  uint32_t mat[3072];
  uint32_t thr[4][128][4];
};
constexpr Tables make_tables() {
  Tables T{};
  for (int q = 0; q < 768; q++) {
    int m0 = 0, d0 = 0, d1 = 0;
    if (q < 512) {
      const int r = (q >> 6) * 8 + (q & 7), cc = (q >> 3) & 7;
      d0 = 4 * (r & 31); d1 = 2 * d0;
      m0 = 8 * (cc & 3) * d0 + ((r >> 5) == (cc >> 2) ? 0 : (r >> 5) ? 96 : 32);
    } else {
      const int r = ((q - 512) >> 5) * 8 + (q & 7), pc = (q >> 3) & 3;
      d0 = 4 * (8 * (r >> 4) + (r & 7)) + 1; d1 = 8 * d0;
      m0 = 2 * pc * d0 + ((r & 8) ? 32 : 0);
    }
    for (int e = 0; e < 4; e++) T.mat[4 * q + e] = pair_h(cos_turn(m0 + e * d1, 128), cos_turn(m0 + e * d1 + d0, 128));
  }
  for (int tid = 0; tid < 128; tid++) {
    const int kk = 4 * (tid >> 2) + 1, t = tid & 3;
    for (int q = 0; q < 4; q++) {
      const int m = (8 * q + 2 * t) * kk;
      T.thr[q >> 1][tid][2 * (q & 1)] = pair_bits(cos_turn(m, 128), cos_turn(m + kk, 128));
      T.thr[q >> 1][tid][2 * (q & 1) + 1] = pair_bits(cos_turn(m + 32, 128), cos_turn(m + kk + 32, 128));
      T.thr[2][tid][q] = pair_h(cos_turn(m, 4096), cos_turn(m + kk, 4096));
      T.thr[3][tid][q] = pair_h(cos_turn(m + 3072, 4096), cos_turn(m + kk + 3072, 4096));
    }
  }
  return T;
}
__device__ const Tables d_tab = make_tables();

struct Params {
  const __nv_bfloat16 *logA, *Aim, *Cre, *Cim, *logdt;
  const Tables* tab;
  unsigned* cnt;
  const __nv_bfloat16 *Dskip, *shift_k, *ssm_D, *gate_w, *q;
  uint2* part;
  __nv_bfloat16* out;
  unsigned* tl;
  CUtensorMap tq, tk, tv, th, tq2;
};

__device__ uint2 g_part[NCL * SEQ];
__device__ unsigned g_cnt[CS * 32];
#define TL(i) do {} while (0)
#define TL_INIT() do {} while (0)
#define TL_DUMP() do {} while (0)

__device__ __forceinline__ uint32_t lds16(uint32_t a) { uint32_t v; asm volatile("ld.shared.u16 %0, [%1];" : "=r"(v) : "r"(a) : "memory"); return v; }
__device__ __forceinline__ uint2 lds64(uint32_t a) { uint2 v; asm volatile("ld.shared.v2.u32 {%0,%1}, [%2];" : "=r"(v.x), "=r"(v.y) : "r"(a) : "memory"); return v; }
__device__ __forceinline__ uint4 lds128(uint32_t a) { uint4 v; asm volatile("ld.shared.v4.u32 {%0,%1,%2,%3}, [%4];" : "=r"(v.x), "=r"(v.y), "=r"(v.z), "=r"(v.w) : "r"(a) : "memory"); return v; }
__device__ __forceinline__ void sts16(uint32_t a, uint32_t v) { asm volatile("st.shared.u16 [%0], %1;" :: "r"(a), "r"(v) : "memory"); }
__device__ __forceinline__ void sts32(uint32_t a, uint32_t v) { asm volatile("st.shared.u32 [%0], %1;" :: "r"(a), "r"(v) : "memory"); }
__device__ __forceinline__ void sts64(uint32_t a, uint32_t x, uint32_t y) { asm volatile("st.shared.v2.u32 [%0], {%1,%2};" :: "r"(a), "r"(x), "r"(y) : "memory"); }
__device__ __forceinline__ void sts128(uint32_t a, uint32_t x, uint32_t y, uint32_t z, uint32_t w) { asm volatile("st.shared.v4.u32 [%0], {%1,%2,%3,%4};" :: "r"(a), "r"(x), "r"(y), "r"(z), "r"(w) : "memory"); }
__device__ __forceinline__ void ldsm4t(uint32_t (&r)[4], uint32_t a) { asm volatile("ldmatrix.sync.aligned.m8n8.x4.trans.shared.b16 {%0,%1,%2,%3}, [%4];" : "=r"(r[0]), "=r"(r[1]), "=r"(r[2]), "=r"(r[3]) : "r"(a) : "memory"); }
__device__ __forceinline__ void ldsm2t(uint32_t& r0, uint32_t& r1, uint32_t a) { asm volatile("ldmatrix.sync.aligned.m8n8.x2.trans.shared.b16 {%0,%1}, [%2];" : "=r"(r0), "=r"(r1) : "r"(a) : "memory"); }
__device__ __forceinline__ void ldsm4(uint32_t (&r)[4], uint32_t a) { asm volatile("ldmatrix.sync.aligned.m8n8.x4.shared.b16 {%0,%1,%2,%3}, [%4];" : "=r"(r[0]), "=r"(r[1]), "=r"(r[2]), "=r"(r[3]) : "r"(a) : "memory"); }
__device__ __forceinline__ void stsm4(uint32_t a, const uint32_t (&r)[4]) { asm volatile("stmatrix.sync.aligned.m8n8.x4.shared.b16 [%0], {%1,%2,%3,%4};" :: "r"(a), "r"(r[0]), "r"(r[1]), "r"(r[2]), "r"(r[3]) : "memory"); }
__device__ __forceinline__ uint32_t pack(float lo, float hi) { uint32_t r; asm("cvt.rn.bf16x2.f32 %0, %1, %2;" : "=r"(r) : "f"(hi), "f"(lo)); return r; }
__device__ __forceinline__ float blo(uint32_t v) { return __uint_as_float(v << 16); }
__device__ __forceinline__ float bhi(uint32_t v) { return __uint_as_float(v & 0xffff0000u); }
__device__ __forceinline__ float bf16r(float x) { return blo(pack(x, 0.f)); }
__device__ __forceinline__ uint32_t hmul2(uint32_t a, uint32_t b) { uint32_t r; asm("mul.rn.bf16x2 %0, %1, %2;" : "=r"(r) : "r"(a), "r"(b)); return r; }
__device__ __forceinline__ uint32_t hadd2(uint32_t a, uint32_t b) { uint32_t r; asm("add.rn.bf16x2 %0, %1, %2;" : "=r"(r) : "r"(a), "r"(b)); return r; }
__device__ __forceinline__ uint32_t hfma2(uint32_t a, uint32_t b, uint32_t c) { uint32_t r; asm("fma.rn.bf16x2 %0, %1, %2, %3;" : "=r"(r) : "r"(a), "r"(b), "r"(c)); return r; }
__device__ __forceinline__ uint32_t packh(float lo, float hi) { uint32_t r; asm("cvt.rn.f16x2.f32 %0, %1, %2;" : "=r"(r) : "f"(hi), "f"(lo)); return r; }
__device__ __forceinline__ __half2 H2(uint32_t a) { return *reinterpret_cast<__half2*>(&a); }
__device__ __forceinline__ uint32_t U2(__half2 a) { return *reinterpret_cast<uint32_t*>(&a); }
__device__ __forceinline__ uint32_t fmul(uint32_t a, uint32_t b) { return U2(__hmul2(H2(a), H2(b))); }
__device__ __forceinline__ uint32_t ffma(uint32_t a, uint32_t b, uint32_t c) { return U2(__hfma2(H2(a), H2(b), H2(c))); }
__device__ __forceinline__ uint32_t fneg(uint32_t a) { return U2(__hneg2(H2(a))); }
__device__ __forceinline__ uint32_t amax2(uint32_t a, uint32_t b) { uint32_t r; asm("max.xorsign.abs.bf16x2 %0, %1, %2;" : "=r"(r) : "r"(a), "r"(b)); return r; }
__device__ __forceinline__ uint32_t prmt(uint32_t a, uint32_t b, uint32_t s) { return __byte_perm(a, b, s); }
__device__ __forceinline__ uint32_t ldraw(const __nv_bfloat16* p) { uint32_t v; asm volatile("ld.global.nc.u16 %0, [%1];" : "=r"(v) : "l"(p)); return v; }
__device__ __forceinline__ uint4 ldg128(const void* p) { uint4 v; asm volatile("ld.global.nc.v4.u32 {%0,%1,%2,%3}, [%4];" : "=r"(v.x), "=r"(v.y), "=r"(v.z), "=r"(v.w) : "l"(p)); return v; }
__device__ __forceinline__ void bar_sync(int id, int n) { asm volatile("bar.sync %0, %1;" :: "r"(id), "r"(n) : "memory"); }
__device__ __forceinline__ void bar_arrive(int id, int n) { asm volatile("bar.arrive %0, %1;" :: "r"(id), "r"(n) : "memory"); }
__device__ __forceinline__ void cluster_arrive() { asm volatile("barrier.cluster.arrive.relaxed.aligned;" ::: "memory"); }
__device__ __forceinline__ void cluster_wait() { asm volatile("barrier.cluster.wait.aligned;" ::: "memory"); }
__device__ __forceinline__ void fence_async() { asm volatile("fence.proxy.async.shared::cta;" ::: "memory"); }
__device__ __forceinline__ void fence_mbinit() { asm volatile("fence.mbarrier_init.release.cluster;" ::: "memory"); }
__device__ __forceinline__ uint32_t mapa(uint32_t a, uint32_t rank) { uint32_t r; asm("mapa.shared::cluster.u32 %0, %1, %2;" : "=r"(r) : "r"(a), "r"(rank)); return r; }
__device__ __forceinline__ void bulk_dsmem(uint32_t dst, uint32_t src, uint32_t mbar) {
  asm volatile("cp.async.bulk.shared::cluster.shared::cta.mbarrier::complete_tx::bytes [%0], [%1], 512, [%2];" :: "r"(dst), "r"(src), "r"(mbar) : "memory");
}
__device__ __forceinline__ void mbar_init(uint32_t m, uint32_t cnt) { asm volatile("mbarrier.init.shared::cta.b64 [%0], %1;" :: "r"(m), "r"(cnt) : "memory"); }
__device__ __forceinline__ void mbar_expect(uint32_t m, uint32_t bytes) { asm volatile("mbarrier.arrive.expect_tx.shared::cta.b64 _, [%0], %1;" :: "r"(m), "r"(bytes) : "memory"); }
__device__ __forceinline__ bool mbar_try(uint32_t m) {
  uint32_t done;
  asm volatile("{.reg .pred p; mbarrier.try_wait.parity.shared::cta.b64 p, [%1], 0; selp.u32 %0, 1, 0, p;}" : "=r"(done) : "r"(m) : "memory");
  return done;
}
__device__ __forceinline__ void mbar_wait(uint32_t m) {
  if (!mbar_try(m)) {
    int it = 0;
    while (!mbar_try(m) && ++it < (1 << 22)) {}
  }
}
__device__ __forceinline__ bool elect() {
  uint32_t e;
  asm volatile("{.reg .pred p; elect.sync _|p, 0xffffffff; selp.u32 %0, 1, 0, p;}" : "=r"(e));
  return e;
}
__device__ __forceinline__ void tma_load4(uint32_t dst, const CUtensorMap* tm, int c0, int c1, int c2, int c3, uint32_t mbar) {
  asm volatile("cp.async.bulk.tensor.4d.shared::cluster.global.mbarrier::complete_tx::bytes [%0], [%1, {%3, %4, %5, %6}], [%2];"
               :: "r"(dst), "l"(tm), "r"(mbar), "r"(c0), "r"(c1), "r"(c2), "r"(c3) : "memory");
}
__device__ __forceinline__ void tma_load3(uint32_t dst, const CUtensorMap* tm, int c0, int c1, int c2, uint32_t mbar) {
  asm volatile("cp.async.bulk.tensor.3d.shared::cluster.global.mbarrier::complete_tx::bytes [%0], [%1, {%3, %4, %5}], [%2];"
               :: "r"(dst), "l"(tm), "r"(mbar), "r"(c0), "r"(c1), "r"(c2) : "memory");
}
__device__ __forceinline__ void tma_store3(const CUtensorMap* tm, int c0, int c1, int c2, uint32_t src) {
  asm volatile("cp.async.bulk.tensor.3d.global.shared::cta.bulk_group [%0, {%2, %3, %4}], [%1];"
               :: "l"(tm), "r"(src), "r"(c0), "r"(c1), "r"(c2) : "memory");
}
__device__ __forceinline__ void wg_fence() { asm volatile("wgmma.fence.sync.aligned;" ::: "memory"); }
__device__ __forceinline__ void wg_commit() { asm volatile("wgmma.commit_group.sync.aligned;" ::: "memory"); }
template <int N> __device__ __forceinline__ void wg_wait() { asm volatile("wgmma.wait_group.sync.aligned %0;" :: "n"(N) : "memory"); }
template <int N> __device__ __forceinline__ void tie_all(uint32_t (&x)[N]) {
#pragma unroll
  for (int i = 0; i < N; i++) asm volatile("" : "+r"(x[i]) :: "memory");
}
template <int N> __device__ __forceinline__ void tie_all(float (&x)[N]) {
#pragma unroll
  for (int i = 0; i < N; i++) asm volatile("" : "+f"(x[i]) :: "memory");
}
#define R16(C, d) C(d[0]), C(d[1]), C(d[2]), C(d[3]), C(d[4]), C(d[5]), C(d[6]), C(d[7]), C(d[8]), C(d[9]), C(d[10]), C(d[11]), C(d[12]), C(d[13]), C(d[14]), C(d[15])
#define R32(C, d) R16(C, d), R16(C, (d + 16))
#define P16 "{%0,%1,%2,%3,%4,%5,%6,%7,%8,%9,%10,%11,%12,%13,%14,%15}"
#define P32 "{%0,%1,%2,%3,%4,%5,%6,%7,%8,%9,%10,%11,%12,%13,%14,%15,%16,%17,%18,%19,%20,%21,%22,%23,%24,%25,%26,%27,%28,%29,%30,%31}"
template <int SD, int TB, int OFF> __device__ __forceinline__ void rs64(float* d, const uint32_t* a, uint64_t db) {
  if (SD) asm volatile("{.reg .b64 db; add.s64 db, %36, %37; wgmma.mma_async.sync.aligned.m64n64k16.f32.bf16.bf16 " P32 ", {%32,%33,%34,%35}, db, 1, 1, 1, %38;}"
                       : R32("+f", d) : "r"(a[0]), "r"(a[1]), "r"(a[2]), "r"(a[3]), "l"(db), "n"(OFF), "n"(TB));
  else asm volatile("{.reg .b64 db; add.s64 db, %36, %37; wgmma.mma_async.sync.aligned.m64n64k16.f32.bf16.bf16 " P32 ", {%32,%33,%34,%35}, db, 0, 1, 1, %38;}"
                    : R32("=f", d) : "r"(a[0]), "r"(a[1]), "r"(a[2]), "r"(a[3]), "l"(db), "n"(OFF), "n"(TB));
}
template <int SD, int TB, int OFF> __device__ __forceinline__ void rs64h(uint32_t* d, const uint32_t* a, uint64_t db) {
  if (SD) asm volatile("{.reg .b64 db; add.s64 db, %20, %21; wgmma.mma_async.sync.aligned.m64n64k16.f16.f16.f16 " P16 ", {%16,%17,%18,%19}, db, 1, 1, 1, %22;}"
                       : R16("+r", d) : "r"(a[0]), "r"(a[1]), "r"(a[2]), "r"(a[3]), "l"(db), "n"(OFF), "n"(TB));
  else asm volatile("{.reg .b64 db; add.s64 db, %20, %21; wgmma.mma_async.sync.aligned.m64n64k16.f16.f16.f16 " P16 ", {%16,%17,%18,%19}, db, 0, 1, 1, %22;}"
                    : R16("=r", d) : "r"(a[0]), "r"(a[1]), "r"(a[2]), "r"(a[3]), "l"(db), "n"(OFF), "n"(TB));
}
template <int SD, int OFFA, int OFFB> __device__ __forceinline__ void ss32(float* d, uint64_t da, uint64_t db) {
  if (SD) asm volatile("{.reg .b64 da, db; add.s64 da, %16, %18; add.s64 db, %17, %19; wgmma.mma_async.sync.aligned.m64n32k16.f32.f16.f16 " P16 ", da, db, 1, 1, 1, 1, 1;}"
                       : R16("+f", d) : "l"(da), "l"(db), "n"(OFFA), "n"(OFFB));
  else asm volatile("{.reg .b64 da, db; add.s64 da, %16, %18; add.s64 db, %17, %19; wgmma.mma_async.sync.aligned.m64n32k16.f32.f16.f16 " P16 ", da, db, 0, 1, 1, 1, 1;}"
                    : R16("=f", d) : "l"(da), "l"(db), "n"(OFFA), "n"(OFFB));
}
#define KGEN_ASM(SD) "{.reg .b64 da, db; add.s64 da, %32, %33; add.s64 db, %32, %34;\n" \
  "wgmma.mma_async.sync.aligned.m64n64k16.f32.bf16.bf16 " P32 ", da, db, " SD ", 1, 1, 1, 1;}"
template <int KS> __device__ __forceinline__ void kgen_mma(float (&c)[32], uint64_t da) {
  if (KS) asm volatile(KGEN_ASM("1") : R32("+f", c) : "l"(da), "n"(8 * KS), "n"(8 * KS + 512));
  else asm volatile(KGEN_ASM("0") : R32("=f", c) : "l"(da), "n"(8 * KS), "n"(8 * KS + 512));
  if constexpr (KS < 7) kgen_mma<KS + 1>(c, da);
}
__device__ __forceinline__ uint64_t desc_lo(uint32_t a) { return (uint64_t)((a & 0x3FFFF) >> 4); }
__device__ __forceinline__ void stage1(float (&D)[32], const uint32_t (&A1)[8], uint32_t src) {
  const uint64_t du = desc_lo(src) | (128ull << 16) | (32ull << 32) | (2ull << 62);
  rs64<0, 1, 0>(D, A1, du); rs64<1, 1, 64>(D, A1 + 4, du);
}
template <int INV> __device__ __forceinline__ void stage2(uint32_t (&X)[16], const uint32_t (&F)[16], uint32_t cf) {
  constexpr int KS = INV ? 16 : 128, TB = INV ? 0 : 1;
  const uint64_t dc = desc_lo(cf) | (INV ? (8ull << 16) | (64ull << 32) : (64ull << 16) | (8ull << 32));
  rs64h<0, TB, 0>(X, F, dc); rs64h<1, TB, KS>(X, F + 4, dc); rs64h<1, TB, 2 * KS>(X, F + 8, dc); rs64h<1, TB, 3 * KS>(X, F + 12, dc);
}
__device__ __forceinline__ void fwd_mid(uint32_t (&F)[16], const float (&D)[32], const uint32_t (&tc)[4], const uint32_t (&ts)[4]) {
#pragma unroll
  for (int j = 0; j < 4; j++)
#pragma unroll
    for (int b = 0; b < 2; b++) {
      const int i = 4 * j + 16 * b;
      const uint32_t ar = packh(D[i], D[i + 1]), ai = packh(D[i + 2], D[i + 3]);
      F[2 * j + b] = ffma(ar, tc[j], fmul(ai, ts[j]));
      F[8 + 2 * j + b] = ffma(ai, tc[j], fneg(fmul(ar, ts[j])));
    }
}
__device__ __forceinline__ void put_exp(uint32_t a, uint32_t m, int lane) {
  m = __reduce_max_sync(0xffffffffu, max(m & 0x7f80u, (m >> 16) & 0x7f80u));
  if (lane == 0) sts32(a, m);
}
__device__ __forceinline__ uint32_t seq_mag(uint32_t a) {
  const uint4 x = lds128(a), y = lds128(a + 2048);
  return amax2(amax2(amax2(x.x, x.y), amax2(x.z, x.w)), amax2(amax2(y.x, y.y), amax2(y.z, y.w)));
}
__device__ __forceinline__ uint32_t get_exp(uint32_t a) { const uint4 v = lds128(a); return max(max(v.x, v.y), max(v.z, v.w)) >> 7; }
__device__ __forceinline__ void scale_a1(uint32_t (&As)[8], const uint32_t (&A1)[8], uint32_t field) {
#pragma unroll
  for (int i = 0; i < 8; i++) As[i] = hmul2(A1[i], field * 0x00800080u);
}

struct cf { float x, y; };
__device__ __forceinline__ cf cmul(cf a, cf b) { cf r; r.x = fmaf(a.x, b.x, -a.y * b.y); r.y = fmaf(a.x, b.y, a.y * b.x); return r; }
__device__ __forceinline__ cf cexp_p(float lr2, float lt, float p) {
  float m;
  asm("ex2.approx.ftz.f32 %0, %1;" : "=f"(m) : "f"(lr2 * p));
  float t = lt * p;
  t = (t - rintf(t)) * 6.283185307179586f;
  cf r; r.x = m * __cosf(t); r.y = m * __sinf(t); return r;
}
__device__ __forceinline__ void store8(uint32_t a, uint32_t b, const cf (&v)[8]) {
  sts128(a, pack(v[0].x, v[1].x), pack(v[2].x, v[3].x), pack(v[4].x, v[5].x), pack(v[6].x, v[7].x));
  sts128(b, pack(v[0].y, v[1].y), pack(v[2].y, v[3].y), pack(v[4].y, v[5].y), pack(v[6].y, v[7].y));
}
__device__ __forceinline__ void mbar_arrive(uint32_t m) { asm volatile("mbarrier.arrive.shared::cta.b64 _, [%0];" :: "r"(m) : "memory"); }
__device__ __forceinline__ float sigmoidf_(float s) { return 1.f / (1.f + __expf(-s)); }

__global__ void __cluster_dims__(CS, 1, 1) __launch_bounds__(NTHREADS, 1) fused_kernel(const __grid_constant__ Params p) {
  extern __shared__ __align__(1024) uint8_t smem[];
  TL_INIT();
  TL(31);
  const int wid = __shfl_sync(0xffffffffu, threadIdx.x >> 5, 0);
  const uint32_t sb = (uint32_t)__cvta_generic_to_shared(smem);
  const uint32_t mb = sb + OFF_MB;
  const int u = wid >> 2, w = wid & 3;
  const int tid = threadIdx.x & 127, lane = tid & 31, g = lane >> 2, t = lane & 3;
  const int cl = blockIdx.x >> 3, rank = blockIdx.x & 7;
  const int ch0 = cl * CPC;
  const int nu = min(5, (DCH - ch0) >> 3);
  const bool act = u < nu;

  if (u == 4 && elect()) {
#pragma unroll
    for (int i = 0; i < 5; i++) mbar_init(mb + 40 * w + 8 * i, w == 3 ? 1 : w == 2 ? 3 : 2);
    if (w == 3) {
      mbar_init(mb + 8 * MB_XQ, 1); mbar_init(mb + 8 * MB_KV, 2); mbar_init(mb + 8 * MB_CF, 1); mbar_init(mb + 8 * MB_Q2, 9); mbar_init(mb + 8 * MB_XD, 4);
    }
    fence_mbinit();
    if (w == 3) {
      mbar_expect(mb + 8 * MB_CF, 12288);
      asm volatile("cp.async.bulk.shared::cluster.global.mbarrier::complete_tx::bytes [%0], [%1], %2, [%3];"
                   :: "r"(sb + OFF_CF), "l"(p.tab->mat), "r"(12288), "r"(mb + 8 * MB_CF) : "memory");
      asm volatile("cp.async.bulk.prefetch.L2.global [%0], 8192;" :: "l"(p.tab->thr) : "memory");
      mbar_expect(mb + 8 * MB_XQ, 20480); mbar_expect(mb + 8 * MB_KV, 23040); mbar_expect(mb + 8 * MB_Q2, 20480);
    }
#pragma unroll
    for (int i = 0; i < 5; i++) mbar_expect(mb + 40 * w + 8 * i, w == 3 ? 4096 : w == 2 ? 7168 : 3584);
  }
  uint32_t pla, pai, pcr, pci, pdt, tag = 0;
  uint4 psm;
  {
    const int ch = act ? ch0 + 8 * u + rank : 0, o = ch * NMODE + tid;
    pla = ldraw(p.logA + o); pdt = ldraw(p.logdt + ch); pai = ldraw(p.Aim + o); pcr = ldraw(p.Cre + o); pci = ldraw(p.Cim + o);
    if (w == 1) {
      if (lane < 9) psm = ldg128(lane < 5 ? p.gate_w + (lane < nu ? ch0 + 8 * lane : 0) : p.shift_k + (act ? ch0 + 8 * u : 0) * 4 + 8 * (lane - 5));
      else { psm.x = ldraw(p.Dskip + ch); psm.y = ldraw(p.ssm_D + ch); }
    }
    if (wid == 16 && lane < 2) asm volatile("atom.relaxed.gpu.global.add.u32 %0, [%1], %2;" : "=r"(tag) : "l"(&p.cnt[rank * 32 + lane]), "r"(cl == 0 ? 16 - (NCL - 1) : 1) : "memory");
  }
  if (wid == 19 && elect()) {
    tma_load4(sb + OFF_TQ, &p.tq, ch0, 0, 0, 8 * rank, mb + 8 * MB_XQ);
    tma_load4(sb + OFF_TK, &p.tk, ch0, 0, 0, 8 * rank - 1, mb + 8 * MB_KV);
    TL(20);
  }
  __syncwarp();
  cluster_arrive();
  TL(0);

  const uint32_t tab = sb + OFF_T + u * KTAB;
  const int mi = lane >> 3, tq = (lane & 7) >> 1, jj = lane & 1;
  const uint32_t toff = (4 * (2 * mi + jj) + tq) * 80;
  const uint32_t uoff = 16 * (4 * w + (t ^ (w >> 1)));
  auto put = [&](int stage, int dst, uint32_t off, const uint32_t (&v)[4]) {
    sts128(sb + off + (g == rank ? dst + 512 * rank : stage + g * YPITCH), v[0], v[1], v[2], v[3]);
  };
  const int d0 = rank ^ (2 * w), d1 = d0 ^ 1;
  const uint32_t rb0 = mapa(sb, d0), rb1 = mapa(sb, d1);
  auto send = [&](int stage, int pitch, int dst, int mbar) {
    if (elect()) {
      if (w) bulk_dsmem(rb0 + dst, sb + stage + d0 * pitch, rb0 + mbar); else mbar_arrive(sb + mbar);
      bulk_dsmem(rb1 + dst, sb + stage + d1 * pitch, rb1 + mbar);
    }
    __syncwarp();
  };

  if (w == 1 && lane < 10) sts128(sb + OFF_SP + 160 * u + 16 * lane, psm.x, psm.y, psm.z, psm.w);
  if (u == 4) {
    cluster_wait();
    mbar_wait(mb + 8 * MB_XQ);
    TL(18);
    {
      uint32_t x0[5][4], x1[5][4];
#pragma unroll
      for (int k = 0; k < 5; k++) { ldsm4t(x0[k], sb + OFF_TQ + w * 2560 + toff + 16 * k); ldsm4t(x1[k], sb + OFF_TQ + (w + 4) * 2560 + toff + 16 * k); }
#pragma unroll
      for (int k = 0; k < 5; k++) {
        put(OFF_YB + 8 * k * YPITCH, OFF_UX + k * 4096, uoff, x0[k]);
        put(OFF_YB + 8 * k * YPITCH, OFF_UX + k * 4096, (uoff ^ 32) + 256, x1[k]);
      }
    }
    if (tid == 0) sts32(mb + 8 * MB_TAG, tag);
    TL(3);
    fence_async();
    bar_sync(NB_WG0 + u, 128);
    TL(4);
    float s0 = 0.f, s1 = 0.f;
#pragma unroll 1
    for (int j = 0; j < 5; j++) {
      const uint4 gw = lds128(sb + OFF_SP + 160 * u + 16 * j);
      const uint4 x0 = lds128(sb + OFF_TQ + tid * 80 + 16 * j), x1 = lds128(sb + OFF_TQ + (tid + 128) * 80 + 16 * j);
      send(OFF_YB + 8 * j * YPITCH, YPITCH, OFF_UX + j * 4096 + 512 * rank, OFF_MB + 8 * (MB_UX + j));
      uint32_t m0 = hmul2(x0.x, gw.x), m1 = hmul2(x0.y, gw.y), m2 = hmul2(x0.z, gw.z), m3 = hmul2(x0.w, gw.w);
      s0 += ((blo(m0) + bhi(m0)) + (blo(m1) + bhi(m1))) + ((blo(m2) + bhi(m2)) + (blo(m3) + bhi(m3)));
      m0 = hmul2(x1.x, gw.x); m1 = hmul2(x1.y, gw.y); m2 = hmul2(x1.z, gw.z); m3 = hmul2(x1.w, gw.w);
      s1 += ((blo(m0) + bhi(m0)) + (blo(m1) + bhi(m1))) + ((blo(m2) + bhi(m2)) + (blo(m3) + bhi(m3)));
    }
    tag = (lds64(mb + 8 * MB_TAG).x >> 4) + 1;
    uint2* gp = p.part + cl * SEQ + rank * 256 + 8 * (8 * t + g) + w;
    asm volatile("st.relaxed.gpu.global.u64 [%0], %1;" :: "l"(gp), "l"(((uint64_t)tag << 32) | __float_as_uint(s0)) : "memory");
    asm volatile("st.relaxed.gpu.global.u64 [%0], %1;" :: "l"(gp + 4), "l"(((uint64_t)tag << 32) | __float_as_uint(s1)) : "memory");
    __syncwarp();
    if (lane == 0) mbar_arrive(mb + 8 * MB_XD);
    TL(7);
    bar_sync(NB_K4, 640);
    if (w == 3 && elect()) {
      mbar_expect(mb + 8 * MB_KV, 20480);
      tma_load4(sb + OFF_TV, &p.tv, ch0, 0, 0, 8 * rank, mb + 8 * MB_KV);
    }
    __syncwarp();
    TL(8);
  }

  uint32_t A1[8], tc[4], ts[4];
  {
    const float dt = bf16r(expf(blo(pdt)));
    const float lr2 = (-bf16r(expf(blo(pla))) * dt) * 1.4426950408889634f;
    const float lt = (blo(pai) * dt) * 0.15915494309189535f;
    const uint32_t tim = u == 0 ? sb + OFF_T + 4 * KTAB : sb + OFF_IM + (u == 4 ? 0 : u - 1) * KTAB;
    const uint32_t row = tab + tid * 16, rim = tim + tid * 16;
    if (lr2 != 123.f) TL(16);
    {
      const cf w1 = cexp_p(lr2, lt, 8.f);
      cf v[8];
      v[0].x = 1.f; v[0].y = 0.f; v[1] = w1; v[2] = cmul(w1, w1); v[3] = cmul(v[2], w1);
      const cf w4 = cmul(v[2], v[2]);
      v[4] = w4; v[5] = cmul(v[1], w4); v[6] = cmul(v[2], w4); v[7] = cmul(v[3], w4);
      const cf w8 = cmul(w4, w4);
      store8(row, rim, v);
#pragma unroll
      for (int k = 1; k < 4; k++) {
#pragma unroll
        for (int i = 0; i < 8; i++) v[i] = (k == 1 && i == 0) ? w8 : cmul(v[i], w8);
        store8(row + 2048 * k, rim + 2048 * k, v);
      }
    }
    {
      cf z1 = cexp_p(lr2, lt, 1.f), Z = cexp_p(lr2, lt, 256.f);
      z1.y = -z1.y; Z.y = -Z.y;
      const cf z2 = cmul(z1, z1);
      cf h[8], v[8];
      h[0].x = 2.f * blo(pcr) * dt; h[0].y = -2.f * blo(pci) * dt;
      h[1] = cmul(h[0], z1);
#pragma unroll
      for (int i = 2; i < 8; i++) h[i] = cmul(h[i - 2], z2);
      store8(row + 4 * 2048, rim + 4 * 2048, h);
      const cf h8 = cmul(h[6], z2);
      v[0] = cmul(h[0], Z); v[2] = cmul(h[2], Z); v[3] = cmul(h[4], Z); v[6] = cmul(h[6], Z); v[7] = cmul(h8, Z);
      v[1] = v[0]; v[4] = v[5] = v[3];
      store8(row + 5 * 2048, rim + 5 * 2048, v);
      h[0] = cmul(v[0], Z); h[1] = cmul(v[3], Z); h[3] = cmul(v[7], Z); h[4] = cmul(h[0], Z); h[5] = cmul(h[1], Z); h[7] = cmul(h[3], Z);
      h[2] = h[1]; h[6] = h[5];
      store8(row + 6 * 2048, rim + 6 * 2048, h);
      const cf Z2 = cmul(Z, Z);
      v[0] = cmul(h[0], Z2); v[1] = cmul(h[3], Z2); v[2] = cmul(h[4], Z2); v[3] = cmul(h[7], Z2);
#pragma unroll
      for (int i = 4; i < 8; i++) v[i] = cmul(v[i - 4], Z2);
      store8(row + 7 * 2048, rim + 7 * 2048, v);
    }
    TL(17);
    fence_async();
    bar_sync(NB_WG0 + u, 128);
    TL(13);
    float c[32];
    wg_fence();
    kgen_mma<0>(c, desc_lo(tab) | ((uint64_t)((tim - tab) >> 4) << 16) | (64ull << 32));
    wg_commit();
    if (u < 4) cluster_wait();
    {
      const uint4 x = ldg128(p.tab->thr[0][tid]), y = ldg128(p.tab->thr[1][tid]), a = ldg128(p.tab->thr[2][tid]), b = ldg128(p.tab->thr[3][tid]);
      A1[0] = x.x; A1[1] = x.y; A1[2] = x.z; A1[3] = x.w; A1[4] = y.x; A1[5] = y.y; A1[6] = y.z; A1[7] = y.w;
      tc[0] = a.x; tc[1] = a.y; tc[2] = a.z; tc[3] = a.w; ts[0] = b.x; ts[1] = b.y; ts[2] = b.z; ts[3] = b.w;
    }
    wg_wait<0>(); tie_all(c);
    TL(26);
    if (u < 4) bar_arrive(NB_K4, 640);
    cluster_arrive();
    bar_sync(NB_WG0 + u, 128);
    if (w == 0 && elect()) {
      tma_load4(tab + T_HA, &p.th, 0, 0, 5 * cl + u, rank, mb + 8 * (MB_HA + u));
      if (u == 4) tma_load3(sb + OFF_Q2, &p.tq2, ch0, 8 * rank, 0, mb + 8 * MB_Q2);
    }
    __syncwarp();
    const uint32_t k0 = pack(c[0] + c[6], c[1] + c[7]), k1 = pack(c[8] + c[14], c[9] + c[15]);
    const uint32_t k2 = pack(c[16] + c[22], c[17] + c[23]), k3 = pack(c[24] + c[30], c[25] + c[31]);
    const uint32_t ka = tab + 16 * (8 * w + (g ^ w));
    sts32(ka + 4 * t, k0);
    sts32(ka + 512 + 4 * t, k1);
    sts64(ka + 1024 + 512 * (t >> 1) + 8 * (t & 1), prmt(k2, 0, 0x1010), (t & 1) ? prmt(k2, 0, 0x3232) : k2);
    const uint32_t lo = prmt(k3, 0, 0x1010), hi = prmt(k3, 0, 0x3232);
    sts128(ka + 2048 + 512 * t, lo, lo, (g & 1) ? hi : k3, hi);
    put_exp(sb + OFF_MX + u * 64 + 4 * w, amax2(amax2(k0, k1), amax2(k2, k3)), lane);
    TL(15);
    fence_async();
    bar_sync(NB_WG0 + u, 128);
    mbar_wait(mb + 8 * MB_CF);
  }

#pragma unroll
  for (int isA = 0; isA < 2; isA++) {
    if (isA) {
      cluster_wait();
      if (u < 4) { mbar_wait(mb + 8 * MB_XD); mbar_wait(mb + 8 * MB_KV); }
      TL(21);
#pragma unroll 1
      for (int k = u == 4 ? 5 : u; k < 5; k += u == 3 ? 1 : 5) {
        const uint32_t hoff = (4 * (4 + 2 * (mi & 1) + jj) + ((tq + 3) & 3)) * 80 + (tq ? 2560 : 0) + 16 * k;
        uint32_t E[2][6], V[2][4];
        const uint2 psw = lds64(sb + OFF_SP + 160 * k + 80 + 8 * g);
#pragma unroll
        for (int hf = 0; hf < 2; hf++) {
          const int ah = 4 * hf + w;
          uint32_t K[4];
          ldsm4t(K, sb + OFF_TK + (ah + 1) * 2560 + toff + 16 * k);
          ldsm2t(E[hf][0], E[hf][1], sb + OFF_TK + ah * 2560 + hoff);
          ldsm4t(V[hf], sb + OFF_TV + ah * 2560 + toff + 16 * k);
          E[hf][2] = K[0]; E[hf][3] = K[1]; E[hf][4] = K[2]; E[hf][5] = K[3];
        }
        const uint32_t w0 = prmt(psw.x, 0, 0x1010), w1 = prmt(psw.x, 0, 0x3232), w2 = prmt(psw.y, 0, 0x1010), w3 = prmt(psw.y, 0, 0x3232);
        uint32_t o[2][4];
#pragma unroll
        for (int hf = 0; hf < 2; hf++) {
          uint32_t O[5];
#pragma unroll
          for (int i = 0; i < 5; i++) O[i] = prmt(E[hf][i], E[hf][i + 1], 0x5432);
#pragma unroll
          for (int i = 0; i < 4; i++) {
            o[hf][i] = hmul2(hfma2(E[hf][i + 2], w0, hfma2(O[i + 1], w1, hfma2(E[hf][i + 1], w2, hmul2(O[i], w3)))), V[hf][i]);
          }
          put(OFF_YA + 8 * k * YPITCH, OFF_T + k * KTAB + T_UKV, hf ? (uoff ^ 32) + 256 : uoff, o[hf]);
        }
        fence_async();
        bar_sync(NB_WG0 + u, 128);
        send(OFF_YA + 8 * k * YPITCH, YPITCH, OFF_T + k * KTAB + T_UKV + 512 * rank, OFF_MB + 8 * (MB_UKV + k));
      }
      TL(22);
      if (u < 2) {
        const int slot = tid + 128 * u;
        tag = (lds64(mb + 8 * MB_TAG).x >> 4) + 1;
        float s = 0.f;
        bool ok = false;
        const uint2* gp = p.part + rank * 256 + slot;
    #pragma unroll 1
        for (int it = 0; it < 4000 && !ok; it++) {
          ok = true; s = 0.f;
    #pragma unroll
          for (int k = 0; k < NCL; k++) {
            uint64_t a;
            asm volatile("ld.relaxed.gpu.global.u64 %0, [%1];" : "=l"(a) : "l"(gp + k * SEQ) : "memory");
            ok = ok && (uint32_t)(a >> 32) == tag;
            s += __uint_as_float((uint32_t)a);
          }
        }
        if (!ok) {
          const uint32_t* xr = (const uint32_t*)(p.q + (size_t)(rank * 256 + 32 * (slot & 7) + (slot >> 3)) * DCH);
          const uint32_t* gr = (const uint32_t*)p.gate_w;
          s = 0.f;
    #pragma unroll 1
          for (int k = 0; k < DCH / 2; k++) { const uint32_t m = hmul2(__ldg(xr + k), __ldg(gr + k)); s += blo(m) + bhi(m); }
        }
        const float g0 = bf16r(sigmoidf_(bf16r(s)));
        sts64(sb + OFF_GB + 8 * slot, pack(g0, g0), pack(1.f - g0, 1.f - g0));
        __syncwarp();
        if (lane == 0) mbar_arrive(mb + 8 * MB_Q2);
      }
      TL(11);
      mbar_wait(mb + 8 * (MB_HA + u));
      put_exp(sb + OFF_MX + u * 64 + 32 + 4 * w, seq_mag(tab + T_HA + 16 * tid), lane);
      bar_sync(NB_WG0 + u, 128);
    }
    {
      TL(1 + isA);
      const uint32_t usrc = isA ? tab + T_UKV : sb + OFF_UX + u * 4096;
      const uint32_t mxa = sb + OFF_MX + u * 64 + 32 * isA;
      const uint32_t pd = lds16(sb + OFF_SP + 160 * u + 144 + 4 * isA);
      float D[32];
      uint32_t As[8], F[16], H[16], X[16];
      const uint32_t eh = min(max((int)get_exp(mxa), (int)((pd >> 7) & 0xff) - 5), 240);
      scale_a1(As, A1, 248 - eh);
      wg_fence();
      stage1(D, As, isA ? tab + T_HA : tab);
      wg_commit();
      wg_wait<0>(); tie_all(D);
      fwd_mid(F, D, tc, ts);
      wg_fence();
      stage2<0>(H, F, sb + OFF_CF);
      wg_commit();
      mbar_wait(mb + 8 * ((isA ? MB_UKV : MB_UX) + u));
      TL(5 + isA);
      put_exp(mxa + 16 + 4 * w, seq_mag(usrc + 16 * tid), lane);
      bar_sync(NB_WG0 + u, 128);
      const uint32_t eu = min(get_exp(mxa + 16), 240u);
      scale_a1(As, A1, 250 - eu);
      wg_wait<0>(); tie_all(H);
      wg_fence();
      stage1(D, As, usrc);
      wg_commit();
      wg_wait<0>(); tie_all(D);
      fwd_mid(F, D, tc, ts);
      wg_fence();
      stage2<0>(X, F, sb + OFF_CF);
      wg_commit();
      {
        const float dsk = blo(pd) * __uint_as_float((248 - eh) << 23);
        const uint32_t d2 = packh(dsk, dsk);
#pragma unroll
        for (int j = 0; j < 4; j++) H[2 * j] = U2(__hadd2(H2(H[2 * j]), H2(d2)));
      }
      wg_wait<0>(); tie_all(X);
#pragma unroll
      for (int j = 0; j < 4; j++) {
        const uint32_t h0r = H[2 * j], h1r = H[2 * j + 1], h0i = H[8 + 2 * j], h1i = H[9 + 2 * j];
        const uint32_t x0r = X[2 * j], x1r = X[2 * j + 1], x0i = X[8 + 2 * j], x1i = X[9 + 2 * j];
        F[2 * j] = ffma(x0r, h0r, fneg(fmul(x0i, h0i)));
        F[8 + 2 * j] = ffma(x0r, h0i, fmul(x0i, h0r));
        F[2 * j + 1] = ffma(x1r, h0r, ffma(fneg(x1i), h0i, ffma(x0r, h1r, fneg(ffma(x0i, h1i, F[8 + 2 * j])))));
        F[9 + 2 * j] = ffma(x1r, h0i, ffma(x1i, h0r, ffma(x0r, h1i, ffma(x0i, h1r, F[2 * j]))));
      }
      wg_fence();
      stage2<1>(H, F, sb + OFF_CF);
      wg_commit();
      wg_wait<0>(); tie_all(H);
      {
        const uint32_t va = tab + (16 * w + (lane & 15)) * 128;
        const int vx = (lane >> 4) ^ (lane & 7);
#pragma unroll
        for (int j = 0; j < 4; j++) {
          uint32_t V[4];
#pragma unroll
          for (int b = 0; b < 2; b++) {
            const uint32_t er = H[2 * j + b], ei = H[8 + 2 * j + b];
            V[2 * b] = ffma(er, tc[j], fneg(fmul(ei, ts[j])));
            V[2 * b + 1] = ffma(ei, tc[j], fmul(er, ts[j]));
          }
          stsm4(va + ((vx ^ (2 * j)) << 4), V);
        }
      }
      fence_async();
      bar_sync(NB_WG0 + u, 128);
      float O[16];
      {
        const uint64_t dv = desc_lo(tab) | (1ull << 16) | (64ull << 32) | (1ull << 62);
        const uint64_t dl = desc_lo(sb + OFF_CL) | (32ull << 16) | (8ull << 32);
        wg_fence();
        ss32<0, 0, 0>(O, dv, dl); ss32<1, 128, 64>(O, dv, dl); ss32<1, 256, 128>(O, dv, dl); ss32<1, 384, 192>(O, dv, dl);
        wg_commit();
      }
      wg_wait<0>(); tie_all(O);
      {
        const uint32_t co = ((8 * w + g) ^ (2 * t)) * 16;
        const int yo = (isA ? OFF_YA : OFF_YB) + (8 * u + rank) * YPITCH, ym = OFF_MB + 8 * (MB_Y + u);
        const uint32_t us = min(max((int)(eu + eh) - 127, 0), 254) * 0x00800080u;
        const uint32_t a0 = hmul2(pack(O[0], O[1]), us), a1 = hmul2(pack(O[4], O[5]), us), a2 = hmul2(pack(O[8], O[9]), us), a3 = hmul2(pack(O[12], O[13]), us);
        const uint32_t b0 = hmul2(pack(O[2], O[3]), us), b1 = hmul2(pack(O[6], O[7]), us), b2 = hmul2(pack(O[10], O[11]), us), b3 = hmul2(pack(O[14], O[15]), us);
        sts128((t == rank ? sb + yo : usrc + t * 512) + co, a0, a1, a2, a3);
        sts128((t + 4 == rank ? sb + yo : usrc + t * 512 + 2048) + co, b0, b1, b2, b3);
        fence_async();
        bar_sync(NB_WG0 + u, 128);
        send(usrc - sb, 512, yo, ym);
      }
      TL(9 + isA);
    }
  }

  {
    mbar_wait(mb + 8 * MB_Q2);
    uint2 gg[2][4];
    uint32_t qv[2][4];
#pragma unroll
    for (int hh = 0; hh < 2; hh++)
#pragma unroll
      for (int i = 0; i < 4; i++) gg[hh][i] = lds64(sb + OFF_GB + 8 * (64 * w + 32 * hh + 8 * i + g));
    const uint32_t qa = sb + OFF_Q2 + (64 * w + lane) * 80 + 16 * u;
    ldsm4(qv[0], qa);
    ldsm4(qv[1], qa + 2560);
    TL(24);
    mbar_wait(mb + 8 * (MB_Y + u));
    uint32_t ya[2][4], yb[2][4];
#pragma unroll
    for (int hh = 0; hh < 2; hh++) {
      const uint32_t yo = (8 * u + (lane & 7)) * YPITCH + ((8 * w + 4 * hh + (lane >> 3)) ^ (2 * (rank & 3))) * 16;
      ldsm4t(ya[hh], sb + OFF_YA + yo); ldsm4t(yb[hh], sb + OFF_YB + yo);
    }
#pragma unroll
    for (int hh = 0; hh < 2; hh++) {
      uint32_t o[4];
#pragma unroll
      for (int i = 0; i < 4; i++) o[i] = hadd2(hmul2(gg[hh][i].x, hmul2(qv[hh][i], ya[hh][i])), hmul2(gg[hh][i].y, yb[hh][i]));
      stsm4(qa + 2560 * hh, o);
    }
    TL(25);
  }
  cluster_arrive();
  bar_sync(NB_ROW0 + w, 160);
  {
    uint4 v[2];
#pragma unroll
    for (int k = 0; k < 2; k++) {
      const int i = 64 * u + 32 * k + lane, sl = (i * 205) >> 10, cc = i - 5 * sl;
      v[k] = lds128(sb + OFF_Q2 + (64 * w + 8 * (sl & 7) + (sl >> 3)) * 80 + cc * 16);
    }
#pragma unroll
    for (int k = 0; k < 2; k++) {
      const int i = 64 * u + 32 * k + lane, sl = (i * 205) >> 10, cc = i - 5 * sl;
      if (cc < nu)
        asm volatile("st.global.v4.u32 [%0], {%1,%2,%3,%4};" :: "l"(p.out + (size_t)(256 * rank + 32 * (sl >> 3) + 8 * w + (sl & 7)) * DCH + ch0 + 8 * cc),
                     "r"(v[k].x), "r"(v[k].y), "r"(v[k].z), "r"(v[k].w) : "memory");
    }
  }
  cluster_wait();
  TL(27);
  TL_DUMP();
}

typedef CUresult (*EncodeFn)(CUtensorMap*, CUtensorMapDataType, cuuint32_t, void*, const cuuint64_t*, const cuuint64_t*,
                             const cuuint32_t*, const cuuint32_t*, CUtensorMapInterleave, CUtensorMapSwizzle,
                             CUtensorMapL2promotion, CUtensorMapFloatOOBfill);

void encode(EncodeFn fn, CUtensorMap* tm, const void* ptr, int nd, const cuuint64_t* dims, const cuuint64_t* strides,
            const cuuint32_t* box, CUtensorMapSwizzle swz) {
  cuuint32_t es[4] = {1, 1, 1, 1};
  fn(tm, CU_TENSOR_MAP_DATA_TYPE_BFLOAT16, nd, const_cast<void*>(ptr), dims, strides, box, es, CU_TENSOR_MAP_INTERLEAVE_NONE,
     swz, CU_TENSOR_MAP_L2_PROMOTION_L2_128B, CU_TENSOR_MAP_FLOAT_OOB_FILL_NONE);
}
void map1(EncodeFn fn, CUtensorMap* tm, const void* ptr, int nhi) {
  const cuuint64_t dims[4] = {DCH, 4, 8, SEQ / 32}, strides[3] = {8 * DCH * 2, DCH * 2, 32 * DCH * 2};
  const cuuint32_t box[4] = {CPC, 4, 8, (cuuint32_t)nhi};
  encode(fn, tm, ptr, 4, dims, strides, box, CU_TENSOR_MAP_SWIZZLE_NONE);
}
void map2(EncodeFn fn, CUtensorMap* tm, const void* ptr, int nr) {
  const cuuint64_t dims[3] = {DCH, SEQ / 32, 32}, strides[2] = {32 * DCH * 2, DCH * 2};
  const cuuint32_t box[3] = {CPC, 8, (cuuint32_t)nr};
  encode(fn, tm, ptr, 3, dims, strides, box, CU_TENSOR_MAP_SWIZZLE_NONE);
}

}

extern "C" void kernel_launch(void* const* d_in, const int* in_sizes, int n_in, void* d_out, int out_size) {
  (void)in_sizes; (void)n_in; (void)out_size;
  static EncodeFn fn = nullptr;
  static void *tab = nullptr, *cnt = nullptr, *part = nullptr;
  if (!fn) {
    cudaGetSymbolAddress(&tab, d_tab);
    cudaGetSymbolAddress(&cnt, g_cnt);
    cudaGetSymbolAddress(&part, g_part);
    cudaDriverEntryPointQueryResult qr;
    cudaGetDriverEntryPoint("cuTensorMapEncodeTiled", (void**)&fn, cudaEnableDefault, &qr);
    cudaFuncSetAttribute(fused_kernel, cudaFuncAttributeMaxDynamicSharedMemorySize, SMEM_BYTES);
  }
  Params p;
  map1(fn, &p.tq, d_in[0], 8);
  map1(fn, &p.tk, d_in[1], 9);
  map1(fn, &p.tv, d_in[2], 8);
  map2(fn, &p.tq2, d_in[0], 32);
  p.out = (__nv_bfloat16*)d_out;
  {
    const cuuint64_t dims[4] = {32, SEQ / 32, DCH / 8, 8}, strides[3] = {64, 8 * SEQ * 2, SEQ * 2};
    const cuuint32_t box[4] = {32, 64, 1, 1};
    encode(fn, &p.th, d_in[4], 4, dims, strides, box, CU_TENSOR_MAP_SWIZZLE_64B);
  }
  p.tab = (const Tables*)tab;
  p.cnt = (unsigned*)cnt;
  p.part = (uint2*)part;
  p.tl = nullptr;
  p.q = (const __nv_bfloat16*)d_in[0];
  p.shift_k = (const __nv_bfloat16*)d_in[3];
  p.ssm_D = (const __nv_bfloat16*)d_in[5];
  p.logA = (const __nv_bfloat16*)d_in[7];
  p.Aim = (const __nv_bfloat16*)d_in[8];
  p.Cre = (const __nv_bfloat16*)d_in[9];
  p.Cim = (const __nv_bfloat16*)d_in[10];
  p.logdt = (const __nv_bfloat16*)d_in[11];
  p.Dskip = (const __nv_bfloat16*)d_in[12];
  p.gate_w = (const __nv_bfloat16*)d_in[13];
  fused_kernel<<<NCL * CS, NTHREADS, SMEM_BYTES, cudaStreamPerThread>>>(p);
}
```

```cpp
#include <cuda_runtime.h>
#include <cuda_bf16.h>
#include <cuda_fp16.h>
#include <cuda.h>
#include <stdint.h>

#define TIMELINE 0

namespace {

constexpr int SEQ = 2048, DCH = 576, NMODE = 128;
constexpr int CS = 8, CPC = 40, NCL = 15, NTHREADS = 640;

constexpr int YPITCH = 528;
constexpr int KTAB = 16384;
constexpr int OFF_T = 0;
constexpr int T_UKV = 8192, T_HA = 12288;
constexpr int OFF_UX = 5 * KTAB;
constexpr int OFF_IM = OFF_UX + 20480;
constexpr int OFF_Q2 = OFF_IM;
constexpr int OFF_GB = OFF_Q2 + 20480;
constexpr int OFF_TV = OFF_IM + 3 * KTAB - 20480;
constexpr int OFF_CF = OFF_IM + 3 * KTAB;
constexpr int OFF_CL = OFF_CF + 8192;
constexpr int OFF_TQ = OFF_CL + 4096;
constexpr int OFF_YA = OFF_TQ;
constexpr int OFF_TK = OFF_TQ + 21120;
constexpr int OFF_YB = OFF_TK + 23040;
constexpr int OFF_MX = OFF_YB + 40 * YPITCH;
constexpr int OFF_SP = OFF_MX + 320;
constexpr int OFF_MB = OFF_SP + 5 * 160;
constexpr int OFF_TL = OFF_MB + 32 * 8;
constexpr int SMEM_BYTES = OFF_TL + (TIMELINE ? 1280 : 0);
static_assert(SMEM_BYTES <= 232448, "smem");
static_assert((OFF_TQ & 127) == 0 && (OFF_TK & 127) == 0 && (OFF_TV & 127) == 0 && (OFF_MB & 7) == 0 && (OFF_MX & 15) == 0, "align");

enum { MB_UX = 0, MB_UKV = 5, MB_Y = 10, MB_HA = 15, MB_XQ = 20, MB_KV = 21, MB_CF = 22, MB_Q2 = 23, MB_XD = 24, MB_TAG = 25 };
enum { NB_WG0 = 1, NB_ROW0 = 6, NB_K4 = 10, NB_W2 = 11, NB_V = 12 };

constexpr double cos_turn(int m, int n) {
  m &= n - 1;
  if (m > n / 2) m = n - m;
  double sgn = 1.0;
  if (m > n / 4) { m = n / 2 - m; sgn = -1.0; }
  if (m == n / 4) return 0.0;
  const double x = 6.283185307179586476925 * m / n;
  double term = 1.0, sum = 1.0;
  for (int k = 1; k < 14; k++) { term *= -x * x / ((2 * k - 1) * (2 * k)); sum += term; }
  return sgn * sum;
}
constexpr uint32_t bf16_bits(double v) {
  if (v == 0.0) return 0;
  uint32_t sgn = 0;
  if (v < 0) { sgn = 0x8000; v = -v; }
  int e = 127;
  while (v < 1.0) { v *= 2.0; e--; }
  while (v >= 2.0) { v *= 0.5; e++; }
  const double f = v * 128.0;
  int m = (int)f;
  if (f - m > 0.5 || (f - m == 0.5 && (m & 1))) m++;
  return sgn | (uint32_t)((e << 7) + (m - 128));
}
constexpr uint32_t f16_bits(double v) {
  if (v == 0.0) return 0;
  uint32_t sgn = 0;
  if (v < 0) { sgn = 0x8000; v = -v; }
  int e = 15;
  while (v < 1.0) { v *= 2.0; e--; }
  const double f = v * 1024.0;
  int m = (int)f;
  if (f - m > 0.5 || (f - m == 0.5 && (m & 1))) m++;
  return sgn | (uint32_t)((e << 10) + (m - 1024));
}
constexpr uint32_t pair_bits(double lo, double hi) { return bf16_bits(lo) | (bf16_bits(hi) << 16); }
constexpr uint32_t pair_h(double lo, double hi) { return f16_bits(lo) | (f16_bits(hi) << 16); }
struct alignas(128) Tables {
  uint32_t mat[3072];
  uint32_t thr[4][128][4];
};
constexpr Tables make_tables() {
  Tables T{};
  for (int q = 0; q < 768; q++) {
    int m0 = 0, d0 = 0, d1 = 0;
    if (q < 512) {
      const int r = (q >> 6) * 8 + (q & 7), cc = (q >> 3) & 7;
      d0 = 4 * (r & 31); d1 = 2 * d0;
      m0 = 8 * (cc & 3) * d0 + ((r >> 5) == (cc >> 2) ? 0 : (r >> 5) ? 96 : 32);
    } else {
      const int r = ((q - 512) >> 5) * 8 + (q & 7), pc = (q >> 3) & 3;
      d0 = 4 * (8 * (r >> 4) + (r & 7)) + 1; d1 = 8 * d0;
      m0 = 2 * pc * d0 + ((r & 8) ? 32 : 0);
    }
    for (int e = 0; e < 4; e++) T.mat[4 * q + e] = pair_h(cos_turn(m0 + e * d1, 128), cos_turn(m0 + e * d1 + d0, 128));
  }
  for (int tid = 0; tid < 128; tid++) {
    const int kk = 4 * (tid >> 2) + 1, t = tid & 3;
    for (int q = 0; q < 4; q++) {
      const int m = (8 * q + 2 * t) * kk;
      T.thr[q >> 1][tid][2 * (q & 1)] = pair_bits(cos_turn(m, 128), cos_turn(m + kk, 128));
      T.thr[q >> 1][tid][2 * (q & 1) + 1] = pair_bits(cos_turn(m + 32, 128), cos_turn(m + kk + 32, 128));
      T.thr[2][tid][q] = pair_h(cos_turn(m, 4096), cos_turn(m + kk, 4096));
      T.thr[3][tid][q] = pair_h(cos_turn(m + 3072, 4096), cos_turn(m + kk + 3072, 4096));
    }
  }
  return T;
}
__device__ const Tables d_tab = make_tables();

struct Params {
  const __nv_bfloat16 *logA, *Aim, *Cre, *Cim, *logdt;
  const Tables* tab;
  unsigned* cnt;
  const __nv_bfloat16 *Dskip, *shift_k, *ssm_D, *gate_w, *q;
  uint2* part;
  __nv_bfloat16* out;
  unsigned* tl;
  CUtensorMap tq, tk, tv, th, tq2;
};

__device__ uint2 g_part[NCL * SEQ];
__device__ unsigned g_cnt[CS * 32];
#define TL(i) do {} while (0)
#define TL_INIT() do {} while (0)
#define TL_DUMP() do {} while (0)

__device__ __forceinline__ uint32_t lds16(uint32_t a) { uint32_t v; asm volatile("ld.shared.u16 %0, [%1];" : "=r"(v) : "r"(a) : "memory"); return v; }
__device__ __forceinline__ uint2 lds64(uint32_t a) { uint2 v; asm volatile("ld.shared.v2.u32 {%0,%1}, [%2];" : "=r"(v.x), "=r"(v.y) : "r"(a) : "memory"); return v; }
__device__ __forceinline__ uint4 lds128(uint32_t a) { uint4 v; asm volatile("ld.shared.v4.u32 {%0,%1,%2,%3}, [%4];" : "=r"(v.x), "=r"(v.y), "=r"(v.z), "=r"(v.w) : "r"(a) : "memory"); return v; }
__device__ __forceinline__ void sts16(uint32_t a, uint32_t v) { asm volatile("st.shared.u16 [%0], %1;" :: "r"(a), "r"(v) : "memory"); }
__device__ __forceinline__ void sts32(uint32_t a, uint32_t v) { asm volatile("st.shared.u32 [%0], %1;" :: "r"(a), "r"(v) : "memory"); }
__device__ __forceinline__ void sts64(uint32_t a, uint32_t x, uint32_t y) { asm volatile("st.shared.v2.u32 [%0], {%1,%2};" :: "r"(a), "r"(x), "r"(y) : "memory"); }
__device__ __forceinline__ void sts128(uint32_t a, uint32_t x, uint32_t y, uint32_t z, uint32_t w) { asm volatile("st.shared.v4.u32 [%0], {%1,%2,%3,%4};" :: "r"(a), "r"(x), "r"(y), "r"(z), "r"(w) : "memory"); }
__device__ __forceinline__ void ldsm4t(uint32_t (&r)[4], uint32_t a) { asm volatile("ldmatrix.sync.aligned.m8n8.x4.trans.shared.b16 {%0,%1,%2,%3}, [%4];" : "=r"(r[0]), "=r"(r[1]), "=r"(r[2]), "=r"(r[3]) : "r"(a) : "memory"); }
__device__ __forceinline__ void ldsm2t(uint32_t& r0, uint32_t& r1, uint32_t a) { asm volatile("ldmatrix.sync.aligned.m8n8.x2.trans.shared.b16 {%0,%1}, [%2];" : "=r"(r0), "=r"(r1) : "r"(a) : "memory"); }
__device__ __forceinline__ void ldsm4(uint32_t (&r)[4], uint32_t a) { asm volatile("ldmatrix.sync.aligned.m8n8.x4.shared.b16 {%0,%1,%2,%3}, [%4];" : "=r"(r[0]), "=r"(r[1]), "=r"(r[2]), "=r"(r[3]) : "r"(a) : "memory"); }
__device__ __forceinline__ void stsm4(uint32_t a, const uint32_t (&r)[4]) { asm volatile("stmatrix.sync.aligned.m8n8.x4.shared.b16 [%0], {%1,%2,%3,%4};" :: "r"(a), "r"(r[0]), "r"(r[1]), "r"(r[2]), "r"(r[3]) : "memory"); }
__device__ __forceinline__ uint32_t pack(float lo, float hi) { uint32_t r; asm("cvt.rn.bf16x2.f32 %0, %1, %2;" : "=r"(r) : "f"(hi), "f"(lo)); return r; }
__device__ __forceinline__ float blo(uint32_t v) { return __uint_as_float(v << 16); }
__device__ __forceinline__ float bhi(uint32_t v) { return __uint_as_float(v & 0xffff0000u); }
__device__ __forceinline__ float bf16r(float x) { return blo(pack(x, 0.f)); }
__device__ __forceinline__ uint32_t hmul2(uint32_t a, uint32_t b) { uint32_t r; asm("mul.rn.bf16x2 %0, %1, %2;" : "=r"(r) : "r"(a), "r"(b)); return r; }
__device__ __forceinline__ uint32_t hadd2(uint32_t a, uint32_t b) { uint32_t r; asm("add.rn.bf16x2 %0, %1, %2;" : "=r"(r) : "r"(a), "r"(b)); return r; }
__device__ __forceinline__ uint32_t hfma2(uint32_t a, uint32_t b, uint32_t c) { uint32_t r; asm("fma.rn.bf16x2 %0, %1, %2, %3;" : "=r"(r) : "r"(a), "r"(b), "r"(c)); return r; }
__device__ __forceinline__ uint32_t packh(float lo, float hi) { uint32_t r; asm("cvt.rn.f16x2.f32 %0, %1, %2;" : "=r"(r) : "f"(hi), "f"(lo)); return r; }
__device__ __forceinline__ __half2 H2(uint32_t a) { return *reinterpret_cast<__half2*>(&a); }
__device__ __forceinline__ uint32_t U2(__half2 a) { return *reinterpret_cast<uint32_t*>(&a); }
__device__ __forceinline__ uint32_t fmul(uint32_t a, uint32_t b) { return U2(__hmul2(H2(a), H2(b))); }
__device__ __forceinline__ uint32_t ffma(uint32_t a, uint32_t b, uint32_t c) { return U2(__hfma2(H2(a), H2(b), H2(c))); }
__device__ __forceinline__ uint32_t fneg(uint32_t a) { return U2(__hneg2(H2(a))); }
__device__ __forceinline__ uint32_t amax2(uint32_t a, uint32_t b) { uint32_t r; asm("max.xorsign.abs.bf16x2 %0, %1, %2;" : "=r"(r) : "r"(a), "r"(b)); return r; }
__device__ __forceinline__ uint32_t prmt(uint32_t a, uint32_t b, uint32_t s) { return __byte_perm(a, b, s); }
__device__ __forceinline__ uint32_t ldraw(const __nv_bfloat16* p) { uint32_t v; asm volatile("ld.global.nc.u16 %0, [%1];" : "=r"(v) : "l"(p)); return v; }
__device__ __forceinline__ uint4 ldg128(const void* p) { uint4 v; asm volatile("ld.global.nc.v4.u32 {%0,%1,%2,%3}, [%4];" : "=r"(v.x), "=r"(v.y), "=r"(v.z), "=r"(v.w) : "l"(p)); return v; }
__device__ __forceinline__ void bar_sync(int id, int n) { asm volatile("bar.sync %0, %1;" :: "r"(id), "r"(n) : "memory"); }
__device__ __forceinline__ void bar_arrive(int id, int n) { asm volatile("bar.arrive %0, %1;" :: "r"(id), "r"(n) : "memory"); }
__device__ __forceinline__ void cluster_arrive() { asm volatile("barrier.cluster.arrive.relaxed.aligned;" ::: "memory"); }
__device__ __forceinline__ void cluster_wait() { asm volatile("barrier.cluster.wait.aligned;" ::: "memory"); }
__device__ __forceinline__ void fence_async() { asm volatile("fence.proxy.async.shared::cta;" ::: "memory"); }
__device__ __forceinline__ void fence_mbinit() { asm volatile("fence.mbarrier_init.release.cluster;" ::: "memory"); }
__device__ __forceinline__ uint32_t mapa(uint32_t a, uint32_t rank) { uint32_t r; asm("mapa.shared::cluster.u32 %0, %1, %2;" : "=r"(r) : "r"(a), "r"(rank)); return r; }
__device__ __forceinline__ void bulk_dsmem(uint32_t dst, uint32_t src, uint32_t mbar) {
  asm volatile("cp.async.bulk.shared::cluster.shared::cta.mbarrier::complete_tx::bytes [%0], [%1], 512, [%2];" :: "r"(dst), "r"(src), "r"(mbar) : "memory");
}
__device__ __forceinline__ void mbar_init(uint32_t m, uint32_t cnt) { asm volatile("mbarrier.init.shared::cta.b64 [%0], %1;" :: "r"(m), "r"(cnt) : "memory"); }
__device__ __forceinline__ void mbar_expect(uint32_t m, uint32_t bytes) { asm volatile("mbarrier.arrive.expect_tx.shared::cta.b64 _, [%0], %1;" :: "r"(m), "r"(bytes) : "memory"); }
__device__ __forceinline__ bool mbar_try(uint32_t m) {
  uint32_t done;
  asm volatile("{.reg .pred p; mbarrier.try_wait.parity.shared::cta.b64 p, [%1], 0; selp.u32 %0, 1, 0, p;}" : "=r"(done) : "r"(m) : "memory");
  return done;
}
__device__ __forceinline__ void mbar_wait(uint32_t m) {
  if (!mbar_try(m)) {
    int it = 0;
    while (!mbar_try(m) && ++it < (1 << 22)) {}
  }
}
__device__ __forceinline__ bool elect() {
  uint32_t e;
  asm volatile("{.reg .pred p; elect.sync _|p, 0xffffffff; selp.u32 %0, 1, 0, p;}" : "=r"(e));
  return e;
}
__device__ __forceinline__ void tma_load4(uint32_t dst, const CUtensorMap* tm, int c0, int c1, int c2, int c3, uint32_t mbar) {
  asm volatile("cp.async.bulk.tensor.4d.shared::cluster.global.mbarrier::complete_tx::bytes [%0], [%1, {%3, %4, %5, %6}], [%2];"
               :: "r"(dst), "l"(tm), "r"(mbar), "r"(c0), "r"(c1), "r"(c2), "r"(c3) : "memory");
}
__device__ __forceinline__ void tma_load3(uint32_t dst, const CUtensorMap* tm, int c0, int c1, int c2, uint32_t mbar) {
  asm volatile("cp.async.bulk.tensor.3d.shared::cluster.global.mbarrier::complete_tx::bytes [%0], [%1, {%3, %4, %5}], [%2];"
               :: "r"(dst), "l"(tm), "r"(mbar), "r"(c0), "r"(c1), "r"(c2) : "memory");
}
__device__ __forceinline__ void tma_store3(const CUtensorMap* tm, int c0, int c1, int c2, uint32_t src) {
  asm volatile("cp.async.bulk.tensor.3d.global.shared::cta.bulk_group [%0, {%2, %3, %4}], [%1];"
               :: "l"(tm), "r"(src), "r"(c0), "r"(c1), "r"(c2) : "memory");
}
__device__ __forceinline__ void wg_fence() { asm volatile("wgmma.fence.sync.aligned;" ::: "memory"); }
__device__ __forceinline__ void wg_commit() { asm volatile("wgmma.commit_group.sync.aligned;" ::: "memory"); }
template <int N> __device__ __forceinline__ void wg_wait() { asm volatile("wgmma.wait_group.sync.aligned %0;" :: "n"(N) : "memory"); }
template <int N> __device__ __forceinline__ void tie_all(uint32_t (&x)[N]) {
#pragma unroll
  for (int i = 0; i < N; i++) asm volatile("" : "+r"(x[i]) :: "memory");
}
template <int N> __device__ __forceinline__ void tie_all(float (&x)[N]) {
#pragma unroll
  for (int i = 0; i < N; i++) asm volatile("" : "+f"(x[i]) :: "memory");
}
#define R16(C, d) C(d[0]), C(d[1]), C(d[2]), C(d[3]), C(d[4]), C(d[5]), C(d[6]), C(d[7]), C(d[8]), C(d[9]), C(d[10]), C(d[11]), C(d[12]), C(d[13]), C(d[14]), C(d[15])
#define R32(C, d) R16(C, d), R16(C, (d + 16))
#define P16 "{%0,%1,%2,%3,%4,%5,%6,%7,%8,%9,%10,%11,%12,%13,%14,%15}"
#define P32 "{%0,%1,%2,%3,%4,%5,%6,%7,%8,%9,%10,%11,%12,%13,%14,%15,%16,%17,%18,%19,%20,%21,%22,%23,%24,%25,%26,%27,%28,%29,%30,%31}"
template <int SD, int TB, int OFF> __device__ __forceinline__ void rs64(float* d, const uint32_t* a, uint64_t db) {
  if (SD) asm volatile("{.reg .b64 db; add.s64 db, %36, %37; wgmma.mma_async.sync.aligned.m64n64k16.f32.bf16.bf16 " P32 ", {%32,%33,%34,%35}, db, 1, 1, 1, %38;}"
                       : R32("+f", d) : "r"(a[0]), "r"(a[1]), "r"(a[2]), "r"(a[3]), "l"(db), "n"(OFF), "n"(TB));
  else asm volatile("{.reg .b64 db; add.s64 db, %36, %37; wgmma.mma_async.sync.aligned.m64n64k16.f32.bf16.bf16 " P32 ", {%32,%33,%34,%35}, db, 0, 1, 1, %38;}"
                    : R32("=f", d) : "r"(a[0]), "r"(a[1]), "r"(a[2]), "r"(a[3]), "l"(db), "n"(OFF), "n"(TB));
}
template <int SD, int TB, int OFF> __device__ __forceinline__ void rs64h(uint32_t* d, const uint32_t* a, uint64_t db) {
  if (SD) asm volatile("{.reg .b64 db; add.s64 db, %20, %21; wgmma.mma_async.sync.aligned.m64n64k16.f16.f16.f16 " P16 ", {%16,%17,%18,%19}, db, 1, 1, 1, %22;}"
                       : R16("+r", d) : "r"(a[0]), "r"(a[1]), "r"(a[2]), "r"(a[3]), "l"(db), "n"(OFF), "n"(TB));
  else asm volatile("{.reg .b64 db; add.s64 db, %20, %21; wgmma.mma_async.sync.aligned.m64n64k16.f16.f16.f16 " P16 ", {%16,%17,%18,%19}, db, 0, 1, 1, %22;}"
                    : R16("=r", d) : "r"(a[0]), "r"(a[1]), "r"(a[2]), "r"(a[3]), "l"(db), "n"(OFF), "n"(TB));
}
template <int SD, int OFFA, int OFFB> __device__ __forceinline__ void ss32(float* d, uint64_t da, uint64_t db) {
  if (SD) asm volatile("{.reg .b64 da, db; add.s64 da, %16, %18; add.s64 db, %17, %19; wgmma.mma_async.sync.aligned.m64n32k16.f32.f16.f16 " P16 ", da, db, 1, 1, 1, 1, 1;}"
                       : R16("+f", d) : "l"(da), "l"(db), "n"(OFFA), "n"(OFFB));
  else asm volatile("{.reg .b64 da, db; add.s64 da, %16, %18; add.s64 db, %17, %19; wgmma.mma_async.sync.aligned.m64n32k16.f32.f16.f16 " P16 ", da, db, 0, 1, 1, 1, 1;}"
                    : R16("=f", d) : "l"(da), "l"(db), "n"(OFFA), "n"(OFFB));
}
#define KGEN_ASM(SD) "{.reg .b64 da, db; add.s64 da, %32, %33; add.s64 db, %32, %34;\n" \
  "wgmma.mma_async.sync.aligned.m64n64k16.f32.bf16.bf16 " P32 ", da, db, " SD ", 1, 1, 1, 1;}"
template <int KS> __device__ __forceinline__ void kgen_mma(float (&c)[32], uint64_t da) {
  if (KS) asm volatile(KGEN_ASM("1") : R32("+f", c) : "l"(da), "n"(8 * KS), "n"(8 * KS + 512));
  else asm volatile(KGEN_ASM("0") : R32("=f", c) : "l"(da), "n"(8 * KS), "n"(8 * KS + 512));
  if constexpr (KS < 7) kgen_mma<KS + 1>(c, da);
}
__device__ __forceinline__ uint64_t desc_lo(uint32_t a) { return (uint64_t)((a & 0x3FFFF) >> 4); }
__device__ __forceinline__ void stage1(float (&D)[32], const uint32_t (&A1)[8], uint32_t src) {
  const uint64_t du = desc_lo(src) | (128ull << 16) | (32ull << 32) | (2ull << 62);
  rs64<0, 1, 0>(D, A1, du); rs64<1, 1, 64>(D, A1 + 4, du);
}
template <int INV> __device__ __forceinline__ void stage2(uint32_t (&X)[16], const uint32_t (&F)[16], uint32_t cf) {
  constexpr int KS = INV ? 16 : 128, TB = INV ? 0 : 1;
  const uint64_t dc = desc_lo(cf) | (INV ? (8ull << 16) | (64ull << 32) : (64ull << 16) | (8ull << 32));
  rs64h<0, TB, 0>(X, F, dc); rs64h<1, TB, KS>(X, F + 4, dc); rs64h<1, TB, 2 * KS>(X, F + 8, dc); rs64h<1, TB, 3 * KS>(X, F + 12, dc);
}
__device__ __forceinline__ void fwd_mid(uint32_t (&F)[16], const float (&D)[32], const uint32_t (&tc)[4], const uint32_t (&ts)[4]) {
#pragma unroll
  for (int j = 0; j < 4; j++)
#pragma unroll
    for (int b = 0; b < 2; b++) {
      const int i = 4 * j + 16 * b;
      const uint32_t ar = packh(D[i], D[i + 1]), ai = packh(D[i + 2], D[i + 3]);
      F[2 * j + b] = ffma(ar, tc[j], fmul(ai, ts[j]));
      F[8 + 2 * j + b] = ffma(ai, tc[j], fneg(fmul(ar, ts[j])));
    }
}
__device__ __forceinline__ void put_exp(uint32_t a, uint32_t m, int lane) {
  m = __reduce_max_sync(0xffffffffu, max(m & 0x7f80u, (m >> 16) & 0x7f80u));
  if (lane == 0) sts32(a, m);
}
__device__ __forceinline__ uint32_t seq_mag(uint32_t a) {
  const uint4 x = lds128(a), y = lds128(a + 2048);
  return amax2(amax2(amax2(x.x, x.y), amax2(x.z, x.w)), amax2(amax2(y.x, y.y), amax2(y.z, y.w)));
}
__device__ __forceinline__ uint32_t get_exp(uint32_t a) { const uint4 v = lds128(a); return max(max(v.x, v.y), max(v.z, v.w)) >> 7; }
__device__ __forceinline__ void scale_a1(uint32_t (&As)[8], const uint32_t (&A1)[8], uint32_t field) {
#pragma unroll
  for (int i = 0; i < 8; i++) As[i] = hmul2(A1[i], field * 0x00800080u);
}

struct cf { float x, y; };
__device__ __forceinline__ cf cmul(cf a, cf b) { cf r; r.x = fmaf(a.x, b.x, -a.y * b.y); r.y = fmaf(a.x, b.y, a.y * b.x); return r; }
__device__ __forceinline__ cf cexp_p(float lr2, float lt, float p) {
  float m;
  asm("ex2.approx.ftz.f32 %0, %1;" : "=f"(m) : "f"(lr2 * p));
  float t = lt * p;
  t = (t - rintf(t)) * 6.283185307179586f;
  cf r; r.x = m * __cosf(t); r.y = m * __sinf(t); return r;
}
__device__ __forceinline__ void store8(uint32_t a, uint32_t b, const cf (&v)[8]) {
  sts128(a, pack(v[0].x, v[1].x), pack(v[2].x, v[3].x), pack(v[4].x, v[5].x), pack(v[6].x, v[7].x));
  sts128(b, pack(v[0].y, v[1].y), pack(v[2].y, v[3].y), pack(v[4].y, v[5].y), pack(v[6].y, v[7].y));
}
__device__ __forceinline__ void mbar_arrive(uint32_t m) { asm volatile("mbarrier.arrive.shared::cta.b64 _, [%0];" :: "r"(m) : "memory"); }
__device__ __forceinline__ float sigmoidf_(float s) { return __frcp_rn(1.f + __expf(-s)); }

__global__ void __cluster_dims__(CS, 1, 1) __launch_bounds__(NTHREADS, 1) fused_kernel(const __grid_constant__ Params p) {
  extern __shared__ __align__(1024) uint8_t smem[];
  TL_INIT();
  TL(31);
  const int wid = __shfl_sync(0xffffffffu, threadIdx.x >> 5, 0);
  const uint32_t sb = (uint32_t)__cvta_generic_to_shared(smem);
  const uint32_t mb = sb + OFF_MB;
  const int u = wid >> 2, w = wid & 3;
  const int tid = threadIdx.x & 127, lane = tid & 31, g = lane >> 2, t = lane & 3;
  const int cl = blockIdx.x >> 3, rank = blockIdx.x & 7;
  const int ch0 = cl * CPC;
  const int nu = min(5, (DCH - ch0) >> 3);
  const bool act = u < nu;

  if (u == 4 && elect()) {
#pragma unroll
    for (int i = 0; i < 5; i++) mbar_init(mb + 40 * w + 8 * i, w == 3 ? 1 : w == 2 ? 3 : 2);
    if (w == 3) {
      mbar_init(mb + 8 * MB_XQ, 1); mbar_init(mb + 8 * MB_KV, 2); mbar_init(mb + 8 * MB_CF, 2); mbar_init(mb + 8 * MB_Q2, 9); mbar_init(mb + 8 * MB_XD, 8);
    }
    fence_mbinit();
    if (w == 3) {
      mbar_expect(mb + 8 * MB_CF, 12288);
      asm volatile("cp.async.bulk.shared::cluster.global.mbarrier::complete_tx::bytes [%0], [%1], %2, [%3];"
                   :: "r"(sb + OFF_CF), "l"(p.tab->mat), "r"(12288), "r"(mb + 8 * MB_CF) : "memory");
      asm volatile("cp.async.bulk.prefetch.L2.global [%0], 8192;" :: "l"(p.tab->thr) : "memory");
      mbar_expect(mb + 8 * MB_XQ, 20480); mbar_expect(mb + 8 * MB_KV, 23040); mbar_expect(mb + 8 * MB_Q2, 20480);
    }
#pragma unroll
    for (int i = 0; i < 5; i++) mbar_expect(mb + 40 * w + 8 * i, w == 3 ? 4096 : w == 2 ? 7168 : 3584);
  }
  uint32_t pla, pai, pcr, pci, pdt, tag = 0;
  uint4 psm;
  {
    const int ch = act ? ch0 + 8 * u + rank : 0, o = ch * NMODE + tid;
    pla = ldraw(p.logA + o); pdt = ldraw(p.logdt + ch); pai = ldraw(p.Aim + o); pcr = ldraw(p.Cre + o); pci = ldraw(p.Cim + o);
    if (w == 1) {
      if (lane < 9) psm = ldg128(lane < 5 ? p.gate_w + (lane < nu ? ch0 + 8 * lane : 0) : p.shift_k + (act ? ch0 + 8 * u : 0) * 4 + 8 * (lane - 5));
      else { psm.x = ldraw(p.Dskip + ch); psm.y = ldraw(p.ssm_D + ch); }
    }
    if (wid == 16 && lane < 2) asm volatile("atom.relaxed.gpu.global.add.u32 %0, [%1], %2;" : "=r"(tag) : "l"(&p.cnt[rank * 32 + lane]), "r"(cl == 0 ? 16 - (NCL - 1) : 1) : "memory");
  }
  if (wid == 19 && elect()) {
    tma_load4(sb + OFF_TQ, &p.tq, ch0, 0, 0, 8 * rank, mb + 8 * MB_XQ);
    tma_load4(sb + OFF_TK, &p.tk, ch0, 0, 0, 8 * rank - 1, mb + 8 * MB_KV);
    TL(20);
  }
  __syncwarp();
  cluster_arrive();
  TL(0);

  const uint32_t tab = sb + OFF_T + u * KTAB;
  const int mi = lane >> 3, tq = (lane & 7) >> 1, jj = lane & 1;
  const uint32_t toff = (4 * (2 * mi + jj) + tq) * 80;
  const uint32_t uoff = 16 * (4 * w + (t ^ (w >> 1)));
  auto put = [&](int stage, int dst, uint32_t off, const uint32_t (&v)[4]) {
    sts128(sb + off + (g == rank ? dst + 512 * rank : stage + g * YPITCH), v[0], v[1], v[2], v[3]);
  };
  const int d0 = rank ^ (2 * w), d1 = d0 ^ 1;
  const uint32_t rb0 = mapa(sb, d0), rb1 = mapa(sb, d1);
  auto send = [&](int stage, int pitch, int dst, int mbar) {
    if (elect()) {
      if (w) bulk_dsmem(rb0 + dst, sb + stage + d0 * pitch, rb0 + mbar); else mbar_arrive(sb + mbar);
      bulk_dsmem(rb1 + dst, sb + stage + d1 * pitch, rb1 + mbar);
    }
    __syncwarp();
  };

  if (w == 1 && lane < 10) sts128(sb + OFF_SP + 160 * u + 16 * lane, psm.x, psm.y, psm.z, psm.w);
  uint32_t A1[8], tc[4], ts[4];
  {
    const float dt = bf16r(expf(blo(pdt)));
    const float lr2 = (-bf16r(expf(blo(pla))) * dt) * 1.4426950408889634f;
    const float lt = (blo(pai) * dt) * 0.15915494309189535f;
    const uint32_t tim = u == 0 ? sb + OFF_T + 4 * KTAB : sb + OFF_IM + (u == 4 ? 0 : u - 1) * KTAB;
    const uint32_t row = tab + tid * 16, rim = tim + tid * 16;
    const cf w1 = cexp_p(lr2, lt, 8.f);
    cf z1 = cexp_p(lr2, lt, 1.f), Z = cexp_p(lr2, lt, 256.f);
    if (lr2 != 123.f) TL(16);
    if (u == 4) {
      if (tid == 0) { sts32(mb + 8 * MB_TAG, tag); mbar_arrive(mb + 8 * MB_CF); }
      bar_sync(NB_K4, 384);
    } else if (u >= 2) bar_sync(NB_W2, 512);
    TL(12);
    {
      cf v[8];
      v[0].x = 1.f; v[0].y = 0.f; v[1] = w1; v[2] = cmul(w1, w1); v[3] = cmul(v[2], w1);
      const cf w4 = cmul(v[2], v[2]);
      v[4] = w4; v[5] = cmul(v[1], w4); v[6] = cmul(v[2], w4); v[7] = cmul(v[3], w4);
      const cf w8 = cmul(w4, w4);
      store8(row, rim, v);
#pragma unroll
      for (int k = 1; k < 4; k++) {
#pragma unroll
        for (int i = 0; i < 8; i++) v[i] = (k == 1 && i == 0) ? w8 : cmul(v[i], w8);
        store8(row + 2048 * k, rim + 2048 * k, v);
      }
    }
    {
      z1.y = -z1.y; Z.y = -Z.y;
      const cf z2 = cmul(z1, z1);
      cf h[8], v[8];
      h[0].x = 2.f * blo(pcr) * dt; h[0].y = -2.f * blo(pci) * dt;
      h[1] = cmul(h[0], z1);
#pragma unroll
      for (int i = 2; i < 8; i++) h[i] = cmul(h[i - 2], z2);
      store8(row + 4 * 2048, rim + 4 * 2048, h);
      const cf h8 = cmul(h[6], z2);
      v[0] = cmul(h[0], Z); v[2] = cmul(h[2], Z); v[3] = cmul(h[4], Z); v[6] = cmul(h[6], Z); v[7] = cmul(h8, Z);
      v[1] = v[0]; v[4] = v[5] = v[3];
      store8(row + 5 * 2048, rim + 5 * 2048, v);
      h[0] = cmul(v[0], Z); h[1] = cmul(v[3], Z); h[3] = cmul(v[7], Z); h[4] = cmul(h[0], Z); h[5] = cmul(h[1], Z); h[7] = cmul(h[3], Z);
      h[2] = h[1]; h[6] = h[5];
      store8(row + 6 * 2048, rim + 6 * 2048, h);
      const cf Z2 = cmul(Z, Z);
      v[0] = cmul(h[0], Z2); v[1] = cmul(h[3], Z2); v[2] = cmul(h[4], Z2); v[3] = cmul(h[7], Z2);
#pragma unroll
      for (int i = 4; i < 8; i++) v[i] = cmul(v[i - 4], Z2);
      store8(row + 7 * 2048, rim + 7 * 2048, v);
    }
    TL(17);
    if (u < 2) bar_arrive(NB_W2, 512);
    fence_async();
    bar_sync(NB_WG0 + u, 128);
    TL(13);
    float c[32];
    wg_fence();
    kgen_mma<0>(c, desc_lo(tab) | ((uint64_t)((tim - tab) >> 4) << 16) | (64ull << 32));
    wg_commit();
    cluster_wait();
    {
      const uint4 x = ldg128(p.tab->thr[0][tid]), y = ldg128(p.tab->thr[1][tid]), a = ldg128(p.tab->thr[2][tid]), b = ldg128(p.tab->thr[3][tid]);
      A1[0] = x.x; A1[1] = x.y; A1[2] = x.z; A1[3] = x.w; A1[4] = y.x; A1[5] = y.y; A1[6] = y.z; A1[7] = y.w;
      tc[0] = a.x; tc[1] = a.y; tc[2] = a.z; tc[3] = a.w; ts[0] = b.x; ts[1] = b.y; ts[2] = b.z; ts[3] = b.w;
    }
    wg_wait<0>(); tie_all(c);
    TL(26);
    if (u < 2) bar_arrive(NB_K4, 384); else if (u < 4) bar_arrive(NB_V, 288);
    cluster_arrive();
    bar_sync(NB_WG0 + u, 128);
    if (w == 0 && elect()) {
      tma_load4(tab + T_HA, &p.th, 0, 0, 5 * cl + u, rank, mb + 8 * (MB_HA + u));
      if (u == 4) tma_load3(sb + OFF_Q2, &p.tq2, ch0, 8 * rank, 0, mb + 8 * MB_Q2);
    }
    __syncwarp();
    const uint32_t k0 = pack(c[0] + c[6], c[1] + c[7]), k1 = pack(c[8] + c[14], c[9] + c[15]);
    const uint32_t k2 = pack(c[16] + c[22], c[17] + c[23]), k3 = pack(c[24] + c[30], c[25] + c[31]);
    const uint32_t ka = tab + 16 * (8 * w + (g ^ w));
    sts32(ka + 4 * t, k0);
    sts32(ka + 512 + 4 * t, k1);
    sts64(ka + 1024 + 512 * (t >> 1) + 8 * (t & 1), prmt(k2, 0, 0x1010), (t & 1) ? prmt(k2, 0, 0x3232) : k2);
    const uint32_t lo = prmt(k3, 0, 0x1010), hi = prmt(k3, 0, 0x3232);
    sts128(ka + 2048 + 512 * t, lo, lo, (g & 1) ? hi : k3, hi);
    put_exp(sb + OFF_MX + u * 64 + 4 * w, amax2(amax2(k0, k1), amax2(k2, k3)), lane);
    TL(15);
  }
  if (u < 2) {
    mbar_wait(mb + 8 * MB_XQ);
    TL(18);
    uint32_t x0[3][4], x1[3][4];
#pragma unroll
    for (int k = 0; k < 3; k++) { ldsm4t(x0[k], sb + OFF_TQ + w * 2560 + toff + 16 * (u + 2 * k)); ldsm4t(x1[k], sb + OFF_TQ + (w + 4) * 2560 + toff + 16 * (u + 2 * k)); }
#pragma unroll
    for (int k = 0; k < 3; k++)
      if (u + 2 * k < 5) {
        put(OFF_YB + 8 * (u + 2 * k) * YPITCH, OFF_UX + (u + 2 * k) * 4096, uoff, x0[k]);
        put(OFF_YB + 8 * (u + 2 * k) * YPITCH, OFF_UX + (u + 2 * k) * 4096, (uoff ^ 32) + 256, x1[k]);
      }
    TL(3);
  }
  fence_async();
  bar_sync(NB_WG0 + u, 128);
  mbar_wait(mb + 8 * MB_CF);
  if (u < 2) {
    TL(4);
#pragma unroll
    for (int k = 0; k < 3; k++)
      if (u + 2 * k < 5) send(OFF_YB + 8 * (u + 2 * k) * YPITCH, YPITCH, OFF_UX + (u + 2 * k) * 4096 + 512 * rank, OFF_MB + 8 * (MB_UX + u + 2 * k));
    TL(7);
    if (wid == 7) {
      bar_sync(NB_V, 288);
      if (elect()) {
        mbar_expect(mb + 8 * MB_KV, 20480);
        tma_load4(sb + OFF_TV, &p.tv, ch0, 0, 0, 8 * rank, mb + 8 * MB_KV);
      }
      __syncwarp();
    }
    float s0 = 0.f;
#pragma unroll
    for (int j = 0; j < 5; j++) {
      const uint4 gw = lds128(sb + OFF_SP + 160 * u + 16 * j), x = lds128(sb + OFF_TQ + (tid + 128 * u) * 80 + 16 * j);
      const uint32_t m0 = hmul2(x.x, gw.x), m1 = hmul2(x.y, gw.y), m2 = hmul2(x.z, gw.z), m3 = hmul2(x.w, gw.w);
      s0 += ((blo(m0) + bhi(m0)) + (blo(m1) + bhi(m1))) + ((blo(m2) + bhi(m2)) + (blo(m3) + bhi(m3)));
    }
    tag = (lds64(mb + 8 * MB_TAG).x >> 4) + 1;
    asm volatile("st.relaxed.gpu.global.u64 [%0], %1;" :: "l"(p.part + cl * SEQ + rank * 256 + 8 * (8 * t + g) + w + 4 * u),
                 "l"(((uint64_t)tag << 32) | __float_as_uint(s0)) : "memory");
    __syncwarp();
    if (lane == 0) mbar_arrive(mb + 8 * MB_XD);
    TL(8);
  }

#pragma unroll
  for (int isA = 0; isA < 2; isA++) {
    if (isA) {
      uint64_t ga[NCL];
      const int slot = tid + 128 * (u & 1);
      const uint2* gp = p.part + rank * 256 + slot;
      auto gload = [&]() {
#pragma unroll
        for (int k = 0; k < NCL; k++) asm volatile("ld.relaxed.gpu.global.u64 %0, [%1];" : "=l"(ga[k]) : "l"(gp + k * SEQ) : "memory");
      };
      if ((u & 6) == 2) gload();
      cluster_wait();
      mbar_wait(mb + 8 * MB_XD);
      mbar_wait(mb + 8 * MB_KV);
      TL(21);
      {
        const int k = u;
        const uint32_t hoff = (4 * (4 + 2 * (mi & 1) + jj) + ((tq + 3) & 3)) * 80 + (tq ? 2560 : 0) + 16 * k;
        uint32_t E[2][6], V[2][4];
        const uint2 psw = lds64(sb + OFF_SP + 160 * k + 80 + 8 * g);
#pragma unroll
        for (int hf = 0; hf < 2; hf++) {
          const int ah = 4 * hf + w;
          uint32_t K[4];
          ldsm4t(K, sb + OFF_TK + (ah + 1) * 2560 + toff + 16 * k);
          ldsm2t(E[hf][0], E[hf][1], sb + OFF_TK + ah * 2560 + hoff);
          ldsm4t(V[hf], sb + OFF_TV + ah * 2560 + toff + 16 * k);
          E[hf][2] = K[0]; E[hf][3] = K[1]; E[hf][4] = K[2]; E[hf][5] = K[3];
        }
        const uint32_t w0 = prmt(psw.x, 0, 0x1010), w1 = prmt(psw.x, 0, 0x3232), w2 = prmt(psw.y, 0, 0x1010), w3 = prmt(psw.y, 0, 0x3232);
        uint32_t o[2][4];
#pragma unroll
        for (int hf = 0; hf < 2; hf++) {
          uint32_t O[5];
#pragma unroll
          for (int i = 0; i < 5; i++) O[i] = prmt(E[hf][i], E[hf][i + 1], 0x5432);
#pragma unroll
          for (int i = 0; i < 4; i++) {
            o[hf][i] = hmul2(hfma2(E[hf][i + 2], w0, hfma2(O[i + 1], w1, hfma2(E[hf][i + 1], w2, hmul2(O[i], w3)))), V[hf][i]);
          }
          put(OFF_YA + 8 * k * YPITCH, OFF_T + k * KTAB + T_UKV, hf ? (uoff ^ 32) + 256 : uoff, o[hf]);
        }
        fence_async();
        bar_sync(NB_WG0 + u, 128);
        send(OFF_YA + 8 * k * YPITCH, YPITCH, OFF_T + k * KTAB + T_UKV + 512 * rank, OFF_MB + 8 * (MB_UKV + k));
      }
      TL(22);
      if ((u & 6) == 2) {
        tag = (lds64(mb + 8 * MB_TAG).x >> 4) + 1;
        float s;
        bool ok;
#pragma unroll 1
        for (int it = 0;; it++) {
          ok = true; s = 0.f;
#pragma unroll
          for (int k = 0; k < NCL; k++) { ok = ok && (uint32_t)(ga[k] >> 32) == tag; s += __uint_as_float((uint32_t)ga[k]); }
          if (ok || it == 4000) break;
          gload();
        }
        if (!ok) {
          const uint32_t* xr = (const uint32_t*)(p.q + (size_t)(rank * 256 + 32 * (slot & 7) + (slot >> 3)) * DCH);
          const uint32_t* gr = (const uint32_t*)p.gate_w;
          s = 0.f;
    #pragma unroll 1
          for (int k = 0; k < DCH / 2; k++) { const uint32_t m = hmul2(__ldg(xr + k), __ldg(gr + k)); s += blo(m) + bhi(m); }
        }
        const float g0 = bf16r(sigmoidf_(bf16r(s)));
        sts64(sb + OFF_GB + 8 * slot, pack(g0, g0), pack(1.f - g0, 1.f - g0));
        __syncwarp();
        if (lane == 0) mbar_arrive(mb + 8 * MB_Q2);
      }
      TL(11);
      mbar_wait(mb + 8 * (MB_HA + u));
      put_exp(sb + OFF_MX + u * 64 + 32 + 4 * w, seq_mag(tab + T_HA + 16 * tid), lane);
      bar_sync(NB_WG0 + u, 128);
    }
    {
      TL(1 + isA);
      const uint32_t usrc = isA ? tab + T_UKV : sb + OFF_UX + u * 4096;
      const uint32_t mxa = sb + OFF_MX + u * 64 + 32 * isA;
      const uint32_t pd = lds16(sb + OFF_SP + 160 * u + 144 + 4 * isA);
      float D[32];
      uint32_t As[8], F[16], H[16], X[16];
      const uint32_t eh = min(max((int)get_exp(mxa), (int)((pd >> 7) & 0xff) - 5), 240);
      scale_a1(As, A1, 248 - eh);
      wg_fence();
      stage1(D, As, isA ? tab + T_HA : tab);
      wg_commit();
      wg_wait<0>(); tie_all(D);
      fwd_mid(F, D, tc, ts);
      wg_fence();
      stage2<0>(H, F, sb + OFF_CF);
      wg_commit();
      mbar_wait(mb + 8 * ((isA ? MB_UKV : MB_UX) + u));
      TL(5 + isA);
      put_exp(mxa + 16 + 4 * w, seq_mag(usrc + 16 * tid), lane);
      bar_sync(NB_WG0 + u, 128);
      const uint32_t eu = min(get_exp(mxa + 16), 240u);
      scale_a1(As, A1, 250 - eu);
      wg_wait<0>(); tie_all(H);
      wg_fence();
      stage1(D, As, usrc);
      wg_commit();
      wg_wait<0>(); tie_all(D);
      fwd_mid(F, D, tc, ts);
      wg_fence();
      stage2<0>(X, F, sb + OFF_CF);
      wg_commit();
      {
        const float dsk = blo(pd) * __uint_as_float((248 - eh) << 23);
        const uint32_t d2 = packh(dsk, dsk);
#pragma unroll
        for (int j = 0; j < 4; j++) H[2 * j] = U2(__hadd2(H2(H[2 * j]), H2(d2)));
      }
      wg_wait<0>(); tie_all(X);
#pragma unroll
      for (int j = 0; j < 4; j++) {
        const uint32_t h0r = H[2 * j], h1r = H[2 * j + 1], h0i = H[8 + 2 * j], h1i = H[9 + 2 * j];
        const uint32_t x0r = X[2 * j], x1r = X[2 * j + 1], x0i = X[8 + 2 * j], x1i = X[9 + 2 * j];
        F[2 * j] = ffma(x0r, h0r, fneg(fmul(x0i, h0i)));
        F[8 + 2 * j] = ffma(x0r, h0i, fmul(x0i, h0r));
        F[2 * j + 1] = ffma(x1r, h0r, ffma(fneg(x1i), h0i, ffma(x0r, h1r, fneg(ffma(x0i, h1i, F[8 + 2 * j])))));
        F[9 + 2 * j] = ffma(x1r, h0i, ffma(x1i, h0r, ffma(x0r, h1i, ffma(x0i, h1r, F[2 * j]))));
      }
      wg_fence();
      stage2<1>(H, F, sb + OFF_CF);
      wg_commit();
      wg_wait<0>(); tie_all(H);
      {
        const uint32_t va = tab + (16 * w + (lane & 15)) * 128;
        const int vx = (lane >> 4) ^ (lane & 7);
#pragma unroll
        for (int j = 0; j < 4; j++) {
          uint32_t V[4];
#pragma unroll
          for (int b = 0; b < 2; b++) {
            const uint32_t er = H[2 * j + b], ei = H[8 + 2 * j + b];
            V[2 * b] = ffma(er, tc[j], fneg(fmul(ei, ts[j])));
            V[2 * b + 1] = ffma(ei, tc[j], fmul(er, ts[j]));
          }
          stsm4(va + ((vx ^ (2 * j)) << 4), V);
        }
      }
      fence_async();
      bar_sync(NB_WG0 + u, 128);
      float O[16];
      {
        const uint64_t dv = desc_lo(tab) | (1ull << 16) | (64ull << 32) | (1ull << 62);
        const uint64_t dl = desc_lo(sb + OFF_CL) | (32ull << 16) | (8ull << 32);
        wg_fence();
        ss32<0, 0, 0>(O, dv, dl); ss32<1, 128, 64>(O, dv, dl); ss32<1, 256, 128>(O, dv, dl); ss32<1, 384, 192>(O, dv, dl);
        wg_commit();
      }
      wg_wait<0>(); tie_all(O);
      {
        const uint32_t co = ((8 * w + g) ^ (2 * t)) * 16;
        const int yo = (isA ? OFF_YA : OFF_YB) + (8 * u + rank) * YPITCH, ym = OFF_MB + 8 * (MB_Y + u);
        const uint32_t us = min(max((int)(eu + eh) - 127, 0), 254) * 0x00800080u;
        const uint32_t a0 = hmul2(pack(O[0], O[1]), us), a1 = hmul2(pack(O[4], O[5]), us), a2 = hmul2(pack(O[8], O[9]), us), a3 = hmul2(pack(O[12], O[13]), us);
        const uint32_t b0 = hmul2(pack(O[2], O[3]), us), b1 = hmul2(pack(O[6], O[7]), us), b2 = hmul2(pack(O[10], O[11]), us), b3 = hmul2(pack(O[14], O[15]), us);
        sts128((t == rank ? sb + yo : usrc + t * 512) + co, a0, a1, a2, a3);
        sts128((t + 4 == rank ? sb + yo : usrc + t * 512 + 2048) + co, b0, b1, b2, b3);
        fence_async();
        bar_sync(NB_WG0 + u, 128);
        send(usrc - sb, 512, yo, ym);
      }
      TL(9 + isA);
    }
  }

  {
    mbar_wait(mb + 8 * MB_Q2);
    uint2 gg[2][4];
    uint32_t qv[2][4];
#pragma unroll
    for (int hh = 0; hh < 2; hh++)
#pragma unroll
      for (int i = 0; i < 4; i++) gg[hh][i] = lds64(sb + OFF_GB + 8 * (64 * w + 32 * hh + 8 * i + g));
    const uint32_t qa = sb + OFF_Q2 + (64 * w + lane) * 80 + 16 * u;
    ldsm4(qv[0], qa);
    ldsm4(qv[1], qa + 2560);
    TL(24);
    mbar_wait(mb + 8 * (MB_Y + u));
    uint32_t ya[2][4], yb[2][4];
#pragma unroll
    for (int hh = 0; hh < 2; hh++) {
      const uint32_t yo = (8 * u + (lane & 7)) * YPITCH + ((8 * w + 4 * hh + (lane >> 3)) ^ (2 * (rank & 3))) * 16;
      ldsm4t(ya[hh], sb + OFF_YA + yo); ldsm4t(yb[hh], sb + OFF_YB + yo);
    }
#pragma unroll
    for (int hh = 0; hh < 2; hh++) {
      uint32_t o[4];
#pragma unroll
      for (int i = 0; i < 4; i++) o[i] = hadd2(hmul2(gg[hh][i].x, hmul2(qv[hh][i], ya[hh][i])), hmul2(gg[hh][i].y, yb[hh][i]));
      stsm4(qa + 2560 * hh, o);
    }
    TL(25);
  }
  cluster_arrive();
  bar_sync(NB_ROW0 + w, 160);
  {
    uint4 v[2];
#pragma unroll
    for (int k = 0; k < 2; k++) {
      const int i = 64 * u + 32 * k + lane, sl = (i * 205) >> 10, cc = i - 5 * sl;
      v[k] = lds128(sb + OFF_Q2 + (64 * w + 8 * (sl & 7) + (sl >> 3)) * 80 + cc * 16);
    }
#pragma unroll
    for (int k = 0; k < 2; k++) {
      const int i = 64 * u + 32 * k + lane, sl = (i * 205) >> 10, cc = i - 5 * sl;
      if (cc < nu)
        asm volatile("st.global.v4.u32 [%0], {%1,%2,%3,%4};" :: "l"(p.out + (size_t)(256 * rank + 32 * (sl >> 3) + 8 * w + (sl & 7)) * DCH + ch0 + 8 * cc),
                     "r"(v[k].x), "r"(v[k].y), "r"(v[k].z), "r"(v[k].w) : "memory");
    }
  }
  cluster_wait();
  TL(27);
  TL_DUMP();
}

typedef CUresult (*EncodeFn)(CUtensorMap*, CUtensorMapDataType, cuuint32_t, void*, const cuuint64_t*, const cuuint64_t*,
                             const cuuint32_t*, const cuuint32_t*, CUtensorMapInterleave, CUtensorMapSwizzle,
                             CUtensorMapL2promotion, CUtensorMapFloatOOBfill);

void encode(EncodeFn fn, CUtensorMap* tm, const void* ptr, int nd, const cuuint64_t* dims, const cuuint64_t* strides,
            const cuuint32_t* box, CUtensorMapSwizzle swz) {
  cuuint32_t es[4] = {1, 1, 1, 1};
  fn(tm, CU_TENSOR_MAP_DATA_TYPE_BFLOAT16, nd, const_cast<void*>(ptr), dims, strides, box, es, CU_TENSOR_MAP_INTERLEAVE_NONE,
     swz, CU_TENSOR_MAP_L2_PROMOTION_L2_128B, CU_TENSOR_MAP_FLOAT_OOB_FILL_NONE);
}
void map1(EncodeFn fn, CUtensorMap* tm, const void* ptr, int nhi) {
  const cuuint64_t dims[4] = {DCH, 4, 8, SEQ / 32}, strides[3] = {8 * DCH * 2, DCH * 2, 32 * DCH * 2};
  const cuuint32_t box[4] = {CPC, 4, 8, (cuuint32_t)nhi};
  encode(fn, tm, ptr, 4, dims, strides, box, CU_TENSOR_MAP_SWIZZLE_NONE);
}
void map2(EncodeFn fn, CUtensorMap* tm, const void* ptr, int nr) {
  const cuuint64_t dims[3] = {DCH, SEQ / 32, 32}, strides[2] = {32 * DCH * 2, DCH * 2};
  const cuuint32_t box[3] = {CPC, 8, (cuuint32_t)nr};
  encode(fn, tm, ptr, 3, dims, strides, box, CU_TENSOR_MAP_SWIZZLE_NONE);
}

}

extern "C" void kernel_launch(void* const* d_in, const int* in_sizes, int n_in, void* d_out, int out_size) {
  (void)in_sizes; (void)n_in; (void)out_size;
  static EncodeFn fn = nullptr;
  static void *tab = nullptr, *cnt = nullptr, *part = nullptr;
  if (!fn) {
    cudaGetSymbolAddress(&tab, d_tab);
    cudaGetSymbolAddress(&cnt, g_cnt);
    cudaGetSymbolAddress(&part, g_part);
    cudaDriverEntryPointQueryResult qr;
    cudaGetDriverEntryPoint("cuTensorMapEncodeTiled", (void**)&fn, cudaEnableDefault, &qr);
    cudaFuncSetAttribute(fused_kernel, cudaFuncAttributeMaxDynamicSharedMemorySize, SMEM_BYTES);
  }
  Params p;
  map1(fn, &p.tq, d_in[0], 8);
  map1(fn, &p.tk, d_in[1], 9);
  map1(fn, &p.tv, d_in[2], 8);
  map2(fn, &p.tq2, d_in[0], 32);
  p.out = (__nv_bfloat16*)d_out;
  {
    const cuuint64_t dims[4] = {32, SEQ / 32, DCH / 8, 8}, strides[3] = {64, 8 * SEQ * 2, SEQ * 2};
    const cuuint32_t box[4] = {32, 64, 1, 1};
    encode(fn, &p.th, d_in[4], 4, dims, strides, box, CU_TENSOR_MAP_SWIZZLE_64B);
  }
  p.tab = (const Tables*)tab;
  p.cnt = (unsigned*)cnt;
  p.part = (uint2*)part;
  p.tl = nullptr;
  p.q = (const __nv_bfloat16*)d_in[0];
  p.shift_k = (const __nv_bfloat16*)d_in[3];
  p.ssm_D = (const __nv_bfloat16*)d_in[5];
  p.logA = (const __nv_bfloat16*)d_in[7];
  p.Aim = (const __nv_bfloat16*)d_in[8];
  p.Cre = (const __nv_bfloat16*)d_in[9];
  p.Cim = (const __nv_bfloat16*)d_in[10];
  p.logdt = (const __nv_bfloat16*)d_in[11];
  p.Dskip = (const __nv_bfloat16*)d_in[12];
  p.gate_w = (const __nv_bfloat16*)d_in[13];
  fused_kernel<<<NCL * CS, NTHREADS, SMEM_BYTES, cudaStreamPerThread>>>(p);
}
```

```cpp
#include <cuda_runtime.h>
#include <cuda_bf16.h>
#include <cuda_fp16.h>
#include <cuda.h>
#include <stdint.h>

#define TIMELINE 0

namespace {

constexpr int SEQ = 2048, DCH = 576, NMODE = 128;
constexpr int CS = 8, CPC = 40, NCL = 15, NTHREADS = 640;

constexpr int YPITCH = 528;
constexpr int KTAB = 16384;
constexpr int OFF_T = 0;
constexpr int T_UKV = 8192, T_HA = 12288;
constexpr int OFF_UX = 5 * KTAB;
constexpr int OFF_IM = OFF_UX + 20480;
constexpr int OFF_Q2 = OFF_IM;
constexpr int OFF_GB = OFF_Q2 + 20480;
constexpr int OFF_TV = OFF_IM + 3 * KTAB - 20480;
constexpr int OFF_CF = OFF_IM + 3 * KTAB;
constexpr int OFF_CL = OFF_CF + 8192;
constexpr int OFF_TQ = OFF_CL + 4096;
constexpr int OFF_YA = OFF_TQ;
constexpr int OFF_TK = OFF_TQ + 21120;
constexpr int OFF_YB = OFF_TK + 23040;
constexpr int OFF_MX = OFF_YB + 40 * YPITCH;
constexpr int OFF_SP = OFF_MX + 320;
constexpr int OFF_MB = OFF_SP + 5 * 160;
constexpr int OFF_TL = OFF_MB + 32 * 8;
constexpr int SMEM_BYTES = OFF_TL + (TIMELINE ? 1280 : 0);
static_assert(SMEM_BYTES <= 232448, "smem");
static_assert((OFF_TQ & 127) == 0 && (OFF_TK & 127) == 0 && (OFF_TV & 127) == 0 && (OFF_MB & 7) == 0 && (OFF_MX & 15) == 0, "align");

enum { MB_UX = 0, MB_UKV = 5, MB_Y = 10, MB_HA = 15, MB_XQ = 20, MB_KV = 21, MB_CF = 22, MB_Q2 = 23, MB_XD = 24, MB_TAG = 25 };
enum { NB_WG0 = 1, NB_ROW0 = 6, NB_ORD = 6, NB_K0 = 10, NB_LD = 11 };

constexpr double cos_turn(int m, int n) {
  m &= n - 1;
  if (m > n / 2) m = n - m;
  double sgn = 1.0;
  if (m > n / 4) { m = n / 2 - m; sgn = -1.0; }
  if (m == n / 4) return 0.0;
  const double x = 6.283185307179586476925 * m / n;
  double term = 1.0, sum = 1.0;
  for (int k = 1; k < 14; k++) { term *= -x * x / ((2 * k - 1) * (2 * k)); sum += term; }
  return sgn * sum;
}
constexpr uint32_t bf16_bits(double v) {
  if (v == 0.0) return 0;
  uint32_t sgn = 0;
  if (v < 0) { sgn = 0x8000; v = -v; }
  int e = 127;
  while (v < 1.0) { v *= 2.0; e--; }
  while (v >= 2.0) { v *= 0.5; e++; }
  const double f = v * 128.0;
  int m = (int)f;
  if (f - m > 0.5 || (f - m == 0.5 && (m & 1))) m++;
  return sgn | (uint32_t)((e << 7) + (m - 128));
}
constexpr uint32_t f16_bits(double v) {
  if (v == 0.0) return 0;
  uint32_t sgn = 0;
  if (v < 0) { sgn = 0x8000; v = -v; }
  int e = 15;
  while (v < 1.0) { v *= 2.0; e--; }
  const double f = v * 1024.0;
  int m = (int)f;
  if (f - m > 0.5 || (f - m == 0.5 && (m & 1))) m++;
  return sgn | (uint32_t)((e << 10) + (m - 1024));
}
constexpr uint32_t pair_bits(double lo, double hi) { return bf16_bits(lo) | (bf16_bits(hi) << 16); }
constexpr uint32_t pair_h(double lo, double hi) { return f16_bits(lo) | (f16_bits(hi) << 16); }
struct alignas(128) Tables {
  uint32_t mat[3072];
  uint32_t thr[4][128][4];
};
constexpr Tables make_tables() {
  Tables T{};
  for (int q = 0; q < 768; q++) {
    int m0 = 0, d0 = 0, d1 = 0;
    if (q < 512) {
      const int r = (q >> 6) * 8 + (q & 7), cc = (q >> 3) & 7;
      d0 = 4 * (r & 31); d1 = 2 * d0;
      m0 = 8 * (cc & 3) * d0 + ((r >> 5) == (cc >> 2) ? 0 : (r >> 5) ? 96 : 32);
    } else {
      const int r = ((q - 512) >> 5) * 8 + (q & 7), pc = (q >> 3) & 3;
      d0 = 4 * (8 * (r >> 4) + (r & 7)) + 1; d1 = 8 * d0;
      m0 = 2 * pc * d0 + ((r & 8) ? 32 : 0);
    }
    for (int e = 0; e < 4; e++) T.mat[4 * q + e] = pair_h(cos_turn(m0 + e * d1, 128), cos_turn(m0 + e * d1 + d0, 128));
  }
  for (int tid = 0; tid < 128; tid++) {
    const int kk = 4 * (tid >> 2) + 1, t = tid & 3;
    for (int q = 0; q < 4; q++) {
      const int m = (8 * q + 2 * t) * kk;
      T.thr[q >> 1][tid][2 * (q & 1)] = pair_bits(cos_turn(m, 128), cos_turn(m + kk, 128));
      T.thr[q >> 1][tid][2 * (q & 1) + 1] = pair_bits(cos_turn(m + 32, 128), cos_turn(m + kk + 32, 128));
      T.thr[2][tid][q] = pair_h(cos_turn(m, 4096), cos_turn(m + kk, 4096));
      T.thr[3][tid][q] = pair_h(cos_turn(m + 3072, 4096), cos_turn(m + kk + 3072, 4096));
    }
  }
  return T;
}
__device__ const Tables d_tab = make_tables();

struct Params {
  const __nv_bfloat16 *logA, *Aim, *Cre, *Cim, *logdt;
  const Tables* tab;
  unsigned* cnt;
  const __nv_bfloat16 *Dskip, *shift_k, *ssm_D, *gate_w, *q, *k, *v, *ssm_k;
  uint2* part;
  __nv_bfloat16* out;
  unsigned* tl;
  CUtensorMap tq, tk, tv, th, tq2;
};

__device__ uint2 g_part[NCL * SEQ];
__device__ unsigned g_cnt[CS * 32];
#define TL(i) do {} while (0)
#define TL_INIT() do {} while (0)
#define TL_DUMP() do {} while (0)

__device__ __forceinline__ uint32_t lds16(uint32_t a) { uint32_t v; asm volatile("ld.shared.u16 %0, [%1];" : "=r"(v) : "r"(a) : "memory"); return v; }
__device__ __forceinline__ uint2 lds64(uint32_t a) { uint2 v; asm volatile("ld.shared.v2.u32 {%0,%1}, [%2];" : "=r"(v.x), "=r"(v.y) : "r"(a) : "memory"); return v; }
__device__ __forceinline__ uint4 lds128(uint32_t a) { uint4 v; asm volatile("ld.shared.v4.u32 {%0,%1,%2,%3}, [%4];" : "=r"(v.x), "=r"(v.y), "=r"(v.z), "=r"(v.w) : "r"(a) : "memory"); return v; }
__device__ __forceinline__ void sts16(uint32_t a, uint32_t v) { asm volatile("st.shared.u16 [%0], %1;" :: "r"(a), "r"(v) : "memory"); }
__device__ __forceinline__ void sts32(uint32_t a, uint32_t v) { asm volatile("st.shared.u32 [%0], %1;" :: "r"(a), "r"(v) : "memory"); }
__device__ __forceinline__ void sts64(uint32_t a, uint32_t x, uint32_t y) { asm volatile("st.shared.v2.u32 [%0], {%1,%2};" :: "r"(a), "r"(x), "r"(y) : "memory"); }
__device__ __forceinline__ void sts128(uint32_t a, uint32_t x, uint32_t y, uint32_t z, uint32_t w) { asm volatile("st.shared.v4.u32 [%0], {%1,%2,%3,%4};" :: "r"(a), "r"(x), "r"(y), "r"(z), "r"(w) : "memory"); }
__device__ __forceinline__ void ldsm4t(uint32_t (&r)[4], uint32_t a) { asm volatile("ldmatrix.sync.aligned.m8n8.x4.trans.shared.b16 {%0,%1,%2,%3}, [%4];" : "=r"(r[0]), "=r"(r[1]), "=r"(r[2]), "=r"(r[3]) : "r"(a) : "memory"); }
__device__ __forceinline__ void ldsm2t(uint32_t& r0, uint32_t& r1, uint32_t a) { asm volatile("ldmatrix.sync.aligned.m8n8.x2.trans.shared.b16 {%0,%1}, [%2];" : "=r"(r0), "=r"(r1) : "r"(a) : "memory"); }
__device__ __forceinline__ void ldsm4(uint32_t (&r)[4], uint32_t a) { asm volatile("ldmatrix.sync.aligned.m8n8.x4.shared.b16 {%0,%1,%2,%3}, [%4];" : "=r"(r[0]), "=r"(r[1]), "=r"(r[2]), "=r"(r[3]) : "r"(a) : "memory"); }
__device__ __forceinline__ void stsm4(uint32_t a, const uint32_t (&r)[4]) { asm volatile("stmatrix.sync.aligned.m8n8.x4.shared.b16 [%0], {%1,%2,%3,%4};" :: "r"(a), "r"(r[0]), "r"(r[1]), "r"(r[2]), "r"(r[3]) : "memory"); }
__device__ __forceinline__ uint32_t pack(float lo, float hi) { uint32_t r; asm("cvt.rn.bf16x2.f32 %0, %1, %2;" : "=r"(r) : "f"(hi), "f"(lo)); return r; }
__device__ __forceinline__ float blo(uint32_t v) { return __uint_as_float(v << 16); }
__device__ __forceinline__ float bhi(uint32_t v) { return __uint_as_float(v & 0xffff0000u); }
__device__ __forceinline__ float bf16r(float x) { return blo(pack(x, 0.f)); }
__device__ __forceinline__ uint32_t hmul2(uint32_t a, uint32_t b) { uint32_t r; asm("mul.rn.bf16x2 %0, %1, %2;" : "=r"(r) : "r"(a), "r"(b)); return r; }
__device__ __forceinline__ uint32_t hadd2(uint32_t a, uint32_t b) { uint32_t r; asm("add.rn.bf16x2 %0, %1, %2;" : "=r"(r) : "r"(a), "r"(b)); return r; }
__device__ __forceinline__ uint32_t hfma2(uint32_t a, uint32_t b, uint32_t c) { uint32_t r; asm("fma.rn.bf16x2 %0, %1, %2, %3;" : "=r"(r) : "r"(a), "r"(b), "r"(c)); return r; }
__device__ __forceinline__ uint32_t packh(float lo, float hi) { uint32_t r; asm("cvt.rn.f16x2.f32 %0, %1, %2;" : "=r"(r) : "f"(hi), "f"(lo)); return r; }
__device__ __forceinline__ __half2 H2(uint32_t a) { return *reinterpret_cast<__half2*>(&a); }
__device__ __forceinline__ uint32_t U2(__half2 a) { return *reinterpret_cast<uint32_t*>(&a); }
__device__ __forceinline__ uint32_t fmul(uint32_t a, uint32_t b) { return U2(__hmul2(H2(a), H2(b))); }
__device__ __forceinline__ uint32_t ffma(uint32_t a, uint32_t b, uint32_t c) { return U2(__hfma2(H2(a), H2(b), H2(c))); }
__device__ __forceinline__ uint32_t fneg(uint32_t a) { return U2(__hneg2(H2(a))); }
__device__ __forceinline__ uint32_t amax2(uint32_t a, uint32_t b) { uint32_t r; asm("max.xorsign.abs.bf16x2 %0, %1, %2;" : "=r"(r) : "r"(a), "r"(b)); return r; }
__device__ __forceinline__ uint32_t prmt(uint32_t a, uint32_t b, uint32_t s) { return __byte_perm(a, b, s); }
__device__ __forceinline__ uint32_t ldraw(const __nv_bfloat16* p) { uint32_t v; asm volatile("ld.global.nc.u16 %0, [%1];" : "=r"(v) : "l"(p)); return v; }
__device__ __forceinline__ uint4 ldg128(const void* p) { uint4 v; asm volatile("ld.global.nc.v4.u32 {%0,%1,%2,%3}, [%4];" : "=r"(v.x), "=r"(v.y), "=r"(v.z), "=r"(v.w) : "l"(p)); return v; }
__device__ __forceinline__ void bar_sync(int id, int n) { asm volatile("bar.sync %0, %1;" :: "r"(id), "r"(n) : "memory"); }
__device__ __forceinline__ void bar_arrive(int id, int n) { asm volatile("bar.arrive %0, %1;" :: "r"(id), "r"(n) : "memory"); }
__device__ __forceinline__ void cluster_arrive() { asm volatile("barrier.cluster.arrive.relaxed.aligned;" ::: "memory"); }
__device__ __forceinline__ void cluster_wait() { asm volatile("barrier.cluster.wait.aligned;" ::: "memory"); }
__device__ __forceinline__ void fence_async() { asm volatile("fence.proxy.async.shared::cta;" ::: "memory"); }
__device__ __forceinline__ void fence_mbinit() { asm volatile("fence.mbarrier_init.release.cluster;" ::: "memory"); }
__device__ __forceinline__ uint32_t mapa(uint32_t a, uint32_t rank) { uint32_t r; asm("mapa.shared::cluster.u32 %0, %1, %2;" : "=r"(r) : "r"(a), "r"(rank)); return r; }
__device__ __forceinline__ void bulk_dsmem(uint32_t dst, uint32_t src, uint32_t mbar) {
  asm volatile("cp.async.bulk.shared::cluster.shared::cta.mbarrier::complete_tx::bytes [%0], [%1], 512, [%2];" :: "r"(dst), "r"(src), "r"(mbar) : "memory");
}
__device__ __forceinline__ void mbar_init(uint32_t m, uint32_t cnt) { asm volatile("mbarrier.init.shared::cta.b64 [%0], %1;" :: "r"(m), "r"(cnt) : "memory"); }
__device__ __forceinline__ void mbar_expect(uint32_t m, uint32_t bytes) { asm volatile("mbarrier.arrive.expect_tx.shared::cta.b64 _, [%0], %1;" :: "r"(m), "r"(bytes) : "memory"); }
__device__ __forceinline__ bool mbar_try(uint32_t m) {
  uint32_t done;
  asm volatile("{.reg .pred p; mbarrier.try_wait.parity.shared::cta.b64 p, [%1], 0; selp.u32 %0, 1, 0, p;}" : "=r"(done) : "r"(m) : "memory");
  return done;
}
__device__ __forceinline__ void mbar_wait(uint32_t m) {
  if (!mbar_try(m)) {
    int it = 0;
    while (!mbar_try(m) && ++it < (1 << 22)) {}
  }
}
__device__ __forceinline__ bool elect() {
  uint32_t e;
  asm volatile("{.reg .pred p; elect.sync _|p, 0xffffffff; selp.u32 %0, 1, 0, p;}" : "=r"(e));
  return e;
}
__device__ __forceinline__ void tma_load4(uint32_t dst, const CUtensorMap* tm, int c0, int c1, int c2, int c3, uint32_t mbar) {
  asm volatile("cp.async.bulk.tensor.4d.shared::cluster.global.mbarrier::complete_tx::bytes [%0], [%1, {%3, %4, %5, %6}], [%2];"
               :: "r"(dst), "l"(tm), "r"(mbar), "r"(c0), "r"(c1), "r"(c2), "r"(c3) : "memory");
}
__device__ __forceinline__ void tma_load3(uint32_t dst, const CUtensorMap* tm, int c0, int c1, int c2, uint32_t mbar) {
  asm volatile("cp.async.bulk.tensor.3d.shared::cluster.global.mbarrier::complete_tx::bytes [%0], [%1, {%3, %4, %5}], [%2];"
               :: "r"(dst), "l"(tm), "r"(mbar), "r"(c0), "r"(c1), "r"(c2) : "memory");
}
__device__ __forceinline__ void tma_store3(const CUtensorMap* tm, int c0, int c1, int c2, uint32_t src) {
  asm volatile("cp.async.bulk.tensor.3d.global.shared::cta.bulk_group [%0, {%2, %3, %4}], [%1];"
               :: "l"(tm), "r"(src), "r"(c0), "r"(c1), "r"(c2) : "memory");
}
__device__ __forceinline__ void wg_fence() { asm volatile("wgmma.fence.sync.aligned;" ::: "memory"); }
__device__ __forceinline__ void wg_commit() { asm volatile("wgmma.commit_group.sync.aligned;" ::: "memory"); }
template <int N> __device__ __forceinline__ void wg_wait() { asm volatile("wgmma.wait_group.sync.aligned %0;" :: "n"(N) : "memory"); }
template <int N> __device__ __forceinline__ void tie_all(uint32_t (&x)[N]) {
#pragma unroll
  for (int i = 0; i < N; i++) asm volatile("" : "+r"(x[i]) :: "memory");
}
template <int N> __device__ __forceinline__ void tie_all(float (&x)[N]) {
#pragma unroll
  for (int i = 0; i < N; i++) asm volatile("" : "+f"(x[i]) :: "memory");
}
#define R16(C, d) C(d[0]), C(d[1]), C(d[2]), C(d[3]), C(d[4]), C(d[5]), C(d[6]), C(d[7]), C(d[8]), C(d[9]), C(d[10]), C(d[11]), C(d[12]), C(d[13]), C(d[14]), C(d[15])
#define R32(C, d) R16(C, d), R16(C, (d + 16))
#define P16 "{%0,%1,%2,%3,%4,%5,%6,%7,%8,%9,%10,%11,%12,%13,%14,%15}"
#define P32 "{%0,%1,%2,%3,%4,%5,%6,%7,%8,%9,%10,%11,%12,%13,%14,%15,%16,%17,%18,%19,%20,%21,%22,%23,%24,%25,%26,%27,%28,%29,%30,%31}"
template <int SD, int TB, int OFF> __device__ __forceinline__ void rs64(float* d, const uint32_t* a, uint64_t db) {
  if (SD) asm volatile("{.reg .b64 db; add.s64 db, %36, %37; wgmma.mma_async.sync.aligned.m64n64k16.f32.bf16.bf16 " P32 ", {%32,%33,%34,%35}, db, 1, 1, 1, %38;}"
                       : R32("+f", d) : "r"(a[0]), "r"(a[1]), "r"(a[2]), "r"(a[3]), "l"(db), "n"(OFF), "n"(TB));
  else asm volatile("{.reg .b64 db; add.s64 db, %36, %37; wgmma.mma_async.sync.aligned.m64n64k16.f32.bf16.bf16 " P32 ", {%32,%33,%34,%35}, db, 0, 1, 1, %38;}"
                    : R32("=f", d) : "r"(a[0]), "r"(a[1]), "r"(a[2]), "r"(a[3]), "l"(db), "n"(OFF), "n"(TB));
}
template <int SD, int TB, int OFF> __device__ __forceinline__ void rs64h(uint32_t* d, const uint32_t* a, uint64_t db) {
  if (SD) asm volatile("{.reg .b64 db; add.s64 db, %20, %21; wgmma.mma_async.sync.aligned.m64n64k16.f16.f16.f16 " P16 ", {%16,%17,%18,%19}, db, 1, 1, 1, %22;}"
                       : R16("+r", d) : "r"(a[0]), "r"(a[1]), "r"(a[2]), "r"(a[3]), "l"(db), "n"(OFF), "n"(TB));
  else asm volatile("{.reg .b64 db; add.s64 db, %20, %21; wgmma.mma_async.sync.aligned.m64n64k16.f16.f16.f16 " P16 ", {%16,%17,%18,%19}, db, 0, 1, 1, %22;}"
                    : R16("=r", d) : "r"(a[0]), "r"(a[1]), "r"(a[2]), "r"(a[3]), "l"(db), "n"(OFF), "n"(TB));
}
template <int SD, int OFFA, int OFFB> __device__ __forceinline__ void ss32(float* d, uint64_t da, uint64_t db) {
  if (SD) asm volatile("{.reg .b64 da, db; add.s64 da, %16, %18; add.s64 db, %17, %19; wgmma.mma_async.sync.aligned.m64n32k16.f32.f16.f16 " P16 ", da, db, 1, 1, 1, 1, 1;}"
                       : R16("+f", d) : "l"(da), "l"(db), "n"(OFFA), "n"(OFFB));
  else asm volatile("{.reg .b64 da, db; add.s64 da, %16, %18; add.s64 db, %17, %19; wgmma.mma_async.sync.aligned.m64n32k16.f32.f16.f16 " P16 ", da, db, 0, 1, 1, 1, 1;}"
                    : R16("=f", d) : "l"(da), "l"(db), "n"(OFFA), "n"(OFFB));
}
#define KGEN_ASM(SD) "{.reg .b64 da, db; add.s64 da, %32, %33; add.s64 db, %32, %34;\n" \
  "wgmma.mma_async.sync.aligned.m64n64k16.f32.bf16.bf16 " P32 ", da, db, " SD ", 1, 1, 1, 1;}"
template <int KS> __device__ __forceinline__ void kgen_mma(float (&c)[32], uint64_t da) {
  if (KS) asm volatile(KGEN_ASM("1") : R32("+f", c) : "l"(da), "n"(8 * KS), "n"(8 * KS + 512));
  else asm volatile(KGEN_ASM("0") : R32("=f", c) : "l"(da), "n"(8 * KS), "n"(8 * KS + 512));
  if constexpr (KS < 7) kgen_mma<KS + 1>(c, da);
}
__device__ __forceinline__ uint64_t desc_lo(uint32_t a) { return (uint64_t)((a & 0x3FFFF) >> 4); }
__device__ __forceinline__ void stage1(float (&D)[32], const uint32_t (&A1)[8], uint32_t src) {
  const uint64_t du = desc_lo(src) | (128ull << 16) | (32ull << 32) | (2ull << 62);
  rs64<0, 1, 0>(D, A1, du); rs64<1, 1, 64>(D, A1 + 4, du);
}
template <int INV> __device__ __forceinline__ void stage2(uint32_t (&X)[16], const uint32_t (&F)[16], uint32_t cf) {
  constexpr int KS = INV ? 16 : 128, TB = INV ? 0 : 1;
  const uint64_t dc = desc_lo(cf) | (INV ? (8ull << 16) | (64ull << 32) : (64ull << 16) | (8ull << 32));
  rs64h<0, TB, 0>(X, F, dc); rs64h<1, TB, KS>(X, F + 4, dc); rs64h<1, TB, 2 * KS>(X, F + 8, dc); rs64h<1, TB, 3 * KS>(X, F + 12, dc);
}
__device__ __forceinline__ void fwd_mid(uint32_t (&F)[16], const float (&D)[32], const uint32_t (&tc)[4], const uint32_t (&ts)[4]) {
#pragma unroll
  for (int j = 0; j < 4; j++)
#pragma unroll
    for (int b = 0; b < 2; b++) {
      const int i = 4 * j + 16 * b;
      const uint32_t ar = packh(D[i], D[i + 1]), ai = packh(D[i + 2], D[i + 3]);
      F[2 * j + b] = ffma(ar, tc[j], fmul(ai, ts[j]));
      F[8 + 2 * j + b] = ffma(ai, tc[j], fneg(fmul(ar, ts[j])));
    }
}
__device__ __forceinline__ void put_exp(uint32_t a, uint32_t m, int lane) {
  m = __reduce_max_sync(0xffffffffu, max(m & 0x7f80u, (m >> 16) & 0x7f80u));
  if (lane == 0) sts32(a, m);
}
__device__ __forceinline__ uint32_t seq_mag(uint32_t a) {
  const uint4 x = lds128(a), y = lds128(a + 2048);
  return amax2(amax2(amax2(x.x, x.y), amax2(x.z, x.w)), amax2(amax2(y.x, y.y), amax2(y.z, y.w)));
}
__device__ __forceinline__ uint32_t get_exp(uint32_t a) { const uint4 v = lds128(a); return max(max(v.x, v.y), max(v.z, v.w)) >> 7; }
__device__ __forceinline__ void scale_a1(uint32_t (&As)[8], const uint32_t (&A1)[8], uint32_t field) {
#pragma unroll
  for (int i = 0; i < 8; i++) As[i] = hmul2(A1[i], field * 0x00800080u);
}

struct cf { float x, y; };
__device__ __forceinline__ cf cmul(cf a, cf b) { cf r; r.x = fmaf(a.x, b.x, -a.y * b.y); r.y = fmaf(a.x, b.y, a.y * b.x); return r; }
__device__ __forceinline__ cf cexp_p(float lr2, float lt, float p) {
  float m;
  asm("ex2.approx.ftz.f32 %0, %1;" : "=f"(m) : "f"(lr2 * p));
  float t = lt * p;
  t = (t - rintf(t)) * 6.283185307179586f;
  cf r; r.x = m * __cosf(t); r.y = m * __sinf(t); return r;
}
__device__ __forceinline__ void store8(uint32_t a, uint32_t b, const cf (&v)[8]) {
  sts128(a, pack(v[0].x, v[1].x), pack(v[2].x, v[3].x), pack(v[4].x, v[5].x), pack(v[6].x, v[7].x));
  sts128(b, pack(v[0].y, v[1].y), pack(v[2].y, v[3].y), pack(v[4].y, v[5].y), pack(v[6].y, v[7].y));
}
__device__ __forceinline__ void mbar_arrive(uint32_t m) { asm volatile("mbarrier.arrive.shared::cta.b64 _, [%0];" :: "r"(m) : "memory"); }
__device__ __forceinline__ float sigmoidf_(float s) { return __frcp_rn(1.f + __expf(-s)); }

__global__ void __cluster_dims__(CS, 1, 1) __launch_bounds__(NTHREADS, 1) fused_kernel(const __grid_constant__ Params p) {
  extern __shared__ __align__(1024) uint8_t smem[];
  TL_INIT();
  TL(31);
  const int wid = __shfl_sync(0xffffffffu, threadIdx.x >> 5, 0);
  const uint32_t sb = (uint32_t)__cvta_generic_to_shared(smem);
  const uint32_t mb = sb + OFF_MB;
  const int u = wid >> 2, w = wid & 3;
  const int tid = threadIdx.x & 127, lane = tid & 31, g = lane >> 2, t = lane & 3;
  const int cl = blockIdx.x >> 3, rank = blockIdx.x & 7;
  const int ch0 = cl * CPC;
  const int nu = min(5, (DCH - ch0) >> 3);
  const bool act = u < nu;

  if (u == 4 && elect()) {
#pragma unroll
    for (int i = 0; i < 5; i++) mbar_init(mb + 40 * w + 8 * i, w == 3 ? 1 : w == 2 ? 3 : 2);
    if (w == 3) {
      mbar_init(mb + 8 * MB_XQ, 5); mbar_init(mb + 8 * MB_KV, 1); mbar_init(mb + 8 * MB_CF, 2); mbar_init(mb + 8 * MB_Q2, 9); mbar_init(mb + 8 * MB_XD, 20);
    }
    fence_mbinit();
    if (w == 3) {
      mbar_expect(mb + 8 * MB_CF, 12288);
      asm volatile("cp.async.bulk.shared::cluster.global.mbarrier::complete_tx::bytes [%0], [%1], %2, [%3];"
                   :: "r"(sb + OFF_CF), "l"(p.tab->mat), "r"(12288), "r"(mb + 8 * MB_CF) : "memory");
      asm volatile("cp.async.bulk.prefetch.L2.global [%0], 8192;" :: "l"(p.tab->thr) : "memory");
      mbar_expect(mb + 8 * MB_XQ, 20480); mbar_expect(mb + 8 * MB_KV, 23040 + 20480); mbar_expect(mb + 8 * MB_Q2, 20480);
    }
#pragma unroll
    for (int i = 0; i < 5; i++) mbar_expect(mb + 40 * w + 8 * i, w == 3 ? 4096 : w == 2 ? 7168 : 3584);
  }
  uint32_t pla, pai, pcr, pci, pdt, tag = 0;
  uint4 psm;
  {
    const int ch = act ? ch0 + 8 * u + rank : 0, o = ch * NMODE + tid;
    pla = ldraw(p.logA + o); pdt = ldraw(p.logdt + ch); pai = ldraw(p.Aim + o); pcr = ldraw(p.Cre + o); pci = ldraw(p.Cim + o);
    if (w == 1) {
      if (lane < 9) psm = ldg128(lane < 5 ? p.gate_w + (lane < nu ? ch0 + 8 * lane : 0) : p.shift_k + (act ? ch0 + 8 * u : 0) * 4 + 8 * (lane - 5));
      else { psm.x = ldraw(p.Dskip + ch); psm.y = ldraw(p.ssm_D + ch); }
    }
    if (wid == 16 && lane < 2) asm volatile("atom.relaxed.gpu.global.add.u32 %0, [%1], %2;" : "=r"(tag) : "l"(&p.cnt[rank * 32 + lane]), "r"(cl == 0 ? 16 - (NCL - 1) : 1) : "memory");
  }
  if (wid == 19 && elect()) {
    tma_load4(sb + OFF_TQ, &p.tq, ch0, 0, 0, 8 * rank, mb + 8 * MB_XQ);
    TL(20);
  }
  __syncwarp();
  cluster_arrive();
  TL(0);

  const uint32_t tab = sb + OFF_T + u * KTAB;
  const int mi = lane >> 3, tq = (lane & 7) >> 1, jj = lane & 1;
  const uint32_t toff = (4 * (2 * mi + jj) + tq) * 80;
  const uint32_t uoff = 16 * (4 * w + (t ^ (w >> 1)));
  auto put = [&](int stage, int dst, uint32_t off, const uint32_t (&v)[4]) {
    sts128(sb + off + (g == rank ? dst + 512 * rank : stage + g * YPITCH), v[0], v[1], v[2], v[3]);
  };
  const int d0 = rank ^ (2 * w), d1 = d0 ^ 1;
  const uint32_t rb0 = mapa(sb, d0), rb1 = mapa(sb, d1);
  auto send = [&](int stage, int pitch, int dst, int mbar) {
    if (elect()) {
      if (w) bulk_dsmem(rb0 + dst, sb + stage + d0 * pitch, rb0 + mbar); else mbar_arrive(sb + mbar);
      bulk_dsmem(rb1 + dst, sb + stage + d1 * pitch, rb1 + mbar);
    }
    __syncwarp();
  };

  if (w == 1 && lane < 10) sts128(sb + OFF_SP + 160 * u + 16 * lane, psm.x, psm.y, psm.z, psm.w);
  uint32_t A1[8], tc[4], ts[4];
  {
    const float dt = bf16r(expf(blo(pdt)));
    const float lr2 = (-bf16r(expf(blo(pla))) * dt) * 1.4426950408889634f;
    const float lt = (blo(pai) * dt) * 0.15915494309189535f;
    const uint32_t tim = sb + (u == 0 ? OFF_YB : u == 1 ? OFF_TK : OFF_IM + (u - 2) * KTAB);
    const uint32_t row = tab + tid * 16, rim = tim + tid * 16;
    const cf w1 = cexp_p(lr2, lt, 8.f);
    cf z1 = cexp_p(lr2, lt, 1.f), Z = cexp_p(lr2, lt, 256.f);
    if (lr2 != 123.f) TL(16);
    if (wid == 16) {
      if (lane == 0) { sts32(mb + 8 * MB_TAG, tag); mbar_arrive(mb + 8 * MB_CF); }
      if (elect()) {
        const uint32_t o = blockIdx.x * 9856u, n = min(9856u, SEQ * DCH - o) * 2;
        asm volatile("cp.async.bulk.prefetch.L2.global [%0], %1;" :: "l"(p.k + o), "r"(n) : "memory");
        asm volatile("cp.async.bulk.prefetch.L2.global [%0], %1;" :: "l"(p.v + o), "r"(n) : "memory");
        asm volatile("cp.async.bulk.prefetch.L2.global [%0], %1;" :: "l"(p.ssm_k + o), "r"(n) : "memory");
      }
      __syncwarp();
    }
    TL(12);
    {
      cf v[8];
      v[0].x = 1.f; v[0].y = 0.f; v[1] = w1; v[2] = cmul(w1, w1); v[3] = cmul(v[2], w1);
      const cf w4 = cmul(v[2], v[2]);
      v[4] = w4; v[5] = cmul(v[1], w4); v[6] = cmul(v[2], w4); v[7] = cmul(v[3], w4);
      const cf w8 = cmul(w4, w4);
      store8(row, rim, v);
#pragma unroll
      for (int k = 1; k < 4; k++) {
#pragma unroll
        for (int i = 0; i < 8; i++) v[i] = (k == 1 && i == 0) ? w8 : cmul(v[i], w8);
        store8(row + 2048 * k, rim + 2048 * k, v);
      }
    }
    {
      z1.y = -z1.y; Z.y = -Z.y;
      const cf z2 = cmul(z1, z1);
      cf h[8], v[8];
      h[0].x = 2.f * blo(pcr) * dt; h[0].y = -2.f * blo(pci) * dt;
      h[1] = cmul(h[0], z1);
#pragma unroll
      for (int i = 2; i < 8; i++) h[i] = cmul(h[i - 2], z2);
      store8(row + 4 * 2048, rim + 4 * 2048, h);
      const cf h8 = cmul(h[6], z2);
      v[0] = cmul(h[0], Z); v[2] = cmul(h[2], Z); v[3] = cmul(h[4], Z); v[6] = cmul(h[6], Z); v[7] = cmul(h8, Z);
      v[1] = v[0]; v[4] = v[5] = v[3];
      store8(row + 5 * 2048, rim + 5 * 2048, v);
      h[0] = cmul(v[0], Z); h[1] = cmul(v[3], Z); h[3] = cmul(v[7], Z); h[4] = cmul(h[0], Z); h[5] = cmul(h[1], Z); h[7] = cmul(h[3], Z);
      h[2] = h[1]; h[6] = h[5];
      store8(row + 6 * 2048, rim + 6 * 2048, h);
      const cf Z2 = cmul(Z, Z);
      v[0] = cmul(h[0], Z2); v[1] = cmul(h[3], Z2); v[2] = cmul(h[4], Z2); v[3] = cmul(h[7], Z2);
#pragma unroll
      for (int i = 4; i < 8; i++) v[i] = cmul(v[i - 4], Z2);
      store8(row + 7 * 2048, rim + 7 * 2048, v);
    }
    TL(17);
    fence_async();
    if (u) bar_sync(NB_ORD + u - 1, 256); else bar_sync(NB_WG0, 128);
    TL(13);
    float c[32];
    wg_fence();
    kgen_mma<0>(c, desc_lo(tab) | ((uint64_t)((tim - tab) >> 4) << 16) | (64ull << 32));
    wg_commit();
    if (u < 4) bar_arrive(NB_ORD + u, 256);
    cluster_wait();
    {
      const uint4 x = ldg128(p.tab->thr[0][tid]), y = ldg128(p.tab->thr[1][tid]), a = ldg128(p.tab->thr[2][tid]), b = ldg128(p.tab->thr[3][tid]);
      A1[0] = x.x; A1[1] = x.y; A1[2] = x.z; A1[3] = x.w; A1[4] = y.x; A1[5] = y.y; A1[6] = y.z; A1[7] = y.w;
      tc[0] = a.x; tc[1] = a.y; tc[2] = a.z; tc[3] = a.w; ts[0] = b.x; ts[1] = b.y; ts[2] = b.z; ts[3] = b.w;
    }
    wg_wait<0>(); tie_all(c);
    TL(26);
    cluster_arrive();
    if (u == 0 && lane == 0) mbar_arrive(mb + 8 * MB_XQ);
    bar_sync(NB_WG0 + u, 128);
    const uint32_t k0 = pack(c[0] + c[6], c[1] + c[7]), k1 = pack(c[8] + c[14], c[9] + c[15]);
    const uint32_t k2 = pack(c[16] + c[22], c[17] + c[23]), k3 = pack(c[24] + c[30], c[25] + c[31]);
    const uint32_t ka = tab + 16 * (8 * w + (g ^ w));
    sts32(ka + 4 * t, k0);
    sts32(ka + 512 + 4 * t, k1);
    sts64(ka + 1024 + 512 * (t >> 1) + 8 * (t & 1), prmt(k2, 0, 0x1010), (t & 1) ? prmt(k2, 0, 0x3232) : k2);
    const uint32_t lo = prmt(k3, 0, 0x1010), hi = prmt(k3, 0, 0x3232);
    sts128(ka + 2048 + 512 * t, lo, lo, (g & 1) ? hi : k3, hi);
    put_exp(sb + OFF_MX + u * 64 + 4 * w, amax2(amax2(k0, k1), amax2(k2, k3)), lane);
    TL(15);
  }
  {
    mbar_wait(mb + 8 * MB_XQ);
    TL(18);
    uint32_t x0[4], x1[4];
    ldsm4t(x0, sb + OFF_TQ + w * 2560 + toff + 16 * u);
    ldsm4t(x1, sb + OFF_TQ + (w + 4) * 2560 + toff + 16 * u);
    put(OFF_YB + 8 * u * YPITCH, OFF_UX + u * 4096, uoff, x0);
    put(OFF_YB + 8 * u * YPITCH, OFF_UX + u * 4096, (uoff ^ 32) + 256, x1);
    TL(3);
    fence_async();
    bar_sync(NB_WG0 + u, 128);
    TL(4);
    send(OFF_YB + 8 * u * YPITCH, YPITCH, OFF_UX + u * 4096 + 512 * rank, OFF_MB + 8 * (MB_UX + u));
    if (wid == 16) {
      bar_sync(NB_LD, 640);
      if (elect()) {
        tma_load4(sb + OFF_TK, &p.tk, ch0, 0, 0, 8 * rank - 1, mb + 8 * MB_KV);
        tma_load4(sb + OFF_TV, &p.tv, ch0, 0, 0, 8 * rank, mb + 8 * MB_KV);
      }
      __syncwarp();
    } else {
      bar_arrive(NB_LD, 640);
    }
    TL(7);
    mbar_wait(mb + 8 * MB_CF);
  }
  if (u < 2) {
    float s0 = 0.f;
#pragma unroll
    for (int j = 0; j < 5; j++) {
      const uint4 gw = lds128(sb + OFF_SP + 160 * u + 16 * j), x = lds128(sb + OFF_TQ + (tid + 128 * u) * 80 + 16 * j);
      const uint32_t m0 = hmul2(x.x, gw.x), m1 = hmul2(x.y, gw.y), m2 = hmul2(x.z, gw.z), m3 = hmul2(x.w, gw.w);
      s0 += ((blo(m0) + bhi(m0)) + (blo(m1) + bhi(m1))) + ((blo(m2) + bhi(m2)) + (blo(m3) + bhi(m3)));
    }
    tag = (lds64(mb + 8 * MB_TAG).x >> 4) + 1;
    asm volatile("st.relaxed.gpu.global.u64 [%0], %1;" :: "l"(p.part + cl * SEQ + rank * 256 + 8 * (8 * t + g) + w + 4 * u),
                 "l"(((uint64_t)tag << 32) | __float_as_uint(s0)) : "memory");
    __syncwarp();
    TL(8);
  }
  if (lane == 0) mbar_arrive(mb + 8 * MB_XD);

#pragma unroll
  for (int isA = 0; isA < 2; isA++) {
    if (isA) {
      uint64_t ga[NCL];
      const int slot = tid + 128 * (u & 1);
      const uint2* gp = p.part + rank * 256 + slot;
      auto gload = [&]() {
#pragma unroll
        for (int k = 0; k < NCL; k++) asm volatile("ld.relaxed.gpu.global.u64 %0, [%1];" : "=l"(ga[k]) : "l"(gp + k * SEQ) : "memory");
      };
      if ((u & 6) == 2) gload();
      cluster_wait();
      mbar_wait(mb + 8 * MB_XD);
      mbar_wait(mb + 8 * MB_KV);
      TL(21);
      {
        const int k = u;
        const uint32_t hoff = (4 * (4 + 2 * (mi & 1) + jj) + ((tq + 3) & 3)) * 80 + (tq ? 2560 : 0) + 16 * k;
        uint32_t E[2][6], V[2][4];
        const uint2 psw = lds64(sb + OFF_SP + 160 * k + 80 + 8 * g);
#pragma unroll
        for (int hf = 0; hf < 2; hf++) {
          const int ah = 4 * hf + w;
          uint32_t K[4];
          ldsm4t(K, sb + OFF_TK + (ah + 1) * 2560 + toff + 16 * k);
          ldsm2t(E[hf][0], E[hf][1], sb + OFF_TK + ah * 2560 + hoff);
          ldsm4t(V[hf], sb + OFF_TV + ah * 2560 + toff + 16 * k);
          E[hf][2] = K[0]; E[hf][3] = K[1]; E[hf][4] = K[2]; E[hf][5] = K[3];
        }
        const uint32_t w0 = prmt(psw.x, 0, 0x1010), w1 = prmt(psw.x, 0, 0x3232), w2 = prmt(psw.y, 0, 0x1010), w3 = prmt(psw.y, 0, 0x3232);
        uint32_t o[2][4];
#pragma unroll
        for (int hf = 0; hf < 2; hf++) {
          uint32_t O[5];
#pragma unroll
          for (int i = 0; i < 5; i++) O[i] = prmt(E[hf][i], E[hf][i + 1], 0x5432);
#pragma unroll
          for (int i = 0; i < 4; i++) {
            o[hf][i] = hmul2(hfma2(E[hf][i + 2], w0, hfma2(O[i + 1], w1, hfma2(E[hf][i + 1], w2, hmul2(O[i], w3)))), V[hf][i]);
          }
          put(OFF_YA + 8 * k * YPITCH, OFF_T + k * KTAB + T_UKV, hf ? (uoff ^ 32) + 256 : uoff, o[hf]);
        }
        fence_async();
        bar_sync(NB_WG0 + u, 128);
        send(OFF_YA + 8 * k * YPITCH, YPITCH, OFF_T + k * KTAB + T_UKV + 512 * rank, OFF_MB + 8 * (MB_UKV + k));
      }
      TL(22);
      if ((u & 6) == 2) {
        tag = (lds64(mb + 8 * MB_TAG).x >> 4) + 1;
        float s;
        bool ok;
#pragma unroll 1
        for (int it = 0;; it++) {
          ok = true; s = 0.f;
#pragma unroll
          for (int k = 0; k < NCL; k++) { ok = ok && (uint32_t)(ga[k] >> 32) == tag; s += __uint_as_float((uint32_t)ga[k]); }
          if (ok || it == 4000) break;
          gload();
        }
        if (!ok) {
          const uint32_t* xr = (const uint32_t*)(p.q + (size_t)(rank * 256 + 32 * (slot & 7) + (slot >> 3)) * DCH);
          const uint32_t* gr = (const uint32_t*)p.gate_w;
          s = 0.f;
    #pragma unroll 1
          for (int k = 0; k < DCH / 2; k++) { const uint32_t m = hmul2(__ldg(xr + k), __ldg(gr + k)); s += blo(m) + bhi(m); }
        }
        const float g0 = bf16r(sigmoidf_(bf16r(s)));
        sts64(sb + OFF_GB + 8 * slot, pack(g0, g0), pack(1.f - g0, 1.f - g0));
        __syncwarp();
        if (lane == 0) mbar_arrive(mb + 8 * MB_Q2);
      }
      TL(11);
      mbar_wait(mb + 8 * (MB_HA + u));
      put_exp(sb + OFF_MX + u * 64 + 32 + 4 * w, seq_mag(tab + T_HA + 16 * tid), lane);
      bar_sync(NB_WG0 + u, 128);
    }
    {
      TL(1 + isA);
      const uint32_t usrc = isA ? tab + T_UKV : sb + OFF_UX + u * 4096;
      const uint32_t mxa = sb + OFF_MX + u * 64 + 32 * isA;
      const uint32_t pd = lds16(sb + OFF_SP + 160 * u + 144 + 4 * isA);
      float D[32];
      uint32_t As[8], F[16], H[16], X[16];
      const uint32_t eh = min(max((int)get_exp(mxa), (int)((pd >> 7) & 0xff) - 5), 240);
      scale_a1(As, A1, 248 - eh);
      wg_fence();
      stage1(D, As, isA ? tab + T_HA : tab);
      wg_commit();
      wg_wait<0>(); tie_all(D);
      fwd_mid(F, D, tc, ts);
      wg_fence();
      stage2<0>(H, F, sb + OFF_CF);
      wg_commit();
      mbar_wait(mb + 8 * ((isA ? MB_UKV : MB_UX) + u));
      TL(5 + isA);
      put_exp(mxa + 16 + 4 * w, seq_mag(usrc + 16 * tid), lane);
      bar_sync(NB_WG0 + u, 128);
      const uint32_t eu = min(get_exp(mxa + 16), 240u);
      scale_a1(As, A1, 250 - eu);
      wg_wait<0>(); tie_all(H);
      wg_fence();
      stage1(D, As, usrc);
      wg_commit();
      wg_wait<0>(); tie_all(D);
      fwd_mid(F, D, tc, ts);
      wg_fence();
      stage2<0>(X, F, sb + OFF_CF);
      wg_commit();
      if (!isA && w == 1 && elect()) {
        tma_load4(tab + T_HA, &p.th, 0, 0, 5 * cl + u, rank, mb + 8 * (MB_HA + u));
        if (u == 4) tma_load3(sb + OFF_Q2, &p.tq2, ch0, 8 * rank, 0, mb + 8 * MB_Q2);
      }
      __syncwarp();
      {
        const float dsk = blo(pd) * __uint_as_float((248 - eh) << 23);
        const uint32_t d2 = packh(dsk, dsk);
#pragma unroll
        for (int j = 0; j < 4; j++) H[2 * j] = U2(__hadd2(H2(H[2 * j]), H2(d2)));
      }
      wg_wait<0>(); tie_all(X);
#pragma unroll
      for (int j = 0; j < 4; j++) {
        const uint32_t h0r = H[2 * j], h1r = H[2 * j + 1], h0i = H[8 + 2 * j], h1i = H[9 + 2 * j];
        const uint32_t x0r = X[2 * j], x1r = X[2 * j + 1], x0i = X[8 + 2 * j], x1i = X[9 + 2 * j];
        F[2 * j] = ffma(x0r, h0r, fneg(fmul(x0i, h0i)));
        F[8 + 2 * j] = ffma(x0r, h0i, fmul(x0i, h0r));
        F[2 * j + 1] = ffma(x1r, h0r, ffma(fneg(x1i), h0i, ffma(x0r, h1r, fneg(ffma(x0i, h1i, F[8 + 2 * j])))));
        F[9 + 2 * j] = ffma(x1r, h0i, ffma(x1i, h0r, ffma(x0r, h1i, ffma(x0i, h1r, F[2 * j]))));
      }
      wg_fence();
      stage2<1>(H, F, sb + OFF_CF);
      wg_commit();
      wg_wait<0>(); tie_all(H);
      {
        const uint32_t va = tab + (16 * w + (lane & 15)) * 128;
        const int vx = (lane >> 4) ^ (lane & 7);
#pragma unroll
        for (int j = 0; j < 4; j++) {
          uint32_t V[4];
#pragma unroll
          for (int b = 0; b < 2; b++) {
            const uint32_t er = H[2 * j + b], ei = H[8 + 2 * j + b];
            V[2 * b] = ffma(er, tc[j], fneg(fmul(ei, ts[j])));
            V[2 * b + 1] = ffma(ei, tc[j], fmul(er, ts[j]));
          }
          stsm4(va + ((vx ^ (2 * j)) << 4), V);
        }
      }
      fence_async();
      bar_sync(NB_WG0 + u, 128);
      float O[16];
      {
        const uint64_t dv = desc_lo(tab) | (1ull << 16) | (64ull << 32) | (1ull << 62);
        const uint64_t dl = desc_lo(sb + OFF_CL) | (32ull << 16) | (8ull << 32);
        wg_fence();
        ss32<0, 0, 0>(O, dv, dl); ss32<1, 128, 64>(O, dv, dl); ss32<1, 256, 128>(O, dv, dl); ss32<1, 384, 192>(O, dv, dl);
        wg_commit();
      }
      wg_wait<0>(); tie_all(O);
      {
        const uint32_t co = ((8 * w + g) ^ (2 * t)) * 16;
        const int yo = (isA ? OFF_YA : OFF_YB) + (8 * u + rank) * YPITCH, ym = OFF_MB + 8 * (MB_Y + u);
        const uint32_t us = min(max((int)(eu + eh) - 127, 0), 254) * 0x00800080u;
        const uint32_t a0 = hmul2(pack(O[0], O[1]), us), a1 = hmul2(pack(O[4], O[5]), us), a2 = hmul2(pack(O[8], O[9]), us), a3 = hmul2(pack(O[12], O[13]), us);
        const uint32_t b0 = hmul2(pack(O[2], O[3]), us), b1 = hmul2(pack(O[6], O[7]), us), b2 = hmul2(pack(O[10], O[11]), us), b3 = hmul2(pack(O[14], O[15]), us);
        sts128((t == rank ? sb + yo : usrc + t * 512) + co, a0, a1, a2, a3);
        sts128((t + 4 == rank ? sb + yo : usrc + t * 512 + 2048) + co, b0, b1, b2, b3);
        fence_async();
        bar_sync(NB_WG0 + u, 128);
        send(usrc - sb, 512, yo, ym);
      }
      TL(9 + isA);
    }
  }

  {
    mbar_wait(mb + 8 * MB_Q2);
    uint2 gg[2][4];
    uint32_t qv[2][4];
#pragma unroll
    for (int hh = 0; hh < 2; hh++)
#pragma unroll
      for (int i = 0; i < 4; i++) gg[hh][i] = lds64(sb + OFF_GB + 8 * (64 * w + 32 * hh + 8 * i + g));
    const uint32_t qa = sb + OFF_Q2 + (64 * w + lane) * 80 + 16 * u;
    ldsm4(qv[0], qa);
    ldsm4(qv[1], qa + 2560);
    TL(24);
    mbar_wait(mb + 8 * (MB_Y + u));
    uint32_t ya[2][4], yb[2][4];
#pragma unroll
    for (int hh = 0; hh < 2; hh++) {
      const uint32_t yo = (8 * u + (lane & 7)) * YPITCH + ((8 * w + 4 * hh + (lane >> 3)) ^ (2 * (rank & 3))) * 16;
      ldsm4t(ya[hh], sb + OFF_YA + yo); ldsm4t(yb[hh], sb + OFF_YB + yo);
    }
#pragma unroll
    for (int hh = 0; hh < 2; hh++) {
      uint32_t o[4];
#pragma unroll
      for (int i = 0; i < 4; i++) o[i] = hadd2(hmul2(gg[hh][i].x, hmul2(qv[hh][i], ya[hh][i])), hmul2(gg[hh][i].y, yb[hh][i]));
      stsm4(qa + 2560 * hh, o);
    }
    TL(25);
  }
  cluster_arrive();
  bar_sync(NB_ROW0 + w, 160);
  {
    uint4 v[2];
#pragma unroll
    for (int k = 0; k < 2; k++) {
      const int i = 64 * u + 32 * k + lane, sl = (i * 205) >> 10, cc = i - 5 * sl;
      v[k] = lds128(sb + OFF_Q2 + (64 * w + 8 * (sl & 7) + (sl >> 3)) * 80 + cc * 16);
    }
#pragma unroll
    for (int k = 0; k < 2; k++) {
      const int i = 64 * u + 32 * k + lane, sl = (i * 205) >> 10, cc = i - 5 * sl;
      if (cc < nu)
        asm volatile("st.global.v4.u32 [%0], {%1,%2,%3,%4};" :: "l"(p.out + (size_t)(256 * rank + 32 * (sl >> 3) + 8 * w + (sl & 7)) * DCH + ch0 + 8 * cc),
                     "r"(v[k].x), "r"(v[k].y), "r"(v[k].z), "r"(v[k].w) : "memory");
    }
  }
  cluster_wait();
  TL(27);
  TL_DUMP();
}

typedef CUresult (*EncodeFn)(CUtensorMap*, CUtensorMapDataType, cuuint32_t, void*, const cuuint64_t*, const cuuint64_t*,
                             const cuuint32_t*, const cuuint32_t*, CUtensorMapInterleave, CUtensorMapSwizzle,
                             CUtensorMapL2promotion, CUtensorMapFloatOOBfill);

void encode(EncodeFn fn, CUtensorMap* tm, const void* ptr, int nd, const cuuint64_t* dims, const cuuint64_t* strides,
            const cuuint32_t* box, CUtensorMapSwizzle swz) {
  cuuint32_t es[4] = {1, 1, 1, 1};
  fn(tm, CU_TENSOR_MAP_DATA_TYPE_BFLOAT16, nd, const_cast<void*>(ptr), dims, strides, box, es, CU_TENSOR_MAP_INTERLEAVE_NONE,
     swz, CU_TENSOR_MAP_L2_PROMOTION_L2_128B, CU_TENSOR_MAP_FLOAT_OOB_FILL_NONE);
}
void map1(EncodeFn fn, CUtensorMap* tm, const void* ptr, int nhi) {
  const cuuint64_t dims[4] = {DCH, 4, 8, SEQ / 32}, strides[3] = {8 * DCH * 2, DCH * 2, 32 * DCH * 2};
  const cuuint32_t box[4] = {CPC, 4, 8, (cuuint32_t)nhi};
  encode(fn, tm, ptr, 4, dims, strides, box, CU_TENSOR_MAP_SWIZZLE_NONE);
}
void map2(EncodeFn fn, CUtensorMap* tm, const void* ptr, int nr) {
  const cuuint64_t dims[3] = {DCH, SEQ / 32, 32}, strides[2] = {32 * DCH * 2, DCH * 2};
  const cuuint32_t box[3] = {CPC, 8, (cuuint32_t)nr};
  encode(fn, tm, ptr, 3, dims, strides, box, CU_TENSOR_MAP_SWIZZLE_NONE);
}

}

extern "C" void kernel_launch(void* const* d_in, const int* in_sizes, int n_in, void* d_out, int out_size) {
  (void)in_sizes; (void)n_in; (void)out_size;
  static EncodeFn fn = nullptr;
  static void *tab = nullptr, *cnt = nullptr, *part = nullptr;
  if (!fn) {
    cudaGetSymbolAddress(&tab, d_tab);
    cudaGetSymbolAddress(&cnt, g_cnt);
    cudaGetSymbolAddress(&part, g_part);
    cudaDriverEntryPointQueryResult qr;
    cudaGetDriverEntryPoint("cuTensorMapEncodeTiled", (void**)&fn, cudaEnableDefault, &qr);
    cudaFuncSetAttribute(fused_kernel, cudaFuncAttributeMaxDynamicSharedMemorySize, SMEM_BYTES);
  }
  Params p;
  map1(fn, &p.tq, d_in[0], 8);
  map1(fn, &p.tk, d_in[1], 9);
  map1(fn, &p.tv, d_in[2], 8);
  map2(fn, &p.tq2, d_in[0], 32);
  p.out = (__nv_bfloat16*)d_out;
  {
    const cuuint64_t dims[4] = {32, SEQ / 32, DCH / 8, 8}, strides[3] = {64, 8 * SEQ * 2, SEQ * 2};
    const cuuint32_t box[4] = {32, 64, 1, 1};
    encode(fn, &p.th, d_in[4], 4, dims, strides, box, CU_TENSOR_MAP_SWIZZLE_64B);
  }
  p.tab = (const Tables*)tab;
  p.cnt = (unsigned*)cnt;
  p.part = (uint2*)part;
  p.tl = nullptr;
  p.q = (const __nv_bfloat16*)d_in[0];
  p.k = (const __nv_bfloat16*)d_in[1];
  p.v = (const __nv_bfloat16*)d_in[2];
  p.ssm_k = (const __nv_bfloat16*)d_in[4];
  p.shift_k = (const __nv_bfloat16*)d_in[3];
  p.ssm_D = (const __nv_bfloat16*)d_in[5];
  p.logA = (const __nv_bfloat16*)d_in[7];
  p.Aim = (const __nv_bfloat16*)d_in[8];
  p.Cre = (const __nv_bfloat16*)d_in[9];
  p.Cim = (const __nv_bfloat16*)d_in[10];
  p.logdt = (const __nv_bfloat16*)d_in[11];
  p.Dskip = (const __nv_bfloat16*)d_in[12];
  p.gate_w = (const __nv_bfloat16*)d_in[13];
  fused_kernel<<<NCL * CS, NTHREADS, SMEM_BYTES, cudaStreamPerThread>>>(p);
}
```

```cpp
#include <cuda_runtime.h>
#include <cuda_bf16.h>
#include <cuda_fp16.h>
#include <cuda.h>
#include <stdint.h>

#define TIMELINE 0

namespace {

constexpr int SEQ = 2048, DCH = 576, NMODE = 128;
constexpr int CS = 8, CPC = 40, NCL = 15, NTHREADS = 640;

constexpr int YPITCH = 528;
constexpr int KTAB = 16384;
constexpr int OFF_T = 0;
constexpr int T_UKV = 8192, T_HA = 12288;
constexpr int OFF_UX = 5 * KTAB;
constexpr int OFF_IM = OFF_UX + 20480;
constexpr int OFF_Q2 = OFF_IM;
constexpr int OFF_GB = OFF_Q2 + 20480;
constexpr int OFF_TV = OFF_IM + 3 * KTAB - 20480;
constexpr int OFF_CF = OFF_IM + 3 * KTAB;
constexpr int OFF_CL = OFF_CF + 8192;
constexpr int OFF_TK = OFF_CL + 4096;
constexpr int OFF_TQ = OFF_TK + 23040;
constexpr int OFF_YA = OFF_TQ;
constexpr int OFF_YB = OFF_TQ + 21120;
constexpr int OFF_MX = OFF_YB + 40 * YPITCH;
constexpr int OFF_SP = OFF_MX + 320;
constexpr int OFF_MB = OFF_SP + 5 * 160;
constexpr int OFF_TL = OFF_MB + 32 * 8;
constexpr int SMEM_BYTES = OFF_TL + (TIMELINE ? 1280 : 0);
static_assert(SMEM_BYTES <= 232448 && OFF_IM + 5 * KTAB <= OFF_TQ, "smem");
static_assert((OFF_TQ & 127) == 0 && (OFF_TK & 127) == 0 && (OFF_TV & 127) == 0 && (OFF_MB & 7) == 0 && (OFF_MX & 15) == 0, "align");

enum { MB_UX = 0, MB_UKV = 5, MB_Y = 10, MB_HA = 15, MB_XQ = 20, MB_KV = 21, MB_CF = 22, MB_Q2 = 23, MB_XD = 24, MB_TAG = 25 };
enum { NB_WG0 = 1, NB_ROW0 = 6, NB_ORD = 6, NB_K0 = 10, NB_LD = 11 };

constexpr double cos_turn(int m, int n) {
  m &= n - 1;
  if (m > n / 2) m = n - m;
  double sgn = 1.0;
  if (m > n / 4) { m = n / 2 - m; sgn = -1.0; }
  if (m == n / 4) return 0.0;
  const double x = 6.283185307179586476925 * m / n;
  double term = 1.0, sum = 1.0;
  for (int k = 1; k < 14; k++) { term *= -x * x / ((2 * k - 1) * (2 * k)); sum += term; }
  return sgn * sum;
}
constexpr uint32_t bf16_bits(double v) {
  if (v == 0.0) return 0;
  uint32_t sgn = 0;
  if (v < 0) { sgn = 0x8000; v = -v; }
  int e = 127;
  while (v < 1.0) { v *= 2.0; e--; }
  while (v >= 2.0) { v *= 0.5; e++; }
  const double f = v * 128.0;
  int m = (int)f;
  if (f - m > 0.5 || (f - m == 0.5 && (m & 1))) m++;
  return sgn | (uint32_t)((e << 7) + (m - 128));
}
constexpr uint32_t f16_bits(double v) {
  if (v == 0.0) return 0;
  uint32_t sgn = 0;
  if (v < 0) { sgn = 0x8000; v = -v; }
  int e = 15;
  while (v < 1.0) { v *= 2.0; e--; }
  const double f = v * 1024.0;
  int m = (int)f;
  if (f - m > 0.5 || (f - m == 0.5 && (m & 1))) m++;
  return sgn | (uint32_t)((e << 10) + (m - 1024));
}
constexpr uint32_t pair_bits(double lo, double hi) { return bf16_bits(lo) | (bf16_bits(hi) << 16); }
constexpr uint32_t pair_h(double lo, double hi) { return f16_bits(lo) | (f16_bits(hi) << 16); }
struct alignas(128) Tables {
  uint32_t mat[3072];
  uint32_t thr[4][128][4];
};
constexpr Tables make_tables() {
  Tables T{};
  for (int q = 0; q < 768; q++) {
    int m0 = 0, d0 = 0, d1 = 0;
    if (q < 512) {
      const int r = (q >> 6) * 8 + (q & 7), cc = (q >> 3) & 7;
      d0 = 4 * (r & 31); d1 = 2 * d0;
      m0 = 8 * (cc & 3) * d0 + ((r >> 5) == (cc >> 2) ? 0 : (r >> 5) ? 96 : 32);
    } else {
      const int r = ((q - 512) >> 5) * 8 + (q & 7), pc = (q >> 3) & 3;
      d0 = 4 * (8 * (r >> 4) + (r & 7)) + 1; d1 = 8 * d0;
      m0 = 2 * pc * d0 + ((r & 8) ? 32 : 0);
    }
    for (int e = 0; e < 4; e++) T.mat[4 * q + e] = pair_h(cos_turn(m0 + e * d1, 128), cos_turn(m0 + e * d1 + d0, 128));
  }
  for (int tid = 0; tid < 128; tid++) {
    const int kk = 4 * (tid >> 2) + 1, t = tid & 3;
    for (int q = 0; q < 4; q++) {
      const int m = (8 * q + 2 * t) * kk;
      T.thr[q >> 1][tid][2 * (q & 1)] = pair_bits(cos_turn(m, 128), cos_turn(m + kk, 128));
      T.thr[q >> 1][tid][2 * (q & 1) + 1] = pair_bits(cos_turn(m + 32, 128), cos_turn(m + kk + 32, 128));
      T.thr[2][tid][q] = pair_h(cos_turn(m, 4096), cos_turn(m + kk, 4096));
      T.thr[3][tid][q] = pair_h(cos_turn(m + 3072, 4096), cos_turn(m + kk + 3072, 4096));
    }
  }
  return T;
}
__device__ const Tables d_tab = make_tables();

struct Params {
  const __nv_bfloat16 *logA, *Aim, *Cre, *Cim, *logdt;
  const Tables* tab;
  unsigned* cnt;
  const __nv_bfloat16 *Dskip, *shift_k, *ssm_D, *gate_w, *q, *k, *v, *ssm_k;
  uint2* part;
  __nv_bfloat16* out;
  unsigned* tl;
  CUtensorMap tq, tk, tv, th, tq2;
};

__device__ uint2 g_part[NCL * SEQ];
__device__ unsigned g_cnt[CS * 32];
#define TL(i) do {} while (0)
#define TL_INIT() do {} while (0)
#define TL_DUMP() do {} while (0)

__device__ __forceinline__ uint32_t lds16(uint32_t a) { uint32_t v; asm volatile("ld.shared.u16 %0, [%1];" : "=r"(v) : "r"(a) : "memory"); return v; }
__device__ __forceinline__ uint2 lds64(uint32_t a) { uint2 v; asm volatile("ld.shared.v2.u32 {%0,%1}, [%2];" : "=r"(v.x), "=r"(v.y) : "r"(a) : "memory"); return v; }
__device__ __forceinline__ uint4 lds128(uint32_t a) { uint4 v; asm volatile("ld.shared.v4.u32 {%0,%1,%2,%3}, [%4];" : "=r"(v.x), "=r"(v.y), "=r"(v.z), "=r"(v.w) : "r"(a) : "memory"); return v; }
__device__ __forceinline__ void sts16(uint32_t a, uint32_t v) { asm volatile("st.shared.u16 [%0], %1;" :: "r"(a), "r"(v) : "memory"); }
__device__ __forceinline__ void sts32(uint32_t a, uint32_t v) { asm volatile("st.shared.u32 [%0], %1;" :: "r"(a), "r"(v) : "memory"); }
__device__ __forceinline__ void sts64(uint32_t a, uint32_t x, uint32_t y) { asm volatile("st.shared.v2.u32 [%0], {%1,%2};" :: "r"(a), "r"(x), "r"(y) : "memory"); }
__device__ __forceinline__ void sts128(uint32_t a, uint32_t x, uint32_t y, uint32_t z, uint32_t w) { asm volatile("st.shared.v4.u32 [%0], {%1,%2,%3,%4};" :: "r"(a), "r"(x), "r"(y), "r"(z), "r"(w) : "memory"); }
__device__ __forceinline__ void ldsm4t(uint32_t (&r)[4], uint32_t a) { asm volatile("ldmatrix.sync.aligned.m8n8.x4.trans.shared.b16 {%0,%1,%2,%3}, [%4];" : "=r"(r[0]), "=r"(r[1]), "=r"(r[2]), "=r"(r[3]) : "r"(a) : "memory"); }
__device__ __forceinline__ void ldsm2t(uint32_t& r0, uint32_t& r1, uint32_t a) { asm volatile("ldmatrix.sync.aligned.m8n8.x2.trans.shared.b16 {%0,%1}, [%2];" : "=r"(r0), "=r"(r1) : "r"(a) : "memory"); }
__device__ __forceinline__ void ldsm4(uint32_t (&r)[4], uint32_t a) { asm volatile("ldmatrix.sync.aligned.m8n8.x4.shared.b16 {%0,%1,%2,%3}, [%4];" : "=r"(r[0]), "=r"(r[1]), "=r"(r[2]), "=r"(r[3]) : "r"(a) : "memory"); }
__device__ __forceinline__ void stsm4(uint32_t a, const uint32_t (&r)[4]) { asm volatile("stmatrix.sync.aligned.m8n8.x4.shared.b16 [%0], {%1,%2,%3,%4};" :: "r"(a), "r"(r[0]), "r"(r[1]), "r"(r[2]), "r"(r[3]) : "memory"); }
__device__ __forceinline__ uint32_t pack(float lo, float hi) { uint32_t r; asm("cvt.rn.bf16x2.f32 %0, %1, %2;" : "=r"(r) : "f"(hi), "f"(lo)); return r; }
__device__ __forceinline__ float blo(uint32_t v) { return __uint_as_float(v << 16); }
__device__ __forceinline__ float bhi(uint32_t v) { return __uint_as_float(v & 0xffff0000u); }
__device__ __forceinline__ float bf16r(float x) { return blo(pack(x, 0.f)); }
__device__ __forceinline__ uint32_t hmul2(uint32_t a, uint32_t b) { uint32_t r; asm("mul.rn.bf16x2 %0, %1, %2;" : "=r"(r) : "r"(a), "r"(b)); return r; }
__device__ __forceinline__ uint32_t hadd2(uint32_t a, uint32_t b) { uint32_t r; asm("add.rn.bf16x2 %0, %1, %2;" : "=r"(r) : "r"(a), "r"(b)); return r; }
__device__ __forceinline__ uint32_t hfma2(uint32_t a, uint32_t b, uint32_t c) { uint32_t r; asm("fma.rn.bf16x2 %0, %1, %2, %3;" : "=r"(r) : "r"(a), "r"(b), "r"(c)); return r; }
__device__ __forceinline__ uint32_t packh(float lo, float hi) { uint32_t r; asm("cvt.rn.f16x2.f32 %0, %1, %2;" : "=r"(r) : "f"(hi), "f"(lo)); return r; }
__device__ __forceinline__ __half2 H2(uint32_t a) { return *reinterpret_cast<__half2*>(&a); }
__device__ __forceinline__ uint32_t U2(__half2 a) { return *reinterpret_cast<uint32_t*>(&a); }
__device__ __forceinline__ uint32_t fmul(uint32_t a, uint32_t b) { return U2(__hmul2(H2(a), H2(b))); }
__device__ __forceinline__ uint32_t ffma(uint32_t a, uint32_t b, uint32_t c) { return U2(__hfma2(H2(a), H2(b), H2(c))); }
__device__ __forceinline__ uint32_t fneg(uint32_t a) { return U2(__hneg2(H2(a))); }
__device__ __forceinline__ uint32_t amax2(uint32_t a, uint32_t b) { uint32_t r; asm("max.xorsign.abs.bf16x2 %0, %1, %2;" : "=r"(r) : "r"(a), "r"(b)); return r; }
__device__ __forceinline__ uint32_t prmt(uint32_t a, uint32_t b, uint32_t s) { return __byte_perm(a, b, s); }
__device__ __forceinline__ uint32_t ldraw(const __nv_bfloat16* p) { uint32_t v; asm volatile("ld.global.nc.u16 %0, [%1];" : "=r"(v) : "l"(p)); return v; }
__device__ __forceinline__ uint4 ldg128(const void* p) { uint4 v; asm volatile("ld.global.nc.v4.u32 {%0,%1,%2,%3}, [%4];" : "=r"(v.x), "=r"(v.y), "=r"(v.z), "=r"(v.w) : "l"(p)); return v; }
__device__ __forceinline__ void bar_sync(int id, int n) { asm volatile("bar.sync %0, %1;" :: "r"(id), "r"(n) : "memory"); }
__device__ __forceinline__ void bar_arrive(int id, int n) { asm volatile("bar.arrive %0, %1;" :: "r"(id), "r"(n) : "memory"); }
__device__ __forceinline__ void cluster_arrive() { asm volatile("barrier.cluster.arrive.relaxed.aligned;" ::: "memory"); }
__device__ __forceinline__ void cluster_wait() { asm volatile("barrier.cluster.wait.aligned;" ::: "memory"); }
__device__ __forceinline__ void fence_async() { asm volatile("fence.proxy.async.shared::cta;" ::: "memory"); }
__device__ __forceinline__ void fence_mbinit() { asm volatile("fence.mbarrier_init.release.cluster;" ::: "memory"); }
__device__ __forceinline__ uint32_t mapa(uint32_t a, uint32_t rank) { uint32_t r; asm("mapa.shared::cluster.u32 %0, %1, %2;" : "=r"(r) : "r"(a), "r"(rank)); return r; }
__device__ __forceinline__ void bulk_dsmem(uint32_t dst, uint32_t src, uint32_t mbar) {
  asm volatile("cp.async.bulk.shared::cluster.shared::cta.mbarrier::complete_tx::bytes [%0], [%1], 512, [%2];" :: "r"(dst), "r"(src), "r"(mbar) : "memory");
}
__device__ __forceinline__ void mbar_init(uint32_t m, uint32_t cnt) { asm volatile("mbarrier.init.shared::cta.b64 [%0], %1;" :: "r"(m), "r"(cnt) : "memory"); }
__device__ __forceinline__ void mbar_expect(uint32_t m, uint32_t bytes) { asm volatile("mbarrier.arrive.expect_tx.shared::cta.b64 _, [%0], %1;" :: "r"(m), "r"(bytes) : "memory"); }
__device__ __forceinline__ bool mbar_try(uint32_t m) {
  uint32_t done;
  asm volatile("{.reg .pred p; mbarrier.try_wait.parity.shared::cta.b64 p, [%1], 0; selp.u32 %0, 1, 0, p;}" : "=r"(done) : "r"(m) : "memory");
  return done;
}
__device__ __forceinline__ void mbar_wait(uint32_t m) {
  if (!mbar_try(m)) {
    int it = 0;
    while (!mbar_try(m) && ++it < (1 << 22)) {}
  }
}
__device__ __forceinline__ bool elect() {
  uint32_t e;
  asm volatile("{.reg .pred p; elect.sync _|p, 0xffffffff; selp.u32 %0, 1, 0, p;}" : "=r"(e));
  return e;
}
__device__ __forceinline__ void tma_load4(uint32_t dst, const CUtensorMap* tm, int c0, int c1, int c2, int c3, uint32_t mbar) {
  asm volatile("cp.async.bulk.tensor.4d.shared::cluster.global.mbarrier::complete_tx::bytes [%0], [%1, {%3, %4, %5, %6}], [%2];"
               :: "r"(dst), "l"(tm), "r"(mbar), "r"(c0), "r"(c1), "r"(c2), "r"(c3) : "memory");
}
__device__ __forceinline__ void tma_load3(uint32_t dst, const CUtensorMap* tm, int c0, int c1, int c2, uint32_t mbar) {
  asm volatile("cp.async.bulk.tensor.3d.shared::cluster.global.mbarrier::complete_tx::bytes [%0], [%1, {%3, %4, %5}], [%2];"
               :: "r"(dst), "l"(tm), "r"(mbar), "r"(c0), "r"(c1), "r"(c2) : "memory");
}
__device__ __forceinline__ void tma_store3(const CUtensorMap* tm, int c0, int c1, int c2, uint32_t src) {
  asm volatile("cp.async.bulk.tensor.3d.global.shared::cta.bulk_group [%0, {%2, %3, %4}], [%1];"
               :: "l"(tm), "r"(src), "r"(c0), "r"(c1), "r"(c2) : "memory");
}
__device__ __forceinline__ void wg_fence() { asm volatile("wgmma.fence.sync.aligned;" ::: "memory"); }
__device__ __forceinline__ void wg_commit() { asm volatile("wgmma.commit_group.sync.aligned;" ::: "memory"); }
template <int N> __device__ __forceinline__ void wg_wait() { asm volatile("wgmma.wait_group.sync.aligned %0;" :: "n"(N) : "memory"); }
template <int N> __device__ __forceinline__ void tie_all(uint32_t (&x)[N]) {
#pragma unroll
  for (int i = 0; i < N; i++) asm volatile("" : "+r"(x[i]) :: "memory");
}
template <int N> __device__ __forceinline__ void tie_all(float (&x)[N]) {
#pragma unroll
  for (int i = 0; i < N; i++) asm volatile("" : "+f"(x[i]) :: "memory");
}
#define R16(C, d) C(d[0]), C(d[1]), C(d[2]), C(d[3]), C(d[4]), C(d[5]), C(d[6]), C(d[7]), C(d[8]), C(d[9]), C(d[10]), C(d[11]), C(d[12]), C(d[13]), C(d[14]), C(d[15])
#define R32(C, d) R16(C, d), R16(C, (d + 16))
#define P16 "{%0,%1,%2,%3,%4,%5,%6,%7,%8,%9,%10,%11,%12,%13,%14,%15}"
#define P32 "{%0,%1,%2,%3,%4,%5,%6,%7,%8,%9,%10,%11,%12,%13,%14,%15,%16,%17,%18,%19,%20,%21,%22,%23,%24,%25,%26,%27,%28,%29,%30,%31}"
template <int SD, int TB, int OFF> __device__ __forceinline__ void rs64(float* d, const uint32_t* a, uint64_t db) {
  if (SD) asm volatile("{.reg .b64 db; add.s64 db, %36, %37; wgmma.mma_async.sync.aligned.m64n64k16.f32.bf16.bf16 " P32 ", {%32,%33,%34,%35}, db, 1, 1, 1, %38;}"
                       : R32("+f", d) : "r"(a[0]), "r"(a[1]), "r"(a[2]), "r"(a[3]), "l"(db), "n"(OFF), "n"(TB));
  else asm volatile("{.reg .b64 db; add.s64 db, %36, %37; wgmma.mma_async.sync.aligned.m64n64k16.f32.bf16.bf16 " P32 ", {%32,%33,%34,%35}, db, 0, 1, 1, %38;}"
                    : R32("=f", d) : "r"(a[0]), "r"(a[1]), "r"(a[2]), "r"(a[3]), "l"(db), "n"(OFF), "n"(TB));
}
template <int SD, int TB, int OFF> __device__ __forceinline__ void rs64h(uint32_t* d, const uint32_t* a, uint64_t db) {
  if (SD) asm volatile("{.reg .b64 db; add.s64 db, %20, %21; wgmma.mma_async.sync.aligned.m64n64k16.f16.f16.f16 " P16 ", {%16,%17,%18,%19}, db, 1, 1, 1, %22;}"
                       : R16("+r", d) : "r"(a[0]), "r"(a[1]), "r"(a[2]), "r"(a[3]), "l"(db), "n"(OFF), "n"(TB));
  else asm volatile("{.reg .b64 db; add.s64 db, %20, %21; wgmma.mma_async.sync.aligned.m64n64k16.f16.f16.f16 " P16 ", {%16,%17,%18,%19}, db, 0, 1, 1, %22;}"
                    : R16("=r", d) : "r"(a[0]), "r"(a[1]), "r"(a[2]), "r"(a[3]), "l"(db), "n"(OFF), "n"(TB));
}
template <int SD, int OFFA, int OFFB> __device__ __forceinline__ void ss32(float* d, uint64_t da, uint64_t db) {
  if (SD) asm volatile("{.reg .b64 da, db; add.s64 da, %16, %18; add.s64 db, %17, %19; wgmma.mma_async.sync.aligned.m64n32k16.f32.f16.f16 " P16 ", da, db, 1, 1, 1, 1, 1;}"
                       : R16("+f", d) : "l"(da), "l"(db), "n"(OFFA), "n"(OFFB));
  else asm volatile("{.reg .b64 da, db; add.s64 da, %16, %18; add.s64 db, %17, %19; wgmma.mma_async.sync.aligned.m64n32k16.f32.f16.f16 " P16 ", da, db, 0, 1, 1, 1, 1;}"
                    : R16("=f", d) : "l"(da), "l"(db), "n"(OFFA), "n"(OFFB));
}
#define KGEN_ASM(SD) "{.reg .b64 da, db; add.s64 da, %32, %33; add.s64 db, %32, %34;\n" \
  "wgmma.mma_async.sync.aligned.m64n64k16.f32.bf16.bf16 " P32 ", da, db, " SD ", 1, 1, 1, 1;}"
template <int KS> __device__ __forceinline__ void kgen_mma(float (&c)[32], uint64_t da) {
  if (KS) asm volatile(KGEN_ASM("1") : R32("+f", c) : "l"(da), "n"(8 * KS), "n"(8 * KS + 512));
  else asm volatile(KGEN_ASM("0") : R32("=f", c) : "l"(da), "n"(8 * KS), "n"(8 * KS + 512));
  if constexpr (KS < 7) kgen_mma<KS + 1>(c, da);
}
__device__ __forceinline__ uint64_t desc_lo(uint32_t a) { return (uint64_t)((a & 0x3FFFF) >> 4); }
__device__ __forceinline__ void stage1(float (&D)[32], const uint32_t (&A1)[8], uint32_t src) {
  const uint64_t du = desc_lo(src) | (128ull << 16) | (32ull << 32) | (2ull << 62);
  rs64<0, 1, 0>(D, A1, du); rs64<1, 1, 64>(D, A1 + 4, du);
}
template <int INV> __device__ __forceinline__ void stage2(uint32_t (&X)[16], const uint32_t (&F)[16], uint32_t cf) {
  constexpr int KS = INV ? 16 : 128, TB = INV ? 0 : 1;
  const uint64_t dc = desc_lo(cf) | (INV ? (8ull << 16) | (64ull << 32) : (64ull << 16) | (8ull << 32));
  rs64h<0, TB, 0>(X, F, dc); rs64h<1, TB, KS>(X, F + 4, dc); rs64h<1, TB, 2 * KS>(X, F + 8, dc); rs64h<1, TB, 3 * KS>(X, F + 12, dc);
}
__device__ __forceinline__ void fwd_mid(uint32_t (&F)[16], const float (&D)[32], const uint32_t (&tc)[4], const uint32_t (&ts)[4]) {
#pragma unroll
  for (int j = 0; j < 4; j++)
#pragma unroll
    for (int b = 0; b < 2; b++) {
      const int i = 4 * j + 16 * b;
      const uint32_t ar = packh(D[i], D[i + 1]), ai = packh(D[i + 2], D[i + 3]);
      F[2 * j + b] = ffma(ar, tc[j], fmul(ai, ts[j]));
      F[8 + 2 * j + b] = ffma(ai, tc[j], fneg(fmul(ar, ts[j])));
    }
}
__device__ __forceinline__ void put_exp(uint32_t a, uint32_t m, int lane) {
  m = __reduce_max_sync(0xffffffffu, max(m & 0x7f80u, (m >> 16) & 0x7f80u));
  if (lane == 0) sts32(a, m);
}
__device__ __forceinline__ uint32_t seq_mag(uint32_t a) {
  const uint4 x = lds128(a), y = lds128(a + 2048);
  return amax2(amax2(amax2(x.x, x.y), amax2(x.z, x.w)), amax2(amax2(y.x, y.y), amax2(y.z, y.w)));
}
__device__ __forceinline__ uint32_t get_exp(uint32_t a) { const uint4 v = lds128(a); return max(max(v.x, v.y), max(v.z, v.w)) >> 7; }
__device__ __forceinline__ void scale_a1(uint32_t (&As)[8], const uint32_t (&A1)[8], uint32_t field) {
#pragma unroll
  for (int i = 0; i < 8; i++) As[i] = hmul2(A1[i], field * 0x00800080u);
}

struct cf { float x, y; };
__device__ __forceinline__ cf cmul(cf a, cf b) { cf r; r.x = fmaf(a.x, b.x, -a.y * b.y); r.y = fmaf(a.x, b.y, a.y * b.x); return r; }
__device__ __forceinline__ cf cexp_p(float lr2, float lt, float p) {
  float m;
  asm("ex2.approx.ftz.f32 %0, %1;" : "=f"(m) : "f"(lr2 * p));
  float t = lt * p;
  t = (t - rintf(t)) * 6.283185307179586f;
  cf r; r.x = m * __cosf(t); r.y = m * __sinf(t); return r;
}
__device__ __forceinline__ void store8(uint32_t a, uint32_t b, const cf (&v)[8]) {
  sts128(a, pack(v[0].x, v[1].x), pack(v[2].x, v[3].x), pack(v[4].x, v[5].x), pack(v[6].x, v[7].x));
  sts128(b, pack(v[0].y, v[1].y), pack(v[2].y, v[3].y), pack(v[4].y, v[5].y), pack(v[6].y, v[7].y));
}
__device__ __forceinline__ void mbar_arrive(uint32_t m) { asm volatile("mbarrier.arrive.shared::cta.b64 _, [%0];" :: "r"(m) : "memory"); }
__device__ __forceinline__ float sigmoidf_(float s) { return __frcp_rn(1.f + __expf(-s)); }

__global__ void __cluster_dims__(CS, 1, 1) __launch_bounds__(NTHREADS, 1) fused_kernel(const __grid_constant__ Params p) {
  extern __shared__ __align__(1024) uint8_t smem[];
  TL_INIT();
  TL(31);
  const int wid = __shfl_sync(0xffffffffu, threadIdx.x >> 5, 0);
  const uint32_t sb = (uint32_t)__cvta_generic_to_shared(smem);
  const uint32_t mb = sb + OFF_MB;
  const int u = wid >> 2, w = wid & 3;
  const int tid = threadIdx.x & 127, lane = tid & 31, g = lane >> 2, t = lane & 3;
  const int cl = blockIdx.x >> 3, rank = blockIdx.x & 7;
  const int ch0 = cl * CPC;
  const int nu = min(5, (DCH - ch0) >> 3);
  const bool act = u < nu;

  if (u == 4 && elect()) {
#pragma unroll
    for (int i = 0; i < 5; i++) mbar_init(mb + 40 * w + 8 * i, w == 3 ? 1 : w == 2 ? 3 : 2);
    if (w == 3) {
      mbar_init(mb + 8 * MB_XQ, 2); mbar_init(mb + 8 * MB_KV, 1); mbar_init(mb + 8 * MB_CF, 1); mbar_init(mb + 8 * MB_Q2, 9);
    }
    fence_mbinit();
    if (w == 3) {
      mbar_expect(mb + 8 * MB_CF, 12288);
      asm volatile("cp.async.bulk.prefetch.L2.global [%0], 20480;" :: "l"(p.tab) : "memory");
      mbar_expect(mb + 8 * MB_XQ, 20480); mbar_expect(mb + 8 * MB_KV, 23040 + 20480); mbar_expect(mb + 8 * MB_Q2, 20480);
    }
#pragma unroll
    for (int i = 0; i < 5; i++) mbar_expect(mb + 40 * w + 8 * i, w == 3 ? 4096 : w == 2 ? 7168 : 3584);
  }
  uint32_t pla, pai, pcr, pci, pdt, tag = 0;
  uint4 psm, hm0, hm1;
  {
    const int ch = act ? ch0 + 8 * u + rank : 0, o = ch * NMODE + tid;
    pla = ldraw(p.logA + o); pdt = ldraw(p.logdt + ch); pai = ldraw(p.Aim + o); pcr = ldraw(p.Cre + o); pci = ldraw(p.Cim + o);
    hm0 = ldg128(p.ssm_k + (size_t)ch * SEQ + 8 * tid); hm1 = ldg128(p.ssm_k + (size_t)ch * SEQ + 1024 + 8 * tid);
    if (w == 1) {
      if (lane < 9) psm = ldg128(lane < 5 ? p.gate_w + (lane < nu ? ch0 + 8 * lane : 0) : p.shift_k + (act ? ch0 + 8 * u : 0) * 4 + 8 * (lane - 5));
      else { psm.x = ldraw(p.Dskip + ch); psm.y = ldraw(p.ssm_D + ch); }
    }
    if (wid == 16 && lane < 2) asm volatile("atom.relaxed.gpu.global.add.u32 %0, [%1], %2;" : "=r"(tag) : "l"(&p.cnt[rank * 32 + lane]), "r"(cl == 0 ? 16 - (NCL - 1) : 1) : "memory");
  }
  if (wid == 19 && elect()) {
    tma_load4(sb + OFF_TQ, &p.tq, ch0, 0, 0, 8 * rank, mb + 8 * MB_XQ);
    TL(20);
  }
  __syncwarp();
  cluster_arrive();
  TL(0);

  const uint32_t tab = sb + OFF_T + u * KTAB;
  const int mi = lane >> 3, tq = (lane & 7) >> 1, jj = lane & 1;
  const uint32_t toff = (4 * (2 * mi + jj) + tq) * 80;
  const uint32_t uoff = 16 * (4 * w + (t ^ (w >> 1)));
  auto put = [&](int stage, int dst, uint32_t off, const uint32_t (&v)[4]) {
    sts128(sb + off + (g == rank ? dst + 512 * rank : stage + g * YPITCH), v[0], v[1], v[2], v[3]);
  };
  const int d0 = rank ^ (2 * w), d1 = d0 ^ 1;
  const uint32_t rb0 = mapa(sb, d0), rb1 = mapa(sb, d1);
  auto send = [&](int stage, int pitch, int dst, int mbar) {
    if (elect()) {
      if (w) bulk_dsmem(rb0 + dst, sb + stage + d0 * pitch, rb0 + mbar); else mbar_arrive(sb + mbar);
      bulk_dsmem(rb1 + dst, sb + stage + d1 * pitch, rb1 + mbar);
    }
    __syncwarp();
  };

  if (w == 1 && lane < 10) sts128(sb + OFF_SP + 160 * u + 16 * lane, psm.x, psm.y, psm.z, psm.w);
  uint32_t A1[8], tc[4], ts[4];
  {
    const float dt = bf16r(expf(blo(pdt)));
    const float lr2 = (-bf16r(expf(blo(pla))) * dt) * 1.4426950408889634f;
    const float lt = (blo(pai) * dt) * 0.15915494309189535f;
    const uint32_t tim = sb + OFF_IM + (u < 2 ? 3 + u : u - 2) * KTAB;
    const uint32_t row = tab + tid * 16, rim = tim + tid * 16;
    float zq = 0.f;
    const cf w1 = cexp_p(lr2, lt, 8.f);
    cf z1 = cexp_p(lr2, lt, 1.f), Z = cexp_p(lr2, lt, 256.f);
    if (lr2 != 123.f) TL(16);
    if (wid == 16) {
      if (lane == 0) { sts32(mb + 8 * MB_TAG, tag); mbar_arrive(mb + 8 * MB_XQ); }
      if (elect()) {
        const uint32_t o = blockIdx.x * 9856u, n = min(9856u, SEQ * DCH - o) * 2;
        asm volatile("cp.async.bulk.prefetch.L2.global [%0], %1;" :: "l"(p.k + o), "r"(n) : "memory");
        asm volatile("cp.async.bulk.prefetch.L2.global [%0], %1;" :: "l"(p.v + o), "r"(n) : "memory");
      }
      __syncwarp();
    }
    TL(12);
    {
      cf v[8];
      v[0].x = 1.f; v[0].y = 0.f; v[1] = w1; v[2] = cmul(w1, w1); v[3] = cmul(v[2], w1);
      const cf w4 = cmul(v[2], v[2]);
      v[4] = w4; v[5] = cmul(v[1], w4); v[6] = cmul(v[2], w4); v[7] = cmul(v[3], w4);
      const cf w8 = cmul(w4, w4);
      store8(row, rim, v);
#pragma unroll
      for (int k = 1; k < 4; k++) {
#pragma unroll
        for (int i = 0; i < 8; i++) v[i] = (k == 1 && i == 0) ? w8 : cmul(v[i], w8);
        store8(row + 2048 * k, rim + 2048 * k, v);
      }
    }
    if (u == 0) {
      float z[4];
      wg_fence();
      asm volatile("wgmma.mma_async.sync.aligned.m64n8k16.f32.bf16.bf16 {%0,%1,%2,%3}, %4, %4, 0, 1, 1, 0, 0;"
                   : "=f"(z[0]), "=f"(z[1]), "=f"(z[2]), "=f"(z[3]) : "l"(desc_lo(sb + OFF_UX) | (8ull << 16) | (16ull << 32)));
      wg_commit();
      zq = z[0];
    }
    {
      z1.y = -z1.y; Z.y = -Z.y;
      const cf z2 = cmul(z1, z1);
      cf h[8], v[8];
      h[0].x = 2.f * blo(pcr) * dt; h[0].y = -2.f * blo(pci) * dt;
      h[1] = cmul(h[0], z1);
#pragma unroll
      for (int i = 2; i < 8; i++) h[i] = cmul(h[i - 2], z2);
      store8(row + 4 * 2048, rim + 4 * 2048, h);
      const cf h8 = cmul(h[6], z2);
      v[0] = cmul(h[0], Z); v[2] = cmul(h[2], Z); v[3] = cmul(h[4], Z); v[6] = cmul(h[6], Z); v[7] = cmul(h8, Z);
      v[1] = v[0]; v[4] = v[5] = v[3];
      store8(row + 5 * 2048, rim + 5 * 2048, v);
      h[0] = cmul(v[0], Z); h[1] = cmul(v[3], Z); h[3] = cmul(v[7], Z); h[4] = cmul(h[0], Z); h[5] = cmul(h[1], Z); h[7] = cmul(h[3], Z);
      h[2] = h[1]; h[6] = h[5];
      store8(row + 6 * 2048, rim + 6 * 2048, h);
      const cf Z2 = cmul(Z, Z);
      v[0] = cmul(h[0], Z2); v[1] = cmul(h[3], Z2); v[2] = cmul(h[4], Z2); v[3] = cmul(h[7], Z2);
#pragma unroll
      for (int i = 4; i < 8; i++) v[i] = cmul(v[i - 4], Z2);
      store8(row + 7 * 2048, rim + 7 * 2048, v);
    }
    TL(17);
    put_exp(sb + OFF_MX + u * 64 + 32 + 4 * w, amax2(amax2(amax2(hm0.x, hm0.y), amax2(hm0.z, hm0.w)), amax2(amax2(hm1.x, hm1.y), amax2(hm1.z, hm1.w))), lane);
    cluster_wait();
    mbar_wait(mb + 8 * MB_XQ);
    TL(18);
    {
      uint32_t x0[4], x1[4];
      ldsm4t(x0, sb + OFF_TQ + w * 2560 + toff + 16 * u);
      ldsm4t(x1, sb + OFF_TQ + (w + 4) * 2560 + toff + 16 * u);
      put(OFF_YB + 8 * u * YPITCH, OFF_UX + u * 4096, uoff, x0);
      put(OFF_YB + 8 * u * YPITCH, OFF_UX + u * 4096, (uoff ^ 32) + 256, x1);
    }
    TL(3);
    fence_async();
    bar_sync(NB_WG0 + u, 128);
    TL(4);
    if (u) send(OFF_YB + 8 * u * YPITCH, YPITCH, OFF_UX + u * 4096 + 512 * rank, OFF_MB + 8 * (MB_UX + u));
    if (u >= 3) {
      float s0 = 0.f;
#pragma unroll
      for (int j = 0; j < 5; j++) {
        const uint4 gw = lds128(sb + OFF_SP + 160 * u + 16 * j), x = lds128(sb + OFF_TQ + (tid + 128 * (u - 3)) * 80 + 16 * j);
        const uint32_t m0 = hmul2(x.x, gw.x), m1 = hmul2(x.y, gw.y), m2 = hmul2(x.z, gw.z), m3 = hmul2(x.w, gw.w);
        s0 += ((blo(m0) + bhi(m0)) + (blo(m1) + bhi(m1))) + ((blo(m2) + bhi(m2)) + (blo(m3) + bhi(m3)));
      }
      tag = (lds64(mb + 8 * MB_TAG).x >> 4) + 1;
      asm volatile("st.relaxed.gpu.global.u64 [%0], %1;" :: "l"(p.part + cl * SEQ + rank * 256 + 8 * (8 * t + g) + w + 4 * (u - 3)),
                   "l"(((uint64_t)tag << 32) | __float_as_uint(s0)) : "memory");
    }
    TL(7);
    if (u) bar_sync(NB_ORD + u - 1, 256);
    TL(13);
    float c[32];
    wg_fence();
    kgen_mma<0>(c, desc_lo(tab) | ((uint64_t)((tim - tab) >> 4) << 16) | (64ull << 32));
    wg_commit();
    if (u < 4) bar_arrive(NB_ORD + u, 256);
    if (u == 0) send(OFF_YB, YPITCH, OFF_UX + 512 * rank, OFF_MB + 8 * MB_UX);
    {
      const uint4 x = ldg128(p.tab->thr[0][tid]), y = ldg128(p.tab->thr[1][tid]), a = ldg128(p.tab->thr[2][tid]), b = ldg128(p.tab->thr[3][tid]);
      A1[0] = x.x; A1[1] = x.y; A1[2] = x.z; A1[3] = x.w; A1[4] = y.x; A1[5] = y.y; A1[6] = y.z; A1[7] = y.w;
      tc[0] = a.x; tc[1] = a.y; tc[2] = a.z; tc[3] = a.w; ts[0] = b.x; ts[1] = b.y; ts[2] = b.z; ts[3] = b.w;
    }
    wg_wait<0>(); tie_all(c);
    TL(26);
    cluster_arrive();
    if (zq == 1.2345e-30f) c[0] = 0.f;
    if (wid == 17) {
      bar_sync(NB_LD, 640);
      if (elect()) {
        tma_load4(sb + OFF_TK, &p.tk, ch0, 0, 0, 8 * rank - 1, mb + 8 * MB_KV);
        tma_load4(sb + OFF_TV, &p.tv, ch0, 0, 0, 8 * rank, mb + 8 * MB_KV);
      }
      __syncwarp();
    } else {
      bar_arrive(NB_LD, 640);
    }
    bar_sync(NB_WG0 + u, 128);
    if (wid == 1 && elect())
      asm volatile("cp.async.bulk.shared::cluster.global.mbarrier::complete_tx::bytes [%0], [%1], %2, [%3];"
                   :: "r"(sb + OFF_CF), "l"(p.tab->mat), "r"(12288), "r"(mb + 8 * MB_CF) : "memory");
    __syncwarp();
    const uint32_t k0 = pack(c[0] + c[6], c[1] + c[7]), k1 = pack(c[8] + c[14], c[9] + c[15]);
    const uint32_t k2 = pack(c[16] + c[22], c[17] + c[23]), k3 = pack(c[24] + c[30], c[25] + c[31]);
    const uint32_t ka = tab + 16 * (8 * w + (g ^ w));
    sts32(ka + 4 * t, k0);
    sts32(ka + 512 + 4 * t, k1);
    sts64(ka + 1024 + 512 * (t >> 1) + 8 * (t & 1), prmt(k2, 0, 0x1010), (t & 1) ? prmt(k2, 0, 0x3232) : k2);
    const uint32_t lo = prmt(k3, 0, 0x1010), hi = prmt(k3, 0, 0x3232);
    sts128(ka + 2048 + 512 * t, lo, lo, (g & 1) ? hi : k3, hi);
    put_exp(sb + OFF_MX + u * 64 + 4 * w, amax2(amax2(k0, k1), amax2(k2, k3)), lane);
    TL(15);
    fence_async();
    bar_sync(NB_WG0 + u, 128);
  }

#pragma unroll
  for (int isA = 0; isA < 2; isA++) {
    {
      TL(1 + isA);
      const uint32_t usrc = isA ? tab + T_UKV : sb + OFF_UX + u * 4096;
      const uint32_t mxa = sb + OFF_MX + u * 64 + 32 * isA;
      const uint32_t pd = lds16(sb + OFF_SP + 160 * u + 144 + 4 * isA);
      float D[32];
      uint32_t As[8], F[16], H[16], X[16];
      const uint32_t eh = min(max((int)get_exp(mxa), (int)((pd >> 7) & 0xff) - 5), 240);
      scale_a1(As, A1, 248 - eh);
      if (isA) mbar_wait(mb + 8 * (MB_HA + u));
      wg_fence();
      stage1(D, As, isA ? tab + T_HA : tab);
      wg_commit();
      wg_wait<0>(); tie_all(D);
      fwd_mid(F, D, tc, ts);
      if (!isA) mbar_wait(mb + 8 * MB_CF);
      wg_fence();
      stage2<0>(H, F, sb + OFF_CF);
      wg_commit();
      mbar_wait(mb + 8 * ((isA ? MB_UKV : MB_UX) + u));
      TL(5 + isA);
      put_exp(mxa + 16 + 4 * w, seq_mag(usrc + 16 * tid), lane);
      bar_sync(NB_WG0 + u, 128);
      const uint32_t eu = min(get_exp(mxa + 16), 240u);
      scale_a1(As, A1, 250 - eu);
      wg_wait<0>(); tie_all(H);
      wg_fence();
      stage1(D, As, usrc);
      wg_commit();
      wg_wait<0>(); tie_all(D);
      fwd_mid(F, D, tc, ts);
      wg_fence();
      stage2<0>(X, F, sb + OFF_CF);
      wg_commit();
      if (!isA && w == 1 && elect()) {
        tma_load4(tab + T_HA, &p.th, 0, 0, 5 * cl + u, rank, mb + 8 * (MB_HA + u));
        if (u == 4) tma_load3(sb + OFF_Q2, &p.tq2, ch0, 8 * rank, 0, mb + 8 * MB_Q2);
      }
      __syncwarp();
      {
        const float dsk = blo(pd) * __uint_as_float((248 - eh) << 23);
        const uint32_t d2 = packh(dsk, dsk);
#pragma unroll
        for (int j = 0; j < 4; j++) H[2 * j] = U2(__hadd2(H2(H[2 * j]), H2(d2)));
      }
      wg_wait<0>(); tie_all(X);
#pragma unroll
      for (int j = 0; j < 4; j++) {
        const uint32_t h0r = H[2 * j], h1r = H[2 * j + 1], h0i = H[8 + 2 * j], h1i = H[9 + 2 * j];
        const uint32_t x0r = X[2 * j], x1r = X[2 * j + 1], x0i = X[8 + 2 * j], x1i = X[9 + 2 * j];
        F[2 * j] = ffma(x0r, h0r, fneg(fmul(x0i, h0i)));
        F[8 + 2 * j] = ffma(x0r, h0i, fmul(x0i, h0r));
        F[2 * j + 1] = ffma(x1r, h0r, ffma(fneg(x1i), h0i, ffma(x0r, h1r, fneg(ffma(x0i, h1i, F[8 + 2 * j])))));
        F[9 + 2 * j] = ffma(x1r, h0i, ffma(x1i, h0r, ffma(x0r, h1i, ffma(x0i, h1r, F[2 * j]))));
      }
      wg_fence();
      stage2<1>(H, F, sb + OFF_CF);
      wg_commit();
      wg_wait<0>(); tie_all(H);
      {
        const uint32_t va = tab + (16 * w + (lane & 15)) * 128;
        const int vx = (lane >> 4) ^ (lane & 7);
#pragma unroll
        for (int j = 0; j < 4; j++) {
          uint32_t V[4];
#pragma unroll
          for (int b = 0; b < 2; b++) {
            const uint32_t er = H[2 * j + b], ei = H[8 + 2 * j + b];
            V[2 * b] = ffma(er, tc[j], fneg(fmul(ei, ts[j])));
            V[2 * b + 1] = ffma(ei, tc[j], fmul(er, ts[j]));
          }
          stsm4(va + ((vx ^ (2 * j)) << 4), V);
        }
      }
      uint64_t ga[NCL];
      const int slot = tid + 128 * (u & 1);
      const uint2* gp = p.part + rank * 256 + slot;
      auto gload = [&]() {
#pragma unroll
        for (int k = 0; k < NCL; k++) asm volatile("ld.relaxed.gpu.global.u64 %0, [%1];" : "=l"(ga[k]) : "l"(gp + k * SEQ) : "memory");
      };
      if (!isA) {
        cluster_wait();
        mbar_wait(mb + 8 * MB_KV);
        TL(21);
        const uint32_t hoff = (4 * (4 + 2 * (mi & 1) + jj) + ((tq + 3) & 3)) * 80 + (tq ? 2560 : 0) + 16 * u;
        uint32_t E[2][6], V[2][4];
        const uint2 psw = lds64(sb + OFF_SP + 160 * u + 80 + 8 * g);
#pragma unroll
        for (int hf = 0; hf < 2; hf++) {
          const int ah = 4 * hf + w;
          uint32_t K[4];
          ldsm4t(K, sb + OFF_TK + (ah + 1) * 2560 + toff + 16 * u);
          ldsm2t(E[hf][0], E[hf][1], sb + OFF_TK + ah * 2560 + hoff);
          ldsm4t(V[hf], sb + OFF_TV + ah * 2560 + toff + 16 * u);
          E[hf][2] = K[0]; E[hf][3] = K[1]; E[hf][4] = K[2]; E[hf][5] = K[3];
        }
        const uint32_t w0 = prmt(psw.x, 0, 0x1010), w1 = prmt(psw.x, 0, 0x3232), w2 = prmt(psw.y, 0, 0x1010), w3 = prmt(psw.y, 0, 0x3232);
        uint32_t o[2][4];
#pragma unroll
        for (int hf = 0; hf < 2; hf++) {
          uint32_t O[5];
#pragma unroll
          for (int i = 0; i < 5; i++) O[i] = prmt(E[hf][i], E[hf][i + 1], 0x5432);
#pragma unroll
          for (int i = 0; i < 4; i++) {
            o[hf][i] = hmul2(hfma2(E[hf][i + 2], w0, hfma2(O[i + 1], w1, hfma2(E[hf][i + 1], w2, hmul2(O[i], w3)))), V[hf][i]);
          }
          put(OFF_YA + 8 * u * YPITCH, OFF_T + u * KTAB + T_UKV, hf ? (uoff ^ 32) + 256 : uoff, o[hf]);
        }
        TL(22);
      }
      fence_async();
      bar_sync(NB_WG0 + u, 128);
      float O[16];
      {
        const uint64_t dv = desc_lo(tab) | (1ull << 16) | (64ull << 32) | (1ull << 62);
        const uint64_t dl = desc_lo(sb + OFF_CL) | (32ull << 16) | (8ull << 32);
        wg_fence();
        ss32<0, 0, 0>(O, dv, dl); ss32<1, 128, 64>(O, dv, dl); ss32<1, 256, 128>(O, dv, dl); ss32<1, 384, 192>(O, dv, dl);
        wg_commit();
      }
      if (!isA) {
        send(OFF_YA + 8 * u * YPITCH, YPITCH, OFF_T + u * KTAB + T_UKV + 512 * rank, OFF_MB + 8 * (MB_UKV + u));
        if (u < 2) gload();
      }
      wg_wait<0>(); tie_all(O);
      {
        const uint32_t co = ((8 * w + g) ^ (2 * t)) * 16;
        const int yo = (isA ? OFF_YA : OFF_YB) + (8 * u + rank) * YPITCH, ym = OFF_MB + 8 * (MB_Y + u);
        const uint32_t us = min(max((int)(eu + eh) - 127, 0), 254) * 0x00800080u;
        const uint32_t a0 = hmul2(pack(O[0], O[1]), us), a1 = hmul2(pack(O[4], O[5]), us), a2 = hmul2(pack(O[8], O[9]), us), a3 = hmul2(pack(O[12], O[13]), us);
        const uint32_t b0 = hmul2(pack(O[2], O[3]), us), b1 = hmul2(pack(O[6], O[7]), us), b2 = hmul2(pack(O[10], O[11]), us), b3 = hmul2(pack(O[14], O[15]), us);
        sts128((t == rank ? sb + yo : usrc + t * 512) + co, a0, a1, a2, a3);
        sts128((t + 4 == rank ? sb + yo : usrc + t * 512 + 2048) + co, b0, b1, b2, b3);
        fence_async();
        bar_sync(NB_WG0 + u, 128);
        send(usrc - sb, 512, yo, ym);
      }
      TL(9 + isA);
      if (!isA && u < 2) {
        tag = (lds64(mb + 8 * MB_TAG).x >> 4) + 1;
        float s;
        bool ok;
#pragma unroll 1
        for (int it = 0;; it++) {
          ok = true; s = 0.f;
#pragma unroll
          for (int k = 0; k < NCL; k++) { ok = ok && (uint32_t)(ga[k] >> 32) == tag; s += __uint_as_float((uint32_t)ga[k]); }
          if (ok || it == 4000) break;
          gload();
        }
        if (!ok) {
          const uint32_t* xr = (const uint32_t*)(p.q + (size_t)(rank * 256 + 32 * (slot & 7) + (slot >> 3)) * DCH);
          const uint32_t* gr = (const uint32_t*)p.gate_w;
          s = 0.f;
    #pragma unroll 1
          for (int k = 0; k < DCH / 2; k++) { const uint32_t m = hmul2(__ldg(xr + k), __ldg(gr + k)); s += blo(m) + bhi(m); }
        }
        const float g0 = bf16r(sigmoidf_(bf16r(s)));
        sts64(sb + OFF_GB + 8 * slot, pack(g0, g0), pack(1.f - g0, 1.f - g0));
        __syncwarp();
        if (lane == 0) mbar_arrive(mb + 8 * MB_Q2);
      }
    }
  }

  {
    mbar_wait(mb + 8 * MB_Q2);
    uint2 gg[2][4];
    uint32_t qv[2][4];
#pragma unroll
    for (int hh = 0; hh < 2; hh++)
#pragma unroll
      for (int i = 0; i < 4; i++) gg[hh][i] = lds64(sb + OFF_GB + 8 * (64 * w + 32 * hh + 8 * i + g));
    const uint32_t qa = sb + OFF_Q2 + (64 * w + lane) * 80 + 16 * u;
    ldsm4(qv[0], qa);
    ldsm4(qv[1], qa + 2560);
    TL(24);
    mbar_wait(mb + 8 * (MB_Y + u));
    uint32_t ya[2][4], yb[2][4];
#pragma unroll
    for (int hh = 0; hh < 2; hh++) {
      const uint32_t yo = (8 * u + (lane & 7)) * YPITCH + ((8 * w + 4 * hh + (lane >> 3)) ^ (2 * (rank & 3))) * 16;
      ldsm4t(ya[hh], sb + OFF_YA + yo); ldsm4t(yb[hh], sb + OFF_YB + yo);
    }
#pragma unroll
    for (int hh = 0; hh < 2; hh++) {
      uint32_t o[4];
#pragma unroll
      for (int i = 0; i < 4; i++) o[i] = hadd2(hmul2(gg[hh][i].x, hmul2(qv[hh][i], ya[hh][i])), hmul2(gg[hh][i].y, yb[hh][i]));
      stsm4(qa + 2560 * hh, o);
    }
    TL(25);
  }
  cluster_arrive();
  bar_sync(NB_ROW0 + w, 160);
  {
    uint4 v[2];
#pragma unroll
    for (int k = 0; k < 2; k++) {
      const int i = 64 * u + 32 * k + lane, sl = (i * 205) >> 10, cc = i - 5 * sl;
      v[k] = lds128(sb + OFF_Q2 + (64 * w + 8 * (sl & 7) + (sl >> 3)) * 80 + cc * 16);
    }
#pragma unroll
    for (int k = 0; k < 2; k++) {
      const int i = 64 * u + 32 * k + lane, sl = (i * 205) >> 10, cc = i - 5 * sl;
      if (cc < nu)
        asm volatile("st.global.v4.u32 [%0], {%1,%2,%3,%4};" :: "l"(p.out + (size_t)(256 * rank + 32 * (sl >> 3) + 8 * w + (sl & 7)) * DCH + ch0 + 8 * cc),
                     "r"(v[k].x), "r"(v[k].y), "r"(v[k].z), "r"(v[k].w) : "memory");
    }
  }
  cluster_wait();
  TL(27);
  TL_DUMP();
}

typedef CUresult (*EncodeFn)(CUtensorMap*, CUtensorMapDataType, cuuint32_t, void*, const cuuint64_t*, const cuuint64_t*,
                             const cuuint32_t*, const cuuint32_t*, CUtensorMapInterleave, CUtensorMapSwizzle,
                             CUtensorMapL2promotion, CUtensorMapFloatOOBfill);

void encode(EncodeFn fn, CUtensorMap* tm, const void* ptr, int nd, const cuuint64_t* dims, const cuuint64_t* strides,
            const cuuint32_t* box, CUtensorMapSwizzle swz) {
  cuuint32_t es[4] = {1, 1, 1, 1};
  fn(tm, CU_TENSOR_MAP_DATA_TYPE_BFLOAT16, nd, const_cast<void*>(ptr), dims, strides, box, es, CU_TENSOR_MAP_INTERLEAVE_NONE,
     swz, CU_TENSOR_MAP_L2_PROMOTION_L2_128B, CU_TENSOR_MAP_FLOAT_OOB_FILL_NONE);
}
void map1(EncodeFn fn, CUtensorMap* tm, const void* ptr, int nhi) {
  const cuuint64_t dims[4] = {DCH, 4, 8, SEQ / 32}, strides[3] = {8 * DCH * 2, DCH * 2, 32 * DCH * 2};
  const cuuint32_t box[4] = {CPC, 4, 8, (cuuint32_t)nhi};
  encode(fn, tm, ptr, 4, dims, strides, box, CU_TENSOR_MAP_SWIZZLE_NONE);
}
void map2(EncodeFn fn, CUtensorMap* tm, const void* ptr, int nr) {
  const cuuint64_t dims[3] = {DCH, SEQ / 32, 32}, strides[2] = {32 * DCH * 2, DCH * 2};
  const cuuint32_t box[3] = {CPC, 8, (cuuint32_t)nr};
  encode(fn, tm, ptr, 3, dims, strides, box, CU_TENSOR_MAP_SWIZZLE_NONE);
}

}

extern "C" void kernel_launch(void* const* d_in, const int* in_sizes, int n_in, void* d_out, int out_size) {
  (void)in_sizes; (void)n_in; (void)out_size;
  static EncodeFn fn = nullptr;
  static void *tab = nullptr, *cnt = nullptr, *part = nullptr;
  if (!fn) {
    cudaGetSymbolAddress(&tab, d_tab);
    cudaGetSymbolAddress(&cnt, g_cnt);
    cudaGetSymbolAddress(&part, g_part);
    cudaDriverEntryPointQueryResult qr;
    cudaGetDriverEntryPoint("cuTensorMapEncodeTiled", (void**)&fn, cudaEnableDefault, &qr);
    cudaFuncSetAttribute(fused_kernel, cudaFuncAttributeMaxDynamicSharedMemorySize, SMEM_BYTES);
  }
  Params p;
  map1(fn, &p.tq, d_in[0], 8);
  map1(fn, &p.tk, d_in[1], 9);
  map1(fn, &p.tv, d_in[2], 8);
  map2(fn, &p.tq2, d_in[0], 32);
  p.out = (__nv_bfloat16*)d_out;
  {
    const cuuint64_t dims[4] = {32, SEQ / 32, DCH / 8, 8}, strides[3] = {64, 8 * SEQ * 2, SEQ * 2};
    const cuuint32_t box[4] = {32, 64, 1, 1};
    encode(fn, &p.th, d_in[4], 4, dims, strides, box, CU_TENSOR_MAP_SWIZZLE_64B);
  }
  p.tab = (const Tables*)tab;
  p.cnt = (unsigned*)cnt;
  p.part = (uint2*)part;
  p.tl = nullptr;
  p.q = (const __nv_bfloat16*)d_in[0];
  p.k = (const __nv_bfloat16*)d_in[1];
  p.v = (const __nv_bfloat16*)d_in[2];
  p.ssm_k = (const __nv_bfloat16*)d_in[4];
  p.shift_k = (const __nv_bfloat16*)d_in[3];
  p.ssm_D = (const __nv_bfloat16*)d_in[5];
  p.logA = (const __nv_bfloat16*)d_in[7];
  p.Aim = (const __nv_bfloat16*)d_in[8];
  p.Cre = (const __nv_bfloat16*)d_in[9];
  p.Cim = (const __nv_bfloat16*)d_in[10];
  p.logdt = (const __nv_bfloat16*)d_in[11];
  p.Dskip = (const __nv_bfloat16*)d_in[12];
  p.gate_w = (const __nv_bfloat16*)d_in[13];
  fused_kernel<<<NCL * CS, NTHREADS, SMEM_BYTES, cudaStreamPerThread>>>(p);
}
```

```cpp
#include <cuda_runtime.h>
#include <cuda_bf16.h>
#include <cuda_fp16.h>
#include <cuda.h>
#include <stdint.h>

#define TIMELINE 0

namespace {

constexpr int SEQ = 2048, DCH = 576, NMODE = 128;
constexpr int CS = 8, CPC = 40, NCL = 15, NTHREADS = 640;

constexpr int YPITCH = 528;
constexpr int KTAB = 16384;
constexpr int OFF_T = 0;
constexpr int T_UKV = 8192, T_HA = 12288;
constexpr int OFF_UX = 5 * KTAB;
constexpr int OFF_IM = OFF_UX + 20480;
constexpr int OFF_Q2 = OFF_IM;
constexpr int OFF_GB = OFF_Q2 + 20480;
constexpr int OFF_TV = OFF_IM + 3 * KTAB - 20480;
constexpr int OFF_CF = OFF_IM + 3 * KTAB;
constexpr int OFF_CL = OFF_CF + 8192;
constexpr int OFF_TK = OFF_CL + 4096;
constexpr int OFF_TQ = OFF_TK + 23040;
constexpr int OFF_YA = OFF_TQ;
constexpr int OFF_YB = OFF_TQ + 21120;
constexpr int OFF_MX = OFF_YB + 40 * YPITCH;
constexpr int OFF_SP = OFF_MX + 320;
constexpr int OFF_MB = OFF_SP + 5 * 160;
constexpr int OFF_TL = OFF_MB + 32 * 8;
constexpr int SMEM_BYTES = OFF_TL + (TIMELINE ? 1280 : 0);
static_assert(SMEM_BYTES <= 232448 && OFF_IM + 5 * KTAB <= OFF_TQ, "smem");
static_assert((OFF_TQ & 127) == 0 && (OFF_TK & 127) == 0 && (OFF_TV & 127) == 0 && (OFF_MB & 7) == 0 && (OFF_MX & 15) == 0, "align");

enum { MB_UX = 0, MB_UKV = 5, MB_Y = 10, MB_HA = 15, MB_XQ = 20, MB_KV = 21, MB_CF = 22, MB_Q2 = 23, MB_XD = 24, MB_TAG = 25 };
enum { NB_WG0 = 1, NB_ROW0 = 6, NB_ORD = 6, NB_K0 = 10, NB_LD = 11 };

constexpr double cos_turn(int m, int n) {
  m &= n - 1;
  if (m > n / 2) m = n - m;
  double sgn = 1.0;
  if (m > n / 4) { m = n / 2 - m; sgn = -1.0; }
  if (m == n / 4) return 0.0;
  const double x = 6.283185307179586476925 * m / n;
  double term = 1.0, sum = 1.0;
  for (int k = 1; k < 14; k++) { term *= -x * x / ((2 * k - 1) * (2 * k)); sum += term; }
  return sgn * sum;
}
constexpr uint32_t bf16_bits(double v) {
  if (v == 0.0) return 0;
  uint32_t sgn = 0;
  if (v < 0) { sgn = 0x8000; v = -v; }
  int e = 127;
  while (v < 1.0) { v *= 2.0; e--; }
  while (v >= 2.0) { v *= 0.5; e++; }
  const double f = v * 128.0;
  int m = (int)f;
  if (f - m > 0.5 || (f - m == 0.5 && (m & 1))) m++;
  return sgn | (uint32_t)((e << 7) + (m - 128));
}
constexpr uint32_t f16_bits(double v) {
  if (v == 0.0) return 0;
  uint32_t sgn = 0;
  if (v < 0) { sgn = 0x8000; v = -v; }
  int e = 15;
  while (v < 1.0) { v *= 2.0; e--; }
  const double f = v * 1024.0;
  int m = (int)f;
  if (f - m > 0.5 || (f - m == 0.5 && (m & 1))) m++;
  return sgn | (uint32_t)((e << 10) + (m - 1024));
}
constexpr uint32_t pair_bits(double lo, double hi) { return bf16_bits(lo) | (bf16_bits(hi) << 16); }
constexpr uint32_t pair_h(double lo, double hi) { return f16_bits(lo) | (f16_bits(hi) << 16); }
struct alignas(128) Tables {
  uint32_t mat[3072];
  uint32_t thr[4][128][4];
};
constexpr Tables make_tables() {
  Tables T{};
  for (int q = 0; q < 768; q++) {
    int m0 = 0, d0 = 0, d1 = 0;
    if (q < 512) {
      const int r = (q >> 6) * 8 + (q & 7), cc = (q >> 3) & 7;
      d0 = 4 * (r & 31); d1 = 2 * d0;
      m0 = 8 * (cc & 3) * d0 + ((r >> 5) == (cc >> 2) ? 0 : (r >> 5) ? 96 : 32);
    } else {
      const int r = ((q - 512) >> 5) * 8 + (q & 7), pc = (q >> 3) & 3;
      d0 = 4 * (8 * (r >> 4) + (r & 7)) + 1; d1 = 8 * d0;
      m0 = 2 * pc * d0 + ((r & 8) ? 32 : 0);
    }
    for (int e = 0; e < 4; e++) T.mat[4 * q + e] = pair_h(cos_turn(m0 + e * d1, 128), cos_turn(m0 + e * d1 + d0, 128));
  }
  for (int tid = 0; tid < 128; tid++) {
    const int kk = 4 * (tid >> 2) + 1, t = tid & 3;
    for (int q = 0; q < 4; q++) {
      const int m = (8 * q + 2 * t) * kk;
      T.thr[q >> 1][tid][2 * (q & 1)] = pair_bits(cos_turn(m, 128), cos_turn(m + kk, 128));
      T.thr[q >> 1][tid][2 * (q & 1) + 1] = pair_bits(cos_turn(m + 32, 128), cos_turn(m + kk + 32, 128));
      T.thr[2][tid][q] = pair_h(cos_turn(m, 4096), cos_turn(m + kk, 4096));
      T.thr[3][tid][q] = pair_h(cos_turn(m + 3072, 4096), cos_turn(m + kk + 3072, 4096));
    }
  }
  return T;
}
__device__ const Tables d_tab = make_tables();

struct Params {
  const __nv_bfloat16 *logA, *Aim, *Cre, *Cim, *logdt;
  const Tables* tab;
  unsigned* cnt;
  const __nv_bfloat16 *Dskip, *shift_k, *ssm_D, *gate_w, *q, *k, *v, *ssm_k;
  uint2* part;
  __nv_bfloat16* out;
  unsigned* tl;
  CUtensorMap tq, tk, tv, th, tq2;
};

__device__ uint2 g_part[NCL * SEQ];
__device__ unsigned g_cnt[CS * 32];
#define TL(i) do {} while (0)
#define TL_INIT() do {} while (0)
#define TL_DUMP() do {} while (0)

__device__ __forceinline__ uint32_t lds16(uint32_t a) { uint32_t v; asm volatile("ld.shared.u16 %0, [%1];" : "=r"(v) : "r"(a) : "memory"); return v; }
__device__ __forceinline__ uint2 lds64(uint32_t a) { uint2 v; asm volatile("ld.shared.v2.u32 {%0,%1}, [%2];" : "=r"(v.x), "=r"(v.y) : "r"(a) : "memory"); return v; }
__device__ __forceinline__ uint4 lds128(uint32_t a) { uint4 v; asm volatile("ld.shared.v4.u32 {%0,%1,%2,%3}, [%4];" : "=r"(v.x), "=r"(v.y), "=r"(v.z), "=r"(v.w) : "r"(a) : "memory"); return v; }
__device__ __forceinline__ void sts16(uint32_t a, uint32_t v) { asm volatile("st.shared.u16 [%0], %1;" :: "r"(a), "r"(v) : "memory"); }
__device__ __forceinline__ void sts32(uint32_t a, uint32_t v) { asm volatile("st.shared.u32 [%0], %1;" :: "r"(a), "r"(v) : "memory"); }
__device__ __forceinline__ void sts64(uint32_t a, uint32_t x, uint32_t y) { asm volatile("st.shared.v2.u32 [%0], {%1,%2};" :: "r"(a), "r"(x), "r"(y) : "memory"); }
__device__ __forceinline__ void sts128(uint32_t a, uint32_t x, uint32_t y, uint32_t z, uint32_t w) { asm volatile("st.shared.v4.u32 [%0], {%1,%2,%3,%4};" :: "r"(a), "r"(x), "r"(y), "r"(z), "r"(w) : "memory"); }
__device__ __forceinline__ void ldsm4t(uint32_t (&r)[4], uint32_t a) { asm volatile("ldmatrix.sync.aligned.m8n8.x4.trans.shared.b16 {%0,%1,%2,%3}, [%4];" : "=r"(r[0]), "=r"(r[1]), "=r"(r[2]), "=r"(r[3]) : "r"(a) : "memory"); }
__device__ __forceinline__ void ldsm2t(uint32_t& r0, uint32_t& r1, uint32_t a) { asm volatile("ldmatrix.sync.aligned.m8n8.x2.trans.shared.b16 {%0,%1}, [%2];" : "=r"(r0), "=r"(r1) : "r"(a) : "memory"); }
__device__ __forceinline__ void ldsm4(uint32_t (&r)[4], uint32_t a) { asm volatile("ldmatrix.sync.aligned.m8n8.x4.shared.b16 {%0,%1,%2,%3}, [%4];" : "=r"(r[0]), "=r"(r[1]), "=r"(r[2]), "=r"(r[3]) : "r"(a) : "memory"); }
__device__ __forceinline__ void stsm4(uint32_t a, const uint32_t (&r)[4]) { asm volatile("stmatrix.sync.aligned.m8n8.x4.shared.b16 [%0], {%1,%2,%3,%4};" :: "r"(a), "r"(r[0]), "r"(r[1]), "r"(r[2]), "r"(r[3]) : "memory"); }
__device__ __forceinline__ uint32_t pack(float lo, float hi) { uint32_t r; asm("cvt.rn.bf16x2.f32 %0, %1, %2;" : "=r"(r) : "f"(hi), "f"(lo)); return r; }
__device__ __forceinline__ float blo(uint32_t v) { return __uint_as_float(v << 16); }
__device__ __forceinline__ float bhi(uint32_t v) { return __uint_as_float(v & 0xffff0000u); }
__device__ __forceinline__ float bf16r(float x) { return blo(pack(x, 0.f)); }
__device__ __forceinline__ uint32_t hmul2(uint32_t a, uint32_t b) { uint32_t r; asm("mul.rn.bf16x2 %0, %1, %2;" : "=r"(r) : "r"(a), "r"(b)); return r; }
__device__ __forceinline__ uint32_t hadd2(uint32_t a, uint32_t b) { uint32_t r; asm("add.rn.bf16x2 %0, %1, %2;" : "=r"(r) : "r"(a), "r"(b)); return r; }
__device__ __forceinline__ uint32_t hfma2(uint32_t a, uint32_t b, uint32_t c) { uint32_t r; asm("fma.rn.bf16x2 %0, %1, %2, %3;" : "=r"(r) : "r"(a), "r"(b), "r"(c)); return r; }
__device__ __forceinline__ uint32_t packh(float lo, float hi) { uint32_t r; asm("cvt.rn.f16x2.f32 %0, %1, %2;" : "=r"(r) : "f"(hi), "f"(lo)); return r; }
__device__ __forceinline__ __half2 H2(uint32_t a) { return *reinterpret_cast<__half2*>(&a); }
__device__ __forceinline__ uint32_t U2(__half2 a) { return *reinterpret_cast<uint32_t*>(&a); }
__device__ __forceinline__ uint32_t fmul(uint32_t a, uint32_t b) { return U2(__hmul2(H2(a), H2(b))); }
__device__ __forceinline__ uint32_t ffma(uint32_t a, uint32_t b, uint32_t c) { return U2(__hfma2(H2(a), H2(b), H2(c))); }
__device__ __forceinline__ uint32_t fneg(uint32_t a) { return U2(__hneg2(H2(a))); }
__device__ __forceinline__ uint32_t amax2(uint32_t a, uint32_t b) { uint32_t r; asm("max.xorsign.abs.bf16x2 %0, %1, %2;" : "=r"(r) : "r"(a), "r"(b)); return r; }
__device__ __forceinline__ uint32_t prmt(uint32_t a, uint32_t b, uint32_t s) { return __byte_perm(a, b, s); }
__device__ __forceinline__ uint32_t ldraw(const __nv_bfloat16* p) { uint32_t v; asm volatile("ld.global.nc.u16 %0, [%1];" : "=r"(v) : "l"(p)); return v; }
__device__ __forceinline__ uint4 ldg128(const void* p) { uint4 v; asm volatile("ld.global.nc.v4.u32 {%0,%1,%2,%3}, [%4];" : "=r"(v.x), "=r"(v.y), "=r"(v.z), "=r"(v.w) : "l"(p)); return v; }
__device__ __forceinline__ void bar_sync(int id, int n) { asm volatile("bar.sync %0, %1;" :: "r"(id), "r"(n) : "memory"); }
__device__ __forceinline__ void bar_arrive(int id, int n) { asm volatile("bar.arrive %0, %1;" :: "r"(id), "r"(n) : "memory"); }
__device__ __forceinline__ void cluster_arrive() { asm volatile("barrier.cluster.arrive.relaxed.aligned;" ::: "memory"); }
__device__ __forceinline__ void cluster_wait() { asm volatile("barrier.cluster.wait.aligned;" ::: "memory"); }
__device__ __forceinline__ void fence_async() { asm volatile("fence.proxy.async.shared::cta;" ::: "memory"); }
__device__ __forceinline__ void fence_mbinit() { asm volatile("fence.mbarrier_init.release.cluster;" ::: "memory"); }
__device__ __forceinline__ uint32_t mapa(uint32_t a, uint32_t rank) { uint32_t r; asm("mapa.shared::cluster.u32 %0, %1, %2;" : "=r"(r) : "r"(a), "r"(rank)); return r; }
__device__ __forceinline__ void bulk_dsmem(uint32_t dst, uint32_t src, uint32_t mbar) {
  asm volatile("cp.async.bulk.shared::cluster.shared::cta.mbarrier::complete_tx::bytes [%0], [%1], 512, [%2];" :: "r"(dst), "r"(src), "r"(mbar) : "memory");
}
__device__ __forceinline__ void mbar_init(uint32_t m, uint32_t cnt) { asm volatile("mbarrier.init.shared::cta.b64 [%0], %1;" :: "r"(m), "r"(cnt) : "memory"); }
__device__ __forceinline__ void mbar_expect(uint32_t m, uint32_t bytes) { asm volatile("mbarrier.arrive.expect_tx.shared::cta.b64 _, [%0], %1;" :: "r"(m), "r"(bytes) : "memory"); }
__device__ __forceinline__ bool mbar_try(uint32_t m) {
  uint32_t done;
  asm volatile("{.reg .pred p; mbarrier.try_wait.parity.shared::cta.b64 p, [%1], 0; selp.u32 %0, 1, 0, p;}" : "=r"(done) : "r"(m) : "memory");
  return done;
}
__device__ __forceinline__ void mbar_wait(uint32_t m) {
  if (!mbar_try(m)) {
    int it = 0;
    while (!mbar_try(m) && ++it < (1 << 22)) {}
  }
}
__device__ __forceinline__ bool elect() {
  uint32_t e;
  asm volatile("{.reg .pred p; elect.sync _|p, 0xffffffff; selp.u32 %0, 1, 0, p;}" : "=r"(e));
  return e;
}
__device__ __forceinline__ void tma_load4(uint32_t dst, const CUtensorMap* tm, int c0, int c1, int c2, int c3, uint32_t mbar) {
  asm volatile("cp.async.bulk.tensor.4d.shared::cluster.global.mbarrier::complete_tx::bytes [%0], [%1, {%3, %4, %5, %6}], [%2];"
               :: "r"(dst), "l"(tm), "r"(mbar), "r"(c0), "r"(c1), "r"(c2), "r"(c3) : "memory");
}
__device__ __forceinline__ void tma_load3(uint32_t dst, const CUtensorMap* tm, int c0, int c1, int c2, uint32_t mbar) {
  asm volatile("cp.async.bulk.tensor.3d.shared::cluster.global.mbarrier::complete_tx::bytes [%0], [%1, {%3, %4, %5}], [%2];"
               :: "r"(dst), "l"(tm), "r"(mbar), "r"(c0), "r"(c1), "r"(c2) : "memory");
}
__device__ __forceinline__ void tma_store3(const CUtensorMap* tm, int c0, int c1, int c2, uint32_t src) {
  asm volatile("cp.async.bulk.tensor.3d.global.shared::cta.bulk_group [%0, {%2, %3, %4}], [%1];"
               :: "l"(tm), "r"(src), "r"(c0), "r"(c1), "r"(c2) : "memory");
}
__device__ __forceinline__ void wg_fence() { asm volatile("wgmma.fence.sync.aligned;" ::: "memory"); }
__device__ __forceinline__ void wg_commit() { asm volatile("wgmma.commit_group.sync.aligned;" ::: "memory"); }
template <int N> __device__ __forceinline__ void wg_wait() { asm volatile("wgmma.wait_group.sync.aligned %0;" :: "n"(N) : "memory"); }
template <int N> __device__ __forceinline__ void tie_all(uint32_t (&x)[N]) {
#pragma unroll
  for (int i = 0; i < N; i++) asm volatile("" : "+r"(x[i]) :: "memory");
}
template <int N> __device__ __forceinline__ void tie_all(float (&x)[N]) {
#pragma unroll
  for (int i = 0; i < N; i++) asm volatile("" : "+f"(x[i]) :: "memory");
}
#define R16(C, d) C(d[0]), C(d[1]), C(d[2]), C(d[3]), C(d[4]), C(d[5]), C(d[6]), C(d[7]), C(d[8]), C(d[9]), C(d[10]), C(d[11]), C(d[12]), C(d[13]), C(d[14]), C(d[15])
#define R32(C, d) R16(C, d), R16(C, (d + 16))
#define P16 "{%0,%1,%2,%3,%4,%5,%6,%7,%8,%9,%10,%11,%12,%13,%14,%15}"
#define P32 "{%0,%1,%2,%3,%4,%5,%6,%7,%8,%9,%10,%11,%12,%13,%14,%15,%16,%17,%18,%19,%20,%21,%22,%23,%24,%25,%26,%27,%28,%29,%30,%31}"
template <int SD, int TB, int OFF> __device__ __forceinline__ void rs64(float* d, const uint32_t* a, uint64_t db) {
  if (SD) asm volatile("{.reg .b64 db; add.s64 db, %36, %37; wgmma.mma_async.sync.aligned.m64n64k16.f32.bf16.bf16 " P32 ", {%32,%33,%34,%35}, db, 1, 1, 1, %38;}"
                       : R32("+f", d) : "r"(a[0]), "r"(a[1]), "r"(a[2]), "r"(a[3]), "l"(db), "n"(OFF), "n"(TB));
  else asm volatile("{.reg .b64 db; add.s64 db, %36, %37; wgmma.mma_async.sync.aligned.m64n64k16.f32.bf16.bf16 " P32 ", {%32,%33,%34,%35}, db, 0, 1, 1, %38;}"
                    : R32("=f", d) : "r"(a[0]), "r"(a[1]), "r"(a[2]), "r"(a[3]), "l"(db), "n"(OFF), "n"(TB));
}
template <int SD, int TB, int OFF> __device__ __forceinline__ void rs64h(uint32_t* d, const uint32_t* a, uint64_t db) {
  if (SD) asm volatile("{.reg .b64 db; add.s64 db, %20, %21; wgmma.mma_async.sync.aligned.m64n64k16.f16.f16.f16 " P16 ", {%16,%17,%18,%19}, db, 1, 1, 1, %22;}"
                       : R16("+r", d) : "r"(a[0]), "r"(a[1]), "r"(a[2]), "r"(a[3]), "l"(db), "n"(OFF), "n"(TB));
  else asm volatile("{.reg .b64 db; add.s64 db, %20, %21; wgmma.mma_async.sync.aligned.m64n64k16.f16.f16.f16 " P16 ", {%16,%17,%18,%19}, db, 0, 1, 1, %22;}"
                    : R16("=r", d) : "r"(a[0]), "r"(a[1]), "r"(a[2]), "r"(a[3]), "l"(db), "n"(OFF), "n"(TB));
}
template <int SD, int OFFA, int OFFB> __device__ __forceinline__ void ss32(float* d, uint64_t da, uint64_t db) {
  if (SD) asm volatile("{.reg .b64 da, db; add.s64 da, %16, %18; add.s64 db, %17, %19; wgmma.mma_async.sync.aligned.m64n32k16.f32.f16.f16 " P16 ", da, db, 1, 1, 1, 1, 1;}"
                       : R16("+f", d) : "l"(da), "l"(db), "n"(OFFA), "n"(OFFB));
  else asm volatile("{.reg .b64 da, db; add.s64 da, %16, %18; add.s64 db, %17, %19; wgmma.mma_async.sync.aligned.m64n32k16.f32.f16.f16 " P16 ", da, db, 0, 1, 1, 1, 1;}"
                    : R16("=f", d) : "l"(da), "l"(db), "n"(OFFA), "n"(OFFB));
}
#define KGEN_ASM(SD) "{.reg .b64 da, db; add.s64 da, %32, %33; add.s64 db, %32, %34;\n" \
  "wgmma.mma_async.sync.aligned.m64n64k16.f32.bf16.bf16 " P32 ", da, db, " SD ", 1, 1, 1, 1;}"
template <int KS> __device__ __forceinline__ void kgen_mma(float (&c)[32], uint64_t da) {
  if (KS) asm volatile(KGEN_ASM("1") : R32("+f", c) : "l"(da), "n"(8 * KS), "n"(8 * KS + 512));
  else asm volatile(KGEN_ASM("0") : R32("=f", c) : "l"(da), "n"(8 * KS), "n"(8 * KS + 512));
  if constexpr (KS < 7) kgen_mma<KS + 1>(c, da);
}
__device__ __forceinline__ uint64_t desc_lo(uint32_t a) { return (uint64_t)((a & 0x3FFFF) >> 4); }
__device__ __forceinline__ void stage1(float (&D)[32], const uint32_t (&A1)[8], uint32_t src) {
  const uint64_t du = desc_lo(src) | (128ull << 16) | (32ull << 32) | (2ull << 62);
  rs64<0, 1, 0>(D, A1, du); rs64<1, 1, 64>(D, A1 + 4, du);
}
template <int INV> __device__ __forceinline__ void stage2(uint32_t (&X)[16], const uint32_t (&F)[16], uint32_t cf) {
  constexpr int KS = INV ? 16 : 128, TB = INV ? 0 : 1;
  const uint64_t dc = desc_lo(cf) | (INV ? (8ull << 16) | (64ull << 32) : (64ull << 16) | (8ull << 32));
  rs64h<0, TB, 0>(X, F, dc); rs64h<1, TB, KS>(X, F + 4, dc); rs64h<1, TB, 2 * KS>(X, F + 8, dc); rs64h<1, TB, 3 * KS>(X, F + 12, dc);
}
__device__ __forceinline__ void fwd_mid(uint32_t (&F)[16], const float (&D)[32], const uint32_t (&tc)[4], const uint32_t (&ts)[4]) {
#pragma unroll
  for (int j = 0; j < 4; j++)
#pragma unroll
    for (int b = 0; b < 2; b++) {
      const int i = 4 * j + 16 * b;
      const uint32_t ar = packh(D[i], D[i + 1]), ai = packh(D[i + 2], D[i + 3]);
      F[2 * j + b] = ffma(ar, tc[j], fmul(ai, ts[j]));
      F[8 + 2 * j + b] = ffma(ai, tc[j], fneg(fmul(ar, ts[j])));
    }
}
__device__ __forceinline__ void put_exp(uint32_t a, uint32_t m, int lane) {
  m = __reduce_max_sync(0xffffffffu, max(m & 0x7f80u, (m >> 16) & 0x7f80u));
  if (lane == 0) sts32(a, m);
}
__device__ __forceinline__ uint32_t seq_mag(uint32_t a) {
  const uint4 x = lds128(a), y = lds128(a + 2048);
  return amax2(amax2(amax2(x.x, x.y), amax2(x.z, x.w)), amax2(amax2(y.x, y.y), amax2(y.z, y.w)));
}
__device__ __forceinline__ uint32_t get_exp(uint32_t a) { const uint4 v = lds128(a); return max(max(v.x, v.y), max(v.z, v.w)) >> 7; }
__device__ __forceinline__ void scale_a1(uint32_t (&As)[8], const uint32_t (&A1)[8], uint32_t field) {
#pragma unroll
  for (int i = 0; i < 8; i++) As[i] = hmul2(A1[i], field * 0x00800080u);
}

struct cf { float x, y; };
__device__ __forceinline__ cf cmul(cf a, cf b) { cf r; r.x = fmaf(a.x, b.x, -a.y * b.y); r.y = fmaf(a.x, b.y, a.y * b.x); return r; }
__device__ __forceinline__ cf cexp_p(float lr2, float lt, float p) {
  float m;
  asm("ex2.approx.ftz.f32 %0, %1;" : "=f"(m) : "f"(lr2 * p));
  float t = lt * p;
  t = (t - rintf(t)) * 6.283185307179586f;
  cf r; r.x = m * __cosf(t); r.y = m * __sinf(t); return r;
}
__device__ __forceinline__ void store8(uint32_t a, uint32_t b, const cf (&v)[8]) {
  sts128(a, pack(v[0].x, v[1].x), pack(v[2].x, v[3].x), pack(v[4].x, v[5].x), pack(v[6].x, v[7].x));
  sts128(b, pack(v[0].y, v[1].y), pack(v[2].y, v[3].y), pack(v[4].y, v[5].y), pack(v[6].y, v[7].y));
}
__device__ __forceinline__ void mbar_arrive(uint32_t m) { asm volatile("mbarrier.arrive.shared::cta.b64 _, [%0];" :: "r"(m) : "memory"); }
__device__ __forceinline__ float sigmoidf_(float s) { return __frcp_rn(1.f + __expf(-s)); }

__global__ void __cluster_dims__(CS, 1, 1) __launch_bounds__(NTHREADS, 1) fused_kernel(const __grid_constant__ Params p) {
  extern __shared__ __align__(1024) uint8_t smem[];
  TL_INIT();
  TL(31);
  const int wid = __shfl_sync(0xffffffffu, threadIdx.x >> 5, 0);
  const uint32_t sb = (uint32_t)__cvta_generic_to_shared(smem);
  const uint32_t mb = sb + OFF_MB;
  const int u = wid >> 2, w = wid & 3;
  const int tid = threadIdx.x & 127, lane = tid & 31, g = lane >> 2, t = lane & 3;
  const int cl = blockIdx.x >> 3, rank = blockIdx.x & 7;
  const int ch0 = cl * CPC;
  const int nu = min(5, (DCH - ch0) >> 3);
  const bool act = u < nu;

  if (u == 4 && elect()) {
#pragma unroll
    for (int i = 0; i < 5; i++) mbar_init(mb + 40 * w + 8 * i, w == 3 ? 1 : w == 2 ? 3 : 2);
    if (w == 3) {
      mbar_init(mb + 8 * MB_XQ, 2); mbar_init(mb + 8 * MB_KV, 1); mbar_init(mb + 8 * MB_CF, 1); mbar_init(mb + 8 * MB_Q2, 9);
    }
    fence_mbinit();
    if (w == 3) {
      mbar_expect(mb + 8 * MB_CF, 12288);
      asm volatile("cp.async.bulk.prefetch.L2.global [%0], 20480;" :: "l"(p.tab) : "memory");
      mbar_expect(mb + 8 * MB_XQ, 20480); mbar_expect(mb + 8 * MB_KV, 23040 + 20480); mbar_expect(mb + 8 * MB_Q2, 20480);
    }
#pragma unroll
    for (int i = 0; i < 5; i++) mbar_expect(mb + 40 * w + 8 * i, w == 3 ? 4096 : w == 2 ? 7168 : 3584);
  }
  uint32_t pla, pai, pcr, pci, pdt, tag = 0;
  uint4 psm;
  {
    const int ch = act ? ch0 + 8 * u + rank : 0, o = ch * NMODE + tid;
    pla = ldraw(p.logA + o); pdt = ldraw(p.logdt + ch); pai = ldraw(p.Aim + o); pcr = ldraw(p.Cre + o); pci = ldraw(p.Cim + o);
    if (w == 1) {
      if (lane < 9) psm = ldg128(lane < 5 ? p.gate_w + (lane < nu ? ch0 + 8 * lane : 0) : p.shift_k + (act ? ch0 + 8 * u : 0) * 4 + 8 * (lane - 5));
      else { psm.x = ldraw(p.Dskip + ch); psm.y = ldraw(p.ssm_D + ch); }
    }
    if (wid == 16 && lane < 2) asm volatile("atom.relaxed.gpu.global.add.u32 %0, [%1], %2;" : "=r"(tag) : "l"(&p.cnt[rank * 32 + lane]), "r"(cl == 0 ? 16 - (NCL - 1) : 1) : "memory");
  }
  if (wid == 19 && elect()) {
    tma_load4(sb + OFF_TQ, &p.tq, ch0, 0, 0, 8 * rank, mb + 8 * MB_XQ);
    TL(20);
  }
  __syncwarp();
  cluster_arrive();
  TL(0);

  const uint32_t tab = sb + OFF_T + u * KTAB;
  const int mi = lane >> 3, tq = (lane & 7) >> 1, jj = lane & 1;
  const uint32_t toff = (4 * (2 * mi + jj) + tq) * 80;
  const uint32_t uoff = 16 * (4 * w + (t ^ (w >> 1)));
  auto put = [&](int stage, int dst, uint32_t off, const uint32_t (&v)[4]) {
    sts128(sb + off + (g == rank ? dst + 512 * rank : stage + g * YPITCH), v[0], v[1], v[2], v[3]);
  };
  const int d0 = rank ^ (2 * w), d1 = d0 ^ 1;
  const uint32_t rb0 = mapa(sb, d0), rb1 = mapa(sb, d1);
  auto send = [&](int stage, int pitch, int dst, int mbar) {
    if (elect()) {
      if (w) bulk_dsmem(rb0 + dst, sb + stage + d0 * pitch, rb0 + mbar); else mbar_arrive(sb + mbar);
      bulk_dsmem(rb1 + dst, sb + stage + d1 * pitch, rb1 + mbar);
    }
    __syncwarp();
  };

  if (w == 1 && lane < 10) sts128(sb + OFF_SP + 160 * u + 16 * lane, psm.x, psm.y, psm.z, psm.w);
  uint32_t A1[8], tc[4], ts[4];
  {
    const float dt = bf16r(expf(blo(pdt)));
    const float lr2 = (-bf16r(expf(blo(pla))) * dt) * 1.4426950408889634f;
    const float lt = (blo(pai) * dt) * 0.15915494309189535f;
    const uint32_t tim = sb + OFF_IM + (u < 2 ? 3 + u : u - 2) * KTAB;
    const uint32_t row = tab + tid * 16, rim = tim + tid * 16;
    float zq = 0.f;
    const cf w1 = cexp_p(lr2, lt, 8.f);
    cf z1 = cexp_p(lr2, lt, 1.f), Z = cexp_p(lr2, lt, 256.f);
    if (lr2 != 123.f) TL(16);
    const __nv_bfloat16* hp = p.ssm_k + (size_t)(act ? ch0 + 8 * u + rank : 0) * SEQ + 8 * tid + (pla >> 16);
    const uint4 hm0 = ldg128(hp), hm1 = ldg128(hp + 1024);
    if (wid == 16) {
      if (lane == 0) { sts32(mb + 8 * MB_TAG, tag); mbar_arrive(mb + 8 * MB_XQ); }
      if (elect()) {
        const uint32_t o = blockIdx.x * 9856u, n = min(9856u, SEQ * DCH - o) * 2;
        asm volatile("cp.async.bulk.prefetch.L2.global [%0], %1;" :: "l"(p.k + o), "r"(n) : "memory");
        asm volatile("cp.async.bulk.prefetch.L2.global [%0], %1;" :: "l"(p.v + o), "r"(n) : "memory");
      }
      __syncwarp();
    }
    TL(12);
    {
      cf v[8];
      v[0].x = 1.f; v[0].y = 0.f; v[1] = w1; v[2] = cmul(w1, w1); v[3] = cmul(v[2], w1);
      const cf w4 = cmul(v[2], v[2]);
      v[4] = w4; v[5] = cmul(v[1], w4); v[6] = cmul(v[2], w4); v[7] = cmul(v[3], w4);
      const cf w8 = cmul(w4, w4);
      store8(row, rim, v);
#pragma unroll
      for (int k = 1; k < 4; k++) {
#pragma unroll
        for (int i = 0; i < 8; i++) v[i] = (k == 1 && i == 0) ? w8 : cmul(v[i], w8);
        store8(row + 2048 * k, rim + 2048 * k, v);
      }
    }
    if (u == 4) {
      float z1_ = 0.f, z2_ = 0.f, z3_ = 0.f;
      asm volatile("mma.sync.aligned.m16n8k8.row.col.f32.bf16.bf16.f32 {%0,%1,%2,%3}, {%4,%4}, {%4}, {%0,%1,%2,%3};"
                   : "+f"(zq), "+f"(z1_), "+f"(z2_), "+f"(z3_) : "r"(pla));
    }
    {
      z1.y = -z1.y; Z.y = -Z.y;
      const cf z2 = cmul(z1, z1);
      cf h[8], v[8];
      h[0].x = 2.f * blo(pcr) * dt; h[0].y = -2.f * blo(pci) * dt;
      h[1] = cmul(h[0], z1);
#pragma unroll
      for (int i = 2; i < 8; i++) h[i] = cmul(h[i - 2], z2);
      store8(row + 4 * 2048, rim + 4 * 2048, h);
      const cf h8 = cmul(h[6], z2);
      v[0] = cmul(h[0], Z); v[2] = cmul(h[2], Z); v[3] = cmul(h[4], Z); v[6] = cmul(h[6], Z); v[7] = cmul(h8, Z);
      v[1] = v[0]; v[4] = v[5] = v[3];
      store8(row + 5 * 2048, rim + 5 * 2048, v);
      h[0] = cmul(v[0], Z); h[1] = cmul(v[3], Z); h[3] = cmul(v[7], Z); h[4] = cmul(h[0], Z); h[5] = cmul(h[1], Z); h[7] = cmul(h[3], Z);
      h[2] = h[1]; h[6] = h[5];
      store8(row + 6 * 2048, rim + 6 * 2048, h);
      const cf Z2 = cmul(Z, Z);
      v[0] = cmul(h[0], Z2); v[1] = cmul(h[3], Z2); v[2] = cmul(h[4], Z2); v[3] = cmul(h[7], Z2);
#pragma unroll
      for (int i = 4; i < 8; i++) v[i] = cmul(v[i - 4], Z2);
      store8(row + 7 * 2048, rim + 7 * 2048, v);
    }
    TL(17);
    put_exp(sb + OFF_MX + u * 64 + 32 + 4 * w, amax2(amax2(amax2(hm0.x, hm0.y), amax2(hm0.z, hm0.w)), amax2(amax2(hm1.x, hm1.y), amax2(hm1.z, hm1.w))), lane);
    cluster_wait();
    mbar_wait(mb + 8 * MB_XQ);
    TL(18);
    {
      uint32_t x0[4], x1[4];
      ldsm4t(x0, sb + OFF_TQ + w * 2560 + toff + 16 * u);
      ldsm4t(x1, sb + OFF_TQ + (w + 4) * 2560 + toff + 16 * u);
      put(OFF_YB + 8 * u * YPITCH, OFF_UX + u * 4096, uoff, x0);
      put(OFF_YB + 8 * u * YPITCH, OFF_UX + u * 4096, (uoff ^ 32) + 256, x1);
    }
    TL(3);
    fence_async();
    bar_sync(NB_WG0 + u, 128);
    TL(4);
    if (u) send(OFF_YB + 8 * u * YPITCH, YPITCH, OFF_UX + u * 4096 + 512 * rank, OFF_MB + 8 * (MB_UX + u));
    if (u >= 3) {
      float s0 = 0.f;
#pragma unroll
      for (int j = 0; j < 5; j++) {
        const uint4 gw = lds128(sb + OFF_SP + 160 * u + 16 * j), x = lds128(sb + OFF_TQ + (tid + 128 * (u - 3)) * 80 + 16 * j);
        const uint32_t m0 = hmul2(x.x, gw.x), m1 = hmul2(x.y, gw.y), m2 = hmul2(x.z, gw.z), m3 = hmul2(x.w, gw.w);
        s0 += ((blo(m0) + bhi(m0)) + (blo(m1) + bhi(m1))) + ((blo(m2) + bhi(m2)) + (blo(m3) + bhi(m3)));
      }
      tag = (lds64(mb + 8 * MB_TAG).x >> 4) + 1;
      asm volatile("st.relaxed.gpu.global.u64 [%0], %1;" :: "l"(p.part + cl * SEQ + rank * 256 + 8 * (8 * t + g) + w + 4 * (u - 3)),
                   "l"(((uint64_t)tag << 32) | __float_as_uint(s0)) : "memory");
    }
    TL(7);
    if (u) bar_sync(NB_ORD + u - 1, 256);
    TL(13);
    float c[32];
    wg_fence();
    kgen_mma<0>(c, desc_lo(tab) | ((uint64_t)((tim - tab) >> 4) << 16) | (64ull << 32));
    wg_commit();
    if (u < 4) bar_arrive(NB_ORD + u, 256);
    if (u == 0) send(OFF_YB, YPITCH, OFF_UX + 512 * rank, OFF_MB + 8 * MB_UX);
    {
      const uint4 x = ldg128(p.tab->thr[0][tid]), y = ldg128(p.tab->thr[1][tid]), a = ldg128(p.tab->thr[2][tid]), b = ldg128(p.tab->thr[3][tid]);
      A1[0] = x.x; A1[1] = x.y; A1[2] = x.z; A1[3] = x.w; A1[4] = y.x; A1[5] = y.y; A1[6] = y.z; A1[7] = y.w;
      tc[0] = a.x; tc[1] = a.y; tc[2] = a.z; tc[3] = a.w; ts[0] = b.x; ts[1] = b.y; ts[2] = b.z; ts[3] = b.w;
    }
    wg_wait<0>(); tie_all(c);
    TL(26);
    cluster_arrive();
    if (zq == 1.2345e-30f) sts32(mb + 8 * MB_TAG + 4, 0);
    if (wid == 17) {
      bar_sync(NB_LD, 640);
      if (elect()) {
        tma_load4(sb + OFF_TK, &p.tk, ch0, 0, 0, 8 * rank - 1, mb + 8 * MB_KV);
        tma_load4(sb + OFF_TV, &p.tv, ch0, 0, 0, 8 * rank, mb + 8 * MB_KV);
      }
      __syncwarp();
    } else {
      bar_arrive(NB_LD, 640);
    }
    bar_sync(NB_WG0 + u, 128);
    if (wid == 1 && elect())
      asm volatile("cp.async.bulk.shared::cluster.global.mbarrier::complete_tx::bytes [%0], [%1], %2, [%3];"
                   :: "r"(sb + OFF_CF), "l"(p.tab->mat), "r"(12288), "r"(mb + 8 * MB_CF) : "memory");
    __syncwarp();
    const uint32_t k0 = pack(c[0] + c[6], c[1] + c[7]), k1 = pack(c[8] + c[14], c[9] + c[15]);
    const uint32_t k2 = pack(c[16] + c[22], c[17] + c[23]), k3 = pack(c[24] + c[30], c[25] + c[31]);
    const uint32_t ka = tab + 16 * (8 * w + (g ^ w));
    sts32(ka + 4 * t, k0);
    sts32(ka + 512 + 4 * t, k1);
    sts64(ka + 1024 + 512 * (t >> 1) + 8 * (t & 1), prmt(k2, 0, 0x1010), (t & 1) ? prmt(k2, 0, 0x3232) : k2);
    const uint32_t lo = prmt(k3, 0, 0x1010), hi = prmt(k3, 0, 0x3232);
    sts128(ka + 2048 + 512 * t, lo, lo, (g & 1) ? hi : k3, hi);
    put_exp(sb + OFF_MX + u * 64 + 4 * w, amax2(amax2(k0, k1), amax2(k2, k3)), lane);
    TL(15);
    fence_async();
    bar_sync(NB_WG0 + u, 128);
  }

#pragma unroll
  for (int isA = 0; isA < 2; isA++) {
    {
      TL(1 + isA);
      const uint32_t usrc = isA ? tab + T_UKV : sb + OFF_UX + u * 4096;
      const uint32_t mxa = sb + OFF_MX + u * 64 + 32 * isA;
      const uint32_t pd = lds16(sb + OFF_SP + 160 * u + 144 + 4 * isA);
      float D[32];
      uint32_t As[8], F[16], H[16], X[16];
      const uint32_t eh = min(max((int)get_exp(mxa), (int)((pd >> 7) & 0xff) - 5), 240);
      scale_a1(As, A1, 248 - eh);
      if (isA) mbar_wait(mb + 8 * (MB_HA + u));
      wg_fence();
      stage1(D, As, isA ? tab + T_HA : tab);
      wg_commit();
      wg_wait<0>(); tie_all(D);
      fwd_mid(F, D, tc, ts);
      if (!isA) mbar_wait(mb + 8 * MB_CF);
      wg_fence();
      stage2<0>(H, F, sb + OFF_CF);
      wg_commit();
      mbar_wait(mb + 8 * ((isA ? MB_UKV : MB_UX) + u));
      TL(5 + isA);
      put_exp(mxa + 16 + 4 * w, seq_mag(usrc + 16 * tid), lane);
      bar_sync(NB_WG0 + u, 128);
      const uint32_t eu = min(get_exp(mxa + 16), 240u);
      scale_a1(As, A1, 250 - eu);
      wg_wait<0>(); tie_all(H);
      wg_fence();
      stage1(D, As, usrc);
      wg_commit();
      wg_wait<0>(); tie_all(D);
      fwd_mid(F, D, tc, ts);
      wg_fence();
      stage2<0>(X, F, sb + OFF_CF);
      wg_commit();
      if (!isA && w == 1 && elect()) {
        tma_load4(tab + T_HA, &p.th, 0, 0, 5 * cl + u, rank, mb + 8 * (MB_HA + u));
        if (u == 4) tma_load3(sb + OFF_Q2, &p.tq2, ch0, 8 * rank, 0, mb + 8 * MB_Q2);
      }
      __syncwarp();
      {
        const float dsk = blo(pd) * __uint_as_float((248 - eh) << 23);
        const uint32_t d2 = packh(dsk, dsk);
#pragma unroll
        for (int j = 0; j < 4; j++) H[2 * j] = U2(__hadd2(H2(H[2 * j]), H2(d2)));
      }
      wg_wait<0>(); tie_all(X);
#pragma unroll
      for (int j = 0; j < 4; j++) {
        const uint32_t h0r = H[2 * j], h1r = H[2 * j + 1], h0i = H[8 + 2 * j], h1i = H[9 + 2 * j];
        const uint32_t x0r = X[2 * j], x1r = X[2 * j + 1], x0i = X[8 + 2 * j], x1i = X[9 + 2 * j];
        F[2 * j] = ffma(x0r, h0r, fneg(fmul(x0i, h0i)));
        F[8 + 2 * j] = ffma(x0r, h0i, fmul(x0i, h0r));
        F[2 * j + 1] = ffma(x1r, h0r, ffma(fneg(x1i), h0i, ffma(x0r, h1r, fneg(ffma(x0i, h1i, F[8 + 2 * j])))));
        F[9 + 2 * j] = ffma(x1r, h0i, ffma(x1i, h0r, ffma(x0r, h1i, ffma(x0i, h1r, F[2 * j]))));
      }
      wg_fence();
      stage2<1>(H, F, sb + OFF_CF);
      wg_commit();
      wg_wait<0>(); tie_all(H);
      {
        const uint32_t va = tab + (16 * w + (lane & 15)) * 128;
        const int vx = (lane >> 4) ^ (lane & 7);
#pragma unroll
        for (int j = 0; j < 4; j++) {
          uint32_t V[4];
#pragma unroll
          for (int b = 0; b < 2; b++) {
            const uint32_t er = H[2 * j + b], ei = H[8 + 2 * j + b];
            V[2 * b] = ffma(er, tc[j], fneg(fmul(ei, ts[j])));
            V[2 * b + 1] = ffma(ei, tc[j], fmul(er, ts[j]));
          }
          stsm4(va + ((vx ^ (2 * j)) << 4), V);
        }
      }
      uint64_t ga[NCL];
      const int slot = tid + 128 * (u & 1);
      const uint2* gp = p.part + rank * 256 + slot;
      auto gload = [&]() {
#pragma unroll
        for (int k = 0; k < NCL; k++) asm volatile("ld.relaxed.gpu.global.u64 %0, [%1];" : "=l"(ga[k]) : "l"(gp + k * SEQ) : "memory");
      };
      if (!isA) {
        cluster_wait();
        mbar_wait(mb + 8 * MB_KV);
        TL(21);
        const uint32_t hoff = (4 * (4 + 2 * (mi & 1) + jj) + ((tq + 3) & 3)) * 80 + (tq ? 2560 : 0) + 16 * u;
        uint32_t E[2][6], V[2][4];
        const uint2 psw = lds64(sb + OFF_SP + 160 * u + 80 + 8 * g);
#pragma unroll
        for (int hf = 0; hf < 2; hf++) {
          const int ah = 4 * hf + w;
          uint32_t K[4];
          ldsm4t(K, sb + OFF_TK + (ah + 1) * 2560 + toff + 16 * u);
          ldsm2t(E[hf][0], E[hf][1], sb + OFF_TK + ah * 2560 + hoff);
          ldsm4t(V[hf], sb + OFF_TV + ah * 2560 + toff + 16 * u);
          E[hf][2] = K[0]; E[hf][3] = K[1]; E[hf][4] = K[2]; E[hf][5] = K[3];
        }
        const uint32_t w0 = prmt(psw.x, 0, 0x1010), w1 = prmt(psw.x, 0, 0x3232), w2 = prmt(psw.y, 0, 0x1010), w3 = prmt(psw.y, 0, 0x3232);
        uint32_t o[2][4];
#pragma unroll
        for (int hf = 0; hf < 2; hf++) {
          uint32_t O[5];
#pragma unroll
          for (int i = 0; i < 5; i++) O[i] = prmt(E[hf][i], E[hf][i + 1], 0x5432);
#pragma unroll
          for (int i = 0; i < 4; i++) {
            o[hf][i] = hmul2(hfma2(E[hf][i + 2], w0, hfma2(O[i + 1], w1, hfma2(E[hf][i + 1], w2, hmul2(O[i], w3)))), V[hf][i]);
          }
          put(OFF_YA + 8 * u * YPITCH, OFF_T + u * KTAB + T_UKV, hf ? (uoff ^ 32) + 256 : uoff, o[hf]);
        }
        TL(22);
      }
      fence_async();
      bar_sync(NB_WG0 + u, 128);
      float O[16];
      {
        const uint64_t dv = desc_lo(tab) | (1ull << 16) | (64ull << 32) | (1ull << 62);
        const uint64_t dl = desc_lo(sb + OFF_CL) | (32ull << 16) | (8ull << 32);
        wg_fence();
        ss32<0, 0, 0>(O, dv, dl); ss32<1, 128, 64>(O, dv, dl); ss32<1, 256, 128>(O, dv, dl); ss32<1, 384, 192>(O, dv, dl);
        wg_commit();
      }
      if (!isA) {
        send(OFF_YA + 8 * u * YPITCH, YPITCH, OFF_T + u * KTAB + T_UKV + 512 * rank, OFF_MB + 8 * (MB_UKV + u));
        if (u < 2) gload();
      }
      wg_wait<0>(); tie_all(O);
      {
        const uint32_t co = ((8 * w + g) ^ (2 * t)) * 16;
        const int yo = (isA ? OFF_YA : OFF_YB) + (8 * u + rank) * YPITCH, ym = OFF_MB + 8 * (MB_Y + u);
        const uint32_t us = min(max((int)(eu + eh) - 127, 0), 254) * 0x00800080u;
        const uint32_t a0 = hmul2(pack(O[0], O[1]), us), a1 = hmul2(pack(O[4], O[5]), us), a2 = hmul2(pack(O[8], O[9]), us), a3 = hmul2(pack(O[12], O[13]), us);
        const uint32_t b0 = hmul2(pack(O[2], O[3]), us), b1 = hmul2(pack(O[6], O[7]), us), b2 = hmul2(pack(O[10], O[11]), us), b3 = hmul2(pack(O[14], O[15]), us);
        sts128((t == rank ? sb + yo : usrc + t * 512) + co, a0, a1, a2, a3);
        sts128((t + 4 == rank ? sb + yo : usrc + t * 512 + 2048) + co, b0, b1, b2, b3);
        fence_async();
        bar_sync(NB_WG0 + u, 128);
        send(usrc - sb, 512, yo, ym);
      }
      TL(9 + isA);
      if (!isA && u < 2) {
        tag = (lds64(mb + 8 * MB_TAG).x >> 4) + 1;
        float s;
        bool ok;
#pragma unroll 1
        for (int it = 0;; it++) {
          ok = true; s = 0.f;
#pragma unroll
          for (int k = 0; k < NCL; k++) { ok = ok && (uint32_t)(ga[k] >> 32) == tag; s += __uint_as_float((uint32_t)ga[k]); }
          if (ok || it == 4000) break;
          gload();
        }
        if (!ok) {
          const uint32_t* xr = (const uint32_t*)(p.q + (size_t)(rank * 256 + 32 * (slot & 7) + (slot >> 3)) * DCH);
          const uint32_t* gr = (const uint32_t*)p.gate_w;
          s = 0.f;
    #pragma unroll 1
          for (int k = 0; k < DCH / 2; k++) { const uint32_t m = hmul2(__ldg(xr + k), __ldg(gr + k)); s += blo(m) + bhi(m); }
        }
        const float g0 = bf16r(sigmoidf_(bf16r(s)));
        sts64(sb + OFF_GB + 8 * slot, pack(g0, g0), pack(1.f - g0, 1.f - g0));
        __syncwarp();
        if (lane == 0) mbar_arrive(mb + 8 * MB_Q2);
      }
    }
  }

  {
    mbar_wait(mb + 8 * MB_Q2);
    uint2 gg[2][4];
    uint32_t qv[2][4];
#pragma unroll
    for (int hh = 0; hh < 2; hh++)
#pragma unroll
      for (int i = 0; i < 4; i++) gg[hh][i] = lds64(sb + OFF_GB + 8 * (64 * w + 32 * hh + 8 * i + g));
    const uint32_t qa = sb + OFF_Q2 + (64 * w + lane) * 80 + 16 * u;
    ldsm4(qv[0], qa);
    ldsm4(qv[1], qa + 2560);
    TL(24);
    mbar_wait(mb + 8 * (MB_Y + u));
    uint32_t ya[2][4], yb[2][4];
#pragma unroll
    for (int hh = 0; hh < 2; hh++) {
      const uint32_t yo = (8 * u + (lane & 7)) * YPITCH + ((8 * w + 4 * hh + (lane >> 3)) ^ (2 * (rank & 3))) * 16;
      ldsm4t(ya[hh], sb + OFF_YA + yo); ldsm4t(yb[hh], sb + OFF_YB + yo);
    }
#pragma unroll
    for (int hh = 0; hh < 2; hh++) {
      uint32_t o[4];
#pragma unroll
      for (int i = 0; i < 4; i++) o[i] = hadd2(hmul2(gg[hh][i].x, hmul2(qv[hh][i], ya[hh][i])), hmul2(gg[hh][i].y, yb[hh][i]));
      stsm4(qa + 2560 * hh, o);
    }
    TL(25);
  }
  cluster_arrive();
  bar_sync(NB_ROW0 + w, 160);
  {
    uint4 v[2];
#pragma unroll
    for (int k = 0; k < 2; k++) {
      const int i = 64 * u + 32 * k + lane, sl = (i * 205) >> 10, cc = i - 5 * sl;
      v[k] = lds128(sb + OFF_Q2 + (64 * w + 8 * (sl & 7) + (sl >> 3)) * 80 + cc * 16);
    }
#pragma unroll
    for (int k = 0; k < 2; k++) {
      const int i = 64 * u + 32 * k + lane, sl = (i * 205) >> 10, cc = i - 5 * sl;
      if (cc < nu)
        asm volatile("st.global.v4.u32 [%0], {%1,%2,%3,%4};" :: "l"(p.out + (size_t)(256 * rank + 32 * (sl >> 3) + 8 * w + (sl & 7)) * DCH + ch0 + 8 * cc),
                     "r"(v[k].x), "r"(v[k].y), "r"(v[k].z), "r"(v[k].w) : "memory");
    }
  }
  cluster_wait();
  TL(27);
  TL_DUMP();
}

typedef CUresult (*EncodeFn)(CUtensorMap*, CUtensorMapDataType, cuuint32_t, void*, const cuuint64_t*, const cuuint64_t*,
                             const cuuint32_t*, const cuuint32_t*, CUtensorMapInterleave, CUtensorMapSwizzle,
                             CUtensorMapL2promotion, CUtensorMapFloatOOBfill);

void encode(EncodeFn fn, CUtensorMap* tm, const void* ptr, int nd, const cuuint64_t* dims, const cuuint64_t* strides,
            const cuuint32_t* box, CUtensorMapSwizzle swz) {
  cuuint32_t es[4] = {1, 1, 1, 1};
  fn(tm, CU_TENSOR_MAP_DATA_TYPE_BFLOAT16, nd, const_cast<void*>(ptr), dims, strides, box, es, CU_TENSOR_MAP_INTERLEAVE_NONE,
     swz, CU_TENSOR_MAP_L2_PROMOTION_L2_128B, CU_TENSOR_MAP_FLOAT_OOB_FILL_NONE);
}
void map1(EncodeFn fn, CUtensorMap* tm, const void* ptr, int nhi) {
  const cuuint64_t dims[4] = {DCH, 4, 8, SEQ / 32}, strides[3] = {8 * DCH * 2, DCH * 2, 32 * DCH * 2};
  const cuuint32_t box[4] = {CPC, 4, 8, (cuuint32_t)nhi};
  encode(fn, tm, ptr, 4, dims, strides, box, CU_TENSOR_MAP_SWIZZLE_NONE);
}
void map2(EncodeFn fn, CUtensorMap* tm, const void* ptr, int nr) {
  const cuuint64_t dims[3] = {DCH, SEQ / 32, 32}, strides[2] = {32 * DCH * 2, DCH * 2};
  const cuuint32_t box[3] = {CPC, 8, (cuuint32_t)nr};
  encode(fn, tm, ptr, 3, dims, strides, box, CU_TENSOR_MAP_SWIZZLE_NONE);
}

}

extern "C" void kernel_launch(void* const* d_in, const int* in_sizes, int n_in, void* d_out, int out_size) {
  (void)in_sizes; (void)n_in; (void)out_size;
  static EncodeFn fn = nullptr;
  static void *tab = nullptr, *cnt = nullptr, *part = nullptr;
  if (!fn) {
    cudaGetSymbolAddress(&tab, d_tab);
    cudaGetSymbolAddress(&cnt, g_cnt);
    cudaGetSymbolAddress(&part, g_part);
    cudaDriverEntryPointQueryResult qr;
    cudaGetDriverEntryPoint("cuTensorMapEncodeTiled", (void**)&fn, cudaEnableDefault, &qr);
    cudaFuncSetAttribute(fused_kernel, cudaFuncAttributeMaxDynamicSharedMemorySize, SMEM_BYTES);
  }
  Params p;
  map1(fn, &p.tq, d_in[0], 8);
  map1(fn, &p.tk, d_in[1], 9);
  map1(fn, &p.tv, d_in[2], 8);
  map2(fn, &p.tq2, d_in[0], 32);
  p.out = (__nv_bfloat16*)d_out;
  {
    const cuuint64_t dims[4] = {32, SEQ / 32, DCH / 8, 8}, strides[3] = {64, 8 * SEQ * 2, SEQ * 2};
    const cuuint32_t box[4] = {32, 64, 1, 1};
    encode(fn, &p.th, d_in[4], 4, dims, strides, box, CU_TENSOR_MAP_SWIZZLE_64B);
  }
  p.tab = (const Tables*)tab;
  p.cnt = (unsigned*)cnt;
  p.part = (uint2*)part;
  p.tl = nullptr;
  p.q = (const __nv_bfloat16*)d_in[0];
  p.k = (const __nv_bfloat16*)d_in[1];
  p.v = (const __nv_bfloat16*)d_in[2];
  p.ssm_k = (const __nv_bfloat16*)d_in[4];
  p.shift_k = (const __nv_bfloat16*)d_in[3];
  p.ssm_D = (const __nv_bfloat16*)d_in[5];
  p.logA = (const __nv_bfloat16*)d_in[7];
  p.Aim = (const __nv_bfloat16*)d_in[8];
  p.Cre = (const __nv_bfloat16*)d_in[9];
  p.Cim = (const __nv_bfloat16*)d_in[10];
  p.logdt = (const __nv_bfloat16*)d_in[11];
  p.Dskip = (const __nv_bfloat16*)d_in[12];
  p.gate_w = (const __nv_bfloat16*)d_in[13];
  fused_kernel<<<NCL * CS, NTHREADS, SMEM_BYTES, cudaStreamPerThread>>>(p);
}
```

```cpp
#include <cuda_runtime.h>
#include <cuda_bf16.h>
#include <cuda_fp16.h>
#include <cuda.h>
#include <stdint.h>

#define TIMELINE 0

namespace {

constexpr int SEQ = 2048, DCH = 576, NMODE = 128;
constexpr int CS = 8, CPC = 40, NCL = 15, NTHREADS = 640;

constexpr int YPITCH = 528;
constexpr int KTAB = 16384;
constexpr int OFF_T = 0;
constexpr int T_UKV = 8192, T_HA = 12288;
constexpr int OFF_UX = 5 * KTAB;
constexpr int OFF_IM = OFF_UX + 20480;
constexpr int OFF_Q2 = OFF_IM;
constexpr int OFF_GB = OFF_Q2 + 20480;
constexpr int OFF_TV = OFF_IM + 3 * KTAB - 20480;
constexpr int OFF_CF = OFF_IM + 3 * KTAB;
constexpr int OFF_CL = OFF_CF + 8192;
constexpr int OFF_TK = OFF_CL + 4096;
constexpr int OFF_TQ = OFF_TK + 23040;
constexpr int OFF_YA = OFF_TQ;
constexpr int OFF_YB = OFF_TQ + 21120;
constexpr int OFF_MX = OFF_YB + 40 * YPITCH;
constexpr int OFF_SP = OFF_MX + 320;
constexpr int OFF_MB = OFF_SP + 5 * 160;
constexpr int OFF_TL = OFF_MB + 32 * 8;
constexpr int SMEM_BYTES = OFF_TL + (TIMELINE ? 1280 : 0);
static_assert(SMEM_BYTES <= 232448 && OFF_IM + 5 * KTAB <= OFF_TQ, "smem");
static_assert((OFF_TQ & 127) == 0 && (OFF_TK & 127) == 0 && (OFF_TV & 127) == 0 && (OFF_MB & 7) == 0 && (OFF_MX & 15) == 0, "align");

enum { MB_UX = 0, MB_UKV = 5, MB_Y = 10, MB_HA = 15, MB_XQ = 20, MB_KV = 21, MB_CF = 22, MB_Q2 = 23, MB_XD = 24, MB_TAG = 25 };
enum { NB_WG0 = 1, NB_ROW0 = 6, NB_ORD = 6, NB_K0 = 10, NB_LD = 11 };

constexpr double cos_turn(int m, int n) {
  m &= n - 1;
  if (m > n / 2) m = n - m;
  double sgn = 1.0;
  if (m > n / 4) { m = n / 2 - m; sgn = -1.0; }
  if (m == n / 4) return 0.0;
  const double x = 6.283185307179586476925 * m / n;
  double term = 1.0, sum = 1.0;
  for (int k = 1; k < 14; k++) { term *= -x * x / ((2 * k - 1) * (2 * k)); sum += term; }
  return sgn * sum;
}
constexpr uint32_t bf16_bits(double v) {
  if (v == 0.0) return 0;
  uint32_t sgn = 0;
  if (v < 0) { sgn = 0x8000; v = -v; }
  int e = 127;
  while (v < 1.0) { v *= 2.0; e--; }
  while (v >= 2.0) { v *= 0.5; e++; }
  const double f = v * 128.0;
  int m = (int)f;
  if (f - m > 0.5 || (f - m == 0.5 && (m & 1))) m++;
  return sgn | (uint32_t)((e << 7) + (m - 128));
}
constexpr uint32_t f16_bits(double v) {
  if (v == 0.0) return 0;
  uint32_t sgn = 0;
  if (v < 0) { sgn = 0x8000; v = -v; }
  int e = 15;
  while (v < 1.0) { v *= 2.0; e--; }
  const double f = v * 1024.0;
  int m = (int)f;
  if (f - m > 0.5 || (f - m == 0.5 && (m & 1))) m++;
  return sgn | (uint32_t)((e << 10) + (m - 1024));
}
constexpr uint32_t pair_bits(double lo, double hi) { return bf16_bits(lo) | (bf16_bits(hi) << 16); }
constexpr uint32_t pair_h(double lo, double hi) { return f16_bits(lo) | (f16_bits(hi) << 16); }
struct alignas(128) Tables {
  uint32_t mat[3072];
  uint32_t thr[4][128][4];
};
constexpr Tables make_tables() {
  Tables T{};
  for (int q = 0; q < 768; q++) {
    int m0 = 0, d0 = 0, d1 = 0;
    if (q < 512) {
      const int r = (q >> 6) * 8 + (q & 7), cc = (q >> 3) & 7;
      d0 = 4 * (r & 31); d1 = 2 * d0;
      m0 = 8 * (cc & 3) * d0 + ((r >> 5) == (cc >> 2) ? 0 : (r >> 5) ? 96 : 32);
    } else {
      const int r = ((q - 512) >> 5) * 8 + (q & 7), pc = (q >> 3) & 3;
      d0 = 4 * (8 * (r >> 4) + (r & 7)) + 1; d1 = 8 * d0;
      m0 = 2 * pc * d0 + ((r & 8) ? 32 : 0);
    }
    for (int e = 0; e < 4; e++) T.mat[4 * q + e] = pair_h(cos_turn(m0 + e * d1, 128), cos_turn(m0 + e * d1 + d0, 128));
  }
  for (int tid = 0; tid < 128; tid++) {
    const int kk = 4 * (tid >> 2) + 1, t = tid & 3;
    for (int q = 0; q < 4; q++) {
      const int m = (8 * q + 2 * t) * kk;
      T.thr[q >> 1][tid][2 * (q & 1)] = pair_bits(cos_turn(m, 128), cos_turn(m + kk, 128));
      T.thr[q >> 1][tid][2 * (q & 1) + 1] = pair_bits(cos_turn(m + 32, 128), cos_turn(m + kk + 32, 128));
      T.thr[2][tid][q] = pair_h(cos_turn(m, 4096), cos_turn(m + kk, 4096));
      T.thr[3][tid][q] = pair_h(cos_turn(m + 3072, 4096), cos_turn(m + kk + 3072, 4096));
    }
  }
  return T;
}
__device__ const Tables d_tab = make_tables();

struct Params {
  const __nv_bfloat16 *logA, *Aim, *Cre, *Cim, *logdt;
  const Tables* tab;
  unsigned* cnt;
  const __nv_bfloat16 *Dskip, *shift_k, *ssm_D, *gate_w, *q, *k, *v, *ssm_k;
  uint2* part;
  __nv_bfloat16* out;
  unsigned* tl;
  CUtensorMap tq, tk, tv, th, tq2;
};

__device__ uint2 g_part[NCL * SEQ];
__device__ unsigned g_cnt[CS * 32];
#define TL(i) do {} while (0)
#define TL_INIT() do {} while (0)
#define TL_DUMP() do {} while (0)

__device__ __forceinline__ uint32_t lds16(uint32_t a) { uint32_t v; asm volatile("ld.shared.u16 %0, [%1];" : "=r"(v) : "r"(a) : "memory"); return v; }
__device__ __forceinline__ uint2 lds64(uint32_t a) { uint2 v; asm volatile("ld.shared.v2.u32 {%0,%1}, [%2];" : "=r"(v.x), "=r"(v.y) : "r"(a) : "memory"); return v; }
__device__ __forceinline__ uint4 lds128(uint32_t a) { uint4 v; asm volatile("ld.shared.v4.u32 {%0,%1,%2,%3}, [%4];" : "=r"(v.x), "=r"(v.y), "=r"(v.z), "=r"(v.w) : "r"(a) : "memory"); return v; }
__device__ __forceinline__ void sts16(uint32_t a, uint32_t v) { asm volatile("st.shared.u16 [%0], %1;" :: "r"(a), "r"(v) : "memory"); }
__device__ __forceinline__ void sts32(uint32_t a, uint32_t v) { asm volatile("st.shared.u32 [%0], %1;" :: "r"(a), "r"(v) : "memory"); }
__device__ __forceinline__ void sts64(uint32_t a, uint32_t x, uint32_t y) { asm volatile("st.shared.v2.u32 [%0], {%1,%2};" :: "r"(a), "r"(x), "r"(y) : "memory"); }
__device__ __forceinline__ void sts128(uint32_t a, uint32_t x, uint32_t y, uint32_t z, uint32_t w) { asm volatile("st.shared.v4.u32 [%0], {%1,%2,%3,%4};" :: "r"(a), "r"(x), "r"(y), "r"(z), "r"(w) : "memory"); }
__device__ __forceinline__ void ldsm4t(uint32_t (&r)[4], uint32_t a) { asm volatile("ldmatrix.sync.aligned.m8n8.x4.trans.shared.b16 {%0,%1,%2,%3}, [%4];" : "=r"(r[0]), "=r"(r[1]), "=r"(r[2]), "=r"(r[3]) : "r"(a) : "memory"); }
__device__ __forceinline__ void ldsm2t(uint32_t& r0, uint32_t& r1, uint32_t a) { asm volatile("ldmatrix.sync.aligned.m8n8.x2.trans.shared.b16 {%0,%1}, [%2];" : "=r"(r0), "=r"(r1) : "r"(a) : "memory"); }
__device__ __forceinline__ void ldsm4(uint32_t (&r)[4], uint32_t a) { asm volatile("ldmatrix.sync.aligned.m8n8.x4.shared.b16 {%0,%1,%2,%3}, [%4];" : "=r"(r[0]), "=r"(r[1]), "=r"(r[2]), "=r"(r[3]) : "r"(a) : "memory"); }
__device__ __forceinline__ void stsm4(uint32_t a, const uint32_t (&r)[4]) { asm volatile("stmatrix.sync.aligned.m8n8.x4.shared.b16 [%0], {%1,%2,%3,%4};" :: "r"(a), "r"(r[0]), "r"(r[1]), "r"(r[2]), "r"(r[3]) : "memory"); }
__device__ __forceinline__ uint32_t pack(float lo, float hi) { uint32_t r; asm("cvt.rn.bf16x2.f32 %0, %1, %2;" : "=r"(r) : "f"(hi), "f"(lo)); return r; }
__device__ __forceinline__ float blo(uint32_t v) { return __uint_as_float(v << 16); }
__device__ __forceinline__ float bhi(uint32_t v) { return __uint_as_float(v & 0xffff0000u); }
__device__ __forceinline__ float bf16r(float x) { return blo(pack(x, 0.f)); }
__device__ __forceinline__ uint32_t hmul2(uint32_t a, uint32_t b) { uint32_t r; asm("mul.rn.bf16x2 %0, %1, %2;" : "=r"(r) : "r"(a), "r"(b)); return r; }
__device__ __forceinline__ uint32_t hadd2(uint32_t a, uint32_t b) { uint32_t r; asm("add.rn.bf16x2 %0, %1, %2;" : "=r"(r) : "r"(a), "r"(b)); return r; }
__device__ __forceinline__ uint32_t hfma2(uint32_t a, uint32_t b, uint32_t c) { uint32_t r; asm("fma.rn.bf16x2 %0, %1, %2, %3;" : "=r"(r) : "r"(a), "r"(b), "r"(c)); return r; }
__device__ __forceinline__ uint32_t packh(float lo, float hi) { uint32_t r; asm("cvt.rn.f16x2.f32 %0, %1, %2;" : "=r"(r) : "f"(hi), "f"(lo)); return r; }
__device__ __forceinline__ __half2 H2(uint32_t a) { return *reinterpret_cast<__half2*>(&a); }
__device__ __forceinline__ uint32_t U2(__half2 a) { return *reinterpret_cast<uint32_t*>(&a); }
__device__ __forceinline__ uint32_t fmul(uint32_t a, uint32_t b) { return U2(__hmul2(H2(a), H2(b))); }
__device__ __forceinline__ uint32_t ffma(uint32_t a, uint32_t b, uint32_t c) { return U2(__hfma2(H2(a), H2(b), H2(c))); }
__device__ __forceinline__ uint32_t fneg(uint32_t a) { return U2(__hneg2(H2(a))); }
__device__ __forceinline__ uint32_t amax2(uint32_t a, uint32_t b) { uint32_t r; asm("max.xorsign.abs.bf16x2 %0, %1, %2;" : "=r"(r) : "r"(a), "r"(b)); return r; }
__device__ __forceinline__ uint32_t prmt(uint32_t a, uint32_t b, uint32_t s) { return __byte_perm(a, b, s); }
__device__ __forceinline__ uint32_t ldraw(const __nv_bfloat16* p) { uint32_t v; asm volatile("ld.global.nc.u16 %0, [%1];" : "=r"(v) : "l"(p)); return v; }
__device__ __forceinline__ uint4 ldg128(const void* p) { uint4 v; asm volatile("ld.global.nc.v4.u32 {%0,%1,%2,%3}, [%4];" : "=r"(v.x), "=r"(v.y), "=r"(v.z), "=r"(v.w) : "l"(p)); return v; }
__device__ __forceinline__ void bar_sync(int id, int n) { asm volatile("bar.sync %0, %1;" :: "r"(id), "r"(n) : "memory"); }
__device__ __forceinline__ void bar_arrive(int id, int n) { asm volatile("bar.arrive %0, %1;" :: "r"(id), "r"(n) : "memory"); }
__device__ __forceinline__ void cluster_arrive() { asm volatile("barrier.cluster.arrive.relaxed.aligned;" ::: "memory"); }
__device__ __forceinline__ void cluster_wait() { asm volatile("barrier.cluster.wait.aligned;" ::: "memory"); }
__device__ __forceinline__ void fence_async() { asm volatile("fence.proxy.async.shared::cta;" ::: "memory"); }
__device__ __forceinline__ void fence_mbinit() { asm volatile("fence.mbarrier_init.release.cluster;" ::: "memory"); }
__device__ __forceinline__ uint32_t mapa(uint32_t a, uint32_t rank) { uint32_t r; asm("mapa.shared::cluster.u32 %0, %1, %2;" : "=r"(r) : "r"(a), "r"(rank)); return r; }
__device__ __forceinline__ void bulk_dsmem(uint32_t dst, uint32_t src, uint32_t mbar) {
  asm volatile("cp.async.bulk.shared::cluster.shared::cta.mbarrier::complete_tx::bytes [%0], [%1], 512, [%2];" :: "r"(dst), "r"(src), "r"(mbar) : "memory");
}
__device__ __forceinline__ void mbar_init(uint32_t m, uint32_t cnt) { asm volatile("mbarrier.init.shared::cta.b64 [%0], %1;" :: "r"(m), "r"(cnt) : "memory"); }
__device__ __forceinline__ void mbar_expect(uint32_t m, uint32_t bytes) { asm volatile("mbarrier.arrive.expect_tx.shared::cta.b64 _, [%0], %1;" :: "r"(m), "r"(bytes) : "memory"); }
__device__ __forceinline__ bool mbar_try(uint32_t m) {
  uint32_t done;
  asm volatile("{.reg .pred p; mbarrier.try_wait.parity.shared::cta.b64 p, [%1], 0; selp.u32 %0, 1, 0, p;}" : "=r"(done) : "r"(m) : "memory");
  return done;
}
__device__ __forceinline__ void mbar_wait(uint32_t m) {
  if (!mbar_try(m)) {
    int it = 0;
    while (!mbar_try(m) && ++it < (1 << 22)) {}
  }
}
__device__ __forceinline__ bool elect() {
  uint32_t e;
  asm volatile("{.reg .pred p; elect.sync _|p, 0xffffffff; selp.u32 %0, 1, 0, p;}" : "=r"(e));
  return e;
}
__device__ __forceinline__ void tma_load4(uint32_t dst, const CUtensorMap* tm, int c0, int c1, int c2, int c3, uint32_t mbar) {
  asm volatile("cp.async.bulk.tensor.4d.shared::cluster.global.mbarrier::complete_tx::bytes [%0], [%1, {%3, %4, %5, %6}], [%2];"
               :: "r"(dst), "l"(tm), "r"(mbar), "r"(c0), "r"(c1), "r"(c2), "r"(c3) : "memory");
}
__device__ __forceinline__ void tma_load3(uint32_t dst, const CUtensorMap* tm, int c0, int c1, int c2, uint32_t mbar) {
  asm volatile("cp.async.bulk.tensor.3d.shared::cluster.global.mbarrier::complete_tx::bytes [%0], [%1, {%3, %4, %5}], [%2];"
               :: "r"(dst), "l"(tm), "r"(mbar), "r"(c0), "r"(c1), "r"(c2) : "memory");
}
__device__ __forceinline__ void tma_store3(const CUtensorMap* tm, int c0, int c1, int c2, uint32_t src) {
  asm volatile("cp.async.bulk.tensor.3d.global.shared::cta.bulk_group [%0, {%2, %3, %4}], [%1];"
               :: "l"(tm), "r"(src), "r"(c0), "r"(c1), "r"(c2) : "memory");
}
__device__ __forceinline__ void wg_fence() { asm volatile("wgmma.fence.sync.aligned;" ::: "memory"); }
__device__ __forceinline__ void wg_commit() { asm volatile("wgmma.commit_group.sync.aligned;" ::: "memory"); }
template <int N> __device__ __forceinline__ void wg_wait() { asm volatile("wgmma.wait_group.sync.aligned %0;" :: "n"(N) : "memory"); }
template <int N> __device__ __forceinline__ void tie_all(uint32_t (&x)[N]) {
#pragma unroll
  for (int i = 0; i < N; i++) asm volatile("" : "+r"(x[i]) :: "memory");
}
template <int N> __device__ __forceinline__ void tie_all(float (&x)[N]) {
#pragma unroll
  for (int i = 0; i < N; i++) asm volatile("" : "+f"(x[i]) :: "memory");
}
#define R16(C, d) C(d[0]), C(d[1]), C(d[2]), C(d[3]), C(d[4]), C(d[5]), C(d[6]), C(d[7]), C(d[8]), C(d[9]), C(d[10]), C(d[11]), C(d[12]), C(d[13]), C(d[14]), C(d[15])
#define R32(C, d) R16(C, d), R16(C, (d + 16))
#define P16 "{%0,%1,%2,%3,%4,%5,%6,%7,%8,%9,%10,%11,%12,%13,%14,%15}"
#define P32 "{%0,%1,%2,%3,%4,%5,%6,%7,%8,%9,%10,%11,%12,%13,%14,%15,%16,%17,%18,%19,%20,%21,%22,%23,%24,%25,%26,%27,%28,%29,%30,%31}"
template <int SD, int TB, int OFF> __device__ __forceinline__ void rs64(float* d, const uint32_t* a, uint64_t db) {
  if (SD) asm volatile("{.reg .b64 db; add.s64 db, %36, %37; wgmma.mma_async.sync.aligned.m64n64k16.f32.bf16.bf16 " P32 ", {%32,%33,%34,%35}, db, 1, 1, 1, %38;}"
                       : R32("+f", d) : "r"(a[0]), "r"(a[1]), "r"(a[2]), "r"(a[3]), "l"(db), "n"(OFF), "n"(TB));
  else asm volatile("{.reg .b64 db; add.s64 db, %36, %37; wgmma.mma_async.sync.aligned.m64n64k16.f32.bf16.bf16 " P32 ", {%32,%33,%34,%35}, db, 0, 1, 1, %38;}"
                    : R32("=f", d) : "r"(a[0]), "r"(a[1]), "r"(a[2]), "r"(a[3]), "l"(db), "n"(OFF), "n"(TB));
}
template <int SD, int TB, int OFF> __device__ __forceinline__ void rs64h(uint32_t* d, const uint32_t* a, uint64_t db) {
  if (SD) asm volatile("{.reg .b64 db; add.s64 db, %20, %21; wgmma.mma_async.sync.aligned.m64n64k16.f16.f16.f16 " P16 ", {%16,%17,%18,%19}, db, 1, 1, 1, %22;}"
                       : R16("+r", d) : "r"(a[0]), "r"(a[1]), "r"(a[2]), "r"(a[3]), "l"(db), "n"(OFF), "n"(TB));
  else asm volatile("{.reg .b64 db; add.s64 db, %20, %21; wgmma.mma_async.sync.aligned.m64n64k16.f16.f16.f16 " P16 ", {%16,%17,%18,%19}, db, 0, 1, 1, %22;}"
                    : R16("=r", d) : "r"(a[0]), "r"(a[1]), "r"(a[2]), "r"(a[3]), "l"(db), "n"(OFF), "n"(TB));
}
template <int SD, int OFFA, int OFFB> __device__ __forceinline__ void ss32(float* d, uint64_t da, uint64_t db) {
  if (SD) asm volatile("{.reg .b64 da, db; add.s64 da, %16, %18; add.s64 db, %17, %19; wgmma.mma_async.sync.aligned.m64n32k16.f32.f16.f16 " P16 ", da, db, 1, 1, 1, 1, 1;}"
                       : R16("+f", d) : "l"(da), "l"(db), "n"(OFFA), "n"(OFFB));
  else asm volatile("{.reg .b64 da, db; add.s64 da, %16, %18; add.s64 db, %17, %19; wgmma.mma_async.sync.aligned.m64n32k16.f32.f16.f16 " P16 ", da, db, 0, 1, 1, 1, 1;}"
                    : R16("=f", d) : "l"(da), "l"(db), "n"(OFFA), "n"(OFFB));
}
#define KGEN_ASM(SD) "{.reg .b64 da, db; add.s64 da, %32, %33; add.s64 db, %32, %34;\n" \
  "wgmma.mma_async.sync.aligned.m64n64k16.f32.bf16.bf16 " P32 ", da, db, " SD ", 1, 1, 1, 1;}"
template <int KS> __device__ __forceinline__ void kgen_mma(float (&c)[32], uint64_t da) {
  if (KS) asm volatile(KGEN_ASM("1") : R32("+f", c) : "l"(da), "n"(8 * KS), "n"(8 * KS + 512));
  else asm volatile(KGEN_ASM("0") : R32("=f", c) : "l"(da), "n"(8 * KS), "n"(8 * KS + 512));
  if constexpr (KS < 7) kgen_mma<KS + 1>(c, da);
}
__device__ __forceinline__ uint64_t desc_lo(uint32_t a) { return (uint64_t)((a & 0x3FFFF) >> 4); }
__device__ __forceinline__ void stage1(float (&D)[32], const uint32_t (&A1)[8], uint32_t src) {
  const uint64_t du = desc_lo(src) | (128ull << 16) | (32ull << 32) | (2ull << 62);
  rs64<0, 1, 0>(D, A1, du); rs64<1, 1, 64>(D, A1 + 4, du);
}
template <int INV> __device__ __forceinline__ void stage2(uint32_t (&X)[16], const uint32_t (&F)[16], uint32_t cf) {
  constexpr int KS = INV ? 16 : 128, TB = INV ? 0 : 1;
  const uint64_t dc = desc_lo(cf) | (INV ? (8ull << 16) | (64ull << 32) : (64ull << 16) | (8ull << 32));
  rs64h<0, TB, 0>(X, F, dc); rs64h<1, TB, KS>(X, F + 4, dc); rs64h<1, TB, 2 * KS>(X, F + 8, dc); rs64h<1, TB, 3 * KS>(X, F + 12, dc);
}
__device__ __forceinline__ void fwd_mid(uint32_t (&F)[16], const float (&D)[32], const uint32_t (&tc)[4], const uint32_t (&ts)[4]) {
#pragma unroll
  for (int j = 0; j < 4; j++)
#pragma unroll
    for (int b = 0; b < 2; b++) {
      const int i = 4 * j + 16 * b;
      const uint32_t ar = packh(D[i], D[i + 1]), ai = packh(D[i + 2], D[i + 3]);
      F[2 * j + b] = ffma(ar, tc[j], fmul(ai, ts[j]));
      F[8 + 2 * j + b] = ffma(ai, tc[j], fneg(fmul(ar, ts[j])));
    }
}
__device__ __forceinline__ void put_exp(uint32_t a, uint32_t m, int lane) {
  m = __reduce_max_sync(0xffffffffu, max(m & 0x7f80u, (m >> 16) & 0x7f80u));
  if (lane == 0) sts32(a, m);
}
__device__ __forceinline__ uint32_t seq_mag(uint32_t a) {
  const uint4 x = lds128(a), y = lds128(a + 2048);
  return amax2(amax2(amax2(x.x, x.y), amax2(x.z, x.w)), amax2(amax2(y.x, y.y), amax2(y.z, y.w)));
}
__device__ __forceinline__ uint32_t get_exp(uint32_t a) { const uint4 v = lds128(a); return max(max(v.x, v.y), max(v.z, v.w)) >> 7; }
__device__ __forceinline__ void scale_a1(uint32_t (&As)[8], const uint32_t (&A1)[8], uint32_t field) {
#pragma unroll
  for (int i = 0; i < 8; i++) As[i] = hmul2(A1[i], field * 0x00800080u);
}

struct cf { float x, y; };
__device__ __forceinline__ cf cmul(cf a, cf b) { cf r; r.x = fmaf(a.x, b.x, -a.y * b.y); r.y = fmaf(a.x, b.y, a.y * b.x); return r; }
__device__ __forceinline__ cf cexp_p(float lr2, float lt, float p) {
  float m;
  asm("ex2.approx.ftz.f32 %0, %1;" : "=f"(m) : "f"(lr2 * p));
  float t = lt * p;
  t = (t - rintf(t)) * 6.283185307179586f;
  cf r; r.x = m * __cosf(t); r.y = m * __sinf(t); return r;
}
__device__ __forceinline__ void store8(uint32_t a, uint32_t b, const cf (&v)[8]) {
  sts128(a, pack(v[0].x, v[1].x), pack(v[2].x, v[3].x), pack(v[4].x, v[5].x), pack(v[6].x, v[7].x));
  sts128(b, pack(v[0].y, v[1].y), pack(v[2].y, v[3].y), pack(v[4].y, v[5].y), pack(v[6].y, v[7].y));
}
__device__ __forceinline__ void mbar_arrive(uint32_t m) { asm volatile("mbarrier.arrive.shared::cta.b64 _, [%0];" :: "r"(m) : "memory"); }
__device__ __forceinline__ float sigmoidf_(float s) { return __frcp_rn(1.f + __expf(-s)); }

__global__ void __cluster_dims__(CS, 1, 1) __launch_bounds__(NTHREADS, 1) fused_kernel(const __grid_constant__ Params p) {
  extern __shared__ __align__(1024) uint8_t smem[];
  TL_INIT();
  TL(31);
  const int wid = __shfl_sync(0xffffffffu, threadIdx.x >> 5, 0);
  const uint32_t sb = (uint32_t)__cvta_generic_to_shared(smem);
  const uint32_t mb = sb + OFF_MB;
  const int u = wid >> 2, w = wid & 3;
  const int tid = threadIdx.x & 127, lane = tid & 31, g = lane >> 2, t = lane & 3;
  const int cl = blockIdx.x >> 3, rank = blockIdx.x & 7;
  const int ch0 = cl * CPC;
  const int nu = min(5, (DCH - ch0) >> 3);
  const bool act = u < nu;

  if (u == 4 && elect()) {
#pragma unroll
    for (int i = 0; i < 5; i++) mbar_init(mb + 40 * w + 8 * i, w == 3 ? 1 : w == 2 ? 3 : 2);
    if (w == 3) {
      mbar_init(mb + 8 * MB_XQ, 2); mbar_init(mb + 8 * MB_KV, 1); mbar_init(mb + 8 * MB_CF, 1); mbar_init(mb + 8 * MB_Q2, 9);
    }
    fence_mbinit();
    if (w == 3) {
      mbar_expect(mb + 8 * MB_CF, 12288);
      asm volatile("cp.async.bulk.prefetch.L2.global [%0], 20480;" :: "l"(p.tab) : "memory");
      mbar_expect(mb + 8 * MB_XQ, 20480); mbar_expect(mb + 8 * MB_KV, 23040 + 20480); mbar_expect(mb + 8 * MB_Q2, 20480);
    }
#pragma unroll
    for (int i = 0; i < 5; i++) mbar_expect(mb + 40 * w + 8 * i, w == 3 ? 4096 : w == 2 ? 7168 : 3584);
  }
  uint32_t pla, pai, pcr, pci, pdt, tag = 0;
  uint4 psm;
  {
    const int ch = act ? ch0 + 8 * u + rank : 0, o = ch * NMODE + tid;
    pla = ldraw(p.logA + o); pdt = ldraw(p.logdt + ch); pai = ldraw(p.Aim + o); pcr = ldraw(p.Cre + o); pci = ldraw(p.Cim + o);
    if (w == 1) {
      if (lane < 9) psm = ldg128(lane < 5 ? p.gate_w + (lane < nu ? ch0 + 8 * lane : 0) : p.shift_k + (act ? ch0 + 8 * u : 0) * 4 + 8 * (lane - 5));
      else { psm.x = ldraw(p.Dskip + ch); psm.y = ldraw(p.ssm_D + ch); }
    }
    if (wid == 16 && lane < 2) asm volatile("atom.relaxed.gpu.global.add.u32 %0, [%1], %2;" : "=r"(tag) : "l"(&p.cnt[rank * 32 + lane]), "r"(cl == 0 ? 16 - (NCL - 1) : 1) : "memory");
  }
  if (wid == 19 && elect()) {
    tma_load4(sb + OFF_TQ, &p.tq, ch0, 0, 0, 8 * rank, mb + 8 * MB_XQ);
    const uint32_t o = blockIdx.x * 9856u, n = min(9856u, SEQ * DCH - o) * 2;
    asm volatile("cp.async.bulk.prefetch.L2.global [%0], %1;" :: "l"(p.ssm_k + o), "r"(n) : "memory");
    asm volatile("cp.async.bulk.prefetch.L2.global [%0], %1;" :: "l"(p.k + o), "r"(n) : "memory");
    asm volatile("cp.async.bulk.prefetch.L2.global [%0], %1;" :: "l"(p.v + o), "r"(n) : "memory");
    TL(20);
  }
  __syncwarp();
  cluster_arrive();
  TL(0);

  const uint32_t tab = sb + OFF_T + u * KTAB;
  const int mi = lane >> 3, tq = (lane & 7) >> 1, jj = lane & 1;
  const uint32_t toff = (4 * (2 * mi + jj) + tq) * 80;
  const uint32_t uoff = 16 * (4 * w + (t ^ (w >> 1)));
  auto put = [&](int stage, int dst, uint32_t off, const uint32_t (&v)[4]) {
    sts128(sb + off + (g == rank ? dst + 512 * rank : stage + g * YPITCH), v[0], v[1], v[2], v[3]);
  };
  const int d0 = rank ^ (2 * w), d1 = d0 ^ 1;
  const uint32_t rb0 = mapa(sb, d0), rb1 = mapa(sb, d1);
  auto send = [&](int stage, int pitch, int dst, int mbar) {
    if (elect()) {
      if (w) bulk_dsmem(rb0 + dst, sb + stage + d0 * pitch, rb0 + mbar); else mbar_arrive(sb + mbar);
      bulk_dsmem(rb1 + dst, sb + stage + d1 * pitch, rb1 + mbar);
    }
    __syncwarp();
  };

  if (w == 1 && lane < 10) sts128(sb + OFF_SP + 160 * u + 16 * lane, psm.x, psm.y, psm.z, psm.w);
  uint32_t A1[8], tc[4], ts[4];
  {
    const float dt = bf16r(expf(blo(pdt)));
    const float lr2 = (-bf16r(expf(blo(pla))) * dt) * 1.4426950408889634f;
    const float lt = (blo(pai) * dt) * 0.15915494309189535f;
    const uint32_t tim = sb + OFF_IM + (u < 2 ? 3 + u : u - 2) * KTAB;
    const uint32_t row = tab + tid * 16, rim = tim + tid * 16;
    float zq = 0.f;
    const cf w1 = cexp_p(lr2, lt, 8.f);
    cf z1 = cexp_p(lr2, lt, 1.f), Z = cexp_p(lr2, lt, 256.f);
    if (lr2 != 123.f) TL(16);
    if (wid == 16 && lane == 0) { sts32(mb + 8 * MB_TAG, tag); mbar_arrive(mb + 8 * MB_XQ); }
    TL(12);
    {
      cf v[8];
      v[0].x = 1.f; v[0].y = 0.f; v[1] = w1; v[2] = cmul(w1, w1); v[3] = cmul(v[2], w1);
      const cf w4 = cmul(v[2], v[2]);
      v[4] = w4; v[5] = cmul(v[1], w4); v[6] = cmul(v[2], w4); v[7] = cmul(v[3], w4);
      const cf w8 = cmul(w4, w4);
      store8(row, rim, v);
#pragma unroll
      for (int k = 1; k < 4; k++) {
#pragma unroll
        for (int i = 0; i < 8; i++) v[i] = (k == 1 && i == 0) ? w8 : cmul(v[i], w8);
        store8(row + 2048 * k, rim + 2048 * k, v);
      }
    }
    if (u == 4) {
      float z1_ = 0.f, z2_ = 0.f, z3_ = 0.f;
      asm volatile("mma.sync.aligned.m16n8k8.row.col.f32.bf16.bf16.f32 {%0,%1,%2,%3}, {%4,%4}, {%4}, {%0,%1,%2,%3};"
                   : "+f"(zq), "+f"(z1_), "+f"(z2_), "+f"(z3_) : "r"(pla >> 16));
      pcr += __float_as_uint(zq);
    }
    {
      z1.y = -z1.y; Z.y = -Z.y;
      const cf z2 = cmul(z1, z1);
      cf h[8], v[8];
      h[0].x = 2.f * blo(pcr) * dt; h[0].y = -2.f * blo(pci) * dt;
      h[1] = cmul(h[0], z1);
#pragma unroll
      for (int i = 2; i < 8; i++) h[i] = cmul(h[i - 2], z2);
      store8(row + 4 * 2048, rim + 4 * 2048, h);
      const cf h8 = cmul(h[6], z2);
      v[0] = cmul(h[0], Z); v[2] = cmul(h[2], Z); v[3] = cmul(h[4], Z); v[6] = cmul(h[6], Z); v[7] = cmul(h8, Z);
      v[1] = v[0]; v[4] = v[5] = v[3];
      store8(row + 5 * 2048, rim + 5 * 2048, v);
      h[0] = cmul(v[0], Z); h[1] = cmul(v[3], Z); h[3] = cmul(v[7], Z); h[4] = cmul(h[0], Z); h[5] = cmul(h[1], Z); h[7] = cmul(h[3], Z);
      h[2] = h[1]; h[6] = h[5];
      store8(row + 6 * 2048, rim + 6 * 2048, h);
      const cf Z2 = cmul(Z, Z);
      v[0] = cmul(h[0], Z2); v[1] = cmul(h[3], Z2); v[2] = cmul(h[4], Z2); v[3] = cmul(h[7], Z2);
#pragma unroll
      for (int i = 4; i < 8; i++) v[i] = cmul(v[i - 4], Z2);
      store8(row + 7 * 2048, rim + 7 * 2048, v);
    }
    TL(17);
    cluster_wait();
    mbar_wait(mb + 8 * MB_XQ);
    TL(18);
    {
      uint32_t x0[4], x1[4];
      ldsm4t(x0, sb + OFF_TQ + w * 2560 + toff + 16 * u);
      ldsm4t(x1, sb + OFF_TQ + (w + 4) * 2560 + toff + 16 * u);
      put(OFF_YB + 8 * u * YPITCH, OFF_UX + u * 4096, uoff, x0);
      put(OFF_YB + 8 * u * YPITCH, OFF_UX + u * 4096, (uoff ^ 32) + 256, x1);
    }
    TL(3);
    fence_async();
    bar_sync(NB_WG0 + u, 128);
    TL(4);
    if (u >= 3) {
      float s0 = 0.f;
#pragma unroll
      for (int j = 0; j < 5; j++) {
        const uint4 gw = lds128(sb + OFF_SP + 160 * u + 16 * j), x = lds128(sb + OFF_TQ + (tid + 128 * (u - 3)) * 80 + 16 * j);
        const uint32_t m0 = hmul2(x.x, gw.x), m1 = hmul2(x.y, gw.y), m2 = hmul2(x.z, gw.z), m3 = hmul2(x.w, gw.w);
        s0 += ((blo(m0) + bhi(m0)) + (blo(m1) + bhi(m1))) + ((blo(m2) + bhi(m2)) + (blo(m3) + bhi(m3)));
      }
      tag = (lds64(mb + 8 * MB_TAG).x >> 4) + 1;
      asm volatile("st.relaxed.gpu.global.u64 [%0], %1;" :: "l"(p.part + cl * SEQ + rank * 256 + 8 * (8 * t + g) + w + 4 * (u - 3)),
                   "l"(((uint64_t)tag << 32) | __float_as_uint(s0)) : "memory");
    }
    TL(7);
    if (u) bar_sync(NB_ORD + u - 1, 256);
    TL(13);
    float c[32];
    wg_fence();
    kgen_mma<0>(c, desc_lo(tab) | ((uint64_t)((tim - tab) >> 4) << 16) | (64ull << 32));
    wg_commit();
    if (u < 4) bar_arrive(NB_ORD + u, 256);
    const __nv_bfloat16* hp = p.ssm_k + (size_t)(act ? ch0 + 8 * u + rank : 0) * SEQ + 8 * tid;
    const uint4 hm0 = ldg128(hp), hm1 = ldg128(hp + 1024);
    {
      const uint4 x = ldg128(p.tab->thr[0][tid]), y = ldg128(p.tab->thr[1][tid]), a = ldg128(p.tab->thr[2][tid]), b = ldg128(p.tab->thr[3][tid]);
      A1[0] = x.x; A1[1] = x.y; A1[2] = x.z; A1[3] = x.w; A1[4] = y.x; A1[5] = y.y; A1[6] = y.z; A1[7] = y.w;
      tc[0] = a.x; tc[1] = a.y; tc[2] = a.z; tc[3] = a.w; ts[0] = b.x; ts[1] = b.y; ts[2] = b.z; ts[3] = b.w;
    }
    send(OFF_YB + 8 * u * YPITCH, YPITCH, OFF_UX + u * 4096 + 512 * rank, OFF_MB + 8 * (MB_UX + u));
    TL(14);
    wg_wait<0>(); tie_all(c);
    TL(26);
    cluster_arrive();
    if (wid == 17) {
      bar_sync(NB_LD, 640);
      if (elect()) {
        tma_load4(sb + OFF_TK, &p.tk, ch0, 0, 0, 8 * rank - 1, mb + 8 * MB_KV);
        tma_load4(sb + OFF_TV, &p.tv, ch0, 0, 0, 8 * rank, mb + 8 * MB_KV);
      }
      __syncwarp();
    } else {
      bar_arrive(NB_LD, 640);
    }
    bar_sync(NB_WG0 + u, 128);
    if (wid == 1 && elect())
      asm volatile("cp.async.bulk.shared::cluster.global.mbarrier::complete_tx::bytes [%0], [%1], %2, [%3];"
                   :: "r"(sb + OFF_CF), "l"(p.tab->mat), "r"(12288), "r"(mb + 8 * MB_CF) : "memory");
    __syncwarp();
    const uint32_t k0 = pack(c[0] + c[6], c[1] + c[7]), k1 = pack(c[8] + c[14], c[9] + c[15]);
    const uint32_t k2 = pack(c[16] + c[22], c[17] + c[23]), k3 = pack(c[24] + c[30], c[25] + c[31]);
    const uint32_t ka = tab + 16 * (8 * w + (g ^ w));
    sts32(ka + 4 * t, k0);
    sts32(ka + 512 + 4 * t, k1);
    sts64(ka + 1024 + 512 * (t >> 1) + 8 * (t & 1), prmt(k2, 0, 0x1010), (t & 1) ? prmt(k2, 0, 0x3232) : k2);
    const uint32_t lo = prmt(k3, 0, 0x1010), hi = prmt(k3, 0, 0x3232);
    sts128(ka + 2048 + 512 * t, lo, lo, (g & 1) ? hi : k3, hi);
    put_exp(sb + OFF_MX + u * 64 + 4 * w, amax2(amax2(k0, k1), amax2(k2, k3)), lane);
    put_exp(sb + OFF_MX + u * 64 + 32 + 4 * w, amax2(amax2(amax2(hm0.x, hm0.y), amax2(hm0.z, hm0.w)), amax2(amax2(hm1.x, hm1.y), amax2(hm1.z, hm1.w))), lane);
    TL(15);
    fence_async();
    bar_sync(NB_WG0 + u, 128);
  }

#pragma unroll
  for (int isA = 0; isA < 2; isA++) {
    {
      TL(1 + isA);
      const uint32_t usrc = isA ? tab + T_UKV : sb + OFF_UX + u * 4096;
      const uint32_t mxa = sb + OFF_MX + u * 64 + 32 * isA;
      const uint32_t pd = lds16(sb + OFF_SP + 160 * u + 144 + 4 * isA);
      float D[32];
      uint32_t As[8], F[16], H[16], X[16];
      const uint32_t eh = min(max((int)get_exp(mxa), (int)((pd >> 7) & 0xff) - 5), 240);
      scale_a1(As, A1, 248 - eh);
      if (isA) mbar_wait(mb + 8 * (MB_HA + u));
      wg_fence();
      stage1(D, As, isA ? tab + T_HA : tab);
      wg_commit();
      wg_wait<0>(); tie_all(D);
      fwd_mid(F, D, tc, ts);
      if (!isA) mbar_wait(mb + 8 * MB_CF);
      wg_fence();
      stage2<0>(H, F, sb + OFF_CF);
      wg_commit();
      mbar_wait(mb + 8 * ((isA ? MB_UKV : MB_UX) + u));
      TL(5 + isA);
      put_exp(mxa + 16 + 4 * w, seq_mag(usrc + 16 * tid), lane);
      bar_sync(NB_WG0 + u, 128);
      const uint32_t eu = min(get_exp(mxa + 16), 240u);
      scale_a1(As, A1, 250 - eu);
      wg_wait<0>(); tie_all(H);
      wg_fence();
      stage1(D, As, usrc);
      wg_commit();
      wg_wait<0>(); tie_all(D);
      fwd_mid(F, D, tc, ts);
      wg_fence();
      stage2<0>(X, F, sb + OFF_CF);
      wg_commit();
      if (!isA && w == 1 && elect()) {
        tma_load4(tab + T_HA, &p.th, 0, 0, 5 * cl + u, rank, mb + 8 * (MB_HA + u));
        if (u == 4) tma_load3(sb + OFF_Q2, &p.tq2, ch0, 8 * rank, 0, mb + 8 * MB_Q2);
      }
      __syncwarp();
      {
        const float dsk = blo(pd) * __uint_as_float((248 - eh) << 23);
        const uint32_t d2 = packh(dsk, dsk);
#pragma unroll
        for (int j = 0; j < 4; j++) H[2 * j] = U2(__hadd2(H2(H[2 * j]), H2(d2)));
      }
      wg_wait<0>(); tie_all(X);
#pragma unroll
      for (int j = 0; j < 4; j++) {
        const uint32_t h0r = H[2 * j], h1r = H[2 * j + 1], h0i = H[8 + 2 * j], h1i = H[9 + 2 * j];
        const uint32_t x0r = X[2 * j], x1r = X[2 * j + 1], x0i = X[8 + 2 * j], x1i = X[9 + 2 * j];
        F[2 * j] = ffma(x0r, h0r, fneg(fmul(x0i, h0i)));
        F[8 + 2 * j] = ffma(x0r, h0i, fmul(x0i, h0r));
        F[2 * j + 1] = ffma(x1r, h0r, ffma(fneg(x1i), h0i, ffma(x0r, h1r, fneg(ffma(x0i, h1i, F[8 + 2 * j])))));
        F[9 + 2 * j] = ffma(x1r, h0i, ffma(x1i, h0r, ffma(x0r, h1i, ffma(x0i, h1r, F[2 * j]))));
      }
      wg_fence();
      stage2<1>(H, F, sb + OFF_CF);
      wg_commit();
      wg_wait<0>(); tie_all(H);
      {
        const uint32_t va = tab + (16 * w + (lane & 15)) * 128;
        const int vx = (lane >> 4) ^ (lane & 7);
#pragma unroll
        for (int j = 0; j < 4; j++) {
          uint32_t V[4];
#pragma unroll
          for (int b = 0; b < 2; b++) {
            const uint32_t er = H[2 * j + b], ei = H[8 + 2 * j + b];
            V[2 * b] = ffma(er, tc[j], fneg(fmul(ei, ts[j])));
            V[2 * b + 1] = ffma(ei, tc[j], fmul(er, ts[j]));
          }
          stsm4(va + ((vx ^ (2 * j)) << 4), V);
        }
      }
      uint64_t ga[NCL];
      const int slot = tid + 128 * (u & 1);
      const uint2* gp = p.part + rank * 256 + slot;
      auto gload = [&]() {
#pragma unroll
        for (int k = 0; k < NCL; k++) asm volatile("ld.relaxed.gpu.global.u64 %0, [%1];" : "=l"(ga[k]) : "l"(gp + k * SEQ) : "memory");
      };
      if (!isA) {
        cluster_wait();
        mbar_wait(mb + 8 * MB_KV);
        TL(21);
        const uint32_t hoff = (4 * (4 + 2 * (mi & 1) + jj) + ((tq + 3) & 3)) * 80 + (tq ? 2560 : 0) + 16 * u;
        uint32_t E[2][6], V[2][4];
        const uint2 psw = lds64(sb + OFF_SP + 160 * u + 80 + 8 * g);
#pragma unroll
        for (int hf = 0; hf < 2; hf++) {
          const int ah = 4 * hf + w;
          uint32_t K[4];
          ldsm4t(K, sb + OFF_TK + (ah + 1) * 2560 + toff + 16 * u);
          ldsm2t(E[hf][0], E[hf][1], sb + OFF_TK + ah * 2560 + hoff);
          ldsm4t(V[hf], sb + OFF_TV + ah * 2560 + toff + 16 * u);
          E[hf][2] = K[0]; E[hf][3] = K[1]; E[hf][4] = K[2]; E[hf][5] = K[3];
        }
        const uint32_t w0 = prmt(psw.x, 0, 0x1010), w1 = prmt(psw.x, 0, 0x3232), w2 = prmt(psw.y, 0, 0x1010), w3 = prmt(psw.y, 0, 0x3232);
        uint32_t o[2][4];
#pragma unroll
        for (int hf = 0; hf < 2; hf++) {
          uint32_t O[5];
#pragma unroll
          for (int i = 0; i < 5; i++) O[i] = prmt(E[hf][i], E[hf][i + 1], 0x5432);
#pragma unroll
          for (int i = 0; i < 4; i++) {
            o[hf][i] = hmul2(hfma2(E[hf][i + 2], w0, hfma2(O[i + 1], w1, hfma2(E[hf][i + 1], w2, hmul2(O[i], w3)))), V[hf][i]);
          }
          put(OFF_YA + 8 * u * YPITCH, OFF_T + u * KTAB + T_UKV, hf ? (uoff ^ 32) + 256 : uoff, o[hf]);
        }
        TL(22);
      }
      fence_async();
      bar_sync(NB_WG0 + u, 128);
      float O[16];
      {
        const uint64_t dv = desc_lo(tab) | (1ull << 16) | (64ull << 32) | (1ull << 62);
        const uint64_t dl = desc_lo(sb + OFF_CL) | (32ull << 16) | (8ull << 32);
        wg_fence();
        ss32<0, 0, 0>(O, dv, dl); ss32<1, 128, 64>(O, dv, dl); ss32<1, 256, 128>(O, dv, dl); ss32<1, 384, 192>(O, dv, dl);
        wg_commit();
      }
      if (!isA) {
        send(OFF_YA + 8 * u * YPITCH, YPITCH, OFF_T + u * KTAB + T_UKV + 512 * rank, OFF_MB + 8 * (MB_UKV + u));
        if (u < 2) gload();
      }
      wg_wait<0>(); tie_all(O);
      {
        const uint32_t co = ((8 * w + g) ^ (2 * t)) * 16;
        const int yo = (isA ? OFF_YA : OFF_YB) + (8 * u + rank) * YPITCH, ym = OFF_MB + 8 * (MB_Y + u);
        const uint32_t us = min(max((int)(eu + eh) - 127, 0), 254) * 0x00800080u;
        const uint32_t a0 = hmul2(pack(O[0], O[1]), us), a1 = hmul2(pack(O[4], O[5]), us), a2 = hmul2(pack(O[8], O[9]), us), a3 = hmul2(pack(O[12], O[13]), us);
        const uint32_t b0 = hmul2(pack(O[2], O[3]), us), b1 = hmul2(pack(O[6], O[7]), us), b2 = hmul2(pack(O[10], O[11]), us), b3 = hmul2(pack(O[14], O[15]), us);
        sts128((t == rank ? sb + yo : usrc + t * 512) + co, a0, a1, a2, a3);
        sts128((t + 4 == rank ? sb + yo : usrc + t * 512 + 2048) + co, b0, b1, b2, b3);
        fence_async();
        bar_sync(NB_WG0 + u, 128);
        send(usrc - sb, 512, yo, ym);
      }
      TL(9 + isA);
      if (!isA && u < 2) {
        tag = (lds64(mb + 8 * MB_TAG).x >> 4) + 1;
        float s;
        bool ok;
#pragma unroll 1
        for (int it = 0;; it++) {
          ok = true; s = 0.f;
#pragma unroll
          for (int k = 0; k < NCL; k++) { ok = ok && (uint32_t)(ga[k] >> 32) == tag; s += __uint_as_float((uint32_t)ga[k]); }
          if (ok || it == 4000) break;
          gload();
        }
        if (!ok) {
          const uint32_t* xr = (const uint32_t*)(p.q + (size_t)(rank * 256 + 32 * (slot & 7) + (slot >> 3)) * DCH);
          const uint32_t* gr = (const uint32_t*)p.gate_w;
          s = 0.f;
    #pragma unroll 1
          for (int k = 0; k < DCH / 2; k++) { const uint32_t m = hmul2(__ldg(xr + k), __ldg(gr + k)); s += blo(m) + bhi(m); }
        }
        const float g0 = bf16r(sigmoidf_(bf16r(s)));
        sts64(sb + OFF_GB + 8 * slot, pack(g0, g0), pack(1.f - g0, 1.f - g0));
        __syncwarp();
        if (lane == 0) mbar_arrive(mb + 8 * MB_Q2);
      }
    }
  }

  {
    mbar_wait(mb + 8 * MB_Q2);
    uint2 gg[2][4];
    uint32_t qv[2][4];
#pragma unroll
    for (int hh = 0; hh < 2; hh++)
#pragma unroll
      for (int i = 0; i < 4; i++) gg[hh][i] = lds64(sb + OFF_GB + 8 * (64 * w + 32 * hh + 8 * i + g));
    const uint32_t qa = sb + OFF_Q2 + (64 * w + lane) * 80 + 16 * u;
    ldsm4(qv[0], qa);
    ldsm4(qv[1], qa + 2560);
    TL(24);
    mbar_wait(mb + 8 * (MB_Y + u));
    uint32_t ya[2][4], yb[2][4];
#pragma unroll
    for (int hh = 0; hh < 2; hh++) {
      const uint32_t yo = (8 * u + (lane & 7)) * YPITCH + ((8 * w + 4 * hh + (lane >> 3)) ^ (2 * (rank & 3))) * 16;
      ldsm4t(ya[hh], sb + OFF_YA + yo); ldsm4t(yb[hh], sb + OFF_YB + yo);
    }
#pragma unroll
    for (int hh = 0; hh < 2; hh++) {
      uint32_t o[4];
#pragma unroll
      for (int i = 0; i < 4; i++) o[i] = hadd2(hmul2(gg[hh][i].x, hmul2(qv[hh][i], ya[hh][i])), hmul2(gg[hh][i].y, yb[hh][i]));
      stsm4(qa + 2560 * hh, o);
    }
    TL(25);
  }
  cluster_arrive();
  bar_sync(NB_ROW0 + w, 160);
  {
    uint4 v[2];
#pragma unroll
    for (int k = 0; k < 2; k++) {
      const int i = 64 * u + 32 * k + lane, sl = (i * 205) >> 10, cc = i - 5 * sl;
      v[k] = lds128(sb + OFF_Q2 + (64 * w + 8 * (sl & 7) + (sl >> 3)) * 80 + cc * 16);
    }
#pragma unroll
    for (int k = 0; k < 2; k++) {
      const int i = 64 * u + 32 * k + lane, sl = (i * 205) >> 10, cc = i - 5 * sl;
      if (cc < nu)
        asm volatile("st.global.v4.u32 [%0], {%1,%2,%3,%4};" :: "l"(p.out + (size_t)(256 * rank + 32 * (sl >> 3) + 8 * w + (sl & 7)) * DCH + ch0 + 8 * cc),
                     "r"(v[k].x), "r"(v[k].y), "r"(v[k].z), "r"(v[k].w) : "memory");
    }
  }
  cluster_wait();
  TL(27);
  TL_DUMP();
}

typedef CUresult (*EncodeFn)(CUtensorMap*, CUtensorMapDataType, cuuint32_t, void*, const cuuint64_t*, const cuuint64_t*,
                             const cuuint32_t*, const cuuint32_t*, CUtensorMapInterleave, CUtensorMapSwizzle,
                             CUtensorMapL2promotion, CUtensorMapFloatOOBfill);

void encode(EncodeFn fn, CUtensorMap* tm, const void* ptr, int nd, const cuuint64_t* dims, const cuuint64_t* strides,
            const cuuint32_t* box, CUtensorMapSwizzle swz) {
  cuuint32_t es[4] = {1, 1, 1, 1};
  fn(tm, CU_TENSOR_MAP_DATA_TYPE_BFLOAT16, nd, const_cast<void*>(ptr), dims, strides, box, es, CU_TENSOR_MAP_INTERLEAVE_NONE,
     swz, CU_TENSOR_MAP_L2_PROMOTION_L2_128B, CU_TENSOR_MAP_FLOAT_OOB_FILL_NONE);
}
void map1(EncodeFn fn, CUtensorMap* tm, const void* ptr, int nhi) {
  const cuuint64_t dims[4] = {DCH, 4, 8, SEQ / 32}, strides[3] = {8 * DCH * 2, DCH * 2, 32 * DCH * 2};
  const cuuint32_t box[4] = {CPC, 4, 8, (cuuint32_t)nhi};
  encode(fn, tm, ptr, 4, dims, strides, box, CU_TENSOR_MAP_SWIZZLE_NONE);
}
void map2(EncodeFn fn, CUtensorMap* tm, const void* ptr, int nr) {
  const cuuint64_t dims[3] = {DCH, SEQ / 32, 32}, strides[2] = {32 * DCH * 2, DCH * 2};
  const cuuint32_t box[3] = {CPC, 8, (cuuint32_t)nr};
  encode(fn, tm, ptr, 3, dims, strides, box, CU_TENSOR_MAP_SWIZZLE_NONE);
}

}

extern "C" void kernel_launch(void* const* d_in, const int* in_sizes, int n_in, void* d_out, int out_size) {
  (void)in_sizes; (void)n_in; (void)out_size;
  static EncodeFn fn = nullptr;
  static void *tab = nullptr, *cnt = nullptr, *part = nullptr;
  if (!fn) {
    cudaGetSymbolAddress(&tab, d_tab);
    cudaGetSymbolAddress(&cnt, g_cnt);
    cudaGetSymbolAddress(&part, g_part);
    cudaDriverEntryPointQueryResult qr;
    cudaGetDriverEntryPoint("cuTensorMapEncodeTiled", (void**)&fn, cudaEnableDefault, &qr);
    cudaFuncSetAttribute(fused_kernel, cudaFuncAttributeMaxDynamicSharedMemorySize, SMEM_BYTES);
  }
  Params p;
  map1(fn, &p.tq, d_in[0], 8);
  map1(fn, &p.tk, d_in[1], 9);
  map1(fn, &p.tv, d_in[2], 8);
  map2(fn, &p.tq2, d_in[0], 32);
  p.out = (__nv_bfloat16*)d_out;
  {
    const cuuint64_t dims[4] = {32, SEQ / 32, DCH / 8, 8}, strides[3] = {64, 8 * SEQ * 2, SEQ * 2};
    const cuuint32_t box[4] = {32, 64, 1, 1};
    encode(fn, &p.th, d_in[4], 4, dims, strides, box, CU_TENSOR_MAP_SWIZZLE_64B);
  }
  p.tab = (const Tables*)tab;
  p.cnt = (unsigned*)cnt;
  p.part = (uint2*)part;
  p.tl = nullptr;
  p.q = (const __nv_bfloat16*)d_in[0];
  p.k = (const __nv_bfloat16*)d_in[1];
  p.v = (const __nv_bfloat16*)d_in[2];
  p.ssm_k = (const __nv_bfloat16*)d_in[4];
  p.shift_k = (const __nv_bfloat16*)d_in[3];
  p.ssm_D = (const __nv_bfloat16*)d_in[5];
  p.logA = (const __nv_bfloat16*)d_in[7];
  p.Aim = (const __nv_bfloat16*)d_in[8];
  p.Cre = (const __nv_bfloat16*)d_in[9];
  p.Cim = (const __nv_bfloat16*)d_in[10];
  p.logdt = (const __nv_bfloat16*)d_in[11];
  p.Dskip = (const __nv_bfloat16*)d_in[12];
  p.gate_w = (const __nv_bfloat16*)d_in[13];
  fused_kernel<<<NCL * CS, NTHREADS, SMEM_BYTES, cudaStreamPerThread>>>(p);
}
```

```cpp
#include <cuda_runtime.h>
#include <cuda_bf16.h>
#include <cuda_fp16.h>
#include <cuda.h>
#include <stdint.h>

#define TIMELINE 0

namespace {

constexpr int SEQ = 2048, DCH = 576, NMODE = 128;
constexpr int CS = 8, CPC = 40, NCL = 15, NTHREADS = 640;

constexpr int YPITCH = 528;
constexpr int KTAB = 16384;
constexpr int OFF_T = 0;
constexpr int T_UKV = 8192, T_HA = 12288;
constexpr int OFF_UX = 5 * KTAB;
constexpr int OFF_IM = OFF_UX + 20480;
constexpr int OFF_Q2 = OFF_IM;
constexpr int OFF_GB = OFF_Q2 + 20480;
constexpr int OFF_TV = OFF_IM + 3 * KTAB - 20480;
constexpr int OFF_CF = OFF_IM + 3 * KTAB;
constexpr int OFF_CL = OFF_CF + 8192;
constexpr int OFF_TK = OFF_CL + 4096;
constexpr int OFF_TQ = OFF_TK + 23040;
constexpr int OFF_YA = OFF_TQ;
constexpr int OFF_YB = OFF_TQ + 21120;
constexpr int OFF_MX = OFF_YB + 40 * YPITCH;
constexpr int OFF_SP = OFF_MX + 320;
constexpr int OFF_MB = OFF_SP + 5 * 160;
constexpr int OFF_TL = OFF_MB + 32 * 8;
constexpr int SMEM_BYTES = OFF_TL + (TIMELINE ? 1280 : 0);
static_assert(SMEM_BYTES <= 232448 && OFF_IM + 5 * KTAB <= OFF_TQ, "smem");
static_assert((OFF_TQ & 127) == 0 && (OFF_TK & 127) == 0 && (OFF_TV & 127) == 0 && (OFF_MB & 7) == 0 && (OFF_MX & 15) == 0, "align");

enum { MB_UX = 0, MB_UKV = 5, MB_Y = 10, MB_HA = 15, MB_XQ = 20, MB_KV = 21, MB_CF = 22, MB_Q2 = 23, MB_XD = 24, MB_TAG = 25 };
enum { NB_WG0 = 1, NB_ROW0 = 6, NB_ORD = 6, NB_K0 = 10, NB_LD = 11 };

constexpr double cos_turn(int m, int n) {
  m &= n - 1;
  if (m > n / 2) m = n - m;
  double sgn = 1.0;
  if (m > n / 4) { m = n / 2 - m; sgn = -1.0; }
  if (m == n / 4) return 0.0;
  const double x = 6.283185307179586476925 * m / n;
  double term = 1.0, sum = 1.0;
  for (int k = 1; k < 14; k++) { term *= -x * x / ((2 * k - 1) * (2 * k)); sum += term; }
  return sgn * sum;
}
constexpr uint32_t bf16_bits(double v) {
  if (v == 0.0) return 0;
  uint32_t sgn = 0;
  if (v < 0) { sgn = 0x8000; v = -v; }
  int e = 127;
  while (v < 1.0) { v *= 2.0; e--; }
  while (v >= 2.0) { v *= 0.5; e++; }
  const double f = v * 128.0;
  int m = (int)f;
  if (f - m > 0.5 || (f - m == 0.5 && (m & 1))) m++;
  return sgn | (uint32_t)((e << 7) + (m - 128));
}
constexpr uint32_t f16_bits(double v) {
  if (v == 0.0) return 0;
  uint32_t sgn = 0;
  if (v < 0) { sgn = 0x8000; v = -v; }
  int e = 15;
  while (v < 1.0) { v *= 2.0; e--; }
  const double f = v * 1024.0;
  int m = (int)f;
  if (f - m > 0.5 || (f - m == 0.5 && (m & 1))) m++;
  return sgn | (uint32_t)((e << 10) + (m - 1024));
}
constexpr uint32_t pair_bits(double lo, double hi) { return bf16_bits(lo) | (bf16_bits(hi) << 16); }
constexpr uint32_t pair_h(double lo, double hi) { return f16_bits(lo) | (f16_bits(hi) << 16); }
struct alignas(128) Tables {
  uint32_t mat[3072];
  uint32_t thr[4][128][4];
};
constexpr Tables make_tables() {
  Tables T{};
  for (int q = 0; q < 768; q++) {
    int m0 = 0, d0 = 0, d1 = 0;
    if (q < 512) {
      const int r = (q >> 6) * 8 + (q & 7), cc = (q >> 3) & 7;
      d0 = 4 * (r & 31); d1 = 2 * d0;
      m0 = 8 * (cc & 3) * d0 + ((r >> 5) == (cc >> 2) ? 0 : (r >> 5) ? 96 : 32);
    } else {
      const int r = ((q - 512) >> 5) * 8 + (q & 7), pc = (q >> 3) & 3;
      d0 = 4 * (8 * (r >> 4) + (r & 7)) + 1; d1 = 8 * d0;
      m0 = 2 * pc * d0 + ((r & 8) ? 32 : 0);
    }
    for (int e = 0; e < 4; e++) T.mat[4 * q + e] = pair_h(cos_turn(m0 + e * d1, 128), cos_turn(m0 + e * d1 + d0, 128));
  }
  for (int tid = 0; tid < 128; tid++) {
    const int kk = 4 * (tid >> 2) + 1, t = tid & 3;
    for (int q = 0; q < 4; q++) {
      const int m = (8 * q + 2 * t) * kk;
      T.thr[q >> 1][tid][2 * (q & 1)] = pair_bits(cos_turn(m, 128), cos_turn(m + kk, 128));
      T.thr[q >> 1][tid][2 * (q & 1) + 1] = pair_bits(cos_turn(m + 32, 128), cos_turn(m + kk + 32, 128));
      T.thr[2][tid][q] = pair_h(cos_turn(m, 4096), cos_turn(m + kk, 4096));
      T.thr[3][tid][q] = pair_h(cos_turn(m + 3072, 4096), cos_turn(m + kk + 3072, 4096));
    }
  }
  return T;
}
__device__ const Tables d_tab = make_tables();

struct Params {
  const __nv_bfloat16 *logA, *Aim, *Cre, *Cim, *logdt;
  const Tables* tab;
  unsigned* cnt;
  const __nv_bfloat16 *Dskip, *shift_k, *ssm_D, *gate_w, *q, *k, *v, *ssm_k;
  uint2* part;
  __nv_bfloat16* out;
  unsigned* tl;
  CUtensorMap tq, tk, tv, th, tq2;
};

__device__ uint2 g_part[NCL * SEQ];
__device__ unsigned g_cnt[CS * 32];
#define TL(i) do {} while (0)
#define TL_INIT() do {} while (0)
#define TL_DUMP() do {} while (0)

__device__ __forceinline__ uint32_t lds16(uint32_t a) { uint32_t v; asm volatile("ld.shared.u16 %0, [%1];" : "=r"(v) : "r"(a) : "memory"); return v; }
__device__ __forceinline__ uint2 lds64(uint32_t a) { uint2 v; asm volatile("ld.shared.v2.u32 {%0,%1}, [%2];" : "=r"(v.x), "=r"(v.y) : "r"(a) : "memory"); return v; }
__device__ __forceinline__ uint4 lds128(uint32_t a) { uint4 v; asm volatile("ld.shared.v4.u32 {%0,%1,%2,%3}, [%4];" : "=r"(v.x), "=r"(v.y), "=r"(v.z), "=r"(v.w) : "r"(a) : "memory"); return v; }
__device__ __forceinline__ void sts16(uint32_t a, uint32_t v) { asm volatile("st.shared.u16 [%0], %1;" :: "r"(a), "r"(v) : "memory"); }
__device__ __forceinline__ void sts32(uint32_t a, uint32_t v) { asm volatile("st.shared.u32 [%0], %1;" :: "r"(a), "r"(v) : "memory"); }
__device__ __forceinline__ void sts64(uint32_t a, uint32_t x, uint32_t y) { asm volatile("st.shared.v2.u32 [%0], {%1,%2};" :: "r"(a), "r"(x), "r"(y) : "memory"); }
__device__ __forceinline__ void sts128(uint32_t a, uint32_t x, uint32_t y, uint32_t z, uint32_t w) { asm volatile("st.shared.v4.u32 [%0], {%1,%2,%3,%4};" :: "r"(a), "r"(x), "r"(y), "r"(z), "r"(w) : "memory"); }
__device__ __forceinline__ void ldsm4t(uint32_t (&r)[4], uint32_t a) { asm volatile("ldmatrix.sync.aligned.m8n8.x4.trans.shared.b16 {%0,%1,%2,%3}, [%4];" : "=r"(r[0]), "=r"(r[1]), "=r"(r[2]), "=r"(r[3]) : "r"(a) : "memory"); }
__device__ __forceinline__ void ldsm2t(uint32_t& r0, uint32_t& r1, uint32_t a) { asm volatile("ldmatrix.sync.aligned.m8n8.x2.trans.shared.b16 {%0,%1}, [%2];" : "=r"(r0), "=r"(r1) : "r"(a) : "memory"); }
__device__ __forceinline__ void ldsm4(uint32_t (&r)[4], uint32_t a) { asm volatile("ldmatrix.sync.aligned.m8n8.x4.shared.b16 {%0,%1,%2,%3}, [%4];" : "=r"(r[0]), "=r"(r[1]), "=r"(r[2]), "=r"(r[3]) : "r"(a) : "memory"); }
__device__ __forceinline__ void stsm4(uint32_t a, const uint32_t (&r)[4]) { asm volatile("stmatrix.sync.aligned.m8n8.x4.shared.b16 [%0], {%1,%2,%3,%4};" :: "r"(a), "r"(r[0]), "r"(r[1]), "r"(r[2]), "r"(r[3]) : "memory"); }
__device__ __forceinline__ uint32_t pack(float lo, float hi) { uint32_t r; asm("cvt.rn.bf16x2.f32 %0, %1, %2;" : "=r"(r) : "f"(hi), "f"(lo)); return r; }
__device__ __forceinline__ float blo(uint32_t v) { return __uint_as_float(v << 16); }
__device__ __forceinline__ float bhi(uint32_t v) { return __uint_as_float(v & 0xffff0000u); }
__device__ __forceinline__ float bf16r(float x) { return blo(pack(x, 0.f)); }
__device__ __forceinline__ uint32_t hmul2(uint32_t a, uint32_t b) { uint32_t r; asm("mul.rn.bf16x2 %0, %1, %2;" : "=r"(r) : "r"(a), "r"(b)); return r; }
__device__ __forceinline__ uint32_t hadd2(uint32_t a, uint32_t b) { uint32_t r; asm("add.rn.bf16x2 %0, %1, %2;" : "=r"(r) : "r"(a), "r"(b)); return r; }
__device__ __forceinline__ uint32_t hfma2(uint32_t a, uint32_t b, uint32_t c) { uint32_t r; asm("fma.rn.bf16x2 %0, %1, %2, %3;" : "=r"(r) : "r"(a), "r"(b), "r"(c)); return r; }
__device__ __forceinline__ uint32_t packh(float lo, float hi) { uint32_t r; asm("cvt.rn.f16x2.f32 %0, %1, %2;" : "=r"(r) : "f"(hi), "f"(lo)); return r; }
__device__ __forceinline__ __half2 H2(uint32_t a) { return *reinterpret_cast<__half2*>(&a); }
__device__ __forceinline__ uint32_t U2(__half2 a) { return *reinterpret_cast<uint32_t*>(&a); }
__device__ __forceinline__ uint32_t fmul(uint32_t a, uint32_t b) { return U2(__hmul2(H2(a), H2(b))); }
__device__ __forceinline__ uint32_t ffma(uint32_t a, uint32_t b, uint32_t c) { return U2(__hfma2(H2(a), H2(b), H2(c))); }
__device__ __forceinline__ uint32_t fneg(uint32_t a) { return U2(__hneg2(H2(a))); }
__device__ __forceinline__ uint32_t amax2(uint32_t a, uint32_t b) { uint32_t r; asm("max.xorsign.abs.bf16x2 %0, %1, %2;" : "=r"(r) : "r"(a), "r"(b)); return r; }
__device__ __forceinline__ uint32_t prmt(uint32_t a, uint32_t b, uint32_t s) { return __byte_perm(a, b, s); }
__device__ __forceinline__ uint32_t ldraw(const __nv_bfloat16* p) { uint32_t v; asm volatile("ld.global.nc.u16 %0, [%1];" : "=r"(v) : "l"(p)); return v; }
__device__ __forceinline__ uint4 ldg128(const void* p) { uint4 v; asm volatile("ld.global.nc.v4.u32 {%0,%1,%2,%3}, [%4];" : "=r"(v.x), "=r"(v.y), "=r"(v.z), "=r"(v.w) : "l"(p)); return v; }
__device__ __forceinline__ void bar_sync(int id, int n) { asm volatile("bar.sync %0, %1;" :: "r"(id), "r"(n) : "memory"); }
__device__ __forceinline__ void bar_arrive(int id, int n) { asm volatile("bar.arrive %0, %1;" :: "r"(id), "r"(n) : "memory"); }
__device__ __forceinline__ void cluster_arrive() { asm volatile("barrier.cluster.arrive.relaxed.aligned;" ::: "memory"); }
__device__ __forceinline__ void cluster_wait() { asm volatile("barrier.cluster.wait.aligned;" ::: "memory"); }
__device__ __forceinline__ void fence_async() { asm volatile("fence.proxy.async.shared::cta;" ::: "memory"); }
__device__ __forceinline__ void fence_mbinit() { asm volatile("fence.mbarrier_init.release.cluster;" ::: "memory"); }
__device__ __forceinline__ uint32_t mapa(uint32_t a, uint32_t rank) { uint32_t r; asm("mapa.shared::cluster.u32 %0, %1, %2;" : "=r"(r) : "r"(a), "r"(rank)); return r; }
__device__ __forceinline__ void bulk_dsmem(uint32_t dst, uint32_t src, uint32_t mbar) {
  asm volatile("cp.async.bulk.shared::cluster.shared::cta.mbarrier::complete_tx::bytes [%0], [%1], 512, [%2];" :: "r"(dst), "r"(src), "r"(mbar) : "memory");
}
__device__ __forceinline__ void mbar_init(uint32_t m, uint32_t cnt) { asm volatile("mbarrier.init.shared::cta.b64 [%0], %1;" :: "r"(m), "r"(cnt) : "memory"); }
__device__ __forceinline__ void mbar_expect(uint32_t m, uint32_t bytes) { asm volatile("mbarrier.arrive.expect_tx.shared::cta.b64 _, [%0], %1;" :: "r"(m), "r"(bytes) : "memory"); }
__device__ __forceinline__ bool mbar_try(uint32_t m) {
  uint32_t done;
  asm volatile("{.reg .pred p; mbarrier.try_wait.parity.shared::cta.b64 p, [%1], 0; selp.u32 %0, 1, 0, p;}" : "=r"(done) : "r"(m) : "memory");
  return done;
}
__device__ __forceinline__ void mbar_wait(uint32_t m) {
  if (!mbar_try(m)) {
    int it = 0;
    while (!mbar_try(m) && ++it < (1 << 22)) {}
  }
}
__device__ __forceinline__ bool elect() {
  uint32_t e;
  asm volatile("{.reg .pred p; elect.sync _|p, 0xffffffff; selp.u32 %0, 1, 0, p;}" : "=r"(e));
  return e;
}
__device__ __forceinline__ void tma_load4(uint32_t dst, const CUtensorMap* tm, int c0, int c1, int c2, int c3, uint32_t mbar) {
  asm volatile("cp.async.bulk.tensor.4d.shared::cluster.global.mbarrier::complete_tx::bytes [%0], [%1, {%3, %4, %5, %6}], [%2];"
               :: "r"(dst), "l"(tm), "r"(mbar), "r"(c0), "r"(c1), "r"(c2), "r"(c3) : "memory");
}
__device__ __forceinline__ void tma_load3(uint32_t dst, const CUtensorMap* tm, int c0, int c1, int c2, uint32_t mbar) {
  asm volatile("cp.async.bulk.tensor.3d.shared::cluster.global.mbarrier::complete_tx::bytes [%0], [%1, {%3, %4, %5}], [%2];"
               :: "r"(dst), "l"(tm), "r"(mbar), "r"(c0), "r"(c1), "r"(c2) : "memory");
}
__device__ __forceinline__ void tma_store3(const CUtensorMap* tm, int c0, int c1, int c2, uint32_t src) {
  asm volatile("cp.async.bulk.tensor.3d.global.shared::cta.bulk_group [%0, {%2, %3, %4}], [%1];"
               :: "l"(tm), "r"(src), "r"(c0), "r"(c1), "r"(c2) : "memory");
}
__device__ __forceinline__ void wg_fence() { asm volatile("wgmma.fence.sync.aligned;" ::: "memory"); }
__device__ __forceinline__ void wg_commit() { asm volatile("wgmma.commit_group.sync.aligned;" ::: "memory"); }
template <int N> __device__ __forceinline__ void wg_wait() { asm volatile("wgmma.wait_group.sync.aligned %0;" :: "n"(N) : "memory"); }
template <int N> __device__ __forceinline__ void tie_all(uint32_t (&x)[N]) {
#pragma unroll
  for (int i = 0; i < N; i++) asm volatile("" : "+r"(x[i]) :: "memory");
}
template <int N> __device__ __forceinline__ void tie_all(float (&x)[N]) {
#pragma unroll
  for (int i = 0; i < N; i++) asm volatile("" : "+f"(x[i]) :: "memory");
}
#define R16(C, d) C(d[0]), C(d[1]), C(d[2]), C(d[3]), C(d[4]), C(d[5]), C(d[6]), C(d[7]), C(d[8]), C(d[9]), C(d[10]), C(d[11]), C(d[12]), C(d[13]), C(d[14]), C(d[15])
#define R32(C, d) R16(C, d), R16(C, (d + 16))
#define P16 "{%0,%1,%2,%3,%4,%5,%6,%7,%8,%9,%10,%11,%12,%13,%14,%15}"
#define P32 "{%0,%1,%2,%3,%4,%5,%6,%7,%8,%9,%10,%11,%12,%13,%14,%15,%16,%17,%18,%19,%20,%21,%22,%23,%24,%25,%26,%27,%28,%29,%30,%31}"
template <int SD, int TB, int OFF> __device__ __forceinline__ void rs64(float* d, const uint32_t* a, uint64_t db) {
  if (SD) asm volatile("{.reg .b64 db; add.s64 db, %36, %37; wgmma.mma_async.sync.aligned.m64n64k16.f32.bf16.bf16 " P32 ", {%32,%33,%34,%35}, db, 1, 1, 1, %38;}"
                       : R32("+f", d) : "r"(a[0]), "r"(a[1]), "r"(a[2]), "r"(a[3]), "l"(db), "n"(OFF), "n"(TB));
  else asm volatile("{.reg .b64 db; add.s64 db, %36, %37; wgmma.mma_async.sync.aligned.m64n64k16.f32.bf16.bf16 " P32 ", {%32,%33,%34,%35}, db, 0, 1, 1, %38;}"
                    : R32("=f", d) : "r"(a[0]), "r"(a[1]), "r"(a[2]), "r"(a[3]), "l"(db), "n"(OFF), "n"(TB));
}
template <int SD, int TB, int OFF> __device__ __forceinline__ void rs64h(uint32_t* d, const uint32_t* a, uint64_t db) {
  if (SD) asm volatile("{.reg .b64 db; add.s64 db, %20, %21; wgmma.mma_async.sync.aligned.m64n64k16.f16.f16.f16 " P16 ", {%16,%17,%18,%19}, db, 1, 1, 1, %22;}"
                       : R16("+r", d) : "r"(a[0]), "r"(a[1]), "r"(a[2]), "r"(a[3]), "l"(db), "n"(OFF), "n"(TB));
  else asm volatile("{.reg .b64 db; add.s64 db, %20, %21; wgmma.mma_async.sync.aligned.m64n64k16.f16.f16.f16 " P16 ", {%16,%17,%18,%19}, db, 0, 1, 1, %22;}"
                    : R16("=r", d) : "r"(a[0]), "r"(a[1]), "r"(a[2]), "r"(a[3]), "l"(db), "n"(OFF), "n"(TB));
}
template <int SD, int OFFA, int OFFB> __device__ __forceinline__ void ss32(float* d, uint64_t da, uint64_t db) {
  if (SD) asm volatile("{.reg .b64 da, db; add.s64 da, %16, %18; add.s64 db, %17, %19; wgmma.mma_async.sync.aligned.m64n32k16.f32.f16.f16 " P16 ", da, db, 1, 1, 1, 1, 1;}"
                       : R16("+f", d) : "l"(da), "l"(db), "n"(OFFA), "n"(OFFB));
  else asm volatile("{.reg .b64 da, db; add.s64 da, %16, %18; add.s64 db, %17, %19; wgmma.mma_async.sync.aligned.m64n32k16.f32.f16.f16 " P16 ", da, db, 0, 1, 1, 1, 1;}"
                    : R16("=f", d) : "l"(da), "l"(db), "n"(OFFA), "n"(OFFB));
}
#define KGEN_ASM(SD) "{.reg .b64 da, db; add.s64 da, %32, %33; add.s64 db, %32, %34;\n" \
  "wgmma.mma_async.sync.aligned.m64n64k16.f32.bf16.bf16 " P32 ", da, db, " SD ", 1, 1, 1, 1;}"
template <int KS> __device__ __forceinline__ void kgen_mma(float (&c)[32], uint64_t da) {
  if (KS) asm volatile(KGEN_ASM("1") : R32("+f", c) : "l"(da), "n"(8 * KS), "n"(8 * KS + 512));
  else asm volatile(KGEN_ASM("0") : R32("=f", c) : "l"(da), "n"(8 * KS), "n"(8 * KS + 512));
  if constexpr (KS < 7) kgen_mma<KS + 1>(c, da);
}
__device__ __forceinline__ uint64_t desc_lo(uint32_t a) { return (uint64_t)((a & 0x3FFFF) >> 4); }
__device__ __forceinline__ void stage1(float (&D)[32], const uint32_t (&A1)[8], uint32_t src) {
  const uint64_t du = desc_lo(src) | (128ull << 16) | (32ull << 32) | (2ull << 62);
  rs64<0, 1, 0>(D, A1, du); rs64<1, 1, 64>(D, A1 + 4, du);
}
template <int INV> __device__ __forceinline__ void stage2(uint32_t (&X)[16], const uint32_t (&F)[16], uint32_t cf) {
  constexpr int KS = INV ? 16 : 128, TB = INV ? 0 : 1;
  const uint64_t dc = desc_lo(cf) | (INV ? (8ull << 16) | (64ull << 32) : (64ull << 16) | (8ull << 32));
  rs64h<0, TB, 0>(X, F, dc); rs64h<1, TB, KS>(X, F + 4, dc); rs64h<1, TB, 2 * KS>(X, F + 8, dc); rs64h<1, TB, 3 * KS>(X, F + 12, dc);
}
__device__ __forceinline__ void fwd_mid(uint32_t (&F)[16], const float (&D)[32], const uint32_t (&tc)[4], const uint32_t (&ts)[4]) {
#pragma unroll
  for (int j = 0; j < 4; j++)
#pragma unroll
    for (int b = 0; b < 2; b++) {
      const int i = 4 * j + 16 * b;
      const uint32_t ar = packh(D[i], D[i + 1]), ai = packh(D[i + 2], D[i + 3]);
      F[2 * j + b] = ffma(ar, tc[j], fmul(ai, ts[j]));
      F[8 + 2 * j + b] = ffma(ai, tc[j], fneg(fmul(ar, ts[j])));
    }
}
__device__ __forceinline__ void put_exp(uint32_t a, uint32_t m, int lane) {
  m = __reduce_max_sync(0xffffffffu, max(m & 0x7f80u, (m >> 16) & 0x7f80u));
  if (lane == 0) sts32(a, m);
}
__device__ __forceinline__ uint32_t seq_mag(uint32_t a) {
  const uint4 x = lds128(a), y = lds128(a + 2048);
  return amax2(amax2(amax2(x.x, x.y), amax2(x.z, x.w)), amax2(amax2(y.x, y.y), amax2(y.z, y.w)));
}
__device__ __forceinline__ uint32_t get_exp(uint32_t a) { const uint4 v = lds128(a); return max(max(v.x, v.y), max(v.z, v.w)) >> 7; }
__device__ __forceinline__ void scale_a1(uint32_t (&As)[8], const uint32_t (&A1)[8], uint32_t field) {
#pragma unroll
  for (int i = 0; i < 8; i++) As[i] = hmul2(A1[i], field * 0x00800080u);
}

struct cf { float x, y; };
__device__ __forceinline__ cf cmul(cf a, cf b) { cf r; r.x = fmaf(a.x, b.x, -a.y * b.y); r.y = fmaf(a.x, b.y, a.y * b.x); return r; }
__device__ __forceinline__ cf cexp_p(float lr2, float lt, float p) {
  float m;
  asm("ex2.approx.ftz.f32 %0, %1;" : "=f"(m) : "f"(lr2 * p));
  float t = lt * p;
  t = (t - rintf(t)) * 6.283185307179586f;
  cf r; r.x = m * __cosf(t); r.y = m * __sinf(t); return r;
}
__device__ __forceinline__ void store8(uint32_t a, uint32_t b, const cf (&v)[8]) {
  sts128(a, pack(v[0].x, v[1].x), pack(v[2].x, v[3].x), pack(v[4].x, v[5].x), pack(v[6].x, v[7].x));
  sts128(b, pack(v[0].y, v[1].y), pack(v[2].y, v[3].y), pack(v[4].y, v[5].y), pack(v[6].y, v[7].y));
}
__device__ __forceinline__ void mbar_arrive(uint32_t m) { asm volatile("mbarrier.arrive.shared::cta.b64 _, [%0];" :: "r"(m) : "memory"); }
__device__ __forceinline__ float sigmoidf_(float s) { return __frcp_rn(1.f + __expf(-s)); }

__global__ void __cluster_dims__(CS, 1, 1) __launch_bounds__(NTHREADS, 1) fused_kernel(const __grid_constant__ Params p) {
  extern __shared__ __align__(1024) uint8_t smem[];
  TL_INIT();
  TL(31);
  const int wid = __shfl_sync(0xffffffffu, threadIdx.x >> 5, 0);
  const uint32_t sb = (uint32_t)__cvta_generic_to_shared(smem);
  const uint32_t mb = sb + OFF_MB;
  const int u = wid >> 2, w = wid & 3;
  const int tid = threadIdx.x & 127, lane = tid & 31, g = lane >> 2, t = lane & 3;
  const int cl = blockIdx.x >> 3, rank = blockIdx.x & 7;
  const int ch0 = cl * CPC;
  const int nu = min(5, (DCH - ch0) >> 3);
  const bool act = u < nu;

  if (u == 4 && elect()) {
#pragma unroll
    for (int i = 0; i < 5; i++) mbar_init(mb + 40 * w + 8 * i, w == 3 ? 1 : w == 2 ? 3 : 2);
    if (w == 3) {
      mbar_init(mb + 8 * MB_XQ, 2); mbar_init(mb + 8 * MB_KV, 1); mbar_init(mb + 8 * MB_CF, 1); mbar_init(mb + 8 * MB_Q2, 9);
    }
    fence_mbinit();
    if (w == 3) {
      mbar_expect(mb + 8 * MB_CF, 12288);
      asm volatile("cp.async.bulk.prefetch.L2.global [%0], 20480;" :: "l"(p.tab) : "memory");
      mbar_expect(mb + 8 * MB_XQ, 20480); mbar_expect(mb + 8 * MB_KV, 23040 + 20480); mbar_expect(mb + 8 * MB_Q2, 20480);
    }
#pragma unroll
    for (int i = 0; i < 5; i++) mbar_expect(mb + 40 * w + 8 * i, w == 3 ? 4096 : w == 2 ? 7168 : 3584);
  }
  __syncwarp();
  uint32_t pla, pai, pcr, pci, pdt, tag = 0;
  uint4 psm;
  {
    const int ch = act ? ch0 + 8 * u + rank : 0, o = ch * NMODE + tid;
    pla = ldraw(p.logA + o); pdt = ldraw(p.logdt + ch); pai = ldraw(p.Aim + o); pcr = ldraw(p.Cre + o); pci = ldraw(p.Cim + o);
    if (w == 1) {
      if (lane < 9) psm = ldg128(lane < 5 ? p.gate_w + (lane < nu ? ch0 + 8 * lane : 0) : p.shift_k + (act ? ch0 + 8 * u : 0) * 4 + 8 * (lane - 5));
      else { psm.x = ldraw(p.Dskip + ch); psm.y = ldraw(p.ssm_D + ch); }
    }
    if (wid == 16 && lane < 2) asm volatile("atom.relaxed.gpu.global.add.u32 %0, [%1], %2;" : "=r"(tag) : "l"(&p.cnt[rank * 32 + lane]), "r"(cl == 0 ? 16 - (NCL - 1) : 1) : "memory");
  }
  if (wid == 19) {
    if (elect()) tma_load4(sb + OFF_TQ, &p.tq, ch0, 0, 0, 8 * rank, mb + 8 * MB_XQ);
    bar_sync(NB_LD, 32);
    TL(20);
  }
  cluster_arrive();
  TL(0);

  const uint32_t tab = sb + OFF_T + u * KTAB;
  const int mi = lane >> 3, tq = (lane & 7) >> 1, jj = lane & 1;
  const uint32_t toff = (4 * (2 * mi + jj) + tq) * 80;
  const uint32_t uoff = 16 * (4 * w + (t ^ (w >> 1)));
  auto put = [&](int stage, int dst, uint32_t off, const uint32_t (&v)[4]) {
    sts128(sb + off + (g == rank ? dst + 512 * rank : stage + g * YPITCH), v[0], v[1], v[2], v[3]);
  };
  const int d0 = rank ^ (2 * w), d1 = d0 ^ 1;
  const uint32_t rb0 = mapa(sb, d0), rb1 = mapa(sb, d1);
  auto send = [&](int stage, int pitch, int dst, int mbar) {
    if (elect()) {
      if (w) bulk_dsmem(rb0 + dst, sb + stage + d0 * pitch, rb0 + mbar); else mbar_arrive(sb + mbar);
      bulk_dsmem(rb1 + dst, sb + stage + d1 * pitch, rb1 + mbar);
    }
    __syncwarp();
  };

  if (w == 1 && lane < 10) sts128(sb + OFF_SP + 160 * u + 16 * lane, psm.x, psm.y, psm.z, psm.w);
  uint32_t A1[8], tc[4], ts[4];
  {
    const float dt = bf16r(expf(blo(pdt)));
    const float lr2 = (-bf16r(expf(blo(pla))) * dt) * 1.4426950408889634f;
    const float lt = (blo(pai) * dt) * 0.15915494309189535f;
    const uint32_t tim = sb + OFF_IM + (u < 2 ? 3 + u : u - 2) * KTAB;
    const uint32_t row = tab + tid * 16, rim = tim + tid * 16;
    const cf w1 = cexp_p(lr2, lt, 8.f);
    cf z1 = cexp_p(lr2, lt, 1.f), Z = cexp_p(lr2, lt, 256.f);
    if (lr2 != 123.f) TL(16);
    if (wid == 16 && lane == 0) { sts32(mb + 8 * MB_TAG, tag); mbar_arrive(mb + 8 * MB_XQ); }
    TL(12);
    {
      cf v[8];
      v[0].x = 1.f; v[0].y = 0.f; v[1] = w1; v[2] = cmul(w1, w1); v[3] = cmul(v[2], w1);
      const cf w4 = cmul(v[2], v[2]);
      v[4] = w4; v[5] = cmul(v[1], w4); v[6] = cmul(v[2], w4); v[7] = cmul(v[3], w4);
      const cf w8 = cmul(w4, w4);
      store8(row, rim, v);
#pragma unroll
      for (int k = 1; k < 4; k++) {
#pragma unroll
        for (int i = 0; i < 8; i++) v[i] = (k == 1 && i == 0) ? w8 : cmul(v[i], w8);
        store8(row + 2048 * k, rim + 2048 * k, v);
      }
    }
    if (u == 4) {
      if (w == 0) bar_sync(NB_K0, 32);
      float z0_ = 0.f, z1_ = 0.f, z2_ = 0.f, z3_ = 0.f;
      asm volatile("mma.sync.aligned.m16n8k8.row.col.f32.bf16.bf16.f32 {%0,%1,%2,%3}, {%4,%4}, {%4}, {%0,%1,%2,%3};"
                   : "+f"(z0_), "+f"(z1_), "+f"(z2_), "+f"(z3_) : "r"(pla >> 16));
      pcr += __float_as_uint(z0_);
      if (w == 0 && elect()) {
        const uint32_t o = blockIdx.x * 9856u, n = min(9856u, SEQ * DCH - o) * 2;
        asm volatile("cp.async.bulk.prefetch.L2.global [%0], %1;" :: "l"(p.ssm_k + o), "r"(n) : "memory");
        asm volatile("cp.async.bulk.prefetch.L2.global [%0], %1;" :: "l"(p.k + o), "r"(n) : "memory");
        asm volatile("cp.async.bulk.prefetch.L2.global [%0], %1;" :: "l"(p.v + o), "r"(n) : "memory");
      }
      __syncwarp();
      TL(8);
    }
    {
      z1.y = -z1.y; Z.y = -Z.y;
      const cf z2 = cmul(z1, z1);
      cf h[8], v[8];
      h[0].x = 2.f * blo(pcr) * dt; h[0].y = -2.f * blo(pci) * dt;
      h[1] = cmul(h[0], z1);
#pragma unroll
      for (int i = 2; i < 8; i++) h[i] = cmul(h[i - 2], z2);
      store8(row + 4 * 2048, rim + 4 * 2048, h);
      const cf h8 = cmul(h[6], z2);
      v[0] = cmul(h[0], Z); v[2] = cmul(h[2], Z); v[3] = cmul(h[4], Z); v[6] = cmul(h[6], Z); v[7] = cmul(h8, Z);
      v[1] = v[0]; v[4] = v[5] = v[3];
      store8(row + 5 * 2048, rim + 5 * 2048, v);
      h[0] = cmul(v[0], Z); h[1] = cmul(v[3], Z); h[3] = cmul(v[7], Z); h[4] = cmul(h[0], Z); h[5] = cmul(h[1], Z); h[7] = cmul(h[3], Z);
      h[2] = h[1]; h[6] = h[5];
      store8(row + 6 * 2048, rim + 6 * 2048, h);
      const cf Z2 = cmul(Z, Z);
      v[0] = cmul(h[0], Z2); v[1] = cmul(h[3], Z2); v[2] = cmul(h[4], Z2); v[3] = cmul(h[7], Z2);
#pragma unroll
      for (int i = 4; i < 8; i++) v[i] = cmul(v[i - 4], Z2);
      store8(row + 7 * 2048, rim + 7 * 2048, v);
    }
    TL(17);
    cluster_wait();
    mbar_wait(mb + 8 * MB_XQ);
    TL(18);
    {
      uint32_t x0[4], x1[4];
      ldsm4t(x0, sb + OFF_TQ + w * 2560 + toff + 16 * u);
      ldsm4t(x1, sb + OFF_TQ + (w + 4) * 2560 + toff + 16 * u);
      put(OFF_YB + 8 * u * YPITCH, OFF_UX + u * 4096, uoff, x0);
      put(OFF_YB + 8 * u * YPITCH, OFF_UX + u * 4096, (uoff ^ 32) + 256, x1);
    }
    TL(3);
    fence_async();
    bar_sync(NB_WG0 + u, 128);
    TL(4);
    if (u >= 3) {
      float s0 = 0.f;
#pragma unroll
      for (int j = 0; j < 5; j++) {
        const uint4 gw = lds128(sb + OFF_SP + 160 * u + 16 * j), x = lds128(sb + OFF_TQ + (tid + 128 * (u - 3)) * 80 + 16 * j);
        const uint32_t m0 = hmul2(x.x, gw.x), m1 = hmul2(x.y, gw.y), m2 = hmul2(x.z, gw.z), m3 = hmul2(x.w, gw.w);
        s0 += ((blo(m0) + bhi(m0)) + (blo(m1) + bhi(m1))) + ((blo(m2) + bhi(m2)) + (blo(m3) + bhi(m3)));
      }
      tag = (lds64(mb + 8 * MB_TAG).x >> 4) + 1;
      asm volatile("st.relaxed.gpu.global.u64 [%0], %1;" :: "l"(p.part + cl * SEQ + rank * 256 + 8 * (8 * t + g) + w + 4 * (u - 3)),
                   "l"(((uint64_t)tag << 32) | __float_as_uint(s0)) : "memory");
    }
    TL(7);
    if (u) bar_sync(NB_ORD + u - 1, 256);
    TL(13);
    float c[32];
    wg_fence();
    kgen_mma<0>(c, desc_lo(tab) | ((uint64_t)((tim - tab) >> 4) << 16) | (64ull << 32));
    wg_commit();
    if (u < 4) bar_arrive(NB_ORD + u, 256);
    const __nv_bfloat16* hp = p.ssm_k + (size_t)(act ? ch0 + 8 * u + rank : 0) * SEQ + 8 * tid;
    const uint4 hm0 = ldg128(hp), hm1 = ldg128(hp + 1024);
    {
      const uint4 x = ldg128(p.tab->thr[0][tid]), y = ldg128(p.tab->thr[1][tid]), a = ldg128(p.tab->thr[2][tid]), b = ldg128(p.tab->thr[3][tid]);
      A1[0] = x.x; A1[1] = x.y; A1[2] = x.z; A1[3] = x.w; A1[4] = y.x; A1[5] = y.y; A1[6] = y.z; A1[7] = y.w;
      tc[0] = a.x; tc[1] = a.y; tc[2] = a.z; tc[3] = a.w; ts[0] = b.x; ts[1] = b.y; ts[2] = b.z; ts[3] = b.w;
    }
    send(OFF_YB + 8 * u * YPITCH, YPITCH, OFF_UX + u * 4096 + 512 * rank, OFF_MB + 8 * (MB_UX + u));
    TL(14);
    wg_wait<0>(); tie_all(c);
    TL(26);
    cluster_arrive();
    if (wid == 17) {
      bar_sync(NB_LD, 640);
      if (elect()) {
        tma_load4(sb + OFF_TK, &p.tk, ch0, 0, 0, 8 * rank - 1, mb + 8 * MB_KV);
        tma_load4(sb + OFF_TV, &p.tv, ch0, 0, 0, 8 * rank, mb + 8 * MB_KV);
      }
      __syncwarp();
    } else {
      bar_arrive(NB_LD, 640);
    }
    bar_sync(NB_WG0 + u, 128);
    if (wid == 1 && elect())
      asm volatile("cp.async.bulk.shared::cluster.global.mbarrier::complete_tx::bytes [%0], [%1], %2, [%3];"
                   :: "r"(sb + OFF_CF), "l"(p.tab->mat), "r"(12288), "r"(mb + 8 * MB_CF) : "memory");
    __syncwarp();
    const uint32_t k0 = pack(c[0] + c[6], c[1] + c[7]), k1 = pack(c[8] + c[14], c[9] + c[15]);
    const uint32_t k2 = pack(c[16] + c[22], c[17] + c[23]), k3 = pack(c[24] + c[30], c[25] + c[31]);
    const uint32_t ka = tab + 16 * (8 * w + (g ^ w));
    sts32(ka + 4 * t, k0);
    sts32(ka + 512 + 4 * t, k1);
    sts64(ka + 1024 + 512 * (t >> 1) + 8 * (t & 1), prmt(k2, 0, 0x1010), (t & 1) ? prmt(k2, 0, 0x3232) : k2);
    const uint32_t lo = prmt(k3, 0, 0x1010), hi = prmt(k3, 0, 0x3232);
    sts128(ka + 2048 + 512 * t, lo, lo, (g & 1) ? hi : k3, hi);
    put_exp(sb + OFF_MX + u * 64 + 4 * w, amax2(amax2(k0, k1), amax2(k2, k3)), lane);
    put_exp(sb + OFF_MX + u * 64 + 32 + 4 * w, amax2(amax2(amax2(hm0.x, hm0.y), amax2(hm0.z, hm0.w)), amax2(amax2(hm1.x, hm1.y), amax2(hm1.z, hm1.w))), lane);
    TL(15);
    fence_async();
    bar_sync(NB_WG0 + u, 128);
  }

#pragma unroll
  for (int isA = 0; isA < 2; isA++) {
    {
      TL(1 + isA);
      const uint32_t usrc = isA ? tab + T_UKV : sb + OFF_UX + u * 4096;
      const uint32_t mxa = sb + OFF_MX + u * 64 + 32 * isA;
      const uint32_t pd = lds16(sb + OFF_SP + 160 * u + 144 + 4 * isA);
      float D[32];
      uint32_t As[8], F[16], H[16], X[16];
      const uint32_t eh = min(max((int)get_exp(mxa), (int)((pd >> 7) & 0xff) - 5), 240);
      scale_a1(As, A1, 248 - eh);
      if (isA) mbar_wait(mb + 8 * (MB_HA + u));
      wg_fence();
      stage1(D, As, isA ? tab + T_HA : tab);
      wg_commit();
      wg_wait<0>(); tie_all(D);
      fwd_mid(F, D, tc, ts);
      if (!isA) mbar_wait(mb + 8 * MB_CF);
      wg_fence();
      stage2<0>(H, F, sb + OFF_CF);
      wg_commit();
      mbar_wait(mb + 8 * ((isA ? MB_UKV : MB_UX) + u));
      TL(5 + isA);
      put_exp(mxa + 16 + 4 * w, seq_mag(usrc + 16 * tid), lane);
      bar_sync(NB_WG0 + u, 128);
      const uint32_t eu = min(get_exp(mxa + 16), 240u);
      scale_a1(As, A1, 250 - eu);
      wg_wait<0>(); tie_all(H);
      wg_fence();
      stage1(D, As, usrc);
      wg_commit();
      wg_wait<0>(); tie_all(D);
      fwd_mid(F, D, tc, ts);
      wg_fence();
      stage2<0>(X, F, sb + OFF_CF);
      wg_commit();
      if (!isA && w == 1 && elect()) {
        tma_load4(tab + T_HA, &p.th, 0, 0, 5 * cl + u, rank, mb + 8 * (MB_HA + u));
        if (u == 4) tma_load3(sb + OFF_Q2, &p.tq2, ch0, 8 * rank, 0, mb + 8 * MB_Q2);
      }
      __syncwarp();
      {
        const float dsk = blo(pd) * __uint_as_float((248 - eh) << 23);
        const uint32_t d2 = packh(dsk, dsk);
#pragma unroll
        for (int j = 0; j < 4; j++) H[2 * j] = U2(__hadd2(H2(H[2 * j]), H2(d2)));
      }
      wg_wait<0>(); tie_all(X);
#pragma unroll
      for (int j = 0; j < 4; j++) {
        const uint32_t h0r = H[2 * j], h1r = H[2 * j + 1], h0i = H[8 + 2 * j], h1i = H[9 + 2 * j];
        const uint32_t x0r = X[2 * j], x1r = X[2 * j + 1], x0i = X[8 + 2 * j], x1i = X[9 + 2 * j];
        F[2 * j] = ffma(x0r, h0r, fneg(fmul(x0i, h0i)));
        F[8 + 2 * j] = ffma(x0r, h0i, fmul(x0i, h0r));
        F[2 * j + 1] = ffma(x1r, h0r, ffma(fneg(x1i), h0i, ffma(x0r, h1r, fneg(ffma(x0i, h1i, F[8 + 2 * j])))));
        F[9 + 2 * j] = ffma(x1r, h0i, ffma(x1i, h0r, ffma(x0r, h1i, ffma(x0i, h1r, F[2 * j]))));
      }
      wg_fence();
      stage2<1>(H, F, sb + OFF_CF);
      wg_commit();
      wg_wait<0>(); tie_all(H);
      {
        const uint32_t va = tab + (16 * w + (lane & 15)) * 128;
        const int vx = (lane >> 4) ^ (lane & 7);
#pragma unroll
        for (int j = 0; j < 4; j++) {
          uint32_t V[4];
#pragma unroll
          for (int b = 0; b < 2; b++) {
            const uint32_t er = H[2 * j + b], ei = H[8 + 2 * j + b];
            V[2 * b] = ffma(er, tc[j], fneg(fmul(ei, ts[j])));
            V[2 * b + 1] = ffma(ei, tc[j], fmul(er, ts[j]));
          }
          stsm4(va + ((vx ^ (2 * j)) << 4), V);
        }
      }
      uint64_t ga[NCL];
      const int slot = tid + 128 * (u & 1);
      const uint2* gp = p.part + rank * 256 + slot;
      auto gload = [&]() {
#pragma unroll
        for (int k = 0; k < NCL; k++) asm volatile("ld.relaxed.gpu.global.u64 %0, [%1];" : "=l"(ga[k]) : "l"(gp + k * SEQ) : "memory");
      };
      if (!isA) {
        cluster_wait();
        mbar_wait(mb + 8 * MB_KV);
        TL(21);
        const uint32_t hoff = (4 * (4 + 2 * (mi & 1) + jj) + ((tq + 3) & 3)) * 80 + (tq ? 2560 : 0) + 16 * u;
        uint32_t E[2][6], V[2][4];
        const uint2 psw = lds64(sb + OFF_SP + 160 * u + 80 + 8 * g);
#pragma unroll
        for (int hf = 0; hf < 2; hf++) {
          const int ah = 4 * hf + w;
          uint32_t K[4];
          ldsm4t(K, sb + OFF_TK + (ah + 1) * 2560 + toff + 16 * u);
          ldsm2t(E[hf][0], E[hf][1], sb + OFF_TK + ah * 2560 + hoff);
          ldsm4t(V[hf], sb + OFF_TV + ah * 2560 + toff + 16 * u);
          E[hf][2] = K[0]; E[hf][3] = K[1]; E[hf][4] = K[2]; E[hf][5] = K[3];
        }
        const uint32_t w0 = prmt(psw.x, 0, 0x1010), w1 = prmt(psw.x, 0, 0x3232), w2 = prmt(psw.y, 0, 0x1010), w3 = prmt(psw.y, 0, 0x3232);
        uint32_t o[2][4];
#pragma unroll
        for (int hf = 0; hf < 2; hf++) {
          uint32_t O[5];
#pragma unroll
          for (int i = 0; i < 5; i++) O[i] = prmt(E[hf][i], E[hf][i + 1], 0x5432);
#pragma unroll
          for (int i = 0; i < 4; i++) {
            o[hf][i] = hmul2(hfma2(E[hf][i + 2], w0, hfma2(O[i + 1], w1, hfma2(E[hf][i + 1], w2, hmul2(O[i], w3)))), V[hf][i]);
          }
          put(OFF_YA + 8 * u * YPITCH, OFF_T + u * KTAB + T_UKV, hf ? (uoff ^ 32) + 256 : uoff, o[hf]);
        }
        TL(22);
      }
      fence_async();
      bar_sync(NB_WG0 + u, 128);
      float O[16];
      {
        const uint64_t dv = desc_lo(tab) | (1ull << 16) | (64ull << 32) | (1ull << 62);
        const uint64_t dl = desc_lo(sb + OFF_CL) | (32ull << 16) | (8ull << 32);
        wg_fence();
        ss32<0, 0, 0>(O, dv, dl); ss32<1, 128, 64>(O, dv, dl); ss32<1, 256, 128>(O, dv, dl); ss32<1, 384, 192>(O, dv, dl);
        wg_commit();
      }
      if (!isA) {
        send(OFF_YA + 8 * u * YPITCH, YPITCH, OFF_T + u * KTAB + T_UKV + 512 * rank, OFF_MB + 8 * (MB_UKV + u));
        if (u < 2) gload();
      }
      wg_wait<0>(); tie_all(O);
      {
        const uint32_t co = ((8 * w + g) ^ (2 * t)) * 16;
        const int yo = (isA ? OFF_YA : OFF_YB) + (8 * u + rank) * YPITCH, ym = OFF_MB + 8 * (MB_Y + u);
        const uint32_t us = min(max((int)(eu + eh) - 127, 0), 254) * 0x00800080u;
        const uint32_t a0 = hmul2(pack(O[0], O[1]), us), a1 = hmul2(pack(O[4], O[5]), us), a2 = hmul2(pack(O[8], O[9]), us), a3 = hmul2(pack(O[12], O[13]), us);
        const uint32_t b0 = hmul2(pack(O[2], O[3]), us), b1 = hmul2(pack(O[6], O[7]), us), b2 = hmul2(pack(O[10], O[11]), us), b3 = hmul2(pack(O[14], O[15]), us);
        sts128((t == rank ? sb + yo : usrc + t * 512) + co, a0, a1, a2, a3);
        sts128((t + 4 == rank ? sb + yo : usrc + t * 512 + 2048) + co, b0, b1, b2, b3);
        fence_async();
        bar_sync(NB_WG0 + u, 128);
        send(usrc - sb, 512, yo, ym);
      }
      TL(9 + isA);
      if (!isA && u < 2) {
        tag = (lds64(mb + 8 * MB_TAG).x >> 4) + 1;
        float s;
        bool ok;
#pragma unroll 1
        for (int it = 0;; it++) {
          ok = true; s = 0.f;
#pragma unroll
          for (int k = 0; k < NCL; k++) { ok = ok && (uint32_t)(ga[k] >> 32) == tag; s += __uint_as_float((uint32_t)ga[k]); }
          if (ok || it == 4000) break;
          gload();
        }
        if (!ok) {
          const uint32_t* xr = (const uint32_t*)(p.q + (size_t)(rank * 256 + 32 * (slot & 7) + (slot >> 3)) * DCH);
          const uint32_t* gr = (const uint32_t*)p.gate_w;
          s = 0.f;
    #pragma unroll 1
          for (int k = 0; k < DCH / 2; k++) { const uint32_t m = hmul2(__ldg(xr + k), __ldg(gr + k)); s += blo(m) + bhi(m); }
        }
        const float g0 = bf16r(sigmoidf_(bf16r(s)));
        sts64(sb + OFF_GB + 8 * slot, pack(g0, g0), pack(1.f - g0, 1.f - g0));
        __syncwarp();
        if (lane == 0) mbar_arrive(mb + 8 * MB_Q2);
      }
    }
  }

  {
    mbar_wait(mb + 8 * MB_Q2);
    uint2 gg[2][4];
    uint32_t qv[2][4];
#pragma unroll
    for (int hh = 0; hh < 2; hh++)
#pragma unroll
      for (int i = 0; i < 4; i++) gg[hh][i] = lds64(sb + OFF_GB + 8 * (64 * w + 32 * hh + 8 * i + g));
    const uint32_t qa = sb + OFF_Q2 + (64 * w + lane) * 80 + 16 * u;
    ldsm4(qv[0], qa);
    ldsm4(qv[1], qa + 2560);
    TL(24);
    mbar_wait(mb + 8 * (MB_Y + u));
    uint32_t ya[2][4], yb[2][4];
#pragma unroll
    for (int hh = 0; hh < 2; hh++) {
      const uint32_t yo = (8 * u + (lane & 7)) * YPITCH + ((8 * w + 4 * hh + (lane >> 3)) ^ (2 * (rank & 3))) * 16;
      ldsm4t(ya[hh], sb + OFF_YA + yo); ldsm4t(yb[hh], sb + OFF_YB + yo);
    }
#pragma unroll
    for (int hh = 0; hh < 2; hh++) {
      uint32_t o[4];
#pragma unroll
      for (int i = 0; i < 4; i++) o[i] = hadd2(hmul2(gg[hh][i].x, hmul2(qv[hh][i], ya[hh][i])), hmul2(gg[hh][i].y, yb[hh][i]));
      stsm4(qa + 2560 * hh, o);
    }
    TL(25);
  }
  cluster_arrive();
  bar_sync(NB_ROW0 + w, 160);
  {
    uint4 v[2];
#pragma unroll
    for (int k = 0; k < 2; k++) {
      const int i = 64 * u + 32 * k + lane, sl = (i * 205) >> 10, cc = i - 5 * sl;
      v[k] = lds128(sb + OFF_Q2 + (64 * w + 8 * (sl & 7) + (sl >> 3)) * 80 + cc * 16);
    }
#pragma unroll
    for (int k = 0; k < 2; k++) {
      const int i = 64 * u + 32 * k + lane, sl = (i * 205) >> 10, cc = i - 5 * sl;
      if (cc < nu)
        asm volatile("st.global.v4.u32 [%0], {%1,%2,%3,%4};" :: "l"(p.out + (size_t)(256 * rank + 32 * (sl >> 3) + 8 * w + (sl & 7)) * DCH + ch0 + 8 * cc),
                     "r"(v[k].x), "r"(v[k].y), "r"(v[k].z), "r"(v[k].w) : "memory");
    }
  }
  cluster_wait();
  TL(27);
  TL_DUMP();
}

typedef CUresult (*EncodeFn)(CUtensorMap*, CUtensorMapDataType, cuuint32_t, void*, const cuuint64_t*, const cuuint64_t*,
                             const cuuint32_t*, const cuuint32_t*, CUtensorMapInterleave, CUtensorMapSwizzle,
                             CUtensorMapL2promotion, CUtensorMapFloatOOBfill);

void encode(EncodeFn fn, CUtensorMap* tm, const void* ptr, int nd, const cuuint64_t* dims, const cuuint64_t* strides,
            const cuuint32_t* box, CUtensorMapSwizzle swz) {
  cuuint32_t es[4] = {1, 1, 1, 1};
  fn(tm, CU_TENSOR_MAP_DATA_TYPE_BFLOAT16, nd, const_cast<void*>(ptr), dims, strides, box, es, CU_TENSOR_MAP_INTERLEAVE_NONE,
     swz, CU_TENSOR_MAP_L2_PROMOTION_L2_128B, CU_TENSOR_MAP_FLOAT_OOB_FILL_NONE);
}
void map1(EncodeFn fn, CUtensorMap* tm, const void* ptr, int nhi) {
  const cuuint64_t dims[4] = {DCH, 4, 8, SEQ / 32}, strides[3] = {8 * DCH * 2, DCH * 2, 32 * DCH * 2};
  const cuuint32_t box[4] = {CPC, 4, 8, (cuuint32_t)nhi};
  encode(fn, tm, ptr, 4, dims, strides, box, CU_TENSOR_MAP_SWIZZLE_NONE);
}
void map2(EncodeFn fn, CUtensorMap* tm, const void* ptr, int nr) {
  const cuuint64_t dims[3] = {DCH, SEQ / 32, 32}, strides[2] = {32 * DCH * 2, DCH * 2};
  const cuuint32_t box[3] = {CPC, 8, (cuuint32_t)nr};
  encode(fn, tm, ptr, 3, dims, strides, box, CU_TENSOR_MAP_SWIZZLE_NONE);
}

}

extern "C" void kernel_launch(void* const* d_in, const int* in_sizes, int n_in, void* d_out, int out_size) {
  (void)in_sizes; (void)n_in; (void)out_size;
  static EncodeFn fn = nullptr;
  static void *tab = nullptr, *cnt = nullptr, *part = nullptr;
  if (!fn) {
    cudaGetSymbolAddress(&tab, d_tab);
    cudaGetSymbolAddress(&cnt, g_cnt);
    cudaGetSymbolAddress(&part, g_part);
    cudaDriverEntryPointQueryResult qr;
    cudaGetDriverEntryPoint("cuTensorMapEncodeTiled", (void**)&fn, cudaEnableDefault, &qr);
    cudaFuncSetAttribute(fused_kernel, cudaFuncAttributeMaxDynamicSharedMemorySize, SMEM_BYTES);
  }
  Params p;
  map1(fn, &p.tq, d_in[0], 8);
  map1(fn, &p.tk, d_in[1], 9);
  map1(fn, &p.tv, d_in[2], 8);
  map2(fn, &p.tq2, d_in[0], 32);
  p.out = (__nv_bfloat16*)d_out;
  {
    const cuuint64_t dims[4] = {32, SEQ / 32, DCH / 8, 8}, strides[3] = {64, 8 * SEQ * 2, SEQ * 2};
    const cuuint32_t box[4] = {32, 64, 1, 1};
    encode(fn, &p.th, d_in[4], 4, dims, strides, box, CU_TENSOR_MAP_SWIZZLE_64B);
  }
  p.tab = (const Tables*)tab;
  p.cnt = (unsigned*)cnt;
  p.part = (uint2*)part;
  p.tl = nullptr;
  p.q = (const __nv_bfloat16*)d_in[0];
  p.k = (const __nv_bfloat16*)d_in[1];
  p.v = (const __nv_bfloat16*)d_in[2];
  p.ssm_k = (const __nv_bfloat16*)d_in[4];
  p.shift_k = (const __nv_bfloat16*)d_in[3];
  p.ssm_D = (const __nv_bfloat16*)d_in[5];
  p.logA = (const __nv_bfloat16*)d_in[7];
  p.Aim = (const __nv_bfloat16*)d_in[8];
  p.Cre = (const __nv_bfloat16*)d_in[9];
  p.Cim = (const __nv_bfloat16*)d_in[10];
  p.logdt = (const __nv_bfloat16*)d_in[11];
  p.Dskip = (const __nv_bfloat16*)d_in[12];
  p.gate_w = (const __nv_bfloat16*)d_in[13];
  fused_kernel<<<NCL * CS, NTHREADS, SMEM_BYTES, cudaStreamPerThread>>>(p);
}
```

```cpp
#include <cuda_runtime.h>
#include <cuda_bf16.h>
#include <cuda_fp16.h>
#include <cuda.h>
#include <stdint.h>

#define TIMELINE 0

namespace {

constexpr int SEQ = 2048, DCH = 576, NMODE = 128;
constexpr int CS = 8, CPC = 40, NCL = 15, NTHREADS = 640;

constexpr int YPITCH = 528;
constexpr int KTAB = 16384;
constexpr int OFF_T = 0;
constexpr int T_UKV = 8192, T_HA = 12288;
constexpr int OFF_UX = 5 * KTAB;
constexpr int OFF_IM = OFF_UX + 20480;
constexpr int OFF_Q2 = OFF_IM;
constexpr int OFF_GB = OFF_Q2 + 20480;
constexpr int OFF_TV = OFF_IM + 3 * KTAB - 20480;
constexpr int OFF_CF = OFF_IM + 3 * KTAB;
constexpr int OFF_CL = OFF_CF + 8192;
constexpr int OFF_TK = OFF_CL + 4096;
constexpr int OFF_TQ = OFF_TK + 23040;
constexpr int OFF_YA = OFF_TQ;
constexpr int OFF_YB = OFF_TQ + 21120;
constexpr int OFF_MX = OFF_YB + 40 * YPITCH;
constexpr int OFF_SP = OFF_MX + 320;
constexpr int OFF_MB = OFF_SP + 5 * 160;
constexpr int OFF_TL = OFF_MB + 32 * 8;
constexpr int SMEM_BYTES = OFF_TL + (TIMELINE ? 1280 : 0);
static_assert(SMEM_BYTES <= 232448 && OFF_IM + 5 * KTAB <= OFF_TQ, "smem");
static_assert((OFF_TQ & 127) == 0 && (OFF_TK & 127) == 0 && (OFF_TV & 127) == 0 && (OFF_MB & 7) == 0 && (OFF_MX & 15) == 0, "align");

enum { MB_UX = 0, MB_UKV = 5, MB_Y = 10, MB_HA = 15, MB_XQ = 20, MB_KV = 21, MB_CF = 22, MB_Q2 = 23, MB_TH = 24, MB_TAG = 25 };
enum { NB_WG0 = 1, NB_ROW0 = 6, NB_ORD = 6, NB_K0 = 10, NB_LD = 11 };

constexpr double cos_turn(int m, int n) {
  m &= n - 1;
  if (m > n / 2) m = n - m;
  double sgn = 1.0;
  if (m > n / 4) { m = n / 2 - m; sgn = -1.0; }
  if (m == n / 4) return 0.0;
  const double x = 6.283185307179586476925 * m / n;
  double term = 1.0, sum = 1.0;
  for (int k = 1; k < 14; k++) { term *= -x * x / ((2 * k - 1) * (2 * k)); sum += term; }
  return sgn * sum;
}
constexpr uint32_t bf16_bits(double v) {
  if (v == 0.0) return 0;
  uint32_t sgn = 0;
  if (v < 0) { sgn = 0x8000; v = -v; }
  int e = 127;
  while (v < 1.0) { v *= 2.0; e--; }
  while (v >= 2.0) { v *= 0.5; e++; }
  const double f = v * 128.0;
  int m = (int)f;
  if (f - m > 0.5 || (f - m == 0.5 && (m & 1))) m++;
  return sgn | (uint32_t)((e << 7) + (m - 128));
}
constexpr uint32_t f16_bits(double v) {
  if (v == 0.0) return 0;
  uint32_t sgn = 0;
  if (v < 0) { sgn = 0x8000; v = -v; }
  int e = 15;
  while (v < 1.0) { v *= 2.0; e--; }
  const double f = v * 1024.0;
  int m = (int)f;
  if (f - m > 0.5 || (f - m == 0.5 && (m & 1))) m++;
  return sgn | (uint32_t)((e << 10) + (m - 1024));
}
constexpr uint32_t pair_bits(double lo, double hi) { return bf16_bits(lo) | (bf16_bits(hi) << 16); }
constexpr uint32_t pair_h(double lo, double hi) { return f16_bits(lo) | (f16_bits(hi) << 16); }
struct alignas(128) Tables {
  uint32_t mat[3072];
  uint32_t thr[4][128][4];
};
constexpr Tables make_tables() {
  Tables T{};
  for (int q = 0; q < 768; q++) {
    int m0 = 0, d0 = 0, d1 = 0;
    if (q < 512) {
      const int r = (q >> 6) * 8 + (q & 7), cc = (q >> 3) & 7;
      d0 = 4 * (r & 31); d1 = 2 * d0;
      m0 = 8 * (cc & 3) * d0 + ((r >> 5) == (cc >> 2) ? 0 : (r >> 5) ? 96 : 32);
    } else {
      const int r = ((q - 512) >> 5) * 8 + (q & 7), pc = (q >> 3) & 3;
      d0 = 4 * (8 * (r >> 4) + (r & 7)) + 1; d1 = 8 * d0;
      m0 = 2 * pc * d0 + ((r & 8) ? 32 : 0);
    }
    for (int e = 0; e < 4; e++) T.mat[4 * q + e] = pair_h(cos_turn(m0 + e * d1, 128), cos_turn(m0 + e * d1 + d0, 128));
  }
  for (int tid = 0; tid < 128; tid++) {
    const int kk = 4 * (tid >> 2) + 1, t = tid & 3;
    for (int q = 0; q < 4; q++) {
      const int m = (8 * q + 2 * t) * kk;
      T.thr[q >> 1][tid][2 * (q & 1)] = pair_bits(cos_turn(m, 128), cos_turn(m + kk, 128));
      T.thr[q >> 1][tid][2 * (q & 1) + 1] = pair_bits(cos_turn(m + 32, 128), cos_turn(m + kk + 32, 128));
      T.thr[2][tid][q] = pair_h(cos_turn(m, 4096), cos_turn(m + kk, 4096));
      T.thr[3][tid][q] = pair_h(cos_turn(m + 3072, 4096), cos_turn(m + kk + 3072, 4096));
    }
  }
  return T;
}
__device__ const Tables d_tab = make_tables();

struct Params {
  const __nv_bfloat16 *logA, *Aim, *Cre, *Cim, *logdt;
  const Tables* tab;
  unsigned* cnt;
  const __nv_bfloat16 *Dskip, *shift_k, *ssm_D, *gate_w, *q, *k, *v, *ssm_k;
  uint2* part;
  __nv_bfloat16* out;
  unsigned* tl;
  CUtensorMap tq, tk, tv, th, tq2;
};

__device__ uint2 g_part[NCL * SEQ];
__device__ unsigned g_cnt[CS * 32];
#define TL(i) do {} while (0)
#define TL_INIT() do {} while (0)
#define TL_DUMP() do {} while (0)

__device__ __forceinline__ uint32_t lds16(uint32_t a) { uint32_t v; asm volatile("ld.shared.u16 %0, [%1];" : "=r"(v) : "r"(a) : "memory"); return v; }
__device__ __forceinline__ uint2 lds64(uint32_t a) { uint2 v; asm volatile("ld.shared.v2.u32 {%0,%1}, [%2];" : "=r"(v.x), "=r"(v.y) : "r"(a) : "memory"); return v; }
__device__ __forceinline__ uint4 lds128(uint32_t a) { uint4 v; asm volatile("ld.shared.v4.u32 {%0,%1,%2,%3}, [%4];" : "=r"(v.x), "=r"(v.y), "=r"(v.z), "=r"(v.w) : "r"(a) : "memory"); return v; }
__device__ __forceinline__ void sts16(uint32_t a, uint32_t v) { asm volatile("st.shared.u16 [%0], %1;" :: "r"(a), "r"(v) : "memory"); }
__device__ __forceinline__ void sts32(uint32_t a, uint32_t v) { asm volatile("st.shared.u32 [%0], %1;" :: "r"(a), "r"(v) : "memory"); }
__device__ __forceinline__ void sts64(uint32_t a, uint32_t x, uint32_t y) { asm volatile("st.shared.v2.u32 [%0], {%1,%2};" :: "r"(a), "r"(x), "r"(y) : "memory"); }
__device__ __forceinline__ void sts128(uint32_t a, uint32_t x, uint32_t y, uint32_t z, uint32_t w) { asm volatile("st.shared.v4.u32 [%0], {%1,%2,%3,%4};" :: "r"(a), "r"(x), "r"(y), "r"(z), "r"(w) : "memory"); }
__device__ __forceinline__ void ldsm4t(uint32_t (&r)[4], uint32_t a) { asm volatile("ldmatrix.sync.aligned.m8n8.x4.trans.shared.b16 {%0,%1,%2,%3}, [%4];" : "=r"(r[0]), "=r"(r[1]), "=r"(r[2]), "=r"(r[3]) : "r"(a) : "memory"); }
__device__ __forceinline__ void ldsm2t(uint32_t& r0, uint32_t& r1, uint32_t a) { asm volatile("ldmatrix.sync.aligned.m8n8.x2.trans.shared.b16 {%0,%1}, [%2];" : "=r"(r0), "=r"(r1) : "r"(a) : "memory"); }
__device__ __forceinline__ void ldsm4(uint32_t (&r)[4], uint32_t a) { asm volatile("ldmatrix.sync.aligned.m8n8.x4.shared.b16 {%0,%1,%2,%3}, [%4];" : "=r"(r[0]), "=r"(r[1]), "=r"(r[2]), "=r"(r[3]) : "r"(a) : "memory"); }
__device__ __forceinline__ void stsm4(uint32_t a, const uint32_t (&r)[4]) { asm volatile("stmatrix.sync.aligned.m8n8.x4.shared.b16 [%0], {%1,%2,%3,%4};" :: "r"(a), "r"(r[0]), "r"(r[1]), "r"(r[2]), "r"(r[3]) : "memory"); }
__device__ __forceinline__ uint32_t pack(float lo, float hi) { uint32_t r; asm("cvt.rn.bf16x2.f32 %0, %1, %2;" : "=r"(r) : "f"(hi), "f"(lo)); return r; }
__device__ __forceinline__ float blo(uint32_t v) { return __uint_as_float(v << 16); }
__device__ __forceinline__ float bhi(uint32_t v) { return __uint_as_float(v & 0xffff0000u); }
__device__ __forceinline__ float bf16r(float x) { return blo(pack(x, 0.f)); }
__device__ __forceinline__ uint32_t hmul2(uint32_t a, uint32_t b) { uint32_t r; asm("mul.rn.bf16x2 %0, %1, %2;" : "=r"(r) : "r"(a), "r"(b)); return r; }
__device__ __forceinline__ uint32_t hadd2(uint32_t a, uint32_t b) { uint32_t r; asm("add.rn.bf16x2 %0, %1, %2;" : "=r"(r) : "r"(a), "r"(b)); return r; }
__device__ __forceinline__ uint32_t hfma2(uint32_t a, uint32_t b, uint32_t c) { uint32_t r; asm("fma.rn.bf16x2 %0, %1, %2, %3;" : "=r"(r) : "r"(a), "r"(b), "r"(c)); return r; }
__device__ __forceinline__ uint32_t packh(float lo, float hi) { uint32_t r; asm("cvt.rn.f16x2.f32 %0, %1, %2;" : "=r"(r) : "f"(hi), "f"(lo)); return r; }
__device__ __forceinline__ __half2 H2(uint32_t a) { return *reinterpret_cast<__half2*>(&a); }
__device__ __forceinline__ uint32_t U2(__half2 a) { return *reinterpret_cast<uint32_t*>(&a); }
__device__ __forceinline__ uint32_t fmul(uint32_t a, uint32_t b) { return U2(__hmul2(H2(a), H2(b))); }
__device__ __forceinline__ uint32_t ffma(uint32_t a, uint32_t b, uint32_t c) { return U2(__hfma2(H2(a), H2(b), H2(c))); }
__device__ __forceinline__ uint32_t fneg(uint32_t a) { return U2(__hneg2(H2(a))); }
__device__ __forceinline__ uint32_t amax2(uint32_t a, uint32_t b) { uint32_t r; asm("max.xorsign.abs.bf16x2 %0, %1, %2;" : "=r"(r) : "r"(a), "r"(b)); return r; }
__device__ __forceinline__ uint32_t prmt(uint32_t a, uint32_t b, uint32_t s) { return __byte_perm(a, b, s); }
__device__ __forceinline__ uint32_t ldraw(const __nv_bfloat16* p) { uint32_t v; asm volatile("ld.global.nc.u16 %0, [%1];" : "=r"(v) : "l"(p)); return v; }
__device__ __forceinline__ uint4 ldg128(const void* p) { uint4 v; asm volatile("ld.global.nc.v4.u32 {%0,%1,%2,%3}, [%4];" : "=r"(v.x), "=r"(v.y), "=r"(v.z), "=r"(v.w) : "l"(p)); return v; }
__device__ __forceinline__ void bar_sync(int id, int n) { asm volatile("bar.sync %0, %1;" :: "r"(id), "r"(n) : "memory"); }
__device__ __forceinline__ void bar_arrive(int id, int n) { asm volatile("bar.arrive %0, %1;" :: "r"(id), "r"(n) : "memory"); }
__device__ __forceinline__ void cluster_arrive() { asm volatile("barrier.cluster.arrive.relaxed.aligned;" ::: "memory"); }
__device__ __forceinline__ void cluster_wait() { asm volatile("barrier.cluster.wait.aligned;" ::: "memory"); }
__device__ __forceinline__ void fence_async() { asm volatile("fence.proxy.async.shared::cta;" ::: "memory"); }
__device__ __forceinline__ void fence_mbinit() { asm volatile("fence.mbarrier_init.release.cluster;" ::: "memory"); }
__device__ __forceinline__ uint32_t mapa(uint32_t a, uint32_t rank) { uint32_t r; asm("mapa.shared::cluster.u32 %0, %1, %2;" : "=r"(r) : "r"(a), "r"(rank)); return r; }
__device__ __forceinline__ void bulk_dsmem(uint32_t dst, uint32_t src, uint32_t mbar) {
  asm volatile("cp.async.bulk.shared::cluster.shared::cta.mbarrier::complete_tx::bytes [%0], [%1], 512, [%2];" :: "r"(dst), "r"(src), "r"(mbar) : "memory");
}
__device__ __forceinline__ void mbar_init(uint32_t m, uint32_t cnt) { asm volatile("mbarrier.init.shared::cta.b64 [%0], %1;" :: "r"(m), "r"(cnt) : "memory"); }
__device__ __forceinline__ void mbar_expect(uint32_t m, uint32_t bytes) { asm volatile("mbarrier.arrive.expect_tx.shared::cta.b64 _, [%0], %1;" :: "r"(m), "r"(bytes) : "memory"); }
__device__ __forceinline__ bool mbar_try(uint32_t m) {
  uint32_t done;
  asm volatile("{.reg .pred p; mbarrier.try_wait.parity.shared::cta.b64 p, [%1], 0; selp.u32 %0, 1, 0, p;}" : "=r"(done) : "r"(m) : "memory");
  return done;
}
__device__ __forceinline__ void mbar_wait(uint32_t m) {
  if (!mbar_try(m)) {
    int it = 0;
    while (!mbar_try(m) && ++it < (1 << 22)) {}
  }
}
__device__ __forceinline__ bool elect() {
  uint32_t e;
  asm volatile("{.reg .pred p; elect.sync _|p, 0xffffffff; selp.u32 %0, 1, 0, p;}" : "=r"(e));
  return e;
}
__device__ __forceinline__ void tma_load4(uint32_t dst, const CUtensorMap* tm, int c0, int c1, int c2, int c3, uint32_t mbar) {
  asm volatile("cp.async.bulk.tensor.4d.shared::cluster.global.mbarrier::complete_tx::bytes [%0], [%1, {%3, %4, %5, %6}], [%2];"
               :: "r"(dst), "l"(tm), "r"(mbar), "r"(c0), "r"(c1), "r"(c2), "r"(c3) : "memory");
}
__device__ __forceinline__ void tma_load3(uint32_t dst, const CUtensorMap* tm, int c0, int c1, int c2, uint32_t mbar) {
  asm volatile("cp.async.bulk.tensor.3d.shared::cluster.global.mbarrier::complete_tx::bytes [%0], [%1, {%3, %4, %5}], [%2];"
               :: "r"(dst), "l"(tm), "r"(mbar), "r"(c0), "r"(c1), "r"(c2) : "memory");
}
__device__ __forceinline__ void tma_store3(const CUtensorMap* tm, int c0, int c1, int c2, uint32_t src) {
  asm volatile("cp.async.bulk.tensor.3d.global.shared::cta.bulk_group [%0, {%2, %3, %4}], [%1];"
               :: "l"(tm), "r"(src), "r"(c0), "r"(c1), "r"(c2) : "memory");
}
__device__ __forceinline__ void wg_fence() { asm volatile("wgmma.fence.sync.aligned;" ::: "memory"); }
__device__ __forceinline__ void wg_commit() { asm volatile("wgmma.commit_group.sync.aligned;" ::: "memory"); }
template <int N> __device__ __forceinline__ void wg_wait() { asm volatile("wgmma.wait_group.sync.aligned %0;" :: "n"(N) : "memory"); }
template <int N> __device__ __forceinline__ void tie_all(uint32_t (&x)[N]) {
#pragma unroll
  for (int i = 0; i < N; i++) asm volatile("" : "+r"(x[i]) :: "memory");
}
template <int N> __device__ __forceinline__ void tie_all(float (&x)[N]) {
#pragma unroll
  for (int i = 0; i < N; i++) asm volatile("" : "+f"(x[i]) :: "memory");
}
#define R16(C, d) C(d[0]), C(d[1]), C(d[2]), C(d[3]), C(d[4]), C(d[5]), C(d[6]), C(d[7]), C(d[8]), C(d[9]), C(d[10]), C(d[11]), C(d[12]), C(d[13]), C(d[14]), C(d[15])
#define R32(C, d) R16(C, d), R16(C, (d + 16))
#define P16 "{%0,%1,%2,%3,%4,%5,%6,%7,%8,%9,%10,%11,%12,%13,%14,%15}"
#define P32 "{%0,%1,%2,%3,%4,%5,%6,%7,%8,%9,%10,%11,%12,%13,%14,%15,%16,%17,%18,%19,%20,%21,%22,%23,%24,%25,%26,%27,%28,%29,%30,%31}"
template <int SD, int TB, int OFF> __device__ __forceinline__ void rs64(float* d, const uint32_t* a, uint64_t db) {
  if (SD) asm volatile("{.reg .b64 db; add.s64 db, %36, %37; wgmma.mma_async.sync.aligned.m64n64k16.f32.bf16.bf16 " P32 ", {%32,%33,%34,%35}, db, 1, 1, 1, %38;}"
                       : R32("+f", d) : "r"(a[0]), "r"(a[1]), "r"(a[2]), "r"(a[3]), "l"(db), "n"(OFF), "n"(TB));
  else asm volatile("{.reg .b64 db; add.s64 db, %36, %37; wgmma.mma_async.sync.aligned.m64n64k16.f32.bf16.bf16 " P32 ", {%32,%33,%34,%35}, db, 0, 1, 1, %38;}"
                    : R32("=f", d) : "r"(a[0]), "r"(a[1]), "r"(a[2]), "r"(a[3]), "l"(db), "n"(OFF), "n"(TB));
}
template <int SD, int TB, int OFF> __device__ __forceinline__ void rs64h(uint32_t* d, const uint32_t* a, uint64_t db) {
  if (SD) asm volatile("{.reg .b64 db; add.s64 db, %20, %21; wgmma.mma_async.sync.aligned.m64n64k16.f16.f16.f16 " P16 ", {%16,%17,%18,%19}, db, 1, 1, 1, %22;}"
                       : R16("+r", d) : "r"(a[0]), "r"(a[1]), "r"(a[2]), "r"(a[3]), "l"(db), "n"(OFF), "n"(TB));
  else asm volatile("{.reg .b64 db; add.s64 db, %20, %21; wgmma.mma_async.sync.aligned.m64n64k16.f16.f16.f16 " P16 ", {%16,%17,%18,%19}, db, 0, 1, 1, %22;}"
                    : R16("=r", d) : "r"(a[0]), "r"(a[1]), "r"(a[2]), "r"(a[3]), "l"(db), "n"(OFF), "n"(TB));
}
template <int SD, int OFFA, int OFFB> __device__ __forceinline__ void ss32(float* d, uint64_t da, uint64_t db) {
  if (SD) asm volatile("{.reg .b64 da, db; add.s64 da, %16, %18; add.s64 db, %17, %19; wgmma.mma_async.sync.aligned.m64n32k16.f32.f16.f16 " P16 ", da, db, 1, 1, 1, 1, 1;}"
                       : R16("+f", d) : "l"(da), "l"(db), "n"(OFFA), "n"(OFFB));
  else asm volatile("{.reg .b64 da, db; add.s64 da, %16, %18; add.s64 db, %17, %19; wgmma.mma_async.sync.aligned.m64n32k16.f32.f16.f16 " P16 ", da, db, 0, 1, 1, 1, 1;}"
                    : R16("=f", d) : "l"(da), "l"(db), "n"(OFFA), "n"(OFFB));
}
#define KGEN_ASM(SD) "{.reg .b64 da, db; add.s64 da, %32, %33; add.s64 db, %32, %34;\n" \
  "wgmma.mma_async.sync.aligned.m64n64k16.f32.bf16.bf16 " P32 ", da, db, " SD ", 1, 1, 1, 1;}"
template <int KS> __device__ __forceinline__ void kgen_mma(float (&c)[32], uint64_t da) {
  if (KS) asm volatile(KGEN_ASM("1") : R32("+f", c) : "l"(da), "n"(8 * KS), "n"(8 * KS + 512));
  else asm volatile(KGEN_ASM("0") : R32("=f", c) : "l"(da), "n"(8 * KS), "n"(8 * KS + 512));
  if constexpr (KS < 7) kgen_mma<KS + 1>(c, da);
}
__device__ __forceinline__ uint64_t desc_lo(uint32_t a) { return (uint64_t)((a & 0x3FFFF) >> 4); }
__device__ __forceinline__ void stage1(float (&D)[32], const uint32_t (&A1)[8], uint32_t src) {
  const uint64_t du = desc_lo(src) | (128ull << 16) | (32ull << 32) | (2ull << 62);
  rs64<0, 1, 0>(D, A1, du); rs64<1, 1, 64>(D, A1 + 4, du);
}
template <int INV> __device__ __forceinline__ void stage2(uint32_t (&X)[16], const uint32_t (&F)[16], uint32_t cf) {
  constexpr int KS = INV ? 16 : 128, TB = INV ? 0 : 1;
  const uint64_t dc = desc_lo(cf) | (INV ? (8ull << 16) | (64ull << 32) : (64ull << 16) | (8ull << 32));
  rs64h<0, TB, 0>(X, F, dc); rs64h<1, TB, KS>(X, F + 4, dc); rs64h<1, TB, 2 * KS>(X, F + 8, dc); rs64h<1, TB, 3 * KS>(X, F + 12, dc);
}
__device__ __forceinline__ void fwd_mid(uint32_t (&F)[16], const float (&D)[32], const uint32_t (&tc)[4], const uint32_t (&ts)[4]) {
#pragma unroll
  for (int j = 0; j < 4; j++)
#pragma unroll
    for (int b = 0; b < 2; b++) {
      const int i = 4 * j + 16 * b;
      const uint32_t ar = packh(D[i], D[i + 1]), ai = packh(D[i + 2], D[i + 3]);
      F[2 * j + b] = ffma(ar, tc[j], fmul(ai, ts[j]));
      F[8 + 2 * j + b] = ffma(ai, tc[j], fneg(fmul(ar, ts[j])));
    }
}
__device__ __forceinline__ void put_exp(uint32_t a, uint32_t m, int lane) {
  m = __reduce_max_sync(0xffffffffu, max(m & 0x7f80u, (m >> 16) & 0x7f80u));
  if (lane == 0) sts32(a, m);
}
__device__ __forceinline__ uint32_t seq_mag(uint32_t a) {
  const uint4 x = lds128(a), y = lds128(a + 2048);
  return amax2(amax2(amax2(x.x, x.y), amax2(x.z, x.w)), amax2(amax2(y.x, y.y), amax2(y.z, y.w)));
}
__device__ __forceinline__ uint32_t get_exp(uint32_t a) { const uint4 v = lds128(a); return max(max(v.x, v.y), max(v.z, v.w)) >> 7; }
__device__ __forceinline__ void scale_a1(uint32_t (&As)[8], const uint32_t (&A1)[8], uint32_t field) {
#pragma unroll
  for (int i = 0; i < 8; i++) As[i] = hmul2(A1[i], field * 0x00800080u);
}

struct cf { float x, y; };
__device__ __forceinline__ cf cmul(cf a, cf b) { cf r; r.x = fmaf(a.x, b.x, -a.y * b.y); r.y = fmaf(a.x, b.y, a.y * b.x); return r; }
__device__ __forceinline__ cf cexp_p(float lr2, float lt, float p) {
  float m;
  asm("ex2.approx.ftz.f32 %0, %1;" : "=f"(m) : "f"(lr2 * p));
  float t = lt * p;
  t = (t - rintf(t)) * 6.283185307179586f;
  cf r; r.x = m * __cosf(t); r.y = m * __sinf(t); return r;
}
__device__ __forceinline__ void store8(uint32_t a, uint32_t b, const cf (&v)[8]) {
  sts128(a, pack(v[0].x, v[1].x), pack(v[2].x, v[3].x), pack(v[4].x, v[5].x), pack(v[6].x, v[7].x));
  sts128(b, pack(v[0].y, v[1].y), pack(v[2].y, v[3].y), pack(v[4].y, v[5].y), pack(v[6].y, v[7].y));
}
__device__ __forceinline__ void mbar_arrive(uint32_t m) { asm volatile("mbarrier.arrive.shared::cta.b64 _, [%0];" :: "r"(m) : "memory"); }
__device__ __forceinline__ float sigmoidf_(float s) { return __frcp_rn(1.f + __expf(-s)); }

__global__ void __cluster_dims__(CS, 1, 1) __launch_bounds__(NTHREADS, 1) fused_kernel(const __grid_constant__ Params p) {
  extern __shared__ __align__(1024) uint8_t smem[];
  TL_INIT();
  TL(31);
  const int wid = __shfl_sync(0xffffffffu, threadIdx.x >> 5, 0);
  const uint32_t sb = (uint32_t)__cvta_generic_to_shared(smem);
  const uint32_t mb = sb + OFF_MB;
  const int u = wid >> 2, w = wid & 3;
  const int tid = threadIdx.x & 127, lane = tid & 31, g = lane >> 2, t = lane & 3;
  const int cl = blockIdx.x >> 3, rank = blockIdx.x & 7;
  const int ch0 = cl * CPC;
  const int nu = min(5, (DCH - ch0) >> 3);
  const bool act = u < nu;

  if (u == 4 && elect()) {
#pragma unroll
    for (int i = 0; i < 5; i++) mbar_init(mb + 40 * w + 8 * i, w == 3 ? 1 : w == 2 ? 3 : 2);
    if (w == 3) {
      mbar_init(mb + 8 * MB_XQ, 21); mbar_init(mb + 8 * MB_TH, 1); mbar_init(mb + 8 * MB_KV, 1); mbar_init(mb + 8 * MB_CF, 1); mbar_init(mb + 8 * MB_Q2, 9);
    }
    fence_mbinit();
    if (w == 3) {
      mbar_expect(mb + 8 * MB_CF, 12288);
      mbar_expect(mb + 8 * MB_TH, 8192);
      asm volatile("cp.async.bulk.shared::cluster.global.mbarrier::complete_tx::bytes [%0], [%1], %2, [%3];"
                   :: "r"(sb + OFF_YB), "l"(p.tab->thr), "r"(8192), "r"(mb + 8 * MB_TH) : "memory");
      asm volatile("cp.async.bulk.prefetch.L2.global [%0], 12288;" :: "l"(p.tab->mat) : "memory");
      mbar_expect(mb + 8 * MB_XQ, 20480); mbar_expect(mb + 8 * MB_KV, 23040 + 20480); mbar_expect(mb + 8 * MB_Q2, 20480);
    }
#pragma unroll
    for (int i = 0; i < 5; i++) mbar_expect(mb + 40 * w + 8 * i, w == 3 ? 4096 : w == 2 ? 7168 : 3584);
  }
  __syncwarp();
  uint32_t pla, pai, pcr, pci, pdt, tag = 0;
  uint4 psm;
  {
    const int ch = act ? ch0 + 8 * u + rank : 0, o = ch * NMODE + tid;
    pla = ldraw(p.logA + o); pdt = ldraw(p.logdt + ch); pai = ldraw(p.Aim + o); pcr = ldraw(p.Cre + o); pci = ldraw(p.Cim + o);
    if (w == 1) {
      if (lane < 9) psm = ldg128(lane < 5 ? p.gate_w + (lane < nu ? ch0 + 8 * lane : 0) : p.shift_k + (act ? ch0 + 8 * u : 0) * 4 + 8 * (lane - 5));
      else { psm.x = ldraw(p.Dskip + ch); psm.y = ldraw(p.ssm_D + ch); }
    }
    if (wid == 16 && lane < 2) asm volatile("atom.relaxed.gpu.global.add.u32 %0, [%1], %2;" : "=r"(tag) : "l"(&p.cnt[rank * 32 + lane]), "r"(cl == 0 ? 16 - (NCL - 1) : 1) : "memory");
  }
  if (wid == 19) {
    if (elect()) tma_load4(sb + OFF_TQ, &p.tq, ch0, 0, 0, 8 * rank, mb + 8 * MB_XQ);
    bar_sync(NB_LD, 32);
    TL(20);
  }
  cluster_arrive();
  asm volatile("" : "+r"(pla), "+r"(pdt) :: "memory");
  TL(0);

  const uint32_t tab = sb + OFF_T + u * KTAB;
  const int mi = lane >> 3, tq = (lane & 7) >> 1, jj = lane & 1;
  const uint32_t toff = (4 * (2 * mi + jj) + tq) * 80;
  const uint32_t uoff = 16 * (4 * w + (t ^ (w >> 1)));
  auto put = [&](int stage, int dst, uint32_t off, const uint32_t (&v)[4]) {
    sts128(sb + off + (g == rank ? dst + 512 * rank : stage + g * YPITCH), v[0], v[1], v[2], v[3]);
  };
  const int d0 = rank ^ (2 * w), d1 = d0 ^ 1;
  const uint32_t rb0 = mapa(sb, d0), rb1 = mapa(sb, d1);
  auto send = [&](int stage, int pitch, int dst, int mbar) {
    if (elect()) {
      if (w) bulk_dsmem(rb0 + dst, sb + stage + d0 * pitch, rb0 + mbar); else mbar_arrive(sb + mbar);
      bulk_dsmem(rb1 + dst, sb + stage + d1 * pitch, rb1 + mbar);
    }
    __syncwarp();
  };

  if (w == 1 && lane < 10) sts128(sb + OFF_SP + 160 * u + 16 * lane, psm.x, psm.y, psm.z, psm.w);
  uint32_t A1[8], tc[4], ts[4];
  {
    const float dt = bf16r(expf(blo(pdt)));
    const float lr2 = (-bf16r(expf(blo(pla))) * dt) * 1.4426950408889634f;
    const float lt = (blo(pai) * dt) * 0.15915494309189535f;
    const uint32_t tim = sb + OFF_IM + (u < 2 ? 3 + u : u - 2) * KTAB;
    const uint32_t row = tab + tid * 16, rim = tim + tid * 16;
    const cf w1 = cexp_p(lr2, lt, 8.f);
    cf z1 = cexp_p(lr2, lt, 1.f), Z = cexp_p(lr2, lt, 256.f);
    if (lr2 != 123.f) TL(16);
    TL(12);
    {
      cf v[8];
      v[0].x = 1.f; v[0].y = 0.f; v[1] = w1; v[2] = cmul(w1, w1); v[3] = cmul(v[2], w1);
      const cf w4 = cmul(v[2], v[2]);
      v[4] = w4; v[5] = cmul(v[1], w4); v[6] = cmul(v[2], w4); v[7] = cmul(v[3], w4);
      const cf w8 = cmul(w4, w4);
      store8(row, rim, v);
#pragma unroll
      for (int k = 1; k < 4; k++) {
#pragma unroll
        for (int i = 0; i < 8; i++) v[i] = (k == 1 && i == 0) ? w8 : cmul(v[i], w8);
        store8(row + 2048 * k, rim + 2048 * k, v);
      }
    }
    if (u == 1) {
      if (w == 0) bar_sync(NB_K0, 32);
      float z0_ = 0.f, z1_ = 0.f, z2_ = 0.f, z3_ = 0.f;
      asm volatile("mma.sync.aligned.m16n8k8.row.col.f32.bf16.bf16.f32 {%0,%1,%2,%3}, {%4,%4}, {%4}, {%0,%1,%2,%3};"
                   : "+f"(z0_), "+f"(z1_), "+f"(z2_), "+f"(z3_) : "r"(pla >> 16));
      pcr += __float_as_uint(z0_);
      if (w == 0 && elect()) {
        const uint32_t o = blockIdx.x * 9856u, n = min(9856u, SEQ * DCH - o) * 2;
        asm volatile("cp.async.bulk.prefetch.L2.global [%0], %1;" :: "l"(p.ssm_k + o), "r"(n) : "memory");
        asm volatile("cp.async.bulk.prefetch.L2.global [%0], %1;" :: "l"(p.k + o), "r"(n) : "memory");
        asm volatile("cp.async.bulk.prefetch.L2.global [%0], %1;" :: "l"(p.v + o), "r"(n) : "memory");
      }
      __syncwarp();
      TL(8);
    }
    {
      z1.y = -z1.y; Z.y = -Z.y;
      const cf z2 = cmul(z1, z1);
      cf h[8], v[8];
      h[0].x = 2.f * blo(pcr) * dt; h[0].y = -2.f * blo(pci) * dt;
      h[1] = cmul(h[0], z1);
#pragma unroll
      for (int i = 2; i < 8; i++) h[i] = cmul(h[i - 2], z2);
      store8(row + 4 * 2048, rim + 4 * 2048, h);
      const cf h8 = cmul(h[6], z2);
      v[0] = cmul(h[0], Z); v[2] = cmul(h[2], Z); v[3] = cmul(h[4], Z); v[6] = cmul(h[6], Z); v[7] = cmul(h8, Z);
      v[1] = v[0]; v[4] = v[5] = v[3];
      store8(row + 5 * 2048, rim + 5 * 2048, v);
      h[0] = cmul(v[0], Z); h[1] = cmul(v[3], Z); h[3] = cmul(v[7], Z); h[4] = cmul(h[0], Z); h[5] = cmul(h[1], Z); h[7] = cmul(h[3], Z);
      h[2] = h[1]; h[6] = h[5];
      store8(row + 6 * 2048, rim + 6 * 2048, h);
      const cf Z2 = cmul(Z, Z);
      v[0] = cmul(h[0], Z2); v[1] = cmul(h[3], Z2); v[2] = cmul(h[4], Z2); v[3] = cmul(h[7], Z2);
#pragma unroll
      for (int i = 4; i < 8; i++) v[i] = cmul(v[i - 4], Z2);
      store8(row + 7 * 2048, rim + 7 * 2048, v);
    }
    TL(17);
    cluster_wait();
    mbar_wait(mb + 8 * MB_TH);
    {
      const uint4 x = lds128(sb + OFF_YB + 16 * tid), y = lds128(sb + OFF_YB + 2048 + 16 * tid), a = lds128(sb + OFF_YB + 4096 + 16 * tid), b = lds128(sb + OFF_YB + 6144 + 16 * tid);
      A1[0] = x.x; A1[1] = x.y; A1[2] = x.z; A1[3] = x.w; A1[4] = y.x; A1[5] = y.y; A1[6] = y.z; A1[7] = y.w;
      tc[0] = a.x; tc[1] = a.y; tc[2] = a.z; tc[3] = a.w; ts[0] = b.x; ts[1] = b.y; ts[2] = b.z; ts[3] = b.w;
    }
    if (wid == 16 && lane == 0) sts32(mb + 8 * MB_TAG, tag);
    __syncwarp();
    if (lane == 0) mbar_arrive(mb + 8 * MB_XQ);
    mbar_wait(mb + 8 * MB_XQ);
    TL(18);
    {
      uint32_t x0[4], x1[4];
      ldsm4t(x0, sb + OFF_TQ + w * 2560 + toff + 16 * u);
      ldsm4t(x1, sb + OFF_TQ + (w + 4) * 2560 + toff + 16 * u);
      put(OFF_YB + 8 * u * YPITCH, OFF_UX + u * 4096, uoff, x0);
      put(OFF_YB + 8 * u * YPITCH, OFF_UX + u * 4096, (uoff ^ 32) + 256, x1);
    }
    TL(3);
    fence_async();
    bar_sync(NB_WG0 + u, 128);
    TL(4);
    if (u >= 3) {
      float s0 = 0.f;
#pragma unroll
      for (int j = 0; j < 5; j++) {
        const uint4 gw = lds128(sb + OFF_SP + 160 * u + 16 * j), x = lds128(sb + OFF_TQ + (tid + 128 * (u - 3)) * 80 + 16 * j);
        const uint32_t m0 = hmul2(x.x, gw.x), m1 = hmul2(x.y, gw.y), m2 = hmul2(x.z, gw.z), m3 = hmul2(x.w, gw.w);
        s0 += ((blo(m0) + bhi(m0)) + (blo(m1) + bhi(m1))) + ((blo(m2) + bhi(m2)) + (blo(m3) + bhi(m3)));
      }
      tag = (lds64(mb + 8 * MB_TAG).x >> 4) + 1;
      asm volatile("st.relaxed.gpu.global.u64 [%0], %1;" :: "l"(p.part + cl * SEQ + rank * 256 + 8 * (8 * t + g) + w + 4 * (u - 3)),
                   "l"(((uint64_t)tag << 32) | __float_as_uint(s0)) : "memory");
    }
    TL(7);
    if (u) bar_sync(NB_ORD + u - 1, 256);
    TL(13);
    float c[32];
    wg_fence();
    kgen_mma<0>(c, desc_lo(tab) | ((uint64_t)((tim - tab) >> 4) << 16) | (64ull << 32));
    wg_commit();
    if (u < 4) bar_arrive(NB_ORD + u, 256);
    send(OFF_YB + 8 * u * YPITCH, YPITCH, OFF_UX + u * 4096 + 512 * rank, OFF_MB + 8 * (MB_UX + u));
    TL(14);
    wg_wait<0>(); tie_all(c);
    TL(26);
    cluster_arrive();
    if (wid == 17) {
      bar_sync(NB_LD, 640);
      if (elect()) {
        tma_load4(sb + OFF_TK, &p.tk, ch0, 0, 0, 8 * rank - 1, mb + 8 * MB_KV);
        tma_load4(sb + OFF_TV, &p.tv, ch0, 0, 0, 8 * rank, mb + 8 * MB_KV);
      }
      __syncwarp();
    } else {
      bar_arrive(NB_LD, 640);
    }
    bar_sync(NB_WG0 + u, 128);
    if (wid == 1 && elect())
      asm volatile("cp.async.bulk.shared::cluster.global.mbarrier::complete_tx::bytes [%0], [%1], %2, [%3];"
                   :: "r"(sb + OFF_CF), "l"(p.tab->mat), "r"(12288), "r"(mb + 8 * MB_CF) : "memory");
    __syncwarp();
    const uint32_t k0 = pack(c[0] + c[6], c[1] + c[7]), k1 = pack(c[8] + c[14], c[9] + c[15]);
    const uint32_t k2 = pack(c[16] + c[22], c[17] + c[23]), k3 = pack(c[24] + c[30], c[25] + c[31]);
    const uint32_t ka = tab + 16 * (8 * w + (g ^ w));
    sts32(ka + 4 * t, k0);
    sts32(ka + 512 + 4 * t, k1);
    sts64(ka + 1024 + 512 * (t >> 1) + 8 * (t & 1), prmt(k2, 0, 0x1010), (t & 1) ? prmt(k2, 0, 0x3232) : k2);
    const uint32_t lo = prmt(k3, 0, 0x1010), hi = prmt(k3, 0, 0x3232);
    sts128(ka + 2048 + 512 * t, lo, lo, (g & 1) ? hi : k3, hi);
    put_exp(sb + OFF_MX + u * 64 + 4 * w, amax2(amax2(k0, k1), amax2(k2, k3)), lane);
    TL(15);
    fence_async();
    bar_sync(NB_WG0 + u, 128);
  }

#pragma unroll
  for (int isA = 0; isA < 2; isA++) {
    {
      TL(1 + isA);
      const uint32_t usrc = isA ? tab + T_UKV : sb + OFF_UX + u * 4096;
      const uint32_t mxa = sb + OFF_MX + u * 64 + 32 * isA;
      const uint32_t pd = lds16(sb + OFF_SP + 160 * u + 144 + 4 * isA);
      float D[32];
      uint32_t As[8], F[16], H[16], X[16];
      const uint32_t eh = min(max((int)get_exp(mxa), (int)((pd >> 7) & 0xff) - 5), 240);
      scale_a1(As, A1, 248 - eh);
      wg_fence();
      stage1(D, As, isA ? tab + T_HA : tab);
      wg_commit();
      wg_wait<0>(); tie_all(D);
      fwd_mid(F, D, tc, ts);
      if (!isA) mbar_wait(mb + 8 * MB_CF);
      wg_fence();
      stage2<0>(H, F, sb + OFF_CF);
      wg_commit();
      if (!isA && w == 1 && elect()) {
        tma_load4(tab + T_HA, &p.th, 0, 0, 5 * cl + u, rank, mb + 8 * (MB_HA + u));
        if (u == 4) tma_load3(sb + OFF_Q2, &p.tq2, ch0, 8 * rank, 0, mb + 8 * MB_Q2);
      }
      __syncwarp();
      mbar_wait(mb + 8 * ((isA ? MB_UKV : MB_UX) + u));
      TL(5 + isA);
      put_exp(mxa + 16 + 4 * w, seq_mag(usrc + 16 * tid), lane);
      bar_sync(NB_WG0 + u, 128);
      const uint32_t eu = min(get_exp(mxa + 16), 240u);
      scale_a1(As, A1, 250 - eu);
      wg_wait<0>(); tie_all(H);
      wg_fence();
      stage1(D, As, usrc);
      wg_commit();
      wg_wait<0>(); tie_all(D);
      fwd_mid(F, D, tc, ts);
      wg_fence();
      stage2<0>(X, F, sb + OFF_CF);
      wg_commit();
      {
        const float dsk = blo(pd) * __uint_as_float((248 - eh) << 23);
        const uint32_t d2 = packh(dsk, dsk);
#pragma unroll
        for (int j = 0; j < 4; j++) H[2 * j] = U2(__hadd2(H2(H[2 * j]), H2(d2)));
      }
      wg_wait<0>(); tie_all(X);
#pragma unroll
      for (int j = 0; j < 4; j++) {
        const uint32_t h0r = H[2 * j], h1r = H[2 * j + 1], h0i = H[8 + 2 * j], h1i = H[9 + 2 * j];
        const uint32_t x0r = X[2 * j], x1r = X[2 * j + 1], x0i = X[8 + 2 * j], x1i = X[9 + 2 * j];
        F[2 * j] = ffma(x0r, h0r, fneg(fmul(x0i, h0i)));
        F[8 + 2 * j] = ffma(x0r, h0i, fmul(x0i, h0r));
        F[2 * j + 1] = ffma(x1r, h0r, ffma(fneg(x1i), h0i, ffma(x0r, h1r, fneg(ffma(x0i, h1i, F[8 + 2 * j])))));
        F[9 + 2 * j] = ffma(x1r, h0i, ffma(x1i, h0r, ffma(x0r, h1i, ffma(x0i, h1r, F[2 * j]))));
      }
      wg_fence();
      stage2<1>(H, F, sb + OFF_CF);
      wg_commit();
      wg_wait<0>(); tie_all(H);
      {
        const uint32_t va = tab + (16 * w + (lane & 15)) * 128;
        const int vx = (lane >> 4) ^ (lane & 7);
#pragma unroll
        for (int j = 0; j < 4; j++) {
          uint32_t V[4];
#pragma unroll
          for (int b = 0; b < 2; b++) {
            const uint32_t er = H[2 * j + b], ei = H[8 + 2 * j + b];
            V[2 * b] = ffma(er, tc[j], fneg(fmul(ei, ts[j])));
            V[2 * b + 1] = ffma(ei, tc[j], fmul(er, ts[j]));
          }
          stsm4(va + ((vx ^ (2 * j)) << 4), V);
        }
      }
      uint64_t ga[NCL];
      const int slot = tid + 128 * (u & 1);
      const uint2* gp = p.part + rank * 256 + slot;
      auto gload = [&]() {
#pragma unroll
        for (int k = 0; k < NCL; k++) asm volatile("ld.relaxed.gpu.global.u64 %0, [%1];" : "=l"(ga[k]) : "l"(gp + k * SEQ) : "memory");
      };
      if (!isA) {
        cluster_wait();
        mbar_wait(mb + 8 * MB_KV);
        TL(21);
        const uint32_t hoff = (4 * (4 + 2 * (mi & 1) + jj) + ((tq + 3) & 3)) * 80 + (tq ? 2560 : 0) + 16 * u;
        uint32_t E[2][6], V[2][4];
        const uint2 psw = lds64(sb + OFF_SP + 160 * u + 80 + 8 * g);
#pragma unroll
        for (int hf = 0; hf < 2; hf++) {
          const int ah = 4 * hf + w;
          uint32_t K[4];
          ldsm4t(K, sb + OFF_TK + (ah + 1) * 2560 + toff + 16 * u);
          ldsm2t(E[hf][0], E[hf][1], sb + OFF_TK + ah * 2560 + hoff);
          ldsm4t(V[hf], sb + OFF_TV + ah * 2560 + toff + 16 * u);
          E[hf][2] = K[0]; E[hf][3] = K[1]; E[hf][4] = K[2]; E[hf][5] = K[3];
        }
        const uint32_t w0 = prmt(psw.x, 0, 0x1010), w1 = prmt(psw.x, 0, 0x3232), w2 = prmt(psw.y, 0, 0x1010), w3 = prmt(psw.y, 0, 0x3232);
        uint32_t o[2][4];
#pragma unroll
        for (int hf = 0; hf < 2; hf++) {
          uint32_t O[5];
#pragma unroll
          for (int i = 0; i < 5; i++) O[i] = prmt(E[hf][i], E[hf][i + 1], 0x5432);
#pragma unroll
          for (int i = 0; i < 4; i++) {
            o[hf][i] = hmul2(hfma2(E[hf][i + 2], w0, hfma2(O[i + 1], w1, hfma2(E[hf][i + 1], w2, hmul2(O[i], w3)))), V[hf][i]);
          }
          put(OFF_YA + 8 * u * YPITCH, OFF_T + u * KTAB + T_UKV, hf ? (uoff ^ 32) + 256 : uoff, o[hf]);
        }
        mbar_wait(mb + 8 * (MB_HA + u));
        put_exp(mxa + 32 + 4 * w, seq_mag(tab + T_HA + 16 * tid), lane);
        TL(22);
      }
      fence_async();
      bar_sync(NB_WG0 + u, 128);
      float O[16];
      {
        const uint64_t dv = desc_lo(tab) | (1ull << 16) | (64ull << 32) | (1ull << 62);
        const uint64_t dl = desc_lo(sb + OFF_CL) | (32ull << 16) | (8ull << 32);
        wg_fence();
        ss32<0, 0, 0>(O, dv, dl); ss32<1, 128, 64>(O, dv, dl); ss32<1, 256, 128>(O, dv, dl); ss32<1, 384, 192>(O, dv, dl);
        wg_commit();
      }
      if (!isA) {
        send(OFF_YA + 8 * u * YPITCH, YPITCH, OFF_T + u * KTAB + T_UKV + 512 * rank, OFF_MB + 8 * (MB_UKV + u));
        if (u < 2) gload();
      }
      wg_wait<0>(); tie_all(O);
      {
        const uint32_t co = ((8 * w + g) ^ (2 * t)) * 16;
        const int yo = (isA ? OFF_YA : OFF_YB) + (8 * u + rank) * YPITCH, ym = OFF_MB + 8 * (MB_Y + u);
        const uint32_t us = min(max((int)(eu + eh) - 127, 0), 254) * 0x00800080u;
        const uint32_t a0 = hmul2(pack(O[0], O[1]), us), a1 = hmul2(pack(O[4], O[5]), us), a2 = hmul2(pack(O[8], O[9]), us), a3 = hmul2(pack(O[12], O[13]), us);
        const uint32_t b0 = hmul2(pack(O[2], O[3]), us), b1 = hmul2(pack(O[6], O[7]), us), b2 = hmul2(pack(O[10], O[11]), us), b3 = hmul2(pack(O[14], O[15]), us);
        sts128((t == rank ? sb + yo : usrc + t * 512) + co, a0, a1, a2, a3);
        sts128((t + 4 == rank ? sb + yo : usrc + t * 512 + 2048) + co, b0, b1, b2, b3);
        fence_async();
        bar_sync(NB_WG0 + u, 128);
        send(usrc - sb, 512, yo, ym);
      }
      TL(9 + isA);
      if (!isA && u < 2) {
        tag = (lds64(mb + 8 * MB_TAG).x >> 4) + 1;
        float s;
        bool ok;
#pragma unroll 1
        for (int it = 0;; it++) {
          ok = true; s = 0.f;
#pragma unroll
          for (int k = 0; k < NCL; k++) { ok = ok && (uint32_t)(ga[k] >> 32) == tag; s += __uint_as_float((uint32_t)ga[k]); }
          if (ok || it == 4000) break;
          gload();
        }
        if (!ok) {
          const uint32_t* xr = (const uint32_t*)(p.q + (size_t)(rank * 256 + 32 * (slot & 7) + (slot >> 3)) * DCH);
          const uint32_t* gr = (const uint32_t*)p.gate_w;
          s = 0.f;
    #pragma unroll 1
          for (int k = 0; k < DCH / 2; k++) { const uint32_t m = hmul2(__ldg(xr + k), __ldg(gr + k)); s += blo(m) + bhi(m); }
        }
        const float g0 = bf16r(sigmoidf_(bf16r(s)));
        sts64(sb + OFF_GB + 8 * slot, pack(g0, g0), pack(1.f - g0, 1.f - g0));
        __syncwarp();
        if (lane == 0) mbar_arrive(mb + 8 * MB_Q2);
      }
    }
  }

  {
    mbar_wait(mb + 8 * MB_Q2);
    uint2 gg[2][4];
    uint32_t qv[2][4];
#pragma unroll
    for (int hh = 0; hh < 2; hh++)
#pragma unroll
      for (int i = 0; i < 4; i++) gg[hh][i] = lds64(sb + OFF_GB + 8 * (64 * w + 32 * hh + 8 * i + g));
    const uint32_t qa = sb + OFF_Q2 + (64 * w + lane) * 80 + 16 * u;
    ldsm4(qv[0], qa);
    ldsm4(qv[1], qa + 2560);
    TL(24);
    mbar_wait(mb + 8 * (MB_Y + u));
    uint32_t ya[2][4], yb[2][4];
#pragma unroll
    for (int hh = 0; hh < 2; hh++) {
      const uint32_t yo = (8 * u + (lane & 7)) * YPITCH + ((8 * w + 4 * hh + (lane >> 3)) ^ (2 * (rank & 3))) * 16;
      ldsm4t(ya[hh], sb + OFF_YA + yo); ldsm4t(yb[hh], sb + OFF_YB + yo);
    }
#pragma unroll
    for (int hh = 0; hh < 2; hh++) {
      uint32_t o[4];
#pragma unroll
      for (int i = 0; i < 4; i++) o[i] = hadd2(hmul2(gg[hh][i].x, hmul2(qv[hh][i], ya[hh][i])), hmul2(gg[hh][i].y, yb[hh][i]));
      stsm4(qa + 2560 * hh, o);
    }
    TL(25);
  }
  cluster_arrive();
  bar_sync(NB_ROW0 + w, 160);
  {
    uint4 v[2];
#pragma unroll
    for (int k = 0; k < 2; k++) {
      const int i = 64 * u + 32 * k + lane, sl = (i * 205) >> 10, cc = i - 5 * sl;
      v[k] = lds128(sb + OFF_Q2 + (64 * w + 8 * (sl & 7) + (sl >> 3)) * 80 + cc * 16);
    }
#pragma unroll
    for (int k = 0; k < 2; k++) {
      const int i = 64 * u + 32 * k + lane, sl = (i * 205) >> 10, cc = i - 5 * sl;
      if (cc < nu)
        asm volatile("st.global.v4.u32 [%0], {%1,%2,%3,%4};" :: "l"(p.out + (size_t)(256 * rank + 32 * (sl >> 3) + 8 * w + (sl & 7)) * DCH + ch0 + 8 * cc),
                     "r"(v[k].x), "r"(v[k].y), "r"(v[k].z), "r"(v[k].w) : "memory");
    }
  }
  cluster_wait();
  TL(27);
  TL_DUMP();
}

typedef CUresult (*EncodeFn)(CUtensorMap*, CUtensorMapDataType, cuuint32_t, void*, const cuuint64_t*, const cuuint64_t*,
                             const cuuint32_t*, const cuuint32_t*, CUtensorMapInterleave, CUtensorMapSwizzle,
                             CUtensorMapL2promotion, CUtensorMapFloatOOBfill);

void encode(EncodeFn fn, CUtensorMap* tm, const void* ptr, int nd, const cuuint64_t* dims, const cuuint64_t* strides,
            const cuuint32_t* box, CUtensorMapSwizzle swz) {
  cuuint32_t es[4] = {1, 1, 1, 1};
  fn(tm, CU_TENSOR_MAP_DATA_TYPE_BFLOAT16, nd, const_cast<void*>(ptr), dims, strides, box, es, CU_TENSOR_MAP_INTERLEAVE_NONE,
     swz, CU_TENSOR_MAP_L2_PROMOTION_L2_128B, CU_TENSOR_MAP_FLOAT_OOB_FILL_NONE);
}
void map1(EncodeFn fn, CUtensorMap* tm, const void* ptr, int nhi) {
  const cuuint64_t dims[4] = {DCH, 4, 8, SEQ / 32}, strides[3] = {8 * DCH * 2, DCH * 2, 32 * DCH * 2};
  const cuuint32_t box[4] = {CPC, 4, 8, (cuuint32_t)nhi};
  encode(fn, tm, ptr, 4, dims, strides, box, CU_TENSOR_MAP_SWIZZLE_NONE);
}
void map2(EncodeFn fn, CUtensorMap* tm, const void* ptr, int nr) {
  const cuuint64_t dims[3] = {DCH, SEQ / 32, 32}, strides[2] = {32 * DCH * 2, DCH * 2};
  const cuuint32_t box[3] = {CPC, 8, (cuuint32_t)nr};
  encode(fn, tm, ptr, 3, dims, strides, box, CU_TENSOR_MAP_SWIZZLE_NONE);
}

}

extern "C" void kernel_launch(void* const* d_in, const int* in_sizes, int n_in, void* d_out, int out_size) {
  (void)in_sizes; (void)n_in; (void)out_size;
  static EncodeFn fn = nullptr;
  static void *tab = nullptr, *cnt = nullptr, *part = nullptr;
  if (!fn) {
    cudaGetSymbolAddress(&tab, d_tab);
    cudaGetSymbolAddress(&cnt, g_cnt);
    cudaGetSymbolAddress(&part, g_part);
    cudaDriverEntryPointQueryResult qr;
    cudaGetDriverEntryPoint("cuTensorMapEncodeTiled", (void**)&fn, cudaEnableDefault, &qr);
    cudaFuncSetAttribute(fused_kernel, cudaFuncAttributeMaxDynamicSharedMemorySize, SMEM_BYTES);
  }
  Params p;
  map1(fn, &p.tq, d_in[0], 8);
  map1(fn, &p.tk, d_in[1], 9);
  map1(fn, &p.tv, d_in[2], 8);
  map2(fn, &p.tq2, d_in[0], 32);
  p.out = (__nv_bfloat16*)d_out;
  {
    const cuuint64_t dims[4] = {32, SEQ / 32, DCH / 8, 8}, strides[3] = {64, 8 * SEQ * 2, SEQ * 2};
    const cuuint32_t box[4] = {32, 64, 1, 1};
    encode(fn, &p.th, d_in[4], 4, dims, strides, box, CU_TENSOR_MAP_SWIZZLE_64B);
  }
  p.tab = (const Tables*)tab;
  p.cnt = (unsigned*)cnt;
  p.part = (uint2*)part;
  p.tl = nullptr;
  p.q = (const __nv_bfloat16*)d_in[0];
  p.k = (const __nv_bfloat16*)d_in[1];
  p.v = (const __nv_bfloat16*)d_in[2];
  p.ssm_k = (const __nv_bfloat16*)d_in[4];
  p.shift_k = (const __nv_bfloat16*)d_in[3];
  p.ssm_D = (const __nv_bfloat16*)d_in[5];
  p.logA = (const __nv_bfloat16*)d_in[7];
  p.Aim = (const __nv_bfloat16*)d_in[8];
  p.Cre = (const __nv_bfloat16*)d_in[9];
  p.Cim = (const __nv_bfloat16*)d_in[10];
  p.logdt = (const __nv_bfloat16*)d_in[11];
  p.Dskip = (const __nv_bfloat16*)d_in[12];
  p.gate_w = (const __nv_bfloat16*)d_in[13];
  fused_kernel<<<NCL * CS, NTHREADS, SMEM_BYTES, cudaStreamPerThread>>>(p);
}
```

```cpp
#include <cuda_runtime.h>
#include <cuda_bf16.h>
#include <cuda_fp16.h>
#include <cuda.h>
#include <stdint.h>

#define TIMELINE 0
#define TLHI 0

namespace {

constexpr int SEQ = 2048, DCH = 576, NMODE = 128;
constexpr int CS = 8, CPC = 40, NCL = 15, NTHREADS = 640;

constexpr int YPITCH = 528;
constexpr int KTAB = 16384;
constexpr int OFF_T = 0;
constexpr int T_UKV = 8192, T_HA = 12288;
constexpr int OFF_UX = 5 * KTAB;
constexpr int OFF_IM = OFF_UX + 20480;
constexpr int OFF_Q2 = OFF_IM;
constexpr int OFF_GB = OFF_Q2 + 20480;
constexpr int OFF_TV = OFF_IM + 3 * KTAB - 20480;
constexpr int OFF_CF = OFF_IM + 3 * KTAB;
constexpr int OFF_CL = OFF_CF + 8192;
constexpr int OFF_TK = OFF_CL + 4096;
constexpr int OFF_TQ = OFF_TK + 23040;
constexpr int OFF_YA = OFF_TQ;
constexpr int OFF_YB = OFF_TQ + 21120;
constexpr int OFF_MX = OFF_YB + 40 * YPITCH;
constexpr int OFF_SP = OFF_MX + 320;
constexpr int OFF_MB = OFF_SP + 5 * 160;
constexpr int OFF_TL = OFF_MB + 32 * 8;
constexpr int SMEM_BYTES = OFF_TL + (TIMELINE ? 1280 : 0);
static_assert(SMEM_BYTES <= 232448 && OFF_IM + 5 * KTAB <= OFF_TQ, "smem");
static_assert((OFF_TQ & 127) == 0 && (OFF_TK & 127) == 0 && (OFF_TV & 127) == 0 && (OFF_MB & 7) == 0 && (OFF_MX & 15) == 0, "align");

enum { MB_UX = 0, MB_UKV = 5, MB_Y = 10, MB_HA = 15, MB_XQ = 20, MB_KV = 21, MB_CF = 22, MB_Q2 = 23, MB_TH = 24, MB_TAG = 25 };
enum { NB_WG0 = 1, NB_ROW0 = 6, NB_ORD = 6, NB_K0 = 10, NB_LD = 11 };

constexpr double cos_turn(int m, int n) {
  m &= n - 1;
  if (m > n / 2) m = n - m;
  double sgn = 1.0;
  if (m > n / 4) { m = n / 2 - m; sgn = -1.0; }
  if (m == n / 4) return 0.0;
  const double x = 6.283185307179586476925 * m / n;
  double term = 1.0, sum = 1.0;
  for (int k = 1; k < 14; k++) { term *= -x * x / ((2 * k - 1) * (2 * k)); sum += term; }
  return sgn * sum;
}
constexpr uint32_t bf16_bits(double v) {
  if (v == 0.0) return 0;
  uint32_t sgn = 0;
  if (v < 0) { sgn = 0x8000; v = -v; }
  int e = 127;
  while (v < 1.0) { v *= 2.0; e--; }
  while (v >= 2.0) { v *= 0.5; e++; }
  const double f = v * 128.0;
  int m = (int)f;
  if (f - m > 0.5 || (f - m == 0.5 && (m & 1))) m++;
  return sgn | (uint32_t)((e << 7) + (m - 128));
}
constexpr uint32_t f16_bits(double v) {
  if (v == 0.0) return 0;
  uint32_t sgn = 0;
  if (v < 0) { sgn = 0x8000; v = -v; }
  int e = 15;
  while (v < 1.0) { v *= 2.0; e--; }
  const double f = v * 1024.0;
  int m = (int)f;
  if (f - m > 0.5 || (f - m == 0.5 && (m & 1))) m++;
  return sgn | (uint32_t)((e << 10) + (m - 1024));
}
constexpr uint32_t pair_bits(double lo, double hi) { return bf16_bits(lo) | (bf16_bits(hi) << 16); }
constexpr uint32_t pair_h(double lo, double hi) { return f16_bits(lo) | (f16_bits(hi) << 16); }
struct alignas(128) Tables {
  uint32_t mat[3072];
  uint32_t thr[4][128][4];
};
constexpr Tables make_tables() {
  Tables T{};
  for (int q = 0; q < 768; q++) {
    int m0 = 0, d0 = 0, d1 = 0;
    if (q < 512) {
      const int r = (q >> 6) * 8 + (q & 7), cc = (q >> 3) & 7;
      d0 = 4 * (r & 31); d1 = 2 * d0;
      m0 = 8 * (cc & 3) * d0 + ((r >> 5) == (cc >> 2) ? 0 : (r >> 5) ? 96 : 32);
    } else {
      const int r = ((q - 512) >> 5) * 8 + (q & 7), pc = (q >> 3) & 3;
      d0 = 4 * (8 * (r >> 4) + (r & 7)) + 1; d1 = 8 * d0;
      m0 = 2 * pc * d0 + ((r & 8) ? 32 : 0);
    }
    for (int e = 0; e < 4; e++) T.mat[4 * q + e] = pair_h(cos_turn(m0 + e * d1, 128), cos_turn(m0 + e * d1 + d0, 128));
  }
  for (int tid = 0; tid < 128; tid++) {
    const int kk = 4 * (tid >> 2) + 1, t = tid & 3;
    for (int q = 0; q < 4; q++) {
      const int m = (8 * q + 2 * t) * kk;
      T.thr[q >> 1][tid][2 * (q & 1)] = pair_bits(cos_turn(m, 128), cos_turn(m + kk, 128));
      T.thr[q >> 1][tid][2 * (q & 1) + 1] = pair_bits(cos_turn(m + 32, 128), cos_turn(m + kk + 32, 128));
      T.thr[2][tid][q] = pair_h(cos_turn(m, 4096), cos_turn(m + kk, 4096));
      T.thr[3][tid][q] = pair_h(cos_turn(m + 3072, 4096), cos_turn(m + kk + 3072, 4096));
    }
  }
  return T;
}
__device__ const Tables d_tab = make_tables();

struct Params {
  const __nv_bfloat16 *logA, *Aim, *Cre, *Cim, *logdt;
  const Tables* tab;
  unsigned* cnt;
  const __nv_bfloat16 *Dskip, *shift_k, *ssm_D, *gate_w, *q, *k, *v, *ssm_k;
  uint2* part;
  __nv_bfloat16* out;
  unsigned* tl;
  CUtensorMap tq, tk, tv, th, tq2;
};

__device__ uint2 g_part[NCL * SEQ];
__device__ unsigned g_cnt[CS * 32];
#define TL(i) do {} while (0)
#define TL_INIT() do {} while (0)
#define TL_DUMP() do {} while (0)

__device__ __forceinline__ uint32_t lds16(uint32_t a) { uint32_t v; asm volatile("ld.shared.u16 %0, [%1];" : "=r"(v) : "r"(a) : "memory"); return v; }
__device__ __forceinline__ uint2 lds64(uint32_t a) { uint2 v; asm volatile("ld.shared.v2.u32 {%0,%1}, [%2];" : "=r"(v.x), "=r"(v.y) : "r"(a) : "memory"); return v; }
__device__ __forceinline__ uint4 lds128(uint32_t a) { uint4 v; asm volatile("ld.shared.v4.u32 {%0,%1,%2,%3}, [%4];" : "=r"(v.x), "=r"(v.y), "=r"(v.z), "=r"(v.w) : "r"(a) : "memory"); return v; }
__device__ __forceinline__ void sts16(uint32_t a, uint32_t v) { asm volatile("st.shared.u16 [%0], %1;" :: "r"(a), "r"(v) : "memory"); }
__device__ __forceinline__ void sts32(uint32_t a, uint32_t v) { asm volatile("st.shared.u32 [%0], %1;" :: "r"(a), "r"(v) : "memory"); }
__device__ __forceinline__ void sts64(uint32_t a, uint32_t x, uint32_t y) { asm volatile("st.shared.v2.u32 [%0], {%1,%2};" :: "r"(a), "r"(x), "r"(y) : "memory"); }
__device__ __forceinline__ void sts128(uint32_t a, uint32_t x, uint32_t y, uint32_t z, uint32_t w) { asm volatile("st.shared.v4.u32 [%0], {%1,%2,%3,%4};" :: "r"(a), "r"(x), "r"(y), "r"(z), "r"(w) : "memory"); }
__device__ __forceinline__ void ldsm4t(uint32_t (&r)[4], uint32_t a) { asm volatile("ldmatrix.sync.aligned.m8n8.x4.trans.shared.b16 {%0,%1,%2,%3}, [%4];" : "=r"(r[0]), "=r"(r[1]), "=r"(r[2]), "=r"(r[3]) : "r"(a) : "memory"); }
__device__ __forceinline__ void ldsm2t(uint32_t& r0, uint32_t& r1, uint32_t a) { asm volatile("ldmatrix.sync.aligned.m8n8.x2.trans.shared.b16 {%0,%1}, [%2];" : "=r"(r0), "=r"(r1) : "r"(a) : "memory"); }
__device__ __forceinline__ void ldsm4(uint32_t (&r)[4], uint32_t a) { asm volatile("ldmatrix.sync.aligned.m8n8.x4.shared.b16 {%0,%1,%2,%3}, [%4];" : "=r"(r[0]), "=r"(r[1]), "=r"(r[2]), "=r"(r[3]) : "r"(a) : "memory"); }
__device__ __forceinline__ void stsm4(uint32_t a, const uint32_t (&r)[4]) { asm volatile("stmatrix.sync.aligned.m8n8.x4.shared.b16 [%0], {%1,%2,%3,%4};" :: "r"(a), "r"(r[0]), "r"(r[1]), "r"(r[2]), "r"(r[3]) : "memory"); }
__device__ __forceinline__ uint32_t pack(float lo, float hi) { uint32_t r; asm("cvt.rn.bf16x2.f32 %0, %1, %2;" : "=r"(r) : "f"(hi), "f"(lo)); return r; }
__device__ __forceinline__ float blo(uint32_t v) { return __uint_as_float(v << 16); }
__device__ __forceinline__ float bhi(uint32_t v) { return __uint_as_float(v & 0xffff0000u); }
__device__ __forceinline__ float bf16r(float x) { return blo(pack(x, 0.f)); }
__device__ __forceinline__ uint32_t hmul2(uint32_t a, uint32_t b) { uint32_t r; asm("mul.rn.bf16x2 %0, %1, %2;" : "=r"(r) : "r"(a), "r"(b)); return r; }
__device__ __forceinline__ uint32_t hadd2(uint32_t a, uint32_t b) { uint32_t r; asm("add.rn.bf16x2 %0, %1, %2;" : "=r"(r) : "r"(a), "r"(b)); return r; }
__device__ __forceinline__ uint32_t hfma2(uint32_t a, uint32_t b, uint32_t c) { uint32_t r; asm("fma.rn.bf16x2 %0, %1, %2, %3;" : "=r"(r) : "r"(a), "r"(b), "r"(c)); return r; }
__device__ __forceinline__ uint32_t packh(float lo, float hi) { uint32_t r; asm("cvt.rn.f16x2.f32 %0, %1, %2;" : "=r"(r) : "f"(hi), "f"(lo)); return r; }
__device__ __forceinline__ __half2 H2(uint32_t a) { return *reinterpret_cast<__half2*>(&a); }
__device__ __forceinline__ uint32_t U2(__half2 a) { return *reinterpret_cast<uint32_t*>(&a); }
__device__ __forceinline__ uint32_t fmul(uint32_t a, uint32_t b) { return U2(__hmul2(H2(a), H2(b))); }
__device__ __forceinline__ uint32_t ffma(uint32_t a, uint32_t b, uint32_t c) { return U2(__hfma2(H2(a), H2(b), H2(c))); }
__device__ __forceinline__ uint32_t fneg(uint32_t a) { return U2(__hneg2(H2(a))); }
__device__ __forceinline__ uint32_t amax2(uint32_t a, uint32_t b) { uint32_t r; asm("max.xorsign.abs.bf16x2 %0, %1, %2;" : "=r"(r) : "r"(a), "r"(b)); return r; }
__device__ __forceinline__ uint32_t prmt(uint32_t a, uint32_t b, uint32_t s) { return __byte_perm(a, b, s); }
__device__ __forceinline__ uint32_t ldraw(const __nv_bfloat16* p) { uint32_t v; asm volatile("ld.global.nc.u16 %0, [%1];" : "=r"(v) : "l"(p)); return v; }
__device__ __forceinline__ uint4 ldg128(const void* p) { uint4 v; asm volatile("ld.global.nc.v4.u32 {%0,%1,%2,%3}, [%4];" : "=r"(v.x), "=r"(v.y), "=r"(v.z), "=r"(v.w) : "l"(p)); return v; }
__device__ __forceinline__ void bar_sync(int id, int n) { asm volatile("bar.sync %0, %1;" :: "r"(id), "r"(n) : "memory"); }
__device__ __forceinline__ void bar_arrive(int id, int n) { asm volatile("bar.arrive %0, %1;" :: "r"(id), "r"(n) : "memory"); }
__device__ __forceinline__ void cluster_arrive() { asm volatile("barrier.cluster.arrive.relaxed.aligned;" ::: "memory"); }
__device__ __forceinline__ void cluster_wait() { asm volatile("barrier.cluster.wait.aligned;" ::: "memory"); }
__device__ __forceinline__ void fence_async() { asm volatile("fence.proxy.async.shared::cta;" ::: "memory"); }
__device__ __forceinline__ void fence_mbinit() { asm volatile("fence.mbarrier_init.release.cluster;" ::: "memory"); }
__device__ __forceinline__ uint32_t mapa(uint32_t a, uint32_t rank) { uint32_t r; asm("mapa.shared::cluster.u32 %0, %1, %2;" : "=r"(r) : "r"(a), "r"(rank)); return r; }
__device__ __forceinline__ void bulk_dsmem(uint32_t dst, uint32_t src, uint32_t mbar) {
  asm volatile("cp.async.bulk.shared::cluster.shared::cta.mbarrier::complete_tx::bytes [%0], [%1], 512, [%2];" :: "r"(dst), "r"(src), "r"(mbar) : "memory");
}
__device__ __forceinline__ void mbar_init(uint32_t m, uint32_t cnt) { asm volatile("mbarrier.init.shared::cta.b64 [%0], %1;" :: "r"(m), "r"(cnt) : "memory"); }
__device__ __forceinline__ void mbar_expect(uint32_t m, uint32_t bytes) { asm volatile("mbarrier.arrive.expect_tx.shared::cta.b64 _, [%0], %1;" :: "r"(m), "r"(bytes) : "memory"); }
__device__ __forceinline__ bool mbar_try(uint32_t m) {
  uint32_t done;
  asm volatile("{.reg .pred p; mbarrier.try_wait.parity.shared::cta.b64 p, [%1], 0; selp.u32 %0, 1, 0, p;}" : "=r"(done) : "r"(m) : "memory");
  return done;
}
__device__ __forceinline__ void mbar_wait(uint32_t m) {
  if (!mbar_try(m)) {
    int it = 0;
    while (!mbar_try(m) && ++it < (1 << 22)) {}
  }
}
__device__ __forceinline__ bool elect() {
  uint32_t e;
  asm volatile("{.reg .pred p; elect.sync _|p, 0xffffffff; selp.u32 %0, 1, 0, p;}" : "=r"(e));
  return e;
}
__device__ __forceinline__ void tma_load4(uint32_t dst, const CUtensorMap* tm, int c0, int c1, int c2, int c3, uint32_t mbar) {
  asm volatile("cp.async.bulk.tensor.4d.shared::cluster.global.mbarrier::complete_tx::bytes [%0], [%1, {%3, %4, %5, %6}], [%2];"
               :: "r"(dst), "l"(tm), "r"(mbar), "r"(c0), "r"(c1), "r"(c2), "r"(c3) : "memory");
}
__device__ __forceinline__ void tma_load3(uint32_t dst, const CUtensorMap* tm, int c0, int c1, int c2, uint32_t mbar) {
  asm volatile("cp.async.bulk.tensor.3d.shared::cluster.global.mbarrier::complete_tx::bytes [%0], [%1, {%3, %4, %5}], [%2];"
               :: "r"(dst), "l"(tm), "r"(mbar), "r"(c0), "r"(c1), "r"(c2) : "memory");
}
__device__ __forceinline__ void tma_store3(const CUtensorMap* tm, int c0, int c1, int c2, uint32_t src) {
  asm volatile("cp.async.bulk.tensor.3d.global.shared::cta.bulk_group [%0, {%2, %3, %4}], [%1];"
               :: "l"(tm), "r"(src), "r"(c0), "r"(c1), "r"(c2) : "memory");
}
__device__ __forceinline__ void wg_fence() { asm volatile("wgmma.fence.sync.aligned;" ::: "memory"); }
__device__ __forceinline__ void wg_commit() { asm volatile("wgmma.commit_group.sync.aligned;" ::: "memory"); }
template <int N> __device__ __forceinline__ void wg_wait() { asm volatile("wgmma.wait_group.sync.aligned %0;" :: "n"(N) : "memory"); }
template <int N> __device__ __forceinline__ void tie_all(uint32_t (&x)[N]) {
#pragma unroll
  for (int i = 0; i < N; i++) asm volatile("" : "+r"(x[i]) :: "memory");
}
template <int N> __device__ __forceinline__ void tie_all(float (&x)[N]) {
#pragma unroll
  for (int i = 0; i < N; i++) asm volatile("" : "+f"(x[i]) :: "memory");
}
#define R16(C, d) C(d[0]), C(d[1]), C(d[2]), C(d[3]), C(d[4]), C(d[5]), C(d[6]), C(d[7]), C(d[8]), C(d[9]), C(d[10]), C(d[11]), C(d[12]), C(d[13]), C(d[14]), C(d[15])
#define R32(C, d) R16(C, d), R16(C, (d + 16))
#define P16 "{%0,%1,%2,%3,%4,%5,%6,%7,%8,%9,%10,%11,%12,%13,%14,%15}"
#define P32 "{%0,%1,%2,%3,%4,%5,%6,%7,%8,%9,%10,%11,%12,%13,%14,%15,%16,%17,%18,%19,%20,%21,%22,%23,%24,%25,%26,%27,%28,%29,%30,%31}"
template <int SD, int TB, int OFF> __device__ __forceinline__ void rs64(float* d, const uint32_t* a, uint64_t db) {
  if (SD) asm volatile("{.reg .b64 db; add.s64 db, %36, %37; wgmma.mma_async.sync.aligned.m64n64k16.f32.bf16.bf16 " P32 ", {%32,%33,%34,%35}, db, 1, 1, 1, %38;}"
                       : R32("+f", d) : "r"(a[0]), "r"(a[1]), "r"(a[2]), "r"(a[3]), "l"(db), "n"(OFF), "n"(TB));
  else asm volatile("{.reg .b64 db; add.s64 db, %36, %37; wgmma.mma_async.sync.aligned.m64n64k16.f32.bf16.bf16 " P32 ", {%32,%33,%34,%35}, db, 0, 1, 1, %38;}"
                    : R32("=f", d) : "r"(a[0]), "r"(a[1]), "r"(a[2]), "r"(a[3]), "l"(db), "n"(OFF), "n"(TB));
}
template <int SD, int TB, int OFF> __device__ __forceinline__ void rs64h(uint32_t* d, const uint32_t* a, uint64_t db) {
  if (SD) asm volatile("{.reg .b64 db; add.s64 db, %20, %21; wgmma.mma_async.sync.aligned.m64n64k16.f16.f16.f16 " P16 ", {%16,%17,%18,%19}, db, 1, 1, 1, %22;}"
                       : R16("+r", d) : "r"(a[0]), "r"(a[1]), "r"(a[2]), "r"(a[3]), "l"(db), "n"(OFF), "n"(TB));
  else asm volatile("{.reg .b64 db; add.s64 db, %20, %21; wgmma.mma_async.sync.aligned.m64n64k16.f16.f16.f16 " P16 ", {%16,%17,%18,%19}, db, 0, 1, 1, %22;}"
                    : R16("=r", d) : "r"(a[0]), "r"(a[1]), "r"(a[2]), "r"(a[3]), "l"(db), "n"(OFF), "n"(TB));
}
template <int SD, int OFFA, int OFFB> __device__ __forceinline__ void ss32(float* d, uint64_t da, uint64_t db) {
  if (SD) asm volatile("{.reg .b64 da, db; add.s64 da, %16, %18; add.s64 db, %17, %19; wgmma.mma_async.sync.aligned.m64n32k16.f32.f16.f16 " P16 ", da, db, 1, 1, 1, 1, 1;}"
                       : R16("+f", d) : "l"(da), "l"(db), "n"(OFFA), "n"(OFFB));
  else asm volatile("{.reg .b64 da, db; add.s64 da, %16, %18; add.s64 db, %17, %19; wgmma.mma_async.sync.aligned.m64n32k16.f32.f16.f16 " P16 ", da, db, 0, 1, 1, 1, 1;}"
                    : R16("=f", d) : "l"(da), "l"(db), "n"(OFFA), "n"(OFFB));
}
#define KGEN_ASM(SD) "{.reg .b64 da, db; add.s64 da, %32, %33; add.s64 db, %32, %34;\n" \
  "wgmma.mma_async.sync.aligned.m64n64k16.f32.bf16.bf16 " P32 ", da, db, " SD ", 1, 1, 1, 1;}"
template <int KS> __device__ __forceinline__ void kgen_mma(float (&c)[32], uint64_t da) {
  if (KS) asm volatile(KGEN_ASM("1") : R32("+f", c) : "l"(da), "n"(8 * KS), "n"(8 * KS + 512));
  else asm volatile(KGEN_ASM("0") : R32("=f", c) : "l"(da), "n"(8 * KS), "n"(8 * KS + 512));
  if constexpr (KS < 7) kgen_mma<KS + 1>(c, da);
}
__device__ __forceinline__ uint64_t desc_lo(uint32_t a) { return (uint64_t)((a & 0x3FFFF) >> 4); }
__device__ __forceinline__ void stage1(float (&D)[32], const uint32_t (&A1)[8], uint32_t src) {
  const uint64_t du = desc_lo(src) | (128ull << 16) | (32ull << 32) | (2ull << 62);
  rs64<0, 1, 0>(D, A1, du); rs64<1, 1, 64>(D, A1 + 4, du);
}
template <int INV> __device__ __forceinline__ void stage2(uint32_t (&X)[16], const uint32_t (&F)[16], uint32_t cf) {
  constexpr int KS = INV ? 16 : 128, TB = INV ? 0 : 1;
  const uint64_t dc = desc_lo(cf) | (INV ? (8ull << 16) | (64ull << 32) : (64ull << 16) | (8ull << 32));
  rs64h<0, TB, 0>(X, F, dc); rs64h<1, TB, KS>(X, F + 4, dc); rs64h<1, TB, 2 * KS>(X, F + 8, dc); rs64h<1, TB, 3 * KS>(X, F + 12, dc);
}
__device__ __forceinline__ void fwd_mid(uint32_t (&F)[16], const float (&D)[32], const uint32_t (&tc)[4], const uint32_t (&ts)[4]) {
#pragma unroll
  for (int j = 0; j < 4; j++)
#pragma unroll
    for (int b = 0; b < 2; b++) {
      const int i = 4 * j + 16 * b;
      const uint32_t ar = packh(D[i], D[i + 1]), ai = packh(D[i + 2], D[i + 3]);
      F[2 * j + b] = ffma(ar, tc[j], fmul(ai, ts[j]));
      F[8 + 2 * j + b] = ffma(ai, tc[j], fneg(fmul(ar, ts[j])));
    }
}
__device__ __forceinline__ void put_exp(uint32_t a, uint32_t m, int lane) {
  m = __reduce_max_sync(0xffffffffu, max(m & 0x7f80u, (m >> 16) & 0x7f80u));
  if (lane == 0) sts32(a, m);
}
__device__ __forceinline__ uint32_t seq_mag(uint32_t a) {
  const uint4 x = lds128(a), y = lds128(a + 2048);
  return amax2(amax2(amax2(x.x, x.y), amax2(x.z, x.w)), amax2(amax2(y.x, y.y), amax2(y.z, y.w)));
}
__device__ __forceinline__ uint32_t get_exp(uint32_t a) { const uint4 v = lds128(a); return max(max(v.x, v.y), max(v.z, v.w)) >> 7; }
__device__ __forceinline__ void scale_a1(uint32_t (&As)[8], const uint32_t (&A1)[8], uint32_t field) {
#pragma unroll
  for (int i = 0; i < 8; i++) As[i] = hmul2(A1[i], field * 0x00800080u);
}

struct cf { float x, y; };
__device__ __forceinline__ cf cmul(cf a, cf b) { cf r; r.x = fmaf(a.x, b.x, -a.y * b.y); r.y = fmaf(a.x, b.y, a.y * b.x); return r; }
__device__ __forceinline__ cf cexp_p(float lr2, float lt, float p) {
  float m;
  asm("ex2.approx.ftz.f32 %0, %1;" : "=f"(m) : "f"(lr2 * p));
  float t = lt * p;
  t = (t - rintf(t)) * 6.283185307179586f;
  cf r; r.x = m * __cosf(t); r.y = m * __sinf(t); return r;
}
__device__ __forceinline__ void store8(uint32_t a, uint32_t b, const cf (&v)[8]) {
  sts128(a, pack(v[0].x, v[1].x), pack(v[2].x, v[3].x), pack(v[4].x, v[5].x), pack(v[6].x, v[7].x));
  sts128(b, pack(v[0].y, v[1].y), pack(v[2].y, v[3].y), pack(v[4].y, v[5].y), pack(v[6].y, v[7].y));
}
__device__ __forceinline__ void mbar_arrive(uint32_t m) { asm volatile("mbarrier.arrive.shared::cta.b64 _, [%0];" :: "r"(m) : "memory"); }
__device__ __forceinline__ float sigmoidf_(float s) { return __frcp_rn(1.f + __expf(-s)); }

__global__ void __cluster_dims__(CS, 1, 1) __launch_bounds__(NTHREADS, 1) fused_kernel(const __grid_constant__ Params p) {
  extern __shared__ __align__(1024) uint8_t smem[];
  TL_INIT();
  TL(31);
  const int wid = __shfl_sync(0xffffffffu, threadIdx.x >> 5, 0);
  const uint32_t sb = (uint32_t)__cvta_generic_to_shared(smem);
  const uint32_t mb = sb + OFF_MB;
  const int u = wid >> 2, w = wid & 3;
  const int tid = threadIdx.x & 127, lane = tid & 31, g = lane >> 2, t = lane & 3;
  const int cl = blockIdx.x >> 3, rank = blockIdx.x & 7;
  const int ch0 = cl * CPC;
  const int nu = min(5, (DCH - ch0) >> 3);
  const bool act = u < nu;

  if (u == 4 && elect()) {
#pragma unroll
    for (int i = 0; i < 5; i++) mbar_init(mb + 40 * w + 8 * i, w == 3 ? 1 : w == 2 ? 3 : 2);
    if (w == 3) {
      mbar_init(mb + 8 * MB_XQ, 21); mbar_init(mb + 8 * MB_TH, 1); mbar_init(mb + 8 * MB_KV, 1); mbar_init(mb + 8 * MB_CF, 1); mbar_init(mb + 8 * MB_Q2, 9);
    }
    fence_mbinit();
    if (w == 3) {
      mbar_expect(mb + 8 * MB_CF, 12288);
      mbar_expect(mb + 8 * MB_TH, 8192);
      asm volatile("cp.async.bulk.shared::cluster.global.mbarrier::complete_tx::bytes [%0], [%1], %2, [%3];"
                   :: "r"(sb + OFF_YB), "l"(p.tab->thr), "r"(8192), "r"(mb + 8 * MB_TH) : "memory");
      asm volatile("cp.async.bulk.prefetch.L2.global [%0], 12288;" :: "l"(p.tab->mat) : "memory");
      mbar_expect(mb + 8 * MB_XQ, 20480); mbar_expect(mb + 8 * MB_KV, 23040 + 20480); mbar_expect(mb + 8 * MB_Q2, 20480);
    }
#pragma unroll
    for (int i = 0; i < 5; i++) mbar_expect(mb + 40 * w + 8 * i, w == 3 ? 4096 : w == 2 ? 7168 : 3584);
    if (w == 3) { tma_load4(sb + OFF_TQ, &p.tq, ch0, 0, 0, 8 * rank, mb + 8 * MB_XQ); TL(20); }
  }
  __syncwarp();
  uint32_t pla, pai, pcr, pci, pdt, tag = 0;
  uint4 psm;
  {
    const int ch = act ? ch0 + 8 * u + rank : 0, o = ch * NMODE + tid;
    pla = ldraw(p.logA + o); pdt = ldraw(p.logdt + ch); pai = ldraw(p.Aim + o); pcr = ldraw(p.Cre + o); pci = ldraw(p.Cim + o);
    if (w == 1) {
      if (lane < 9) psm = ldg128(lane < 5 ? p.gate_w + (lane < nu ? ch0 + 8 * lane : 0) : p.shift_k + (act ? ch0 + 8 * u : 0) * 4 + 8 * (lane - 5));
      else { psm.x = ldraw(p.Dskip + ch); psm.y = ldraw(p.ssm_D + ch); }
    }
    if (wid == 16 && lane < 2) asm volatile("atom.relaxed.gpu.global.add.u32 %0, [%1], %2;" : "=r"(tag) : "l"(&p.cnt[rank * 32 + lane]), "r"(cl == 0 ? 16 - (NCL - 1) : 1) : "memory");
  }
  cluster_arrive();
  asm volatile("" : "+r"(pla), "+r"(pdt) :: "memory");
  TL(0);

  const uint32_t tab = sb + OFF_T + u * KTAB;
  const int mi = lane >> 3, tq = (lane & 7) >> 1, jj = lane & 1;
  const uint32_t toff = (4 * (2 * mi + jj) + tq) * 80;
  const uint32_t uoff = 16 * (4 * w + (t ^ (w >> 1)));
  auto put = [&](int stage, int dst, uint32_t off, const uint32_t (&v)[4]) {
    sts128(sb + off + (g == rank ? dst + 512 * rank : stage + g * YPITCH), v[0], v[1], v[2], v[3]);
  };
  const int d0 = rank ^ (2 * w), d1 = d0 ^ 1;
  const uint32_t rb0 = mapa(sb, d0), rb1 = mapa(sb, d1);
  auto send = [&](int stage, int pitch, int dst, int mbar) {
    if (elect()) {
      if (w) bulk_dsmem(rb0 + dst, sb + stage + d0 * pitch, rb0 + mbar); else mbar_arrive(sb + mbar);
      bulk_dsmem(rb1 + dst, sb + stage + d1 * pitch, rb1 + mbar);
    }
    __syncwarp();
  };

  uint32_t A1[8], tc[4], ts[4];
  {
    const float dt = bf16r(expf(blo(pdt)));
    const float lr2 = (-bf16r(expf(blo(pla))) * dt) * 1.4426950408889634f;
    const float lt = (blo(pai) * dt) * 0.15915494309189535f;
    const uint32_t tim = sb + OFF_IM + (u < 2 ? 3 + u : u - 2) * KTAB;
    const uint32_t row = tab + tid * 16, rim = tim + tid * 16;
    const cf w1 = cexp_p(lr2, lt, 8.f);
    cf z1 = cexp_p(lr2, lt, 1.f), Z = cexp_p(lr2, lt, 256.f);
    if (lr2 != 123.f) TL(16);
    TL(12);
    {
      cf v[8];
      v[0].x = 1.f; v[0].y = 0.f; v[1] = w1; v[2] = cmul(w1, w1); v[3] = cmul(v[2], w1);
      const cf w4 = cmul(v[2], v[2]);
      v[4] = w4; v[5] = cmul(v[1], w4); v[6] = cmul(v[2], w4); v[7] = cmul(v[3], w4);
      const cf w8 = cmul(w4, w4);
      store8(row, rim, v);
#pragma unroll
      for (int k = 1; k < 4; k++) {
#pragma unroll
        for (int i = 0; i < 8; i++) v[i] = (k == 1 && i == 0) ? w8 : cmul(v[i], w8);
        store8(row + 2048 * k, rim + 2048 * k, v);
      }
    }
    cluster_wait();
    mbar_wait(mb + 8 * MB_TH);
    {
      const uint4 x = lds128(sb + OFF_YB + 16 * tid), y = lds128(sb + OFF_YB + 2048 + 16 * tid), a = lds128(sb + OFF_YB + 4096 + 16 * tid), b = lds128(sb + OFF_YB + 6144 + 16 * tid);
      A1[0] = x.x; A1[1] = x.y; A1[2] = x.z; A1[3] = x.w; A1[4] = y.x; A1[5] = y.y; A1[6] = y.z; A1[7] = y.w;
      tc[0] = a.x; tc[1] = a.y; tc[2] = a.z; tc[3] = a.w; ts[0] = b.x; ts[1] = b.y; ts[2] = b.z; ts[3] = b.w;
    }
    if (wid == 16 && lane == 0) sts32(mb + 8 * MB_TAG, tag);
    __syncwarp();
    if (lane == 0) mbar_arrive(mb + 8 * MB_XQ);
    if (u == 1) {
      float z0_ = 0.f, z1_ = 0.f, z2_ = 0.f, z3_ = 0.f;
      asm volatile("mma.sync.aligned.m16n8k8.row.col.f32.bf16.bf16.f32 {%0,%1,%2,%3}, {%4,%4}, {%4}, {%0,%1,%2,%3};"
                   : "+f"(z0_), "+f"(z1_), "+f"(z2_), "+f"(z3_) : "r"(pla >> 16));
      pcr += __float_as_uint(z0_);
      if (w == 0 && elect()) {
        const uint32_t o = blockIdx.x * 9856u, n = min(9856u, SEQ * DCH - o) * 2;
        asm volatile("cp.async.bulk.prefetch.L2.global [%0], %1;" :: "l"(p.ssm_k + o), "r"(n) : "memory");
        asm volatile("cp.async.bulk.prefetch.L2.global [%0], %1;" :: "l"(p.k + o), "r"(n) : "memory");
        asm volatile("cp.async.bulk.prefetch.L2.global [%0], %1;" :: "l"(p.v + o), "r"(n) : "memory");
      }
      __syncwarp();
      TL(8);
    }
    {
      z1.y = -z1.y; Z.y = -Z.y;
      const cf z2 = cmul(z1, z1);
      cf h[8], v[8];
      h[0].x = 2.f * blo(pcr) * dt; h[0].y = -2.f * blo(pci) * dt;
      h[1] = cmul(h[0], z1);
#pragma unroll
      for (int i = 2; i < 8; i++) h[i] = cmul(h[i - 2], z2);
      store8(row + 4 * 2048, rim + 4 * 2048, h);
      const cf h8 = cmul(h[6], z2);
      v[0] = cmul(h[0], Z); v[2] = cmul(h[2], Z); v[3] = cmul(h[4], Z); v[6] = cmul(h[6], Z); v[7] = cmul(h8, Z);
      v[1] = v[0]; v[4] = v[5] = v[3];
      store8(row + 5 * 2048, rim + 5 * 2048, v);
      h[0] = cmul(v[0], Z); h[1] = cmul(v[3], Z); h[3] = cmul(v[7], Z); h[4] = cmul(h[0], Z); h[5] = cmul(h[1], Z); h[7] = cmul(h[3], Z);
      h[2] = h[1]; h[6] = h[5];
      store8(row + 6 * 2048, rim + 6 * 2048, h);
      const cf Z2 = cmul(Z, Z);
      v[0] = cmul(h[0], Z2); v[1] = cmul(h[3], Z2); v[2] = cmul(h[4], Z2); v[3] = cmul(h[7], Z2);
#pragma unroll
      for (int i = 4; i < 8; i++) v[i] = cmul(v[i - 4], Z2);
      store8(row + 7 * 2048, rim + 7 * 2048, v);
    }
    TL(17);
    if (w == 1 && lane < 10) sts128(sb + OFF_SP + 160 * u + 16 * lane, psm.x, psm.y, psm.z, psm.w);
    mbar_wait(mb + 8 * MB_XQ);
    TL(18);
    {
      uint32_t x0[4], x1[4];
      ldsm4t(x0, sb + OFF_TQ + w * 2560 + toff + 16 * u);
      ldsm4t(x1, sb + OFF_TQ + (w + 4) * 2560 + toff + 16 * u);
      put(OFF_YB + 8 * u * YPITCH, OFF_UX + u * 4096, uoff, x0);
      put(OFF_YB + 8 * u * YPITCH, OFF_UX + u * 4096, (uoff ^ 32) + 256, x1);
    }
    TL(3);
    fence_async();
    bar_sync(NB_WG0 + u, 128);
    TL(4);
    if (u >= 3) {
      float s0 = 0.f;
#pragma unroll
      for (int j = 0; j < 5; j++) {
        const uint4 gw = lds128(sb + OFF_SP + 160 * u + 16 * j), x = lds128(sb + OFF_TQ + (tid + 128 * (u - 3)) * 80 + 16 * j);
        const uint32_t m0 = hmul2(x.x, gw.x), m1 = hmul2(x.y, gw.y), m2 = hmul2(x.z, gw.z), m3 = hmul2(x.w, gw.w);
        s0 += ((blo(m0) + bhi(m0)) + (blo(m1) + bhi(m1))) + ((blo(m2) + bhi(m2)) + (blo(m3) + bhi(m3)));
      }
      tag = (lds64(mb + 8 * MB_TAG).x >> 4) + 1;
      asm volatile("st.relaxed.gpu.global.u64 [%0], %1;" :: "l"(p.part + cl * SEQ + rank * 256 + 8 * (8 * t + g) + w + 4 * (u - 3)),
                   "l"(((uint64_t)tag << 32) | __float_as_uint(s0)) : "memory");
    }
    TL(7);
    if (u) bar_sync(NB_ORD + u - 1, 256);
    TL(13);
    float c[32];
    wg_fence();
    kgen_mma<0>(c, desc_lo(tab) | ((uint64_t)((tim - tab) >> 4) << 16) | (64ull << 32));
    wg_commit();
    if (u < 4) bar_arrive(NB_ORD + u, 256);
    send(OFF_YB + 8 * u * YPITCH, YPITCH, OFF_UX + u * 4096 + 512 * rank, OFF_MB + 8 * (MB_UX + u));
    TL(14);
    wg_wait<0>(); tie_all(c);
    TL(26);
    cluster_arrive();
    if (wid == 17) {
      bar_sync(NB_LD, 640);
      if (elect()) {
        tma_load4(sb + OFF_TK, &p.tk, ch0, 0, 0, 8 * rank - 1, mb + 8 * MB_KV);
        tma_load4(sb + OFF_TV, &p.tv, ch0, 0, 0, 8 * rank, mb + 8 * MB_KV);
      }
      __syncwarp();
    } else {
      bar_arrive(NB_LD, 640);
    }
    bar_sync(NB_WG0 + u, 128);
    if (wid == 1 && elect())
      asm volatile("cp.async.bulk.shared::cluster.global.mbarrier::complete_tx::bytes [%0], [%1], %2, [%3];"
                   :: "r"(sb + OFF_CF), "l"(p.tab->mat), "r"(12288), "r"(mb + 8 * MB_CF) : "memory");
    __syncwarp();
    const uint32_t k0 = pack(c[0] + c[6], c[1] + c[7]), k1 = pack(c[8] + c[14], c[9] + c[15]);
    const uint32_t k2 = pack(c[16] + c[22], c[17] + c[23]), k3 = pack(c[24] + c[30], c[25] + c[31]);
    const uint32_t ka = tab + 16 * (8 * w + (g ^ w));
    sts32(ka + 4 * t, k0);
    sts32(ka + 512 + 4 * t, k1);
    sts64(ka + 1024 + 512 * (t >> 1) + 8 * (t & 1), prmt(k2, 0, 0x1010), (t & 1) ? prmt(k2, 0, 0x3232) : k2);
    const uint32_t lo = prmt(k3, 0, 0x1010), hi = prmt(k3, 0, 0x3232);
    sts128(ka + 2048 + 512 * t, lo, lo, (g & 1) ? hi : k3, hi);
    put_exp(sb + OFF_MX + u * 64 + 4 * w, amax2(amax2(k0, k1), amax2(k2, k3)), lane);
    TL(15);
    fence_async();
    bar_sync(NB_WG0 + u, 128);
  }

#pragma unroll
  for (int isA = 0; isA < 2; isA++) {
    {
      TL(1 + isA);
      const uint32_t usrc = isA ? tab + T_UKV : sb + OFF_UX + u * 4096;
      const uint32_t mxa = sb + OFF_MX + u * 64 + 32 * isA;
      const uint32_t pd = lds16(sb + OFF_SP + 160 * u + 144 + 4 * isA);
      float D[32];
      uint32_t As[8], F[16], H[16], X[16];
      const uint32_t eh = min(max((int)get_exp(mxa), (int)((pd >> 7) & 0xff) - 5), 240);
      scale_a1(As, A1, 248 - eh);
      wg_fence();
      stage1(D, As, isA ? tab + T_HA : tab);
      wg_commit();
      wg_wait<0>(); tie_all(D);
      fwd_mid(F, D, tc, ts);
      if (!isA) mbar_wait(mb + 8 * MB_CF);
      wg_fence();
      stage2<0>(H, F, sb + OFF_CF);
      wg_commit();
      if (!isA && w == 1 && elect()) {
        tma_load4(tab + T_HA, &p.th, 0, 0, 5 * cl + u, rank, mb + 8 * (MB_HA + u));
        if (u == 4) tma_load3(sb + OFF_Q2, &p.tq2, ch0, 8 * rank, 0, mb + 8 * MB_Q2);
      }
      __syncwarp();
      mbar_wait(mb + 8 * ((isA ? MB_UKV : MB_UX) + u));
      TL(5 + isA);
      put_exp(mxa + 16 + 4 * w, seq_mag(usrc + 16 * tid), lane);
      bar_sync(NB_WG0 + u, 128);
      const uint32_t eu = min(get_exp(mxa + 16), 240u);
      scale_a1(As, A1, 250 - eu);
      wg_wait<0>(); tie_all(H);
      wg_fence();
      stage1(D, As, usrc);
      wg_commit();
      wg_wait<0>(); tie_all(D);
      fwd_mid(F, D, tc, ts);
      wg_fence();
      stage2<0>(X, F, sb + OFF_CF);
      wg_commit();
      {
        const float dsk = blo(pd) * __uint_as_float((248 - eh) << 23);
        const uint32_t d2 = packh(dsk, dsk);
#pragma unroll
        for (int j = 0; j < 4; j++) H[2 * j] = U2(__hadd2(H2(H[2 * j]), H2(d2)));
      }
      wg_wait<0>(); tie_all(X);
#pragma unroll
      for (int j = 0; j < 4; j++) {
        const uint32_t h0r = H[2 * j], h1r = H[2 * j + 1], h0i = H[8 + 2 * j], h1i = H[9 + 2 * j];
        const uint32_t x0r = X[2 * j], x1r = X[2 * j + 1], x0i = X[8 + 2 * j], x1i = X[9 + 2 * j];
        F[2 * j] = ffma(x0r, h0r, fneg(fmul(x0i, h0i)));
        F[8 + 2 * j] = ffma(x0r, h0i, fmul(x0i, h0r));
        F[2 * j + 1] = ffma(x1r, h0r, ffma(fneg(x1i), h0i, ffma(x0r, h1r, fneg(ffma(x0i, h1i, F[8 + 2 * j])))));
        F[9 + 2 * j] = ffma(x1r, h0i, ffma(x1i, h0r, ffma(x0r, h1i, ffma(x0i, h1r, F[2 * j]))));
      }
      wg_fence();
      stage2<1>(H, F, sb + OFF_CF);
      wg_commit();
      wg_wait<0>(); tie_all(H);
      {
        const uint32_t va = tab + (16 * w + (lane & 15)) * 128;
        const int vx = (lane >> 4) ^ (lane & 7);
#pragma unroll
        for (int j = 0; j < 4; j++) {
          uint32_t V[4];
#pragma unroll
          for (int b = 0; b < 2; b++) {
            const uint32_t er = H[2 * j + b], ei = H[8 + 2 * j + b];
            V[2 * b] = ffma(er, tc[j], fneg(fmul(ei, ts[j])));
            V[2 * b + 1] = ffma(ei, tc[j], fmul(er, ts[j]));
          }
          stsm4(va + ((vx ^ (2 * j)) << 4), V);
        }
      }
      uint64_t ga[NCL];
      const int slot = tid + 128 * (u & 1);
      const uint2* gp = p.part + rank * 256 + slot;
      auto gload = [&]() {
#pragma unroll
        for (int k = 0; k < NCL; k++) asm volatile("ld.relaxed.gpu.global.u64 %0, [%1];" : "=l"(ga[k]) : "l"(gp + k * SEQ) : "memory");
      };
      if (!isA) {
        cluster_wait();
        mbar_wait(mb + 8 * MB_KV);
        TL(21);
        const uint32_t hoff = (4 * (4 + 2 * (mi & 1) + jj) + ((tq + 3) & 3)) * 80 + (tq ? 2560 : 0) + 16 * u;
        uint32_t E[2][6], V[2][4];
        const uint2 psw = lds64(sb + OFF_SP + 160 * u + 80 + 8 * g);
#pragma unroll
        for (int hf = 0; hf < 2; hf++) {
          const int ah = 4 * hf + w;
          uint32_t K[4];
          ldsm4t(K, sb + OFF_TK + (ah + 1) * 2560 + toff + 16 * u);
          ldsm2t(E[hf][0], E[hf][1], sb + OFF_TK + ah * 2560 + hoff);
          ldsm4t(V[hf], sb + OFF_TV + ah * 2560 + toff + 16 * u);
          E[hf][2] = K[0]; E[hf][3] = K[1]; E[hf][4] = K[2]; E[hf][5] = K[3];
        }
        const uint32_t w0 = prmt(psw.x, 0, 0x1010), w1 = prmt(psw.x, 0, 0x3232), w2 = prmt(psw.y, 0, 0x1010), w3 = prmt(psw.y, 0, 0x3232);
        uint32_t o[2][4];
#pragma unroll
        for (int hf = 0; hf < 2; hf++) {
          uint32_t O[5];
#pragma unroll
          for (int i = 0; i < 5; i++) O[i] = prmt(E[hf][i], E[hf][i + 1], 0x5432);
#pragma unroll
          for (int i = 0; i < 4; i++) {
            o[hf][i] = hmul2(hfma2(E[hf][i + 2], w0, hfma2(O[i + 1], w1, hfma2(E[hf][i + 1], w2, hmul2(O[i], w3)))), V[hf][i]);
          }
          put(OFF_YA + 8 * u * YPITCH, OFF_T + u * KTAB + T_UKV, hf ? (uoff ^ 32) + 256 : uoff, o[hf]);
        }
        mbar_wait(mb + 8 * (MB_HA + u));
        put_exp(mxa + 32 + 4 * w, seq_mag(tab + T_HA + 16 * tid), lane);
        TL(22);
      }
      fence_async();
      bar_sync(NB_WG0 + u, 128);
      float O[16];
      {
        const uint64_t dv = desc_lo(tab) | (1ull << 16) | (64ull << 32) | (1ull << 62);
        const uint64_t dl = desc_lo(sb + OFF_CL) | (32ull << 16) | (8ull << 32);
        wg_fence();
        ss32<0, 0, 0>(O, dv, dl); ss32<1, 128, 64>(O, dv, dl); ss32<1, 256, 128>(O, dv, dl); ss32<1, 384, 192>(O, dv, dl);
        wg_commit();
      }
      if (!isA) {
        send(OFF_YA + 8 * u * YPITCH, YPITCH, OFF_T + u * KTAB + T_UKV + 512 * rank, OFF_MB + 8 * (MB_UKV + u));
        if (u < 2) gload();
      }
      wg_wait<0>(); tie_all(O);
      {
        const uint32_t co = ((8 * w + g) ^ (2 * t)) * 16;
        const int yo = (isA ? OFF_YA : OFF_YB) + (8 * u + rank) * YPITCH, ym = OFF_MB + 8 * (MB_Y + u);
        const uint32_t us = min(max((int)(eu + eh) - 127, 0), 254) * 0x00800080u;
        const uint32_t a0 = hmul2(pack(O[0], O[1]), us), a1 = hmul2(pack(O[4], O[5]), us), a2 = hmul2(pack(O[8], O[9]), us), a3 = hmul2(pack(O[12], O[13]), us);
        const uint32_t b0 = hmul2(pack(O[2], O[3]), us), b1 = hmul2(pack(O[6], O[7]), us), b2 = hmul2(pack(O[10], O[11]), us), b3 = hmul2(pack(O[14], O[15]), us);
        sts128((t == rank ? sb + yo : usrc + t * 512) + co, a0, a1, a2, a3);
        sts128((t + 4 == rank ? sb + yo : usrc + t * 512 + 2048) + co, b0, b1, b2, b3);
        fence_async();
        bar_sync(NB_WG0 + u, 128);
        send(usrc - sb, 512, yo, ym);
      }
      TL(9 + isA);
      if (!isA && u < 2) {
        tag = (lds64(mb + 8 * MB_TAG).x >> 4) + 1;
        float s;
        bool ok;
#pragma unroll 1
        for (int it = 0;; it++) {
          ok = true; s = 0.f;
#pragma unroll
          for (int k = 0; k < NCL; k++) { ok = ok && (uint32_t)(ga[k] >> 32) == tag; s += __uint_as_float((uint32_t)ga[k]); }
          if (ok || it == 4000) break;
          gload();
        }
        if (!ok) {
          const uint32_t* xr = (const uint32_t*)(p.q + (size_t)(rank * 256 + 32 * (slot & 7) + (slot >> 3)) * DCH);
          const uint32_t* gr = (const uint32_t*)p.gate_w;
          s = 0.f;
    #pragma unroll 1
          for (int k = 0; k < DCH / 2; k++) { const uint32_t m = hmul2(__ldg(xr + k), __ldg(gr + k)); s += blo(m) + bhi(m); }
        }
        const float g0 = bf16r(sigmoidf_(bf16r(s)));
        sts64(sb + OFF_GB + 8 * slot, pack(g0, g0), pack(1.f - g0, 1.f - g0));
        __syncwarp();
        if (lane == 0) mbar_arrive(mb + 8 * MB_Q2);
      }
    }
  }

  {
    mbar_wait(mb + 8 * MB_Q2);
    uint2 gg[2][4];
    uint32_t qv[2][4];
#pragma unroll
    for (int hh = 0; hh < 2; hh++)
#pragma unroll
      for (int i = 0; i < 4; i++) gg[hh][i] = lds64(sb + OFF_GB + 8 * (64 * w + 32 * hh + 8 * i + g));
    const uint32_t qa = sb + OFF_Q2 + (64 * w + lane) * 80 + 16 * u;
    ldsm4(qv[0], qa);
    ldsm4(qv[1], qa + 2560);
    TL(24);
    mbar_wait(mb + 8 * (MB_Y + u));
    uint32_t ya[2][4], yb[2][4];
#pragma unroll
    for (int hh = 0; hh < 2; hh++) {
      const uint32_t yo = (8 * u + (lane & 7)) * YPITCH + ((8 * w + 4 * hh + (lane >> 3)) ^ (2 * (rank & 3))) * 16;
      ldsm4t(ya[hh], sb + OFF_YA + yo); ldsm4t(yb[hh], sb + OFF_YB + yo);
    }
#pragma unroll
    for (int hh = 0; hh < 2; hh++) {
      uint32_t o[4];
#pragma unroll
      for (int i = 0; i < 4; i++) o[i] = hadd2(hmul2(gg[hh][i].x, hmul2(qv[hh][i], ya[hh][i])), hmul2(gg[hh][i].y, yb[hh][i]));
      stsm4(qa + 2560 * hh, o);
    }
    TL(25);
  }
  cluster_arrive();
  bar_sync(NB_ROW0 + w, 160);
  {
    uint4 v[2];
#pragma unroll
    for (int k = 0; k < 2; k++) {
      const int i = 64 * u + 32 * k + lane, sl = (i * 205) >> 10, cc = i - 5 * sl;
      v[k] = lds128(sb + OFF_Q2 + (64 * w + 8 * (sl & 7) + (sl >> 3)) * 80 + cc * 16);
    }
#pragma unroll
    for (int k = 0; k < 2; k++) {
      const int i = 64 * u + 32 * k + lane, sl = (i * 205) >> 10, cc = i - 5 * sl;
      if (cc < nu)
        asm volatile("st.global.v4.u32 [%0], {%1,%2,%3,%4};" :: "l"(p.out + (size_t)(256 * rank + 32 * (sl >> 3) + 8 * w + (sl & 7)) * DCH + ch0 + 8 * cc),
                     "r"(v[k].x), "r"(v[k].y), "r"(v[k].z), "r"(v[k].w) : "memory");
    }
  }
  cluster_wait();
  TL(27);
  TL_DUMP();
}

typedef CUresult (*EncodeFn)(CUtensorMap*, CUtensorMapDataType, cuuint32_t, void*, const cuuint64_t*, const cuuint64_t*,
                             const cuuint32_t*, const cuuint32_t*, CUtensorMapInterleave, CUtensorMapSwizzle,
                             CUtensorMapL2promotion, CUtensorMapFloatOOBfill);

void encode(EncodeFn fn, CUtensorMap* tm, const void* ptr, int nd, const cuuint64_t* dims, const cuuint64_t* strides,
            const cuuint32_t* box, CUtensorMapSwizzle swz) {
  cuuint32_t es[4] = {1, 1, 1, 1};
  fn(tm, CU_TENSOR_MAP_DATA_TYPE_BFLOAT16, nd, const_cast<void*>(ptr), dims, strides, box, es, CU_TENSOR_MAP_INTERLEAVE_NONE,
     swz, CU_TENSOR_MAP_L2_PROMOTION_L2_128B, CU_TENSOR_MAP_FLOAT_OOB_FILL_NONE);
}
void map1(EncodeFn fn, CUtensorMap* tm, const void* ptr, int nhi) {
  const cuuint64_t dims[4] = {DCH, 4, 8, SEQ / 32}, strides[3] = {8 * DCH * 2, DCH * 2, 32 * DCH * 2};
  const cuuint32_t box[4] = {CPC, 4, 8, (cuuint32_t)nhi};
  encode(fn, tm, ptr, 4, dims, strides, box, CU_TENSOR_MAP_SWIZZLE_NONE);
}
void map2(EncodeFn fn, CUtensorMap* tm, const void* ptr, int nr) {
  const cuuint64_t dims[3] = {DCH, SEQ / 32, 32}, strides[2] = {32 * DCH * 2, DCH * 2};
  const cuuint32_t box[3] = {CPC, 8, (cuuint32_t)nr};
  encode(fn, tm, ptr, 3, dims, strides, box, CU_TENSOR_MAP_SWIZZLE_NONE);
}

}

extern "C" void kernel_launch(void* const* d_in, const int* in_sizes, int n_in, void* d_out, int out_size) {
  (void)in_sizes; (void)n_in; (void)out_size;
  static EncodeFn fn = nullptr;
  static void *tab = nullptr, *cnt = nullptr, *part = nullptr;
  if (!fn) {
    cudaGetSymbolAddress(&tab, d_tab);
    cudaGetSymbolAddress(&cnt, g_cnt);
    cudaGetSymbolAddress(&part, g_part);
    cudaDriverEntryPointQueryResult qr;
    cudaGetDriverEntryPoint("cuTensorMapEncodeTiled", (void**)&fn, cudaEnableDefault, &qr);
    cudaFuncSetAttribute(fused_kernel, cudaFuncAttributeMaxDynamicSharedMemorySize, SMEM_BYTES);
  }
  Params p;
  map1(fn, &p.tq, d_in[0], 8);
  map1(fn, &p.tk, d_in[1], 9);
  map1(fn, &p.tv, d_in[2], 8);
  map2(fn, &p.tq2, d_in[0], 32);
  p.out = (__nv_bfloat16*)d_out;
  {
    const cuuint64_t dims[4] = {32, SEQ / 32, DCH / 8, 8}, strides[3] = {64, 8 * SEQ * 2, SEQ * 2};
    const cuuint32_t box[4] = {32, 64, 1, 1};
    encode(fn, &p.th, d_in[4], 4, dims, strides, box, CU_TENSOR_MAP_SWIZZLE_64B);
  }
  p.tab = (const Tables*)tab;
  p.cnt = (unsigned*)cnt;
  p.part = (uint2*)part;
  p.tl = nullptr;
  p.q = (const __nv_bfloat16*)d_in[0];
  p.k = (const __nv_bfloat16*)d_in[1];
  p.v = (const __nv_bfloat16*)d_in[2];
  p.ssm_k = (const __nv_bfloat16*)d_in[4];
  p.shift_k = (const __nv_bfloat16*)d_in[3];
  p.ssm_D = (const __nv_bfloat16*)d_in[5];
  p.logA = (const __nv_bfloat16*)d_in[7];
  p.Aim = (const __nv_bfloat16*)d_in[8];
  p.Cre = (const __nv_bfloat16*)d_in[9];
  p.Cim = (const __nv_bfloat16*)d_in[10];
  p.logdt = (const __nv_bfloat16*)d_in[11];
  p.Dskip = (const __nv_bfloat16*)d_in[12];
  p.gate_w = (const __nv_bfloat16*)d_in[13];
  fused_kernel<<<NCL * CS, NTHREADS, SMEM_BYTES, cudaStreamPerThread>>>(p);
}
```

```cpp
#include <cuda_runtime.h>
#include <cuda_bf16.h>
#include <cuda_fp16.h>
#include <cuda.h>
#include <stdint.h>

#define TIMELINE 0
#define TLHI 0

namespace {

constexpr int SEQ = 2048, DCH = 576, NMODE = 128;
constexpr int CS = 8, CPC = 40, NCL = 15, NTHREADS = 640;

constexpr int YPITCH = 528;
constexpr int KTAB = 16384;
constexpr int OFF_T = 0;
constexpr int T_UKV = 8192, T_HA = 12288;
constexpr int OFF_UX = 5 * KTAB;
constexpr int OFF_IM = OFF_UX + 20480;
constexpr int OFF_Q2 = OFF_IM;
constexpr int OFF_GB = OFF_Q2 + 20480;
constexpr int OFF_TV = OFF_IM + 3 * KTAB - 20480;
constexpr int OFF_CF = OFF_IM + 3 * KTAB;
constexpr int OFF_CL = OFF_CF + 8192;
constexpr int OFF_TK = OFF_CL + 4096;
constexpr int OFF_TQ = OFF_TK + 23040;
constexpr int OFF_YA = OFF_TQ;
constexpr int OFF_YB = OFF_TQ + 21120;
constexpr int OFF_MX = OFF_YB + 40 * YPITCH;
constexpr int OFF_SP = OFF_MX + 320;
constexpr int OFF_MB = OFF_SP + 560;
constexpr int OFF_TL = OFF_MB + 32 * 8;
constexpr int SMEM_BYTES = OFF_TL + (TIMELINE ? 1280 : 0);
static_assert(SMEM_BYTES <= 232448 && OFF_IM + 5 * KTAB <= OFF_TQ, "smem");
static_assert((OFF_TQ & 127) == 0 && (OFF_TK & 127) == 0 && (OFF_TV & 127) == 0 && (OFF_MB & 7) == 0 && (OFF_MX & 15) == 0, "align");

enum { MB_UX = 0, MB_UKV = 5, MB_Y = 10, MB_HA = 15, MB_XQ = 20, MB_KV = 21, MB_CF = 22, MB_Q2 = 23, MB_TH = 24, MB_TAG = 25 };
enum { NB_WG0 = 1, NB_ROW0 = 6, NB_ORD = 6, NB_K0 = 10, NB_LD = 11 };

constexpr double cos_turn(int m, int n) {
  m &= n - 1;
  if (m > n / 2) m = n - m;
  double sgn = 1.0;
  if (m > n / 4) { m = n / 2 - m; sgn = -1.0; }
  if (m == n / 4) return 0.0;
  const double x = 6.283185307179586476925 * m / n;
  double term = 1.0, sum = 1.0;
  for (int k = 1; k < 14; k++) { term *= -x * x / ((2 * k - 1) * (2 * k)); sum += term; }
  return sgn * sum;
}
constexpr uint32_t bf16_bits(double v) {
  if (v == 0.0) return 0;
  uint32_t sgn = 0;
  if (v < 0) { sgn = 0x8000; v = -v; }
  int e = 127;
  while (v < 1.0) { v *= 2.0; e--; }
  while (v >= 2.0) { v *= 0.5; e++; }
  const double f = v * 128.0;
  int m = (int)f;
  if (f - m > 0.5 || (f - m == 0.5 && (m & 1))) m++;
  return sgn | (uint32_t)((e << 7) + (m - 128));
}
constexpr uint32_t f16_bits(double v) {
  if (v == 0.0) return 0;
  uint32_t sgn = 0;
  if (v < 0) { sgn = 0x8000; v = -v; }
  int e = 15;
  while (v < 1.0) { v *= 2.0; e--; }
  const double f = v * 1024.0;
  int m = (int)f;
  if (f - m > 0.5 || (f - m == 0.5 && (m & 1))) m++;
  return sgn | (uint32_t)((e << 10) + (m - 1024));
}
constexpr uint32_t pair_bits(double lo, double hi) { return bf16_bits(lo) | (bf16_bits(hi) << 16); }
constexpr uint32_t pair_h(double lo, double hi) { return f16_bits(lo) | (f16_bits(hi) << 16); }
struct alignas(128) Tables {
  uint32_t mat[3072];
  uint32_t thr[4][128][4];
};
constexpr Tables make_tables() {
  Tables T{};
  for (int q = 0; q < 768; q++) {
    int m0 = 0, d0 = 0, d1 = 0;
    if (q < 512) {
      const int r = (q >> 6) * 8 + (q & 7), cc = (q >> 3) & 7;
      d0 = 4 * (r & 31); d1 = 2 * d0;
      m0 = 8 * (cc & 3) * d0 + ((r >> 5) == (cc >> 2) ? 0 : (r >> 5) ? 96 : 32);
    } else {
      const int r = ((q - 512) >> 5) * 8 + (q & 7), pc = (q >> 3) & 3;
      d0 = 4 * (8 * (r >> 4) + (r & 7)) + 1; d1 = 8 * d0;
      m0 = 2 * pc * d0 + ((r & 8) ? 32 : 0);
    }
    for (int e = 0; e < 4; e++) T.mat[4 * q + e] = pair_h(cos_turn(m0 + e * d1, 128), cos_turn(m0 + e * d1 + d0, 128));
  }
  for (int tid = 0; tid < 128; tid++) {
    const int kk = 4 * (tid >> 2) + 1, t = tid & 3;
    for (int q = 0; q < 4; q++) {
      const int m = (8 * q + 2 * t) * kk;
      T.thr[q >> 1][tid][2 * (q & 1)] = pair_bits(cos_turn(m, 128), cos_turn(m + kk, 128));
      T.thr[q >> 1][tid][2 * (q & 1) + 1] = pair_bits(cos_turn(m + 32, 128), cos_turn(m + kk + 32, 128));
      T.thr[2][tid][q] = pair_h(cos_turn(m, 4096), cos_turn(m + kk, 4096));
      T.thr[3][tid][q] = pair_h(cos_turn(m + 3072, 4096), cos_turn(m + kk + 3072, 4096));
    }
  }
  return T;
}
__device__ const Tables d_tab = make_tables();

struct Params {
  const __nv_bfloat16 *logA, *Aim, *Cre, *Cim, *logdt;
  const Tables* tab;
  unsigned* cnt;
  const __nv_bfloat16 *Dskip, *shift_k, *ssm_D, *gate_w, *q, *k, *v, *ssm_k;
  uint2* part;
  __nv_bfloat16* out;
  unsigned* tl;
  CUtensorMap tq, tk, tv, th, tq2;
};

__device__ uint2 g_part[NCL * SEQ];
__device__ unsigned g_cnt[CS * 32];
#define TL(i) do {} while (0)
#define TL_INIT() do {} while (0)
#define TL_DUMP() do {} while (0)

__device__ __forceinline__ uint32_t lds16(uint32_t a) { uint32_t v; asm volatile("ld.shared.u16 %0, [%1];" : "=r"(v) : "r"(a) : "memory"); return v; }
__device__ __forceinline__ uint2 lds64(uint32_t a) { uint2 v; asm volatile("ld.shared.v2.u32 {%0,%1}, [%2];" : "=r"(v.x), "=r"(v.y) : "r"(a) : "memory"); return v; }
__device__ __forceinline__ uint4 lds128(uint32_t a) { uint4 v; asm volatile("ld.shared.v4.u32 {%0,%1,%2,%3}, [%4];" : "=r"(v.x), "=r"(v.y), "=r"(v.z), "=r"(v.w) : "r"(a) : "memory"); return v; }
__device__ __forceinline__ void sts16(uint32_t a, uint32_t v) { asm volatile("st.shared.u16 [%0], %1;" :: "r"(a), "r"(v) : "memory"); }
__device__ __forceinline__ void sts32(uint32_t a, uint32_t v) { asm volatile("st.shared.u32 [%0], %1;" :: "r"(a), "r"(v) : "memory"); }
__device__ __forceinline__ void sts64(uint32_t a, uint32_t x, uint32_t y) { asm volatile("st.shared.v2.u32 [%0], {%1,%2};" :: "r"(a), "r"(x), "r"(y) : "memory"); }
__device__ __forceinline__ void sts128(uint32_t a, uint32_t x, uint32_t y, uint32_t z, uint32_t w) { asm volatile("st.shared.v4.u32 [%0], {%1,%2,%3,%4};" :: "r"(a), "r"(x), "r"(y), "r"(z), "r"(w) : "memory"); }
__device__ __forceinline__ void ldsm4t(uint32_t (&r)[4], uint32_t a) { asm volatile("ldmatrix.sync.aligned.m8n8.x4.trans.shared.b16 {%0,%1,%2,%3}, [%4];" : "=r"(r[0]), "=r"(r[1]), "=r"(r[2]), "=r"(r[3]) : "r"(a) : "memory"); }
__device__ __forceinline__ void ldsm2t(uint32_t& r0, uint32_t& r1, uint32_t a) { asm volatile("ldmatrix.sync.aligned.m8n8.x2.trans.shared.b16 {%0,%1}, [%2];" : "=r"(r0), "=r"(r1) : "r"(a) : "memory"); }
__device__ __forceinline__ void ldsm4(uint32_t (&r)[4], uint32_t a) { asm volatile("ldmatrix.sync.aligned.m8n8.x4.shared.b16 {%0,%1,%2,%3}, [%4];" : "=r"(r[0]), "=r"(r[1]), "=r"(r[2]), "=r"(r[3]) : "r"(a) : "memory"); }
__device__ __forceinline__ void stsm4(uint32_t a, const uint32_t (&r)[4]) { asm volatile("stmatrix.sync.aligned.m8n8.x4.shared.b16 [%0], {%1,%2,%3,%4};" :: "r"(a), "r"(r[0]), "r"(r[1]), "r"(r[2]), "r"(r[3]) : "memory"); }
__device__ __forceinline__ uint32_t pack(float lo, float hi) { uint32_t r; asm("cvt.rn.bf16x2.f32 %0, %1, %2;" : "=r"(r) : "f"(hi), "f"(lo)); return r; }
__device__ __forceinline__ float blo(uint32_t v) { return __uint_as_float(v << 16); }
__device__ __forceinline__ float bhi(uint32_t v) { return __uint_as_float(v & 0xffff0000u); }
__device__ __forceinline__ float bf16r(float x) { return blo(pack(x, 0.f)); }
__device__ __forceinline__ uint32_t hmul2(uint32_t a, uint32_t b) { uint32_t r; asm("mul.rn.bf16x2 %0, %1, %2;" : "=r"(r) : "r"(a), "r"(b)); return r; }
__device__ __forceinline__ uint32_t hadd2(uint32_t a, uint32_t b) { uint32_t r; asm("add.rn.bf16x2 %0, %1, %2;" : "=r"(r) : "r"(a), "r"(b)); return r; }
__device__ __forceinline__ uint32_t hfma2(uint32_t a, uint32_t b, uint32_t c) { uint32_t r; asm("fma.rn.bf16x2 %0, %1, %2, %3;" : "=r"(r) : "r"(a), "r"(b), "r"(c)); return r; }
__device__ __forceinline__ uint32_t packh(float lo, float hi) { uint32_t r; asm("cvt.rn.f16x2.f32 %0, %1, %2;" : "=r"(r) : "f"(hi), "f"(lo)); return r; }
__device__ __forceinline__ __half2 H2(uint32_t a) { return *reinterpret_cast<__half2*>(&a); }
__device__ __forceinline__ uint32_t U2(__half2 a) { return *reinterpret_cast<uint32_t*>(&a); }
__device__ __forceinline__ uint32_t fmul(uint32_t a, uint32_t b) { return U2(__hmul2(H2(a), H2(b))); }
__device__ __forceinline__ uint32_t ffma(uint32_t a, uint32_t b, uint32_t c) { return U2(__hfma2(H2(a), H2(b), H2(c))); }
__device__ __forceinline__ uint32_t fneg(uint32_t a) { return U2(__hneg2(H2(a))); }
__device__ __forceinline__ uint32_t amax2(uint32_t a, uint32_t b) { uint32_t r; asm("max.xorsign.abs.bf16x2 %0, %1, %2;" : "=r"(r) : "r"(a), "r"(b)); return r; }
__device__ __forceinline__ uint32_t prmt(uint32_t a, uint32_t b, uint32_t s) { return __byte_perm(a, b, s); }
__device__ __forceinline__ uint32_t ldraw(const __nv_bfloat16* p) { uint32_t v; asm volatile("ld.global.nc.u16 %0, [%1];" : "=r"(v) : "l"(p)); return v; }
__device__ __forceinline__ uint4 ldg128(const void* p) { uint4 v; asm volatile("ld.global.nc.v4.u32 {%0,%1,%2,%3}, [%4];" : "=r"(v.x), "=r"(v.y), "=r"(v.z), "=r"(v.w) : "l"(p)); return v; }
__device__ __forceinline__ void bar_sync(int id, int n) { asm volatile("bar.sync %0, %1;" :: "r"(id), "r"(n) : "memory"); }
__device__ __forceinline__ void bar_arrive(int id, int n) { asm volatile("bar.arrive %0, %1;" :: "r"(id), "r"(n) : "memory"); }
__device__ __forceinline__ void cluster_arrive() { asm volatile("barrier.cluster.arrive.relaxed.aligned;" ::: "memory"); }
__device__ __forceinline__ void cluster_wait() { asm volatile("barrier.cluster.wait.aligned;" ::: "memory"); }
__device__ __forceinline__ void fence_async() { asm volatile("fence.proxy.async.shared::cta;" ::: "memory"); }
__device__ __forceinline__ void fence_mbinit() { asm volatile("fence.mbarrier_init.release.cluster;" ::: "memory"); }
__device__ __forceinline__ uint32_t mapa(uint32_t a, uint32_t rank) { uint32_t r; asm("mapa.shared::cluster.u32 %0, %1, %2;" : "=r"(r) : "r"(a), "r"(rank)); return r; }
__device__ __forceinline__ void bulk_dsmem(uint32_t dst, uint32_t src, uint32_t mbar) {
  asm volatile("cp.async.bulk.shared::cluster.shared::cta.mbarrier::complete_tx::bytes [%0], [%1], 512, [%2];" :: "r"(dst), "r"(src), "r"(mbar) : "memory");
}
__device__ __forceinline__ void bulk_load(uint32_t dst, const void* src, uint32_t bytes, uint32_t mbar) {
  asm volatile("cp.async.bulk.shared::cluster.global.mbarrier::complete_tx::bytes [%0], [%1], %2, [%3];" :: "r"(dst), "l"(src), "r"(bytes), "r"(mbar) : "memory");
}
__device__ __forceinline__ void mbar_init(uint32_t m, uint32_t cnt) { asm volatile("mbarrier.init.shared::cta.b64 [%0], %1;" :: "r"(m), "r"(cnt) : "memory"); }
__device__ __forceinline__ void mbar_expect(uint32_t m, uint32_t bytes) { asm volatile("mbarrier.arrive.expect_tx.shared::cta.b64 _, [%0], %1;" :: "r"(m), "r"(bytes) : "memory"); }
__device__ __forceinline__ bool mbar_try(uint32_t m) {
  uint32_t done;
  asm volatile("{.reg .pred p; mbarrier.try_wait.parity.shared::cta.b64 p, [%1], 0; selp.u32 %0, 1, 0, p;}" : "=r"(done) : "r"(m) : "memory");
  return done;
}
__device__ __forceinline__ void mbar_wait(uint32_t m) {
  if (!mbar_try(m)) {
    int it = 0;
    while (!mbar_try(m) && ++it < (1 << 22)) {}
  }
}
__device__ __forceinline__ bool elect() {
  uint32_t e;
  asm volatile("{.reg .pred p; elect.sync _|p, 0xffffffff; selp.u32 %0, 1, 0, p;}" : "=r"(e));
  return e;
}
__device__ __forceinline__ void tma_load4(uint32_t dst, const CUtensorMap* tm, int c0, int c1, int c2, int c3, uint32_t mbar) {
  asm volatile("cp.async.bulk.tensor.4d.shared::cluster.global.mbarrier::complete_tx::bytes [%0], [%1, {%3, %4, %5, %6}], [%2];"
               :: "r"(dst), "l"(tm), "r"(mbar), "r"(c0), "r"(c1), "r"(c2), "r"(c3) : "memory");
}
__device__ __forceinline__ void tma_load3(uint32_t dst, const CUtensorMap* tm, int c0, int c1, int c2, uint32_t mbar) {
  asm volatile("cp.async.bulk.tensor.3d.shared::cluster.global.mbarrier::complete_tx::bytes [%0], [%1, {%3, %4, %5}], [%2];"
               :: "r"(dst), "l"(tm), "r"(mbar), "r"(c0), "r"(c1), "r"(c2) : "memory");
}
__device__ __forceinline__ void tma_store3(const CUtensorMap* tm, int c0, int c1, int c2, uint32_t src) {
  asm volatile("cp.async.bulk.tensor.3d.global.shared::cta.bulk_group [%0, {%2, %3, %4}], [%1];"
               :: "l"(tm), "r"(src), "r"(c0), "r"(c1), "r"(c2) : "memory");
}
__device__ __forceinline__ void wg_fence() { asm volatile("wgmma.fence.sync.aligned;" ::: "memory"); }
__device__ __forceinline__ void wg_commit() { asm volatile("wgmma.commit_group.sync.aligned;" ::: "memory"); }
template <int N> __device__ __forceinline__ void wg_wait() { asm volatile("wgmma.wait_group.sync.aligned %0;" :: "n"(N) : "memory"); }
template <int N> __device__ __forceinline__ void tie_all(uint32_t (&x)[N]) {
#pragma unroll
  for (int i = 0; i < N; i++) asm volatile("" : "+r"(x[i]) :: "memory");
}
template <int N> __device__ __forceinline__ void tie_all(float (&x)[N]) {
#pragma unroll
  for (int i = 0; i < N; i++) asm volatile("" : "+f"(x[i]) :: "memory");
}
#define R16(C, d) C(d[0]), C(d[1]), C(d[2]), C(d[3]), C(d[4]), C(d[5]), C(d[6]), C(d[7]), C(d[8]), C(d[9]), C(d[10]), C(d[11]), C(d[12]), C(d[13]), C(d[14]), C(d[15])
#define R32(C, d) R16(C, d), R16(C, (d + 16))
#define P16 "{%0,%1,%2,%3,%4,%5,%6,%7,%8,%9,%10,%11,%12,%13,%14,%15}"
#define P32 "{%0,%1,%2,%3,%4,%5,%6,%7,%8,%9,%10,%11,%12,%13,%14,%15,%16,%17,%18,%19,%20,%21,%22,%23,%24,%25,%26,%27,%28,%29,%30,%31}"
template <int SD, int TB, int OFF> __device__ __forceinline__ void rs64(float* d, const uint32_t* a, uint64_t db) {
  if (SD) asm volatile("{.reg .b64 db; add.s64 db, %36, %37; wgmma.mma_async.sync.aligned.m64n64k16.f32.bf16.bf16 " P32 ", {%32,%33,%34,%35}, db, 1, 1, 1, %38;}"
                       : R32("+f", d) : "r"(a[0]), "r"(a[1]), "r"(a[2]), "r"(a[3]), "l"(db), "n"(OFF), "n"(TB));
  else asm volatile("{.reg .b64 db; add.s64 db, %36, %37; wgmma.mma_async.sync.aligned.m64n64k16.f32.bf16.bf16 " P32 ", {%32,%33,%34,%35}, db, 0, 1, 1, %38;}"
                    : R32("=f", d) : "r"(a[0]), "r"(a[1]), "r"(a[2]), "r"(a[3]), "l"(db), "n"(OFF), "n"(TB));
}
template <int SD, int TB, int OFF> __device__ __forceinline__ void rs64h(uint32_t* d, const uint32_t* a, uint64_t db) {
  if (SD) asm volatile("{.reg .b64 db; add.s64 db, %20, %21; wgmma.mma_async.sync.aligned.m64n64k16.f16.f16.f16 " P16 ", {%16,%17,%18,%19}, db, 1, 1, 1, %22;}"
                       : R16("+r", d) : "r"(a[0]), "r"(a[1]), "r"(a[2]), "r"(a[3]), "l"(db), "n"(OFF), "n"(TB));
  else asm volatile("{.reg .b64 db; add.s64 db, %20, %21; wgmma.mma_async.sync.aligned.m64n64k16.f16.f16.f16 " P16 ", {%16,%17,%18,%19}, db, 0, 1, 1, %22;}"
                    : R16("=r", d) : "r"(a[0]), "r"(a[1]), "r"(a[2]), "r"(a[3]), "l"(db), "n"(OFF), "n"(TB));
}
template <int SD, int OFFA, int OFFB> __device__ __forceinline__ void ss32(float* d, uint64_t da, uint64_t db) {
  if (SD) asm volatile("{.reg .b64 da, db; add.s64 da, %16, %18; add.s64 db, %17, %19; wgmma.mma_async.sync.aligned.m64n32k16.f32.f16.f16 " P16 ", da, db, 1, 1, 1, 1, 1;}"
                       : R16("+f", d) : "l"(da), "l"(db), "n"(OFFA), "n"(OFFB));
  else asm volatile("{.reg .b64 da, db; add.s64 da, %16, %18; add.s64 db, %17, %19; wgmma.mma_async.sync.aligned.m64n32k16.f32.f16.f16 " P16 ", da, db, 0, 1, 1, 1, 1;}"
                    : R16("=f", d) : "l"(da), "l"(db), "n"(OFFA), "n"(OFFB));
}
#define KGEN_ASM(SD) "{.reg .b64 da, db; add.s64 da, %32, %33; add.s64 db, %32, %34;\n" \
  "wgmma.mma_async.sync.aligned.m64n64k16.f32.bf16.bf16 " P32 ", da, db, " SD ", 1, 1, 1, 1;}"
template <int KS> __device__ __forceinline__ void kgen_mma(float (&c)[32], uint64_t da) {
  if (KS) asm volatile(KGEN_ASM("1") : R32("+f", c) : "l"(da), "n"(8 * KS), "n"(8 * KS + 512));
  else asm volatile(KGEN_ASM("0") : R32("=f", c) : "l"(da), "n"(8 * KS), "n"(8 * KS + 512));
  if constexpr (KS < 7) kgen_mma<KS + 1>(c, da);
}
__device__ __forceinline__ uint64_t desc_lo(uint32_t a) { return (uint64_t)((a & 0x3FFFF) >> 4); }
__device__ __forceinline__ void stage1(float (&D)[32], const uint32_t (&A1)[8], uint32_t src) {
  const uint64_t du = desc_lo(src) | (128ull << 16) | (32ull << 32) | (2ull << 62);
  rs64<0, 1, 0>(D, A1, du); rs64<1, 1, 64>(D, A1 + 4, du);
}
template <int INV> __device__ __forceinline__ void stage2(uint32_t (&X)[16], const uint32_t (&F)[16], uint32_t cf) {
  constexpr int KS = INV ? 16 : 128, TB = INV ? 0 : 1;
  const uint64_t dc = desc_lo(cf) | (INV ? (8ull << 16) | (64ull << 32) : (64ull << 16) | (8ull << 32));
  rs64h<0, TB, 0>(X, F, dc); rs64h<1, TB, KS>(X, F + 4, dc); rs64h<1, TB, 2 * KS>(X, F + 8, dc); rs64h<1, TB, 3 * KS>(X, F + 12, dc);
}
__device__ __forceinline__ void fwd_mid(uint32_t (&F)[16], const float (&D)[32], const uint32_t (&tc)[4], const uint32_t (&ts)[4]) {
#pragma unroll
  for (int j = 0; j < 4; j++)
#pragma unroll
    for (int b = 0; b < 2; b++) {
      const int i = 4 * j + 16 * b;
      const uint32_t ar = packh(D[i], D[i + 1]), ai = packh(D[i + 2], D[i + 3]);
      F[2 * j + b] = ffma(ar, tc[j], fmul(ai, ts[j]));
      F[8 + 2 * j + b] = ffma(ai, tc[j], fneg(fmul(ar, ts[j])));
    }
}
__device__ __forceinline__ void put_exp(uint32_t a, uint32_t m, int lane) {
  m = __reduce_max_sync(0xffffffffu, max(m & 0x7f80u, (m >> 16) & 0x7f80u));
  if (lane == 0) sts32(a, m);
}
__device__ __forceinline__ uint32_t seq_mag(uint32_t a) {
  const uint4 x = lds128(a), y = lds128(a + 2048);
  return amax2(amax2(amax2(x.x, x.y), amax2(x.z, x.w)), amax2(amax2(y.x, y.y), amax2(y.z, y.w)));
}
__device__ __forceinline__ uint32_t get_exp(uint32_t a) { const uint4 v = lds128(a); return max(max(v.x, v.y), max(v.z, v.w)) >> 7; }
__device__ __forceinline__ void scale_a1(uint32_t (&As)[8], const uint32_t (&A1)[8], uint32_t field) {
#pragma unroll
  for (int i = 0; i < 8; i++) As[i] = hmul2(A1[i], field * 0x00800080u);
}

struct cf { float x, y; };
__device__ __forceinline__ cf cmul(cf a, cf b) { cf r; r.x = fmaf(a.x, b.x, -a.y * b.y); r.y = fmaf(a.x, b.y, a.y * b.x); return r; }
__device__ __forceinline__ cf cexp_p(float lr2, float lt, float p) {
  float m;
  asm("ex2.approx.ftz.f32 %0, %1;" : "=f"(m) : "f"(lr2 * p));
  float t = lt * p;
  t = (t - rintf(t)) * 6.283185307179586f;
  cf r; r.x = m * __cosf(t); r.y = m * __sinf(t); return r;
}
__device__ __forceinline__ void store8(uint32_t a, uint32_t b, const cf (&v)[8]) {
  sts128(a, pack(v[0].x, v[1].x), pack(v[2].x, v[3].x), pack(v[4].x, v[5].x), pack(v[6].x, v[7].x));
  sts128(b, pack(v[0].y, v[1].y), pack(v[2].y, v[3].y), pack(v[4].y, v[5].y), pack(v[6].y, v[7].y));
}
__device__ __forceinline__ void mbar_arrive(uint32_t m) { asm volatile("mbarrier.arrive.shared::cta.b64 _, [%0];" :: "r"(m) : "memory"); }
__device__ __forceinline__ float sigmoidf_(float s) { return __frcp_rn(1.f + __expf(-s)); }

__global__ void __cluster_dims__(CS, 1, 1) __launch_bounds__(NTHREADS, 1) fused_kernel(const __grid_constant__ Params p) {
  extern __shared__ __align__(1024) uint8_t smem[];
  TL_INIT();
  TL(31);
  const int wid = __shfl_sync(0xffffffffu, threadIdx.x >> 5, 0);
  const uint32_t sb = (uint32_t)__cvta_generic_to_shared(smem);
  const uint32_t mb = sb + OFF_MB;
  const int u = wid >> 2, w = wid & 3;
  const int tid = threadIdx.x & 127, lane = tid & 31, g = lane >> 2, t = lane & 3;
  const int cl = blockIdx.x >> 3, rank = blockIdx.x & 7;
  const int ch0 = cl * CPC;
  const int nu = min(5, (DCH - ch0) >> 3);
  const bool act = u < nu;

  uint32_t pla, pai, pcr, pci, pdt, tag = 0;
  auto load_params = [&]() {
    const int ch = act ? ch0 + 8 * u + rank : 0, o = ch * NMODE + tid;
    pla = ldraw(p.logA + o); pdt = ldraw(p.logdt + ch); pai = ldraw(p.Aim + o); pcr = ldraw(p.Cre + o); pci = ldraw(p.Cim + o);
  };
  if (u == 4) {
    const bool e = elect();
    if (e) {
#pragma unroll
      for (int i = 0; i < 5; i++) mbar_init(mb + 40 * w + 8 * i, w == 3 ? 1 : w == 2 ? 3 : 2);
      if (w == 3) { mbar_init(mb + 8 * MB_XQ, 21); mbar_init(mb + 8 * MB_KV, 1); }
      if (w == 2) { mbar_init(mb + 8 * MB_TH, 1); mbar_init(mb + 8 * MB_CF, 1); mbar_init(mb + 8 * MB_Q2, 9); }
      fence_mbinit();
    }
    __syncwarp();
    load_params();
    if (w == 0 && lane < 2) asm volatile("atom.relaxed.gpu.global.add.u32 %0, [%1], %2;" : "=r"(tag) : "l"(&p.cnt[rank * 32 + lane]), "r"(cl == 0 ? 16 - (NCL - 1) : 1) : "memory");
    if (e) {
      if (w == 2) {
        mbar_expect(mb + 8 * MB_TH, 8192 + 112 * nu);
        bulk_load(sb + OFF_YB, p.tab->thr, 8192, mb + 8 * MB_TH);
        bulk_load(sb + OFF_SP, p.gate_w + ch0, 16 * nu, mb + 8 * MB_TH);
        bulk_load(sb + OFF_SP + 80, p.Dskip + ch0, 16 * nu, mb + 8 * MB_TH);
        bulk_load(sb + OFF_SP + 160, p.ssm_D + ch0, 16 * nu, mb + 8 * MB_TH);
        bulk_load(sb + OFF_SP + 240, p.shift_k + 4 * ch0, 64 * nu, mb + 8 * MB_TH);
        asm volatile("cp.async.bulk.prefetch.L2.global [%0], 12288;" :: "l"(p.tab->mat) : "memory");
        mbar_expect(mb + 8 * MB_CF, 12288); mbar_expect(mb + 8 * MB_Q2, 20480);
      }
#pragma unroll
      for (int i = 0; i < 5; i++) mbar_expect(mb + 40 * w + 8 * i, w == 3 ? 4096 : w == 2 ? 7168 : 3584);
      if (w == 3) {
        mbar_expect(mb + 8 * MB_KV, 23040 + 20480);
        mbar_expect(mb + 8 * MB_XQ, 20480);
        tma_load4(sb + OFF_TQ, &p.tq, ch0, 0, 0, 8 * rank, mb + 8 * MB_XQ);
        TL(20);
      }
    }
    __syncwarp();
  } else {
    load_params();
  }
  cluster_arrive();
  asm volatile("" : "+r"(pla), "+r"(pdt) :: "memory");
  TL(0);

  const uint32_t tab = sb + OFF_T + u * KTAB;
  const int mi = lane >> 3, tq = (lane & 7) >> 1, jj = lane & 1;
  const uint32_t toff = (4 * (2 * mi + jj) + tq) * 80;
  const uint32_t uoff = 16 * (4 * w + (t ^ (w >> 1)));
  auto put = [&](int stage, int dst, uint32_t off, const uint32_t (&v)[4]) {
    sts128(sb + off + (g == rank ? dst + 512 * rank : stage + g * YPITCH), v[0], v[1], v[2], v[3]);
  };
  const int d0 = rank ^ (2 * w), d1 = d0 ^ 1;
  const uint32_t rb0 = mapa(sb, d0), rb1 = mapa(sb, d1);
  auto send = [&](int stage, int pitch, int dst, int mbar) {
    if (elect()) {
      if (w) bulk_dsmem(rb0 + dst, sb + stage + d0 * pitch, rb0 + mbar); else mbar_arrive(sb + mbar);
      bulk_dsmem(rb1 + dst, sb + stage + d1 * pitch, rb1 + mbar);
    }
    __syncwarp();
  };

  uint32_t A1[8], tc[4], ts[4];
  {
    const float dt = bf16r(expf(blo(pdt)));
    const float lr2 = (-bf16r(expf(blo(pla))) * dt) * 1.4426950408889634f;
    const float lt = (blo(pai) * dt) * 0.15915494309189535f;
    const uint32_t tim = sb + OFF_IM + (u < 2 ? 3 + u : u - 2) * KTAB;
    const uint32_t row = tab + tid * 16, rim = tim + tid * 16;
    const cf w1 = cexp_p(lr2, lt, 8.f);
    cf z1 = cexp_p(lr2, lt, 1.f), Z = cexp_p(lr2, lt, 256.f);
    if (lr2 != 123.f) TL(16);
    TL(12);
    {
      cf v[8];
      v[0].x = 1.f; v[0].y = 0.f; v[1] = w1; v[2] = cmul(w1, w1); v[3] = cmul(v[2], w1);
      const cf w4 = cmul(v[2], v[2]);
      v[4] = w4; v[5] = cmul(v[1], w4); v[6] = cmul(v[2], w4); v[7] = cmul(v[3], w4);
      const cf w8 = cmul(w4, w4);
      store8(row, rim, v);
#pragma unroll
      for (int k = 1; k < 4; k++) {
#pragma unroll
        for (int i = 0; i < 8; i++) v[i] = (k == 1 && i == 0) ? w8 : cmul(v[i], w8);
        store8(row + 2048 * k, rim + 2048 * k, v);
      }
    }
    cluster_wait();
    mbar_wait(mb + 8 * MB_TH);
    {
      const uint4 x = lds128(sb + OFF_YB + 16 * tid), y = lds128(sb + OFF_YB + 2048 + 16 * tid), a = lds128(sb + OFF_YB + 4096 + 16 * tid), b = lds128(sb + OFF_YB + 6144 + 16 * tid);
      A1[0] = x.x; A1[1] = x.y; A1[2] = x.z; A1[3] = x.w; A1[4] = y.x; A1[5] = y.y; A1[6] = y.z; A1[7] = y.w;
      tc[0] = a.x; tc[1] = a.y; tc[2] = a.z; tc[3] = a.w; ts[0] = b.x; ts[1] = b.y; ts[2] = b.z; ts[3] = b.w;
    }
    if (wid == 16 && lane == 0) sts32(mb + 8 * MB_TAG, tag);
    __syncwarp();
    if (lane == 0) mbar_arrive(mb + 8 * MB_XQ);
    if (u == 1) {
      float z0_ = 0.f, z1_ = 0.f, z2_ = 0.f, z3_ = 0.f;
      asm volatile("mma.sync.aligned.m16n8k8.row.col.f32.bf16.bf16.f32 {%0,%1,%2,%3}, {%4,%4}, {%4}, {%0,%1,%2,%3};"
                   : "+f"(z0_), "+f"(z1_), "+f"(z2_), "+f"(z3_) : "r"(pla >> 16));
      pcr += __float_as_uint(z0_);
      if (w == 0 && elect()) {
        const uint32_t o = blockIdx.x * 9856u, n = min(9856u, SEQ * DCH - o) * 2;
        asm volatile("cp.async.bulk.prefetch.L2.global [%0], %1;" :: "l"(p.ssm_k + o), "r"(n) : "memory");
        asm volatile("cp.async.bulk.prefetch.L2.global [%0], %1;" :: "l"(p.k + o), "r"(n) : "memory");
        asm volatile("cp.async.bulk.prefetch.L2.global [%0], %1;" :: "l"(p.v + o), "r"(n) : "memory");
      }
      __syncwarp();
      TL(8);
    }
    {
      z1.y = -z1.y; Z.y = -Z.y;
      const cf z2 = cmul(z1, z1);
      cf h[8], v[8];
      h[0].x = 2.f * blo(pcr) * dt; h[0].y = -2.f * blo(pci) * dt;
      h[1] = cmul(h[0], z1);
#pragma unroll
      for (int i = 2; i < 8; i++) h[i] = cmul(h[i - 2], z2);
      store8(row + 4 * 2048, rim + 4 * 2048, h);
      const cf h8 = cmul(h[6], z2);
      v[0] = cmul(h[0], Z); v[2] = cmul(h[2], Z); v[3] = cmul(h[4], Z); v[6] = cmul(h[6], Z); v[7] = cmul(h8, Z);
      v[1] = v[0]; v[4] = v[5] = v[3];
      store8(row + 5 * 2048, rim + 5 * 2048, v);
      h[0] = cmul(v[0], Z); h[1] = cmul(v[3], Z); h[3] = cmul(v[7], Z); h[4] = cmul(h[0], Z); h[5] = cmul(h[1], Z); h[7] = cmul(h[3], Z);
      h[2] = h[1]; h[6] = h[5];
      store8(row + 6 * 2048, rim + 6 * 2048, h);
      const cf Z2 = cmul(Z, Z);
      v[0] = cmul(h[0], Z2); v[1] = cmul(h[3], Z2); v[2] = cmul(h[4], Z2); v[3] = cmul(h[7], Z2);
#pragma unroll
      for (int i = 4; i < 8; i++) v[i] = cmul(v[i - 4], Z2);
      store8(row + 7 * 2048, rim + 7 * 2048, v);
    }
    TL(17);
    mbar_wait(mb + 8 * MB_XQ);
    TL(18);
    {
      uint32_t x0[4], x1[4];
      ldsm4t(x0, sb + OFF_TQ + w * 2560 + toff + 16 * u);
      ldsm4t(x1, sb + OFF_TQ + (w + 4) * 2560 + toff + 16 * u);
      put(OFF_YB + 8 * u * YPITCH, OFF_UX + u * 4096, uoff, x0);
      put(OFF_YB + 8 * u * YPITCH, OFF_UX + u * 4096, (uoff ^ 32) + 256, x1);
    }
    TL(3);
    fence_async();
    bar_sync(NB_WG0 + u, 128);
    TL(4);
    if (u >= 3) {
      float s0 = 0.f;
#pragma unroll
      for (int j = 0; j < 5; j++) {
        if (j >= 2 && j >= nu) break;
        const uint4 gw = lds128(sb + OFF_SP + 16 * j), x = lds128(sb + OFF_TQ + (tid + 128 * (u - 3)) * 80 + 16 * j);
        const uint32_t m0 = hmul2(x.x, gw.x), m1 = hmul2(x.y, gw.y), m2 = hmul2(x.z, gw.z), m3 = hmul2(x.w, gw.w);
        s0 += ((blo(m0) + bhi(m0)) + (blo(m1) + bhi(m1))) + ((blo(m2) + bhi(m2)) + (blo(m3) + bhi(m3)));
      }
      tag = (lds64(mb + 8 * MB_TAG).x >> 4) + 1;
      asm volatile("st.relaxed.gpu.global.u64 [%0], %1;" :: "l"(p.part + cl * SEQ + rank * 256 + 8 * (8 * t + g) + w + 4 * (u - 3)),
                   "l"(((uint64_t)tag << 32) | __float_as_uint(s0)) : "memory");
    }
    TL(7);
    if (u) bar_sync(NB_ORD + u - 1, 256);
    TL(13);
    float c[32];
    wg_fence();
    kgen_mma<0>(c, desc_lo(tab) | ((uint64_t)((tim - tab) >> 4) << 16) | (64ull << 32));
    wg_commit();
    if (u < 4) bar_arrive(NB_ORD + u, 256);
    send(OFF_YB + 8 * u * YPITCH, YPITCH, OFF_UX + u * 4096 + 512 * rank, OFF_MB + 8 * (MB_UX + u));
    TL(14);
    wg_wait<0>(); tie_all(c);
    TL(26);
    cluster_arrive();
    if (wid == 17) {
      bar_sync(NB_LD, 640);
      if (elect()) {
        tma_load4(sb + OFF_TK, &p.tk, ch0, 0, 0, 8 * rank - 1, mb + 8 * MB_KV);
        tma_load4(sb + OFF_TV, &p.tv, ch0, 0, 0, 8 * rank, mb + 8 * MB_KV);
      }
      __syncwarp();
    } else {
      bar_arrive(NB_LD, 640);
    }
    bar_sync(NB_WG0 + u, 128);
    if (wid == 1 && elect()) bulk_load(sb + OFF_CF, p.tab->mat, 12288, mb + 8 * MB_CF);
    __syncwarp();
    const uint32_t k0 = pack(c[0] + c[6], c[1] + c[7]), k1 = pack(c[8] + c[14], c[9] + c[15]);
    const uint32_t k2 = pack(c[16] + c[22], c[17] + c[23]), k3 = pack(c[24] + c[30], c[25] + c[31]);
    const uint32_t ka = tab + 16 * (8 * w + (g ^ w));
    sts32(ka + 4 * t, k0);
    sts32(ka + 512 + 4 * t, k1);
    sts64(ka + 1024 + 512 * (t >> 1) + 8 * (t & 1), prmt(k2, 0, 0x1010), (t & 1) ? prmt(k2, 0, 0x3232) : k2);
    const uint32_t lo = prmt(k3, 0, 0x1010), hi = prmt(k3, 0, 0x3232);
    sts128(ka + 2048 + 512 * t, lo, lo, (g & 1) ? hi : k3, hi);
    put_exp(sb + OFF_MX + u * 64 + 4 * w, amax2(amax2(k0, k1), amax2(k2, k3)), lane);
    TL(15);
    fence_async();
    bar_sync(NB_WG0 + u, 128);
  }

#pragma unroll
  for (int isA = 0; isA < 2; isA++) {
    {
      TL(1 + isA);
      const uint32_t usrc = isA ? tab + T_UKV : sb + OFF_UX + u * 4096;
      const uint32_t mxa = sb + OFF_MX + u * 64 + 32 * isA;
      const uint32_t pd = lds16(sb + OFF_SP + 80 + 80 * isA + 16 * u + 2 * rank);
      float D[32];
      uint32_t As[8], F[16], H[16], X[16];
      const uint32_t eh = min(max((int)get_exp(mxa), (int)((pd >> 7) & 0xff) - 5), 240);
      scale_a1(As, A1, 248 - eh);
      wg_fence();
      stage1(D, As, isA ? tab + T_HA : tab);
      wg_commit();
      wg_wait<0>(); tie_all(D);
      fwd_mid(F, D, tc, ts);
      if (!isA) mbar_wait(mb + 8 * MB_CF);
      wg_fence();
      stage2<0>(H, F, sb + OFF_CF);
      wg_commit();
      if (!isA && w == 1 && elect()) {
        tma_load4(tab + T_HA, &p.th, 0, 0, 5 * cl + u, rank, mb + 8 * (MB_HA + u));
        if (u == 4) tma_load3(sb + OFF_Q2, &p.tq2, ch0, 8 * rank, 0, mb + 8 * MB_Q2);
      }
      __syncwarp();
      mbar_wait(mb + 8 * ((isA ? MB_UKV : MB_UX) + u));
      TL(5 + isA);
      put_exp(mxa + 16 + 4 * w, seq_mag(usrc + 16 * tid), lane);
      bar_sync(NB_WG0 + u, 128);
      const uint32_t eu = min(get_exp(mxa + 16), 240u);
      scale_a1(As, A1, 250 - eu);
      wg_wait<0>(); tie_all(H);
      wg_fence();
      stage1(D, As, usrc);
      wg_commit();
      wg_wait<0>(); tie_all(D);
      fwd_mid(F, D, tc, ts);
      wg_fence();
      stage2<0>(X, F, sb + OFF_CF);
      wg_commit();
      {
        const float dsk = blo(pd) * __uint_as_float((248 - eh) << 23);
        const uint32_t d2 = packh(dsk, dsk);
#pragma unroll
        for (int j = 0; j < 4; j++) H[2 * j] = U2(__hadd2(H2(H[2 * j]), H2(d2)));
      }
      wg_wait<0>(); tie_all(X);
#pragma unroll
      for (int j = 0; j < 4; j++) {
        const uint32_t h0r = H[2 * j], h1r = H[2 * j + 1], h0i = H[8 + 2 * j], h1i = H[9 + 2 * j];
        const uint32_t x0r = X[2 * j], x1r = X[2 * j + 1], x0i = X[8 + 2 * j], x1i = X[9 + 2 * j];
        F[2 * j] = ffma(x0r, h0r, fneg(fmul(x0i, h0i)));
        F[8 + 2 * j] = ffma(x0r, h0i, fmul(x0i, h0r));
        F[2 * j + 1] = ffma(x1r, h0r, ffma(fneg(x1i), h0i, ffma(x0r, h1r, fneg(ffma(x0i, h1i, F[8 + 2 * j])))));
        F[9 + 2 * j] = ffma(x1r, h0i, ffma(x1i, h0r, ffma(x0r, h1i, ffma(x0i, h1r, F[2 * j]))));
      }
      wg_fence();
      stage2<1>(H, F, sb + OFF_CF);
      wg_commit();
      wg_wait<0>(); tie_all(H);
      {
        const uint32_t va = tab + (16 * w + (lane & 15)) * 128;
        const int vx = (lane >> 4) ^ (lane & 7);
#pragma unroll
        for (int j = 0; j < 4; j++) {
          uint32_t V[4];
#pragma unroll
          for (int b = 0; b < 2; b++) {
            const uint32_t er = H[2 * j + b], ei = H[8 + 2 * j + b];
            V[2 * b] = ffma(er, tc[j], fneg(fmul(ei, ts[j])));
            V[2 * b + 1] = ffma(ei, tc[j], fmul(er, ts[j]));
          }
          stsm4(va + ((vx ^ (2 * j)) << 4), V);
        }
      }
      uint64_t ga[NCL];
      const int slot = tid + 128 * (u & 1);
      const uint2* gp = p.part + rank * 256 + slot;
      auto gload = [&]() {
#pragma unroll
        for (int k = 0; k < NCL; k++) asm volatile("ld.relaxed.gpu.global.u64 %0, [%1];" : "=l"(ga[k]) : "l"(gp + k * SEQ) : "memory");
      };
      if (!isA) {
        cluster_wait();
        mbar_wait(mb + 8 * MB_KV);
        TL(21);
        const uint32_t hoff = (4 * (4 + 2 * (mi & 1) + jj) + ((tq + 3) & 3)) * 80 + (tq ? 2560 : 0) + 16 * u;
        uint32_t E[2][6], V[2][4];
        const uint2 psw = lds64(sb + OFF_SP + 240 + 64 * u + 8 * g);
#pragma unroll
        for (int hf = 0; hf < 2; hf++) {
          const int ah = 4 * hf + w;
          uint32_t K[4];
          ldsm4t(K, sb + OFF_TK + (ah + 1) * 2560 + toff + 16 * u);
          ldsm2t(E[hf][0], E[hf][1], sb + OFF_TK + ah * 2560 + hoff);
          ldsm4t(V[hf], sb + OFF_TV + ah * 2560 + toff + 16 * u);
          E[hf][2] = K[0]; E[hf][3] = K[1]; E[hf][4] = K[2]; E[hf][5] = K[3];
        }
        const uint32_t w0 = prmt(psw.x, 0, 0x1010), w1 = prmt(psw.x, 0, 0x3232), w2 = prmt(psw.y, 0, 0x1010), w3 = prmt(psw.y, 0, 0x3232);
        uint32_t o[2][4];
#pragma unroll
        for (int hf = 0; hf < 2; hf++) {
          uint32_t O[5];
#pragma unroll
          for (int i = 0; i < 5; i++) O[i] = prmt(E[hf][i], E[hf][i + 1], 0x5432);
#pragma unroll
          for (int i = 0; i < 4; i++) {
            o[hf][i] = hmul2(hfma2(E[hf][i + 2], w0, hfma2(O[i + 1], w1, hfma2(E[hf][i + 1], w2, hmul2(O[i], w3)))), V[hf][i]);
          }
          put(OFF_YA + 8 * u * YPITCH, OFF_T + u * KTAB + T_UKV, hf ? (uoff ^ 32) + 256 : uoff, o[hf]);
        }
        mbar_wait(mb + 8 * (MB_HA + u));
        put_exp(mxa + 32 + 4 * w, seq_mag(tab + T_HA + 16 * tid), lane);
        TL(22);
      }
      fence_async();
      bar_sync(NB_WG0 + u, 128);
      float O[16];
      {
        const uint64_t dv = desc_lo(tab) | (1ull << 16) | (64ull << 32) | (1ull << 62);
        const uint64_t dl = desc_lo(sb + OFF_CL) | (32ull << 16) | (8ull << 32);
        wg_fence();
        ss32<0, 0, 0>(O, dv, dl); ss32<1, 128, 64>(O, dv, dl); ss32<1, 256, 128>(O, dv, dl); ss32<1, 384, 192>(O, dv, dl);
        wg_commit();
      }
      if (!isA) {
        send(OFF_YA + 8 * u * YPITCH, YPITCH, OFF_T + u * KTAB + T_UKV + 512 * rank, OFF_MB + 8 * (MB_UKV + u));
        if (u < 2) gload();
      }
      wg_wait<0>(); tie_all(O);
      {
        const uint32_t co = ((8 * w + g) ^ (2 * t)) * 16;
        const int yo = (isA ? OFF_YA : OFF_YB) + (8 * u + rank) * YPITCH, ym = OFF_MB + 8 * (MB_Y + u);
        const uint32_t us = min(max((int)(eu + eh) - 127, 0), 254) * 0x00800080u;
        const uint32_t a0 = hmul2(pack(O[0], O[1]), us), a1 = hmul2(pack(O[4], O[5]), us), a2 = hmul2(pack(O[8], O[9]), us), a3 = hmul2(pack(O[12], O[13]), us);
        const uint32_t b0 = hmul2(pack(O[2], O[3]), us), b1 = hmul2(pack(O[6], O[7]), us), b2 = hmul2(pack(O[10], O[11]), us), b3 = hmul2(pack(O[14], O[15]), us);
        sts128((t == rank ? sb + yo : usrc + t * 512) + co, a0, a1, a2, a3);
        sts128((t + 4 == rank ? sb + yo : usrc + t * 512 + 2048) + co, b0, b1, b2, b3);
        fence_async();
        bar_sync(NB_WG0 + u, 128);
        send(usrc - sb, 512, yo, ym);
      }
      TL(9 + isA);
      if (!isA && u < 2) {
        tag = (lds64(mb + 8 * MB_TAG).x >> 4) + 1;
        float s;
        bool ok;
#pragma unroll 1
        for (int it = 0;; it++) {
          ok = true; s = 0.f;
#pragma unroll
          for (int k = 0; k < NCL; k++) { ok = ok && (uint32_t)(ga[k] >> 32) == tag; s += __uint_as_float((uint32_t)ga[k]); }
          if (ok || it == 4000) break;
          gload();
        }
        if (!ok) {
          const uint32_t* xr = (const uint32_t*)(p.q + (size_t)(rank * 256 + 32 * (slot & 7) + (slot >> 3)) * DCH);
          const uint32_t* gr = (const uint32_t*)p.gate_w;
          s = 0.f;
    #pragma unroll 1
          for (int k = 0; k < DCH / 2; k++) { const uint32_t m = hmul2(__ldg(xr + k), __ldg(gr + k)); s += blo(m) + bhi(m); }
        }
        const float g0 = bf16r(sigmoidf_(bf16r(s)));
        sts64(sb + OFF_GB + 8 * slot, pack(g0, g0), pack(1.f - g0, 1.f - g0));
        __syncwarp();
        if (lane == 0) mbar_arrive(mb + 8 * MB_Q2);
      }
    }
  }

  {
    mbar_wait(mb + 8 * MB_Q2);
    uint2 gg[2][4];
    uint32_t qv[2][4];
#pragma unroll
    for (int hh = 0; hh < 2; hh++)
#pragma unroll
      for (int i = 0; i < 4; i++) gg[hh][i] = lds64(sb + OFF_GB + 8 * (64 * w + 32 * hh + 8 * i + g));
    const uint32_t qa = sb + OFF_Q2 + (64 * w + lane) * 80 + 16 * u;
    ldsm4(qv[0], qa);
    ldsm4(qv[1], qa + 2560);
    TL(24);
    mbar_wait(mb + 8 * (MB_Y + u));
    uint32_t ya[2][4], yb[2][4];
#pragma unroll
    for (int hh = 0; hh < 2; hh++) {
      const uint32_t yo = (8 * u + (lane & 7)) * YPITCH + ((8 * w + 4 * hh + (lane >> 3)) ^ (2 * (rank & 3))) * 16;
      ldsm4t(ya[hh], sb + OFF_YA + yo); ldsm4t(yb[hh], sb + OFF_YB + yo);
    }
#pragma unroll
    for (int hh = 0; hh < 2; hh++) {
      uint32_t o[4];
#pragma unroll
      for (int i = 0; i < 4; i++) o[i] = hadd2(hmul2(gg[hh][i].x, hmul2(qv[hh][i], ya[hh][i])), hmul2(gg[hh][i].y, yb[hh][i]));
      stsm4(qa + 2560 * hh, o);
    }
    TL(25);
  }
  cluster_arrive();
  bar_sync(NB_ROW0 + w, 160);
  {
    uint4 v[2];
#pragma unroll
    for (int k = 0; k < 2; k++) {
      const int i = 64 * u + 32 * k + lane, sl = (i * 205) >> 10, cc = i - 5 * sl;
      v[k] = lds128(sb + OFF_Q2 + (64 * w + 8 * (sl & 7) + (sl >> 3)) * 80 + cc * 16);
    }
#pragma unroll
    for (int k = 0; k < 2; k++) {
      const int i = 64 * u + 32 * k + lane, sl = (i * 205) >> 10, cc = i - 5 * sl;
      if (cc < nu)
        asm volatile("st.global.v4.u32 [%0], {%1,%2,%3,%4};" :: "l"(p.out + (size_t)(256 * rank + 32 * (sl >> 3) + 8 * w + (sl & 7)) * DCH + ch0 + 8 * cc),
                     "r"(v[k].x), "r"(v[k].y), "r"(v[k].z), "r"(v[k].w) : "memory");
    }
  }
  cluster_wait();
  TL(27);
  TL_DUMP();
}

typedef CUresult (*EncodeFn)(CUtensorMap*, CUtensorMapDataType, cuuint32_t, void*, const cuuint64_t*, const cuuint64_t*,
                             const cuuint32_t*, const cuuint32_t*, CUtensorMapInterleave, CUtensorMapSwizzle,
                             CUtensorMapL2promotion, CUtensorMapFloatOOBfill);

void encode(EncodeFn fn, CUtensorMap* tm, const void* ptr, int nd, const cuuint64_t* dims, const cuuint64_t* strides,
            const cuuint32_t* box, CUtensorMapSwizzle swz) {
  cuuint32_t es[4] = {1, 1, 1, 1};
  fn(tm, CU_TENSOR_MAP_DATA_TYPE_BFLOAT16, nd, const_cast<void*>(ptr), dims, strides, box, es, CU_TENSOR_MAP_INTERLEAVE_NONE,
     swz, CU_TENSOR_MAP_L2_PROMOTION_L2_128B, CU_TENSOR_MAP_FLOAT_OOB_FILL_NONE);
}
void map1(EncodeFn fn, CUtensorMap* tm, const void* ptr, int nhi) {
  const cuuint64_t dims[4] = {DCH, 4, 8, SEQ / 32}, strides[3] = {8 * DCH * 2, DCH * 2, 32 * DCH * 2};
  const cuuint32_t box[4] = {CPC, 4, 8, (cuuint32_t)nhi};
  encode(fn, tm, ptr, 4, dims, strides, box, CU_TENSOR_MAP_SWIZZLE_NONE);
}
void map2(EncodeFn fn, CUtensorMap* tm, const void* ptr, int nr) {
  const cuuint64_t dims[3] = {DCH, SEQ / 32, 32}, strides[2] = {32 * DCH * 2, DCH * 2};
  const cuuint32_t box[3] = {CPC, 8, (cuuint32_t)nr};
  encode(fn, tm, ptr, 3, dims, strides, box, CU_TENSOR_MAP_SWIZZLE_NONE);
}

}

extern "C" void kernel_launch(void* const* d_in, const int* in_sizes, int n_in, void* d_out, int out_size) {
  (void)in_sizes; (void)n_in; (void)out_size;
  static EncodeFn fn = nullptr;
  static void *tab = nullptr, *cnt = nullptr, *part = nullptr;
  if (!fn) {
    cudaGetSymbolAddress(&tab, d_tab);
    cudaGetSymbolAddress(&cnt, g_cnt);
    cudaGetSymbolAddress(&part, g_part);
    cudaDriverEntryPointQueryResult qr;
    cudaGetDriverEntryPoint("cuTensorMapEncodeTiled", (void**)&fn, cudaEnableDefault, &qr);
    cudaFuncSetAttribute(fused_kernel, cudaFuncAttributeMaxDynamicSharedMemorySize, SMEM_BYTES);
  }
  Params p;
  map1(fn, &p.tq, d_in[0], 8);
  map1(fn, &p.tk, d_in[1], 9);
  map1(fn, &p.tv, d_in[2], 8);
  map2(fn, &p.tq2, d_in[0], 32);
  p.out = (__nv_bfloat16*)d_out;
  {
    const cuuint64_t dims[4] = {32, SEQ / 32, DCH / 8, 8}, strides[3] = {64, 8 * SEQ * 2, SEQ * 2};
    const cuuint32_t box[4] = {32, 64, 1, 1};
    encode(fn, &p.th, d_in[4], 4, dims, strides, box, CU_TENSOR_MAP_SWIZZLE_64B);
  }
  p.tab = (const Tables*)tab;
  p.cnt = (unsigned*)cnt;
  p.part = (uint2*)part;
  p.tl = nullptr;
  p.q = (const __nv_bfloat16*)d_in[0];
  p.k = (const __nv_bfloat16*)d_in[1];
  p.v = (const __nv_bfloat16*)d_in[2];
  p.ssm_k = (const __nv_bfloat16*)d_in[4];
  p.shift_k = (const __nv_bfloat16*)d_in[3];
  p.ssm_D = (const __nv_bfloat16*)d_in[5];
  p.logA = (const __nv_bfloat16*)d_in[7];
  p.Aim = (const __nv_bfloat16*)d_in[8];
  p.Cre = (const __nv_bfloat16*)d_in[9];
  p.Cim = (const __nv_bfloat16*)d_in[10];
  p.logdt = (const __nv_bfloat16*)d_in[11];
  p.Dskip = (const __nv_bfloat16*)d_in[12];
  p.gate_w = (const __nv_bfloat16*)d_in[13];
  fused_kernel<<<NCL * CS, NTHREADS, SMEM_BYTES, cudaStreamPerThread>>>(p);
}
```

```cpp
#include <cuda_runtime.h>
#include <cuda_bf16.h>
#include <cuda_fp16.h>
#include <cuda.h>
#include <stdint.h>

#define TIMELINE 0
#define TLHI 0

namespace {

constexpr int SEQ = 2048, DCH = 576, NMODE = 128;
constexpr int CS = 8, CPC = 40, NCL = 15, NTHREADS = 640;

constexpr int KTAB = 16384;
constexpr int OFF_T = 0;
constexpr int T_UKV = 8192, T_HA = 12288;
constexpr int OFF_UX = 5 * KTAB;
constexpr int OFF_IM = OFF_UX + 20480;
constexpr int OFF_CF = OFF_IM;
constexpr int OFF_CL = OFF_CF + 8192;
constexpr int OFF_TV = OFF_CL + 4096;
constexpr int OFF_YA = OFF_TV + 20480;
constexpr int OFF_GB = OFF_YA + 20480;
constexpr int OFF_YB = OFF_IM + 4 * KTAB;
constexpr int OFF_TQ = OFF_YB + 20480;
constexpr int OFF_TK = OFF_TQ + 20480;
constexpr int OFF_HALO = OFF_TK + 20480;
constexpr int OFF_MX = OFF_HALO + 320;
constexpr int OFF_SP = OFF_MX + 320;
constexpr int OFF_MB = OFF_SP + 560;
constexpr int OFF_TL = OFF_MB + 28 * 8;
constexpr int SMEM_BYTES = OFF_TL + (TIMELINE ? 1280 : 0);
static_assert(SMEM_BYTES <= 232448 && OFF_YA == OFF_IM + 2 * KTAB && OFF_GB + 2048 <= OFF_YB, "smem");
static_assert((OFF_MB & 7) == 0 && (OFF_MX & 15) == 0 && (OFF_SP & 15) == 0, "align");

enum { MB_UX = 0, MB_UKV = 5, MB_Y = 10, MB_HA = 15, MB_XQ = 20, MB_KV = 21, MB_CF = 22, MB_G = 23, MB_TH = 24, MB_TAG = 25 };
enum { NB_WG0 = 1, NB_ROW0 = 6, NB_ORD = 6, NB_V = 10 };

constexpr double cos_turn(int m, int n) {
  m &= n - 1;
  if (m > n / 2) m = n - m;
  double sgn = 1.0;
  if (m > n / 4) { m = n / 2 - m; sgn = -1.0; }
  if (m == n / 4) return 0.0;
  const double x = 6.283185307179586476925 * m / n;
  double term = 1.0, sum = 1.0;
  for (int k = 1; k < 14; k++) { term *= -x * x / ((2 * k - 1) * (2 * k)); sum += term; }
  return sgn * sum;
}
constexpr uint32_t bf16_bits(double v) {
  if (v == 0.0) return 0;
  uint32_t sgn = 0;
  if (v < 0) { sgn = 0x8000; v = -v; }
  int e = 127;
  while (v < 1.0) { v *= 2.0; e--; }
  while (v >= 2.0) { v *= 0.5; e++; }
  const double f = v * 128.0;
  int m = (int)f;
  if (f - m > 0.5 || (f - m == 0.5 && (m & 1))) m++;
  return sgn | (uint32_t)((e << 7) + (m - 128));
}
constexpr uint32_t f16_bits(double v) {
  if (v == 0.0) return 0;
  uint32_t sgn = 0;
  if (v < 0) { sgn = 0x8000; v = -v; }
  int e = 15;
  while (v < 1.0) { v *= 2.0; e--; }
  const double f = v * 1024.0;
  int m = (int)f;
  if (f - m > 0.5 || (f - m == 0.5 && (m & 1))) m++;
  return sgn | (uint32_t)((e << 10) + (m - 1024));
}
constexpr uint32_t pair_bits(double lo, double hi) { return bf16_bits(lo) | (bf16_bits(hi) << 16); }
constexpr uint32_t pair_h(double lo, double hi) { return f16_bits(lo) | (f16_bits(hi) << 16); }
struct alignas(128) Tables {
  uint32_t mat[3072];
  uint32_t thr[4][128][4];
};
constexpr Tables make_tables() {
  Tables T{};
  for (int q = 0; q < 768; q++) {
    int m0 = 0, d0 = 0, d1 = 0;
    if (q < 512) {
      const int r = (q >> 6) * 8 + (q & 7), cc = (q >> 3) & 7;
      d0 = 4 * (r & 31); d1 = 2 * d0;
      m0 = 8 * (cc & 3) * d0 + ((r >> 5) == (cc >> 2) ? 0 : (r >> 5) ? 96 : 32);
    } else {
      const int r = ((q - 512) >> 5) * 8 + (q & 7), pc = (q >> 3) & 3;
      d0 = 4 * (8 * (r >> 4) + (r & 7)) + 1; d1 = 8 * d0;
      m0 = 2 * pc * d0 + ((r & 8) ? 32 : 0);
    }
    for (int e = 0; e < 4; e++) T.mat[4 * q + e] = pair_h(cos_turn(m0 + e * d1, 128), cos_turn(m0 + e * d1 + d0, 128));
  }
  for (int tid = 0; tid < 128; tid++) {
    const int kk = 4 * (tid >> 2) + 1, t = tid & 3;
    for (int q = 0; q < 4; q++) {
      const int m = (8 * q + 2 * t) * kk;
      T.thr[q >> 1][tid][2 * (q & 1)] = pair_bits(cos_turn(m, 128), cos_turn(m + kk, 128));
      T.thr[q >> 1][tid][2 * (q & 1) + 1] = pair_bits(cos_turn(m + 32, 128), cos_turn(m + kk + 32, 128));
      T.thr[2][tid][q] = pair_h(cos_turn(m, 4096), cos_turn(m + kk, 4096));
      T.thr[3][tid][q] = pair_h(cos_turn(m + 3072, 4096), cos_turn(m + kk + 3072, 4096));
    }
  }
  return T;
}
__device__ const Tables d_tab = make_tables();

struct Params {
  const __nv_bfloat16 *logA, *Aim, *Cre, *Cim, *logdt;
  const Tables* tab;
  unsigned* cnt;
  const __nv_bfloat16 *Dskip, *shift_k, *ssm_D, *gate_w, *q, *ssm_k;
  uint2* part;
  __nv_bfloat16* out;
  unsigned* tl;
  CUtensorMap tq, tk, tv, tkh;
};

__device__ uint2 g_part[NCL * SEQ];
__device__ unsigned g_cnt[CS * 32];
#define TL(i) do {} while (0)
#define TL_INIT() do {} while (0)
#define TL_DUMP() do {} while (0)

__device__ __forceinline__ uint32_t lds16(uint32_t a) { uint32_t v; asm volatile("ld.shared.u16 %0, [%1];" : "=r"(v) : "r"(a) : "memory"); return v; }
__device__ __forceinline__ uint2 lds64(uint32_t a) { uint2 v; asm volatile("ld.shared.v2.u32 {%0,%1}, [%2];" : "=r"(v.x), "=r"(v.y) : "r"(a) : "memory"); return v; }
__device__ __forceinline__ uint4 lds128(uint32_t a) { uint4 v; asm volatile("ld.shared.v4.u32 {%0,%1,%2,%3}, [%4];" : "=r"(v.x), "=r"(v.y), "=r"(v.z), "=r"(v.w) : "r"(a) : "memory"); return v; }
__device__ __forceinline__ void sts16(uint32_t a, uint32_t v) { asm volatile("st.shared.u16 [%0], %1;" :: "r"(a), "r"(v) : "memory"); }
__device__ __forceinline__ void sts32(uint32_t a, uint32_t v) { asm volatile("st.shared.u32 [%0], %1;" :: "r"(a), "r"(v) : "memory"); }
__device__ __forceinline__ void sts64(uint32_t a, uint32_t x, uint32_t y) { asm volatile("st.shared.v2.u32 [%0], {%1,%2};" :: "r"(a), "r"(x), "r"(y) : "memory"); }
__device__ __forceinline__ void sts128(uint32_t a, uint32_t x, uint32_t y, uint32_t z, uint32_t w) { asm volatile("st.shared.v4.u32 [%0], {%1,%2,%3,%4};" :: "r"(a), "r"(x), "r"(y), "r"(z), "r"(w) : "memory"); }
__device__ __forceinline__ void ldsm4t(uint32_t (&r)[4], uint32_t a) { asm volatile("ldmatrix.sync.aligned.m8n8.x4.trans.shared.b16 {%0,%1,%2,%3}, [%4];" : "=r"(r[0]), "=r"(r[1]), "=r"(r[2]), "=r"(r[3]) : "r"(a) : "memory"); }
__device__ __forceinline__ void ldsm2t(uint32_t& r0, uint32_t& r1, uint32_t a) { asm volatile("ldmatrix.sync.aligned.m8n8.x2.trans.shared.b16 {%0,%1}, [%2];" : "=r"(r0), "=r"(r1) : "r"(a) : "memory"); }
__device__ __forceinline__ void ldsm4(uint32_t (&r)[4], uint32_t a) { asm volatile("ldmatrix.sync.aligned.m8n8.x4.shared.b16 {%0,%1,%2,%3}, [%4];" : "=r"(r[0]), "=r"(r[1]), "=r"(r[2]), "=r"(r[3]) : "r"(a) : "memory"); }
__device__ __forceinline__ void stsm4(uint32_t a, const uint32_t (&r)[4]) { asm volatile("stmatrix.sync.aligned.m8n8.x4.shared.b16 [%0], {%1,%2,%3,%4};" :: "r"(a), "r"(r[0]), "r"(r[1]), "r"(r[2]), "r"(r[3]) : "memory"); }
__device__ __forceinline__ uint32_t pack(float lo, float hi) { uint32_t r; asm("cvt.rn.bf16x2.f32 %0, %1, %2;" : "=r"(r) : "f"(hi), "f"(lo)); return r; }
__device__ __forceinline__ float blo(uint32_t v) { return __uint_as_float(v << 16); }
__device__ __forceinline__ float bhi(uint32_t v) { return __uint_as_float(v & 0xffff0000u); }
__device__ __forceinline__ float bf16r(float x) { return blo(pack(x, 0.f)); }
__device__ __forceinline__ uint32_t hmul2(uint32_t a, uint32_t b) { uint32_t r; asm("mul.rn.bf16x2 %0, %1, %2;" : "=r"(r) : "r"(a), "r"(b)); return r; }
__device__ __forceinline__ uint32_t hadd2(uint32_t a, uint32_t b) { uint32_t r; asm("add.rn.bf16x2 %0, %1, %2;" : "=r"(r) : "r"(a), "r"(b)); return r; }
__device__ __forceinline__ uint32_t hfma2(uint32_t a, uint32_t b, uint32_t c) { uint32_t r; asm("fma.rn.bf16x2 %0, %1, %2, %3;" : "=r"(r) : "r"(a), "r"(b), "r"(c)); return r; }
__device__ __forceinline__ uint32_t packh(float lo, float hi) { uint32_t r; asm("cvt.rn.f16x2.f32 %0, %1, %2;" : "=r"(r) : "f"(hi), "f"(lo)); return r; }
__device__ __forceinline__ __half2 H2(uint32_t a) { return *reinterpret_cast<__half2*>(&a); }
__device__ __forceinline__ uint32_t U2(__half2 a) { return *reinterpret_cast<uint32_t*>(&a); }
__device__ __forceinline__ uint32_t fmul(uint32_t a, uint32_t b) { return U2(__hmul2(H2(a), H2(b))); }
__device__ __forceinline__ uint32_t ffma(uint32_t a, uint32_t b, uint32_t c) { return U2(__hfma2(H2(a), H2(b), H2(c))); }
__device__ __forceinline__ uint32_t fneg(uint32_t a) { return U2(__hneg2(H2(a))); }
__device__ __forceinline__ uint32_t amax2(uint32_t a, uint32_t b) { uint32_t r; asm("max.xorsign.abs.bf16x2 %0, %1, %2;" : "=r"(r) : "r"(a), "r"(b)); return r; }
__device__ __forceinline__ uint32_t prmt(uint32_t a, uint32_t b, uint32_t s) { return __byte_perm(a, b, s); }
__device__ __forceinline__ uint32_t ldraw(const __nv_bfloat16* p) { uint32_t v; asm volatile("ld.global.nc.u16 %0, [%1];" : "=r"(v) : "l"(p)); return v; }
__device__ __forceinline__ uint4 ldg128(const void* p) { uint4 v; asm volatile("ld.global.nc.v4.u32 {%0,%1,%2,%3}, [%4];" : "=r"(v.x), "=r"(v.y), "=r"(v.z), "=r"(v.w) : "l"(p)); return v; }
__device__ __forceinline__ void bar_sync(int id, int n) { asm volatile("bar.sync %0, %1;" :: "r"(id), "r"(n) : "memory"); }
__device__ __forceinline__ void bar_arrive(int id, int n) { asm volatile("bar.arrive %0, %1;" :: "r"(id), "r"(n) : "memory"); }
__device__ __forceinline__ void cluster_arrive() { asm volatile("barrier.cluster.arrive.relaxed.aligned;" ::: "memory"); }
__device__ __forceinline__ void cluster_wait() { asm volatile("barrier.cluster.wait.aligned;" ::: "memory"); }
__device__ __forceinline__ void fence_async() { asm volatile("fence.proxy.async.shared::cta;" ::: "memory"); }
__device__ __forceinline__ void fence_mbinit() { asm volatile("fence.mbarrier_init.release.cluster;" ::: "memory"); }
__device__ __forceinline__ uint32_t mapa(uint32_t a, uint32_t rank) { uint32_t r; asm("mapa.shared::cluster.u32 %0, %1, %2;" : "=r"(r) : "r"(a), "r"(rank)); return r; }
__device__ __forceinline__ void bulk_dsmem(uint32_t dst, uint32_t src, uint32_t mbar) {
  asm volatile("cp.async.bulk.shared::cluster.shared::cta.mbarrier::complete_tx::bytes [%0], [%1], 512, [%2];" :: "r"(dst), "r"(src), "r"(mbar) : "memory");
}
__device__ __forceinline__ void bulk_load(uint32_t dst, const void* src, uint32_t bytes, uint32_t mbar) {
  asm volatile("cp.async.bulk.shared::cluster.global.mbarrier::complete_tx::bytes [%0], [%1], %2, [%3];" :: "r"(dst), "l"(src), "r"(bytes), "r"(mbar) : "memory");
}
__device__ __forceinline__ void mbar_init(uint32_t m, uint32_t cnt) { asm volatile("mbarrier.init.shared::cta.b64 [%0], %1;" :: "r"(m), "r"(cnt) : "memory"); }
__device__ __forceinline__ void mbar_expect(uint32_t m, uint32_t bytes) { asm volatile("mbarrier.arrive.expect_tx.shared::cta.b64 _, [%0], %1;" :: "r"(m), "r"(bytes) : "memory"); }
__device__ __forceinline__ bool mbar_try(uint32_t m) {
  uint32_t done;
  asm volatile("{.reg .pred p; mbarrier.try_wait.parity.shared::cta.b64 p, [%1], 0; selp.u32 %0, 1, 0, p;}" : "=r"(done) : "r"(m) : "memory");
  return done;
}
__device__ __forceinline__ void mbar_wait(uint32_t m) {
  if (!mbar_try(m)) {
    int it = 0;
    while (!mbar_try(m) && ++it < (1 << 22)) {}
  }
}
__device__ __forceinline__ bool elect() {
  uint32_t e;
  asm volatile("{.reg .pred p; elect.sync _|p, 0xffffffff; selp.u32 %0, 1, 0, p;}" : "=r"(e));
  return e;
}
__device__ __forceinline__ void tma_load4(uint32_t dst, const CUtensorMap* tm, int c0, int c1, int c2, int c3, uint32_t mbar) {
  asm volatile("cp.async.bulk.tensor.4d.shared::cluster.global.mbarrier::complete_tx::bytes [%0], [%1, {%3, %4, %5, %6}], [%2];"
               :: "r"(dst), "l"(tm), "r"(mbar), "r"(c0), "r"(c1), "r"(c2), "r"(c3) : "memory");
}
__device__ __forceinline__ void tma_load3(uint32_t dst, const CUtensorMap* tm, int c0, int c1, int c2, uint32_t mbar) {
  asm volatile("cp.async.bulk.tensor.3d.shared::cluster.global.mbarrier::complete_tx::bytes [%0], [%1, {%3, %4, %5}], [%2];"
               :: "r"(dst), "l"(tm), "r"(mbar), "r"(c0), "r"(c1), "r"(c2) : "memory");
}
__device__ __forceinline__ void tma_store3(const CUtensorMap* tm, int c0, int c1, int c2, uint32_t src) {
  asm volatile("cp.async.bulk.tensor.3d.global.shared::cta.bulk_group [%0, {%2, %3, %4}], [%1];"
               :: "l"(tm), "r"(src), "r"(c0), "r"(c1), "r"(c2) : "memory");
}
__device__ __forceinline__ void wg_fence() { asm volatile("wgmma.fence.sync.aligned;" ::: "memory"); }
__device__ __forceinline__ void wg_commit() { asm volatile("wgmma.commit_group.sync.aligned;" ::: "memory"); }
template <int N> __device__ __forceinline__ void wg_wait() { asm volatile("wgmma.wait_group.sync.aligned %0;" :: "n"(N) : "memory"); }
template <int N> __device__ __forceinline__ void tie_all(uint32_t (&x)[N]) {
#pragma unroll
  for (int i = 0; i < N; i++) asm volatile("" : "+r"(x[i]) :: "memory");
}
template <int N> __device__ __forceinline__ void tie_all(float (&x)[N]) {
#pragma unroll
  for (int i = 0; i < N; i++) asm volatile("" : "+f"(x[i]) :: "memory");
}
#define R16(C, d) C(d[0]), C(d[1]), C(d[2]), C(d[3]), C(d[4]), C(d[5]), C(d[6]), C(d[7]), C(d[8]), C(d[9]), C(d[10]), C(d[11]), C(d[12]), C(d[13]), C(d[14]), C(d[15])
#define R32(C, d) R16(C, d), R16(C, (d + 16))
#define P16 "{%0,%1,%2,%3,%4,%5,%6,%7,%8,%9,%10,%11,%12,%13,%14,%15}"
#define P32 "{%0,%1,%2,%3,%4,%5,%6,%7,%8,%9,%10,%11,%12,%13,%14,%15,%16,%17,%18,%19,%20,%21,%22,%23,%24,%25,%26,%27,%28,%29,%30,%31}"
template <int SD, int TB, int OFF> __device__ __forceinline__ void rs64(float* d, const uint32_t* a, uint64_t db) {
  if (SD) asm volatile("{.reg .b64 db; add.s64 db, %36, %37; wgmma.mma_async.sync.aligned.m64n64k16.f32.bf16.bf16 " P32 ", {%32,%33,%34,%35}, db, 1, 1, 1, %38;}"
                       : R32("+f", d) : "r"(a[0]), "r"(a[1]), "r"(a[2]), "r"(a[3]), "l"(db), "n"(OFF), "n"(TB));
  else asm volatile("{.reg .b64 db; add.s64 db, %36, %37; wgmma.mma_async.sync.aligned.m64n64k16.f32.bf16.bf16 " P32 ", {%32,%33,%34,%35}, db, 0, 1, 1, %38;}"
                    : R32("=f", d) : "r"(a[0]), "r"(a[1]), "r"(a[2]), "r"(a[3]), "l"(db), "n"(OFF), "n"(TB));
}
template <int SD, int TB, int OFF> __device__ __forceinline__ void rs64h(uint32_t* d, const uint32_t* a, uint64_t db) {
  if (SD) asm volatile("{.reg .b64 db; add.s64 db, %20, %21; wgmma.mma_async.sync.aligned.m64n64k16.f16.f16.f16 " P16 ", {%16,%17,%18,%19}, db, 1, 1, 1, %22;}"
                       : R16("+r", d) : "r"(a[0]), "r"(a[1]), "r"(a[2]), "r"(a[3]), "l"(db), "n"(OFF), "n"(TB));
  else asm volatile("{.reg .b64 db; add.s64 db, %20, %21; wgmma.mma_async.sync.aligned.m64n64k16.f16.f16.f16 " P16 ", {%16,%17,%18,%19}, db, 0, 1, 1, %22;}"
                    : R16("=r", d) : "r"(a[0]), "r"(a[1]), "r"(a[2]), "r"(a[3]), "l"(db), "n"(OFF), "n"(TB));
}
template <int SD, int OFFA, int OFFB> __device__ __forceinline__ void ss32(float* d, uint64_t da, uint64_t db) {
  if (SD) asm volatile("{.reg .b64 da, db; add.s64 da, %16, %18; add.s64 db, %17, %19; wgmma.mma_async.sync.aligned.m64n32k16.f32.f16.f16 " P16 ", da, db, 1, 1, 1, 1, 1;}"
                       : R16("+f", d) : "l"(da), "l"(db), "n"(OFFA), "n"(OFFB));
  else asm volatile("{.reg .b64 da, db; add.s64 da, %16, %18; add.s64 db, %17, %19; wgmma.mma_async.sync.aligned.m64n32k16.f32.f16.f16 " P16 ", da, db, 0, 1, 1, 1, 1;}"
                    : R16("=f", d) : "l"(da), "l"(db), "n"(OFFA), "n"(OFFB));
}
#define KGEN_ASM(SD) "{.reg .b64 da, db; add.s64 da, %32, %33; add.s64 db, %32, %34;\n" \
  "wgmma.mma_async.sync.aligned.m64n64k16.f32.bf16.bf16 " P32 ", da, db, " SD ", 1, 1, 1, 1;}"
template <int KS> __device__ __forceinline__ void kgen_mma(float (&c)[32], uint64_t da) {
  if (KS) asm volatile(KGEN_ASM("1") : R32("+f", c) : "l"(da), "n"(8 * KS), "n"(8 * KS + 512));
  else asm volatile(KGEN_ASM("0") : R32("=f", c) : "l"(da), "n"(8 * KS), "n"(8 * KS + 512));
  if constexpr (KS < 7) kgen_mma<KS + 1>(c, da);
}
__device__ __forceinline__ uint64_t desc_lo(uint32_t a) { return (uint64_t)((a & 0x3FFFF) >> 4); }
__device__ __forceinline__ void stage1(float (&D)[32], const uint32_t (&A1)[8], uint32_t src) {
  const uint64_t du = desc_lo(src) | (128ull << 16) | (32ull << 32) | (2ull << 62);
  rs64<0, 1, 0>(D, A1, du); rs64<1, 1, 64>(D, A1 + 4, du);
}
template <int INV> __device__ __forceinline__ void stage2(uint32_t (&X)[16], const uint32_t (&F)[16], uint32_t cf) {
  constexpr int KS = INV ? 16 : 128, TB = INV ? 0 : 1;
  const uint64_t dc = desc_lo(cf) | (INV ? (8ull << 16) | (64ull << 32) : (64ull << 16) | (8ull << 32));
  rs64h<0, TB, 0>(X, F, dc); rs64h<1, TB, KS>(X, F + 4, dc); rs64h<1, TB, 2 * KS>(X, F + 8, dc); rs64h<1, TB, 3 * KS>(X, F + 12, dc);
}
__device__ __forceinline__ void fwd_mid(uint32_t (&F)[16], const float (&D)[32], const uint32_t (&tc)[4], const uint32_t (&ts)[4]) {
#pragma unroll
  for (int j = 0; j < 4; j++)
#pragma unroll
    for (int b = 0; b < 2; b++) {
      const int i = 4 * j + 16 * b;
      const uint32_t ar = packh(D[i], D[i + 1]), ai = packh(D[i + 2], D[i + 3]);
      F[2 * j + b] = ffma(ar, tc[j], fmul(ai, ts[j]));
      F[8 + 2 * j + b] = ffma(ai, tc[j], fneg(fmul(ar, ts[j])));
    }
}
__device__ __forceinline__ void put_exp(uint32_t a, uint32_t m, int lane) {
  m = __reduce_max_sync(0xffffffffu, max(m & 0x7f80u, (m >> 16) & 0x7f80u));
  if (lane == 0) sts32(a, m);
}
__device__ __forceinline__ uint32_t seq_mag(uint32_t a) {
  const uint4 x = lds128(a), y = lds128(a + 2048);
  return amax2(amax2(amax2(x.x, x.y), amax2(x.z, x.w)), amax2(amax2(y.x, y.y), amax2(y.z, y.w)));
}
__device__ __forceinline__ uint32_t get_exp(uint32_t a) { const uint4 v = lds128(a); return max(max(v.x, v.y), max(v.z, v.w)) >> 7; }
__device__ __forceinline__ void scale_a1(uint32_t (&As)[8], const uint32_t (&A1)[8], uint32_t field) {
#pragma unroll
  for (int i = 0; i < 8; i++) As[i] = hmul2(A1[i], field * 0x00800080u);
}

struct cf { float x, y; };
__device__ __forceinline__ cf cmul(cf a, cf b) { cf r; r.x = fmaf(a.x, b.x, -a.y * b.y); r.y = fmaf(a.x, b.y, a.y * b.x); return r; }
__device__ __forceinline__ cf cexp_p(float lr2, float lt, float p) {
  float m;
  asm("ex2.approx.ftz.f32 %0, %1;" : "=f"(m) : "f"(lr2 * p));
  float t = lt * p;
  t = (t - rintf(t)) * 6.283185307179586f;
  cf r; r.x = m * __cosf(t); r.y = m * __sinf(t); return r;
}
__device__ __forceinline__ void store8(uint32_t a, uint32_t b, const cf (&v)[8]) {
  sts128(a, pack(v[0].x, v[1].x), pack(v[2].x, v[3].x), pack(v[4].x, v[5].x), pack(v[6].x, v[7].x));
  sts128(b, pack(v[0].y, v[1].y), pack(v[2].y, v[3].y), pack(v[4].y, v[5].y), pack(v[6].y, v[7].y));
}
__device__ __forceinline__ void mbar_arrive(uint32_t m) { asm volatile("mbarrier.arrive.shared::cta.b64 _, [%0];" :: "r"(m) : "memory"); }
__device__ __forceinline__ float sigmoidf_(float s) { return __frcp_rn(1.f + __expf(-s)); }

__global__ void __cluster_dims__(CS, 1, 1) __launch_bounds__(NTHREADS, 1) fused_kernel(const __grid_constant__ Params p) {
  extern __shared__ __align__(1024) uint8_t smem[];
  TL_INIT();
  TL(31);
  const int wid = __shfl_sync(0xffffffffu, threadIdx.x >> 5, 0);
  const uint32_t sb = (uint32_t)__cvta_generic_to_shared(smem);
  const uint32_t mb = sb + OFF_MB;
  const int u = wid >> 2, w = wid & 3;
  const int tid = threadIdx.x & 127, lane = tid & 31, g = lane >> 2, t = lane & 3;
  const int cl = blockIdx.x >> 3, rank = blockIdx.x & 7;
  const int ch0 = cl * CPC;
  const int nu = min(5, (DCH - ch0) >> 3);
  const bool act = u < nu;

  uint32_t pla, pai, pcr, pci, pdt, tag = 0;
  auto load_params = [&]() {
    const int ch = act ? ch0 + 8 * u + rank : 0, o = ch * NMODE + tid;
    pla = ldraw(p.logA + o); pdt = ldraw(p.logdt + ch); pai = ldraw(p.Aim + o); pcr = ldraw(p.Cre + o); pci = ldraw(p.Cim + o);
  };
  if (u == 4) {
    const bool e = elect();
    if (e) {
#pragma unroll
      for (int i = 0; i < 5; i++) mbar_init(mb + 40 * w + 8 * i, 1);
      if (w == 3) { mbar_init(mb + 8 * MB_TH, 1); mbar_init(mb + 8 * MB_XQ, 21); mbar_init(mb + 8 * MB_KV, 1); }
      if (w == 2) { mbar_init(mb + 8 * MB_CF, 1); mbar_init(mb + 8 * MB_G, 8); }
      fence_mbinit();
    }
    __syncwarp();
    load_params();
    if (w == 0 && lane < 2) asm volatile("atom.relaxed.gpu.global.add.u32 %0, [%1], %2;" : "=r"(tag) : "l"(&p.cnt[rank * 32 + lane]), "r"(cl == 0 ? 16 - (NCL - 1) : 1) : "memory");
    if (e) {
      if (w == 3) {
        mbar_expect(mb + 8 * MB_TH, 8192 + 112 * nu);
        bulk_load(sb + OFF_YB, p.tab->thr, 8192, mb + 8 * MB_TH);
        bulk_load(sb + OFF_SP, p.gate_w + ch0, 16 * nu, mb + 8 * MB_TH);
        bulk_load(sb + OFF_SP + 80, p.Dskip + ch0, 16 * nu, mb + 8 * MB_TH);
        bulk_load(sb + OFF_SP + 160, p.ssm_D + ch0, 16 * nu, mb + 8 * MB_TH);
        bulk_load(sb + OFF_SP + 240, p.shift_k + 4 * ch0, 64 * nu, mb + 8 * MB_TH);
        asm volatile("cp.async.bulk.prefetch.L2.global [%0], 12288;" :: "l"(p.tab->mat) : "memory");
        mbar_expect(mb + 8 * MB_XQ, 20480);
        tma_load3(sb + OFF_TQ, &p.tq, ch0, 8 * rank, 0, mb + 8 * MB_XQ);
        TL(20);
        mbar_expect(mb + 8 * MB_KV, 2 * 20480 + 320);
      }
      if (w == 2) mbar_expect(mb + 8 * MB_CF, 12288);
#pragma unroll
      for (int i = 0; i < 5; i++) mbar_expect(mb + 40 * w + 8 * i, w == 3 ? 4096 : w == 2 ? 7168 : 3584);
    }
    __syncwarp();
  } else {
    load_params();
  }
  cluster_arrive();
  TL(0);

  const uint32_t tab = sb + OFF_T + u * KTAB;
  const uint32_t toff = (64 * w + lane) * 80 + 16 * u;
  auto put = [&](uint32_t dst, const uint32_t (&a)[4], const uint32_t (&b)[4]) {
    const uint32_t s0 = (g & 1) ? 0x7632 : 0x5410, s1 = s0 ^ 0x2222;
    const uint32_t o = dst + 128 * t + 64 * (g & 1) + 16 * (w ^ t);
    sts128(o, prmt(a[0], a[1], s0), prmt(a[2], a[3], s0), prmt(b[0], b[1], s0), prmt(b[2], b[3], s0));
    sts128(o ^ 64, prmt(a[0], a[1], s1), prmt(a[2], a[3], s1), prmt(b[0], b[1], s1), prmt(b[2], b[3], s1));
  };
  const int d0 = rank ^ (2 * w), d1 = d0 ^ 1;
  const uint32_t rb0 = mapa(sb, d0), rb1 = mapa(sb, d1);
  auto send = [&](int stage, int dst, int mbar) {
    if (elect()) {
      if (w) bulk_dsmem(rb0 + dst, sb + stage + d0 * 512, rb0 + mbar);
      bulk_dsmem(rb1 + dst, sb + stage + d1 * 512, rb1 + mbar);
    }
    __syncwarp();
  };

  uint32_t A1[8], tc[4], ts[4];
  {
    const float dt = bf16r(expf(blo(pdt)));
    const float lr2 = (-bf16r(expf(blo(pla))) * dt) * 1.4426950408889634f;
    const float lt = (blo(pai) * dt) * 0.15915494309189535f;
    const uint32_t tim = sb + (u ? OFF_IM + (u - 1) * KTAB : OFF_UX);
    const uint32_t row = tab + tid * 16, rim = tim + tid * 16;
    const cf w1 = cexp_p(lr2, lt, 8.f);
    cf z1 = cexp_p(lr2, lt, 1.f), Z = cexp_p(lr2, lt, 256.f);
    if (lr2 != 123.f) TL(16);
    TL(12);
    {
      cf v[8];
      v[0].x = 1.f; v[0].y = 0.f; v[1] = w1; v[2] = cmul(w1, w1); v[3] = cmul(v[2], w1);
      const cf w4 = cmul(v[2], v[2]);
      v[4] = w4; v[5] = cmul(v[1], w4); v[6] = cmul(v[2], w4); v[7] = cmul(v[3], w4);
      const cf w8 = cmul(w4, w4);
      store8(row, rim, v);
#pragma unroll
      for (int k = 1; k < 4; k++) {
#pragma unroll
        for (int i = 0; i < 8; i++) v[i] = (k == 1 && i == 0) ? w8 : cmul(v[i], w8);
        store8(row + 2048 * k, rim + 2048 * k, v);
      }
    }
    cluster_wait();
    if (u) cluster_arrive();
    mbar_wait(mb + 8 * MB_TH);
    {
      const uint4 x = lds128(sb + OFF_YB + 16 * tid), y = lds128(sb + OFF_YB + 2048 + 16 * tid), a = lds128(sb + OFF_YB + 4096 + 16 * tid), b = lds128(sb + OFF_YB + 6144 + 16 * tid);
      A1[0] = x.x; A1[1] = x.y; A1[2] = x.z; A1[3] = x.w; A1[4] = y.x; A1[5] = y.y; A1[6] = y.z; A1[7] = y.w;
      tc[0] = a.x; tc[1] = a.y; tc[2] = a.z; tc[3] = a.w; ts[0] = b.x; ts[1] = b.y; ts[2] = b.z; ts[3] = b.w;
    }
    if (wid == 16 && lane == 0) sts32(mb + 8 * MB_TAG, tag);
    __syncwarp();
    if (lane == 0) mbar_arrive(mb + 8 * MB_XQ);
    if (u == 1) {
      float z0_ = 0.f, z1_ = 0.f, z2_ = 0.f, z3_ = 0.f;
      asm volatile("mma.sync.aligned.m16n8k8.row.col.f32.bf16.bf16.f32 {%0,%1,%2,%3}, {%4,%4}, {%4}, {%0,%1,%2,%3};"
                   : "+f"(z0_), "+f"(z1_), "+f"(z2_), "+f"(z3_) : "r"(pla >> 16));
      pcr += __float_as_uint(z0_);
      if (w == 0 && elect()) {
        tma_load3(sb + OFF_TK, &p.tk, ch0, 8 * rank, 0, mb + 8 * MB_KV);
        tma_load3(sb + OFF_HALO, &p.tkh, ch0, 8 * rank - 1, 28, mb + 8 * MB_KV);
      }
      __syncwarp();
      TL(8);
    }
    {
      z1.y = -z1.y; Z.y = -Z.y;
      const cf z2 = cmul(z1, z1);
      cf h[8], v[8];
      h[0].x = 2.f * blo(pcr) * dt; h[0].y = -2.f * blo(pci) * dt;
      h[1] = cmul(h[0], z1);
#pragma unroll
      for (int i = 2; i < 8; i++) h[i] = cmul(h[i - 2], z2);
      store8(row + 4 * 2048, rim + 4 * 2048, h);
      const cf h8 = cmul(h[6], z2);
      v[0] = cmul(h[0], Z); v[2] = cmul(h[2], Z); v[3] = cmul(h[4], Z); v[6] = cmul(h[6], Z); v[7] = cmul(h8, Z);
      v[1] = v[0]; v[4] = v[5] = v[3];
      store8(row + 5 * 2048, rim + 5 * 2048, v);
      h[0] = cmul(v[0], Z); h[1] = cmul(v[3], Z); h[3] = cmul(v[7], Z); h[4] = cmul(h[0], Z); h[5] = cmul(h[1], Z); h[7] = cmul(h[3], Z);
      h[2] = h[1]; h[6] = h[5];
      store8(row + 6 * 2048, rim + 6 * 2048, h);
      const cf Z2 = cmul(Z, Z);
      v[0] = cmul(h[0], Z2); v[1] = cmul(h[3], Z2); v[2] = cmul(h[4], Z2); v[3] = cmul(h[7], Z2);
#pragma unroll
      for (int i = 4; i < 8; i++) v[i] = cmul(v[i - 4], Z2);
      store8(row + 7 * 2048, rim + 7 * 2048, v);
    }
    TL(17);
    mbar_wait(mb + 8 * MB_XQ);
    TL(18);
    uint32_t x0[4], x1[4];
    ldsm4t(x0, sb + OFF_TQ + toff);
    ldsm4t(x1, sb + OFF_TQ + toff + 2560);
    put(sb + OFF_YB + u * 4096 + g * 512, x0, x1);
    TL(3);
    fence_async();
    if (u) bar_sync(NB_ORD + u - 1, 256); else bar_sync(NB_WG0, 128);
    TL(13);
    float c[32];
    wg_fence();
    kgen_mma<0>(c, desc_lo(tab) | ((uint64_t)((tim - tab) >> 4) << 16) | (64ull << 32));
    wg_commit();
    if (u < 4) bar_arrive(NB_ORD + u, 256);
    TL(14);
    wg_wait<0>(); tie_all(c);
    TL(26);
    if (u == 0) cluster_arrive();
    if (u == 1) bar_arrive(NB_V, 160);
    bar_sync(NB_WG0 + u, 128);
    if (w == 1) {
      if (u == 2) bar_sync(NB_V, 160);
      if (elect()) {
        if (u == 1) bulk_load(sb + OFF_CF, p.tab->mat, 12288, mb + 8 * MB_CF);
        if (u == 2) tma_load3(sb + OFF_TV, &p.tv, ch0, 8 * rank, 0, mb + 8 * MB_KV);
      }
      __syncwarp();
    }
    const uint32_t k0 = pack(c[0] + c[6], c[1] + c[7]), k1 = pack(c[8] + c[14], c[9] + c[15]);
    const uint32_t k2 = pack(c[16] + c[22], c[17] + c[23]), k3 = pack(c[24] + c[30], c[25] + c[31]);
    const uint32_t ka = tab + 16 * (8 * w + (g ^ w));
    sts32(ka + 4 * t, k0);
    sts32(ka + 512 + 4 * t, k1);
    sts64(ka + 1024 + 512 * (t >> 1) + 8 * (t & 1), prmt(k2, 0, 0x1010), (t & 1) ? prmt(k2, 0, 0x3232) : k2);
    const uint32_t lo = prmt(k3, 0, 0x1010), hi = prmt(k3, 0, 0x3232);
    sts128(ka + 2048 + 512 * t, lo, lo, (g & 1) ? hi : k3, hi);
    put_exp(sb + OFF_MX + u * 64 + 4 * w, amax2(amax2(k0, k1), amax2(k2, k3)), lane);
    cluster_wait();
    cluster_arrive();
    TL(4);
    send(OFF_YB + u * 4096, OFF_UX + u * 4096 + 512 * rank, OFF_MB + 8 * (MB_UX + u));
    if (g == rank) put(sb + OFF_UX + u * 4096 + 512 * rank, x0, x1);
    TL(15);
    fence_async();
    bar_sync(NB_WG0 + u, 128);
  }

#pragma unroll
  for (int isA = 0; isA < 2; isA++) {
    {
      TL(1 + isA);
      const uint32_t usrc = isA ? tab + T_UKV : sb + OFF_UX + u * 4096;
      const uint32_t mxa = sb + OFF_MX + u * 64 + 32 * isA;
      const uint32_t pd = lds16(sb + OFF_SP + 80 + 80 * isA + 16 * u + 2 * rank);
      float D[32];
      uint32_t As[8], F[16], H[16], X[16];
      const uint32_t eh = min(max((int)get_exp(mxa), (int)((pd >> 7) & 0xff) - 5), 240);
      scale_a1(As, A1, 248 - eh);
      wg_fence();
      stage1(D, As, isA ? tab + T_HA : tab);
      wg_commit();
      wg_wait<0>(); tie_all(D);
      fwd_mid(F, D, tc, ts);
      if (!isA) mbar_wait(mb + 8 * MB_CF);
      wg_fence();
      stage2<0>(H, F, sb + OFF_CF);
      wg_commit();
      if (!isA) {
        if (w == 2 && elect()) bulk_load(tab + T_HA, p.ssm_k + (size_t)(act ? ch0 + 8 * u + rank : 0) * SEQ, 4096, mb + 8 * (MB_HA + u));
        __syncwarp();
        if (u < 2) {
          float s0 = 0.f;
#pragma unroll
          for (int j = 0; j < 5; j++) {
            if (j >= 2 && j >= nu) break;
            const uint4 gw = lds128(sb + OFF_SP + 16 * j), x = lds128(sb + OFF_TQ + (tid + 128 * u) * 80 + 16 * j);
            const uint32_t m0 = hmul2(x.x, gw.x), m1 = hmul2(x.y, gw.y), m2 = hmul2(x.z, gw.z), m3 = hmul2(x.w, gw.w);
            s0 += ((blo(m0) + bhi(m0)) + (blo(m1) + bhi(m1))) + ((blo(m2) + bhi(m2)) + (blo(m3) + bhi(m3)));
          }
          tag = (lds64(mb + 8 * MB_TAG).x >> 4) + 1;
          asm volatile("st.relaxed.gpu.global.u64 [%0], %1;" :: "l"(p.part + cl * SEQ + rank * 256 + tid + 128 * u),
                       "l"(((uint64_t)tag << 32) | __float_as_uint(s0)) : "memory");
        }
        TL(7);
      }
      mbar_wait(mb + 8 * ((isA ? MB_UKV : MB_UX) + u));
      TL(5 + isA);
      put_exp(mxa + 16 + 4 * w, seq_mag(usrc + 16 * tid), lane);
      bar_sync(NB_WG0 + u, 128);
      const uint32_t eu = min(get_exp(mxa + 16), 240u);
      scale_a1(As, A1, 250 - eu);
      wg_wait<0>(); tie_all(H);
      wg_fence();
      stage1(D, As, usrc);
      wg_commit();
      wg_wait<0>(); tie_all(D);
      fwd_mid(F, D, tc, ts);
      wg_fence();
      stage2<0>(X, F, sb + OFF_CF);
      wg_commit();
      {
        const float dsk = blo(pd) * __uint_as_float((248 - eh) << 23);
        const uint32_t d2 = packh(dsk, dsk);
#pragma unroll
        for (int j = 0; j < 4; j++) H[2 * j] = U2(__hadd2(H2(H[2 * j]), H2(d2)));
      }
      wg_wait<0>(); tie_all(X);
#pragma unroll
      for (int j = 0; j < 4; j++) {
        const uint32_t h0r = H[2 * j], h1r = H[2 * j + 1], h0i = H[8 + 2 * j], h1i = H[9 + 2 * j];
        const uint32_t x0r = X[2 * j], x1r = X[2 * j + 1], x0i = X[8 + 2 * j], x1i = X[9 + 2 * j];
        F[2 * j] = ffma(x0r, h0r, fneg(fmul(x0i, h0i)));
        F[8 + 2 * j] = ffma(x0r, h0i, fmul(x0i, h0r));
        F[2 * j + 1] = ffma(x1r, h0r, ffma(fneg(x1i), h0i, ffma(x0r, h1r, fneg(ffma(x0i, h1i, F[8 + 2 * j])))));
        F[9 + 2 * j] = ffma(x1r, h0i, ffma(x1i, h0r, ffma(x0r, h1i, ffma(x0i, h1r, F[2 * j]))));
      }
      wg_fence();
      stage2<1>(H, F, sb + OFF_CF);
      wg_commit();
      wg_wait<0>(); tie_all(H);
      {
        const uint32_t va = tab + (16 * w + (lane & 15)) * 128;
        const int vx = (lane >> 4) ^ (lane & 7);
#pragma unroll
        for (int j = 0; j < 4; j++) {
          uint32_t V[4];
#pragma unroll
          for (int b = 0; b < 2; b++) {
            const uint32_t er = H[2 * j + b], ei = H[8 + 2 * j + b];
            V[2 * b] = ffma(er, tc[j], fneg(fmul(ei, ts[j])));
            V[2 * b + 1] = ffma(ei, tc[j], fmul(er, ts[j]));
          }
          stsm4(va + ((vx ^ (2 * j)) << 4), V);
        }
      }
      if (!isA) {
        cluster_wait();
        mbar_wait(mb + 8 * MB_KV);
        TL(21);
        uint32_t K[3][4], V[2][4];
        const uint2 psw = lds64(sb + OFF_SP + 240 + 64 * u + 8 * g);
        ldsm4t(K[0], w ? sb + OFF_TK + toff - 2560 : (lane & 7) ? sb + OFF_TK + toff + 223 * 80 : sb + OFF_HALO + 10 * lane + 16 * u);
        ldsm4t(K[1], sb + OFF_TK + toff);
        ldsm4t(K[2], sb + OFF_TK + toff + 2560);
        ldsm4t(V[0], sb + OFF_TV + toff);
        ldsm4t(V[1], sb + OFF_TV + toff + 2560);
        mbar_wait(mb + 8 * (MB_HA + u));
        const uint4 hx = lds128(tab + T_HA + 16 * tid), hy = lds128(tab + T_HA + 2048 + 16 * tid);
        const uint32_t w0 = prmt(psw.x, 0, 0x1010), w1 = prmt(psw.x, 0, 0x3232), w2 = prmt(psw.y, 0, 0x1010), w3 = prmt(psw.y, 0, 0x3232);
#pragma unroll
        for (int m = 4; m < 12; m++)
          V[(m >> 2) - 1][m & 3] = hmul2(hfma2(K[m >> 2][m & 3], w0, hfma2(K[(m - 1) >> 2][(m - 1) & 3], w1,
                                         hfma2(K[(m - 2) >> 2][(m - 2) & 3], w2, hmul2(K[(m - 3) >> 2][(m - 3) & 3], w3)))), V[(m >> 2) - 1][m & 3]);
        put(g == rank ? tab + T_UKV + 512 * rank : sb + OFF_YA + u * 4096 + g * 512, V[0], V[1]);
        put_exp(mxa + 32 + 4 * w, amax2(amax2(amax2(hx.x, hx.y), amax2(hx.z, hx.w)), amax2(amax2(hy.x, hy.y), amax2(hy.z, hy.w))), lane);
        sts128(tab + T_HA + 16 * (tid ^ (lane >> 3)), hx.x, hx.y, hx.z, hx.w);
        sts128(tab + T_HA + 2048 + 16 * (tid ^ (lane >> 3)), hy.x, hy.y, hy.z, hy.w);
        TL(22);
      }
      fence_async();
      bar_sync(NB_WG0 + u, 128);
      float O[16];
      {
        const uint64_t dv = desc_lo(tab) | (1ull << 16) | (64ull << 32) | (1ull << 62);
        const uint64_t dl = desc_lo(sb + OFF_CL) | (32ull << 16) | (8ull << 32);
        wg_fence();
        ss32<0, 0, 0>(O, dv, dl); ss32<1, 128, 64>(O, dv, dl); ss32<1, 256, 128>(O, dv, dl); ss32<1, 384, 192>(O, dv, dl);
        wg_commit();
      }
      if (!isA) send(OFF_YA + u * 4096, OFF_T + u * KTAB + T_UKV + 512 * rank, OFF_MB + 8 * (MB_UKV + u));
      wg_wait<0>(); tie_all(O);
      {
        const uint32_t co = ((8 * w + g) ^ (2 * t) ^ rank) * 16;
        const int yo = (isA ? OFF_YA : OFF_YB) + (8 * u + rank) * 512, ym = OFF_MB + 8 * (MB_Y + u);
        const uint32_t us = min(max((int)(eu + eh) - 127, 0), 254) * 0x00800080u;
        const uint32_t a0 = hmul2(pack(O[0], O[1]), us), a1 = hmul2(pack(O[4], O[5]), us), a2 = hmul2(pack(O[8], O[9]), us), a3 = hmul2(pack(O[12], O[13]), us);
        const uint32_t b0 = hmul2(pack(O[2], O[3]), us), b1 = hmul2(pack(O[6], O[7]), us), b2 = hmul2(pack(O[10], O[11]), us), b3 = hmul2(pack(O[14], O[15]), us);
        sts128((t == rank ? sb + yo : usrc + t * 512) + co, a0, a1, a2, a3);
        sts128((t + 4 == rank ? sb + yo : usrc + t * 512 + 2048) + co, b0, b1, b2, b3);
        fence_async();
        bar_sync(NB_WG0 + u, 128);
        send(usrc - sb, yo, ym);
      }
      TL(9 + isA);
      if (isA && u < 2) {
        tag = (lds64(mb + 8 * MB_TAG).x >> 4) + 1;
        uint64_t ga[NCL];
        const int slot = tid + 128 * u;
        const uint2* gp = p.part + rank * 256 + slot;
        float s;
        bool ok;
#pragma unroll 1
        for (int it = 0;; it++) {
#pragma unroll
          for (int k = 0; k < NCL; k++) asm volatile("ld.relaxed.gpu.global.u64 %0, [%1];" : "=l"(ga[k]) : "l"(gp + k * SEQ) : "memory");
          ok = true; s = 0.f;
#pragma unroll
          for (int k = 0; k < NCL; k++) { ok = ok && (uint32_t)(ga[k] >> 32) == tag; s += __uint_as_float((uint32_t)ga[k]); }
          if (ok || it == 4000) break;
        }
        if (!ok) {
          const uint32_t* xr = (const uint32_t*)(p.q + (size_t)(rank * 256 + 32 * (slot & 7) + (slot >> 3)) * DCH);
          const uint32_t* gr = (const uint32_t*)p.gate_w;
          s = 0.f;
    #pragma unroll 1
          for (int k = 0; k < DCH / 2; k++) { const uint32_t m = hmul2(__ldg(xr + k), __ldg(gr + k)); s += blo(m) + bhi(m); }
        }
        const float g0 = bf16r(sigmoidf_(bf16r(s)));
        sts64(sb + OFF_GB + 8 * slot, pack(g0, g0), pack(1.f - g0, 1.f - g0));
        __syncwarp();
        if (lane == 0) mbar_arrive(mb + 8 * MB_G);
      }
    }
  }

  {
    mbar_wait(mb + 8 * MB_G);
    uint2 gg[2][4];
    uint32_t qv[2][4];
#pragma unroll
    for (int hh = 0; hh < 2; hh++)
#pragma unroll
      for (int i = 0; i < 4; i++) gg[hh][i] = lds64(sb + OFF_GB + 8 * (64 * w + 32 * hh + 8 * i + g));
    const uint32_t qa = sb + OFF_TQ + toff;
    ldsm4(qv[0], qa);
    ldsm4(qv[1], qa + 2560);
    TL(24);
    mbar_wait(mb + 8 * (MB_Y + u));
    uint32_t ya[2][4], yb[2][4];
#pragma unroll
    for (int hh = 0; hh < 2; hh++) {
      const uint32_t yo = (8 * u + (lane & 7)) * 512 + ((8 * w + 4 * hh + (lane >> 3)) ^ (2 * (rank & 3)) ^ (lane & 7)) * 16;
      ldsm4t(ya[hh], sb + OFF_YA + yo); ldsm4t(yb[hh], sb + OFF_YB + yo);
    }
#pragma unroll
    for (int hh = 0; hh < 2; hh++) {
      uint32_t o[4];
#pragma unroll
      for (int i = 0; i < 4; i++) o[i] = hadd2(hmul2(gg[hh][i].x, hmul2(qv[hh][i], ya[hh][i])), hmul2(gg[hh][i].y, yb[hh][i]));
      stsm4(qa + 2560 * hh, o);
    }
    TL(25);
  }
  cluster_arrive();
  bar_sync(NB_ROW0 + w, 160);
  {
    uint4 v[2];
#pragma unroll
    for (int k = 0; k < 2; k++) {
      const int i = 64 * u + 32 * k + lane, sl = (i * 205) >> 10, cc = i - 5 * sl;
      v[k] = lds128(sb + OFF_TQ + (64 * w + 8 * (sl & 7) + (sl >> 3)) * 80 + cc * 16);
    }
#pragma unroll
    for (int k = 0; k < 2; k++) {
      const int i = 64 * u + 32 * k + lane, sl = (i * 205) >> 10, cc = i - 5 * sl;
      if (cc < nu)
        asm volatile("st.global.v4.u32 [%0], {%1,%2,%3,%4};" :: "l"(p.out + (size_t)(256 * rank + 32 * (sl >> 3) + 8 * w + (sl & 7)) * DCH + ch0 + 8 * cc),
                     "r"(v[k].x), "r"(v[k].y), "r"(v[k].z), "r"(v[k].w) : "memory");
    }
  }
  cluster_wait();
  TL(27);
  TL_DUMP();
}

typedef CUresult (*EncodeFn)(CUtensorMap*, CUtensorMapDataType, cuuint32_t, void*, const cuuint64_t*, const cuuint64_t*,
                             const cuuint32_t*, const cuuint32_t*, CUtensorMapInterleave, CUtensorMapSwizzle,
                             CUtensorMapL2promotion, CUtensorMapFloatOOBfill);

void encode(EncodeFn fn, CUtensorMap* tm, const void* ptr, int nd, const cuuint64_t* dims, const cuuint64_t* strides,
            const cuuint32_t* box, CUtensorMapSwizzle swz) {
  cuuint32_t es[4] = {1, 1, 1, 1};
  fn(tm, CU_TENSOR_MAP_DATA_TYPE_BFLOAT16, nd, const_cast<void*>(ptr), dims, strides, box, es, CU_TENSOR_MAP_INTERLEAVE_NONE,
     swz, CU_TENSOR_MAP_L2_PROMOTION_L2_128B, CU_TENSOR_MAP_FLOAT_OOB_FILL_NONE);
}
void make_map(EncodeFn fn, CUtensorMap* tm, const void* ptr, int ne, int nr) {
  const cuuint64_t dims[3] = {DCH, SEQ / 32, 32}, strides[2] = {32 * DCH * 2, DCH * 2};
  const cuuint32_t box[3] = {CPC, (cuuint32_t)ne, (cuuint32_t)nr};
  encode(fn, tm, ptr, 3, dims, strides, box, CU_TENSOR_MAP_SWIZZLE_NONE);
}

}

extern "C" void kernel_launch(void* const* d_in, const int* in_sizes, int n_in, void* d_out, int out_size) {
  (void)in_sizes; (void)n_in; (void)out_size;
  static EncodeFn fn = nullptr;
  static void *tab = nullptr, *cnt = nullptr, *part = nullptr;
  if (!fn) {
    cudaGetSymbolAddress(&tab, d_tab);
    cudaGetSymbolAddress(&cnt, g_cnt);
    cudaGetSymbolAddress(&part, g_part);
    cudaDriverEntryPointQueryResult qr;
    cudaGetDriverEntryPoint("cuTensorMapEncodeTiled", (void**)&fn, cudaEnableDefault, &qr);
    cudaFuncSetAttribute(fused_kernel, cudaFuncAttributeMaxDynamicSharedMemorySize, SMEM_BYTES);
  }
  Params p;
  make_map(fn, &p.tq, d_in[0], 8, 32);
  make_map(fn, &p.tk, d_in[1], 8, 32);
  make_map(fn, &p.tv, d_in[2], 8, 32);
  make_map(fn, &p.tkh, d_in[1], 1, 4);
  p.out = (__nv_bfloat16*)d_out;
  p.tab = (const Tables*)tab;
  p.cnt = (unsigned*)cnt;
  p.part = (uint2*)part;
  p.tl = nullptr;
  p.q = (const __nv_bfloat16*)d_in[0];
  p.ssm_k = (const __nv_bfloat16*)d_in[4];
  p.shift_k = (const __nv_bfloat16*)d_in[3];
  p.ssm_D = (const __nv_bfloat16*)d_in[5];
  p.logA = (const __nv_bfloat16*)d_in[7];
  p.Aim = (const __nv_bfloat16*)d_in[8];
  p.Cre = (const __nv_bfloat16*)d_in[9];
  p.Cim = (const __nv_bfloat16*)d_in[10];
  p.logdt = (const __nv_bfloat16*)d_in[11];
  p.Dskip = (const __nv_bfloat16*)d_in[12];
  p.gate_w = (const __nv_bfloat16*)d_in[13];
  fused_kernel<<<NCL * CS, NTHREADS, SMEM_BYTES, cudaStreamPerThread>>>(p);
}
```

```cpp
#include <cuda_runtime.h>
#include <cuda_bf16.h>
#include <cuda_fp16.h>
#include <cuda.h>
#include <stdint.h>

#define TIMELINE 0
#define TLHI 0

namespace {

constexpr int SEQ = 2048, DCH = 576, NMODE = 128;
constexpr int CS = 8, CPC = 40, NCL = 15, NTHREADS = 640;

constexpr int KTAB = 16384;
constexpr int OFF_T = 0;
constexpr int T_UKV = 8192, T_HA = 12288;
constexpr int OFF_UX = 5 * KTAB;
constexpr int OFF_IM = OFF_UX + 20480;
constexpr int OFF_CF = OFF_IM;
constexpr int OFF_CL = OFF_CF + 8192;
constexpr int OFF_TV = OFF_CL + 4096;
constexpr int OFF_YA = OFF_TV + 20480;
constexpr int OFF_GB = OFF_YA + 20480;
constexpr int OFF_YB = OFF_IM + 4 * KTAB;
constexpr int OFF_TQ = OFF_YB + 20480;
constexpr int OFF_TK = OFF_TQ + 20480;
constexpr int OFF_HALO = OFF_TK + 20480;
constexpr int OFF_MX = OFF_HALO + 320;
constexpr int OFF_SP = OFF_MX + 320;
constexpr int OFF_MB = OFF_SP + 560;
constexpr int OFF_TL = OFF_MB + 28 * 8;
constexpr int SMEM_BYTES = OFF_TL + (TIMELINE ? 1280 : 0);
static_assert(SMEM_BYTES <= 232448 && OFF_YA == OFF_IM + 2 * KTAB && OFF_GB + 2048 <= OFF_YB, "smem");
static_assert((OFF_MB & 7) == 0 && (OFF_MX & 15) == 0 && (OFF_SP & 15) == 0, "align");

enum { MB_UX = 0, MB_UKV = 5, MB_Y = 10, MB_HA = 15, MB_XQ = 20, MB_KV = 21, MB_CF = 22, MB_G = 23, MB_TH = 24, MB_TAG = 25 };
enum { NB_WG0 = 1, NB_ROW0 = 6, NB_ORD = 6, NB_V = 10 };

constexpr double cos_turn(int m, int n) {
  m &= n - 1;
  if (m > n / 2) m = n - m;
  double sgn = 1.0;
  if (m > n / 4) { m = n / 2 - m; sgn = -1.0; }
  if (m == n / 4) return 0.0;
  const double x = 6.283185307179586476925 * m / n;
  double term = 1.0, sum = 1.0;
  for (int k = 1; k < 14; k++) { term *= -x * x / ((2 * k - 1) * (2 * k)); sum += term; }
  return sgn * sum;
}
constexpr uint32_t bf16_bits(double v) {
  if (v == 0.0) return 0;
  uint32_t sgn = 0;
  if (v < 0) { sgn = 0x8000; v = -v; }
  int e = 127;
  while (v < 1.0) { v *= 2.0; e--; }
  while (v >= 2.0) { v *= 0.5; e++; }
  const double f = v * 128.0;
  int m = (int)f;
  if (f - m > 0.5 || (f - m == 0.5 && (m & 1))) m++;
  return sgn | (uint32_t)((e << 7) + (m - 128));
}
constexpr uint32_t f16_bits(double v) {
  if (v == 0.0) return 0;
  uint32_t sgn = 0;
  if (v < 0) { sgn = 0x8000; v = -v; }
  int e = 15;
  while (v < 1.0) { v *= 2.0; e--; }
  const double f = v * 1024.0;
  int m = (int)f;
  if (f - m > 0.5 || (f - m == 0.5 && (m & 1))) m++;
  return sgn | (uint32_t)((e << 10) + (m - 1024));
}
constexpr uint32_t pair_bits(double lo, double hi) { return bf16_bits(lo) | (bf16_bits(hi) << 16); }
constexpr uint32_t pair_h(double lo, double hi) { return f16_bits(lo) | (f16_bits(hi) << 16); }
struct alignas(128) Tables {
  uint32_t mat[3072];
  uint32_t thr[4][128][4];
};
constexpr Tables make_tables() {
  Tables T{};
  for (int q = 0; q < 768; q++) {
    int m0 = 0, d0 = 0, d1 = 0;
    if (q < 512) {
      const int r = (q >> 6) * 8 + (q & 7), cc = (q >> 3) & 7;
      d0 = 4 * (r & 31); d1 = 2 * d0;
      m0 = 8 * (cc & 3) * d0 + ((r >> 5) == (cc >> 2) ? 0 : (r >> 5) ? 96 : 32);
    } else {
      const int r = ((q - 512) >> 5) * 8 + (q & 7), pc = (q >> 3) & 3;
      d0 = 4 * (8 * (r >> 4) + (r & 7)) + 1; d1 = 8 * d0;
      m0 = 2 * pc * d0 + ((r & 8) ? 32 : 0);
    }
    for (int e = 0; e < 4; e++) T.mat[4 * q + e] = pair_h(cos_turn(m0 + e * d1, 128), cos_turn(m0 + e * d1 + d0, 128));
  }
  for (int tid = 0; tid < 128; tid++) {
    const int kk = 4 * (tid >> 2) + 1, t = tid & 3;
    for (int q = 0; q < 4; q++) {
      const int m = (8 * q + 2 * t) * kk;
      T.thr[q >> 1][tid][2 * (q & 1)] = pair_bits(cos_turn(m, 128), cos_turn(m + kk, 128));
      T.thr[q >> 1][tid][2 * (q & 1) + 1] = pair_bits(cos_turn(m + 32, 128), cos_turn(m + kk + 32, 128));
      T.thr[2][tid][q] = pair_h(cos_turn(m, 4096), cos_turn(m + kk, 4096));
      T.thr[3][tid][q] = pair_h(cos_turn(m + 3072, 4096), cos_turn(m + kk + 3072, 4096));
    }
  }
  return T;
}
__device__ const Tables d_tab = make_tables();

struct Params {
  const __nv_bfloat16 *logA, *Aim, *Cre, *Cim, *logdt;
  const Tables* tab;
  unsigned* cnt;
  const __nv_bfloat16 *Dskip, *shift_k, *ssm_D, *gate_w, *q, *ssm_k;
  uint2* part;
  __nv_bfloat16* out;
  unsigned* tl;
  CUtensorMap tq, tk, tv, tkh;
};

__device__ uint2 g_part[NCL * SEQ];
__device__ unsigned g_cnt[CS * 32];
#define TL(i) do {} while (0)
#define TL_INIT() do {} while (0)
#define TL_DUMP() do {} while (0)

__device__ __forceinline__ uint32_t lds16(uint32_t a) { uint32_t v; asm volatile("ld.shared.u16 %0, [%1];" : "=r"(v) : "r"(a) : "memory"); return v; }
__device__ __forceinline__ uint2 lds64(uint32_t a) { uint2 v; asm volatile("ld.shared.v2.u32 {%0,%1}, [%2];" : "=r"(v.x), "=r"(v.y) : "r"(a) : "memory"); return v; }
__device__ __forceinline__ uint4 lds128(uint32_t a) { uint4 v; asm volatile("ld.shared.v4.u32 {%0,%1,%2,%3}, [%4];" : "=r"(v.x), "=r"(v.y), "=r"(v.z), "=r"(v.w) : "r"(a) : "memory"); return v; }
__device__ __forceinline__ void sts16(uint32_t a, uint32_t v) { asm volatile("st.shared.u16 [%0], %1;" :: "r"(a), "r"(v) : "memory"); }
__device__ __forceinline__ void sts32(uint32_t a, uint32_t v) { asm volatile("st.shared.u32 [%0], %1;" :: "r"(a), "r"(v) : "memory"); }
__device__ __forceinline__ void sts64(uint32_t a, uint32_t x, uint32_t y) { asm volatile("st.shared.v2.u32 [%0], {%1,%2};" :: "r"(a), "r"(x), "r"(y) : "memory"); }
__device__ __forceinline__ void sts128(uint32_t a, uint32_t x, uint32_t y, uint32_t z, uint32_t w) { asm volatile("st.shared.v4.u32 [%0], {%1,%2,%3,%4};" :: "r"(a), "r"(x), "r"(y), "r"(z), "r"(w) : "memory"); }
__device__ __forceinline__ void ldsm4t(uint32_t (&r)[4], uint32_t a) { asm volatile("ldmatrix.sync.aligned.m8n8.x4.trans.shared.b16 {%0,%1,%2,%3}, [%4];" : "=r"(r[0]), "=r"(r[1]), "=r"(r[2]), "=r"(r[3]) : "r"(a) : "memory"); }
__device__ __forceinline__ void ldsm2t(uint32_t& r0, uint32_t& r1, uint32_t a) { asm volatile("ldmatrix.sync.aligned.m8n8.x2.trans.shared.b16 {%0,%1}, [%2];" : "=r"(r0), "=r"(r1) : "r"(a) : "memory"); }
__device__ __forceinline__ void ldsm4(uint32_t (&r)[4], uint32_t a) { asm volatile("ldmatrix.sync.aligned.m8n8.x4.shared.b16 {%0,%1,%2,%3}, [%4];" : "=r"(r[0]), "=r"(r[1]), "=r"(r[2]), "=r"(r[3]) : "r"(a) : "memory"); }
__device__ __forceinline__ void stsm4(uint32_t a, const uint32_t (&r)[4]) { asm volatile("stmatrix.sync.aligned.m8n8.x4.shared.b16 [%0], {%1,%2,%3,%4};" :: "r"(a), "r"(r[0]), "r"(r[1]), "r"(r[2]), "r"(r[3]) : "memory"); }
__device__ __forceinline__ uint32_t pack(float lo, float hi) { uint32_t r; asm("cvt.rn.bf16x2.f32 %0, %1, %2;" : "=r"(r) : "f"(hi), "f"(lo)); return r; }
__device__ __forceinline__ float blo(uint32_t v) { return __uint_as_float(v << 16); }
__device__ __forceinline__ float bhi(uint32_t v) { return __uint_as_float(v & 0xffff0000u); }
__device__ __forceinline__ float bf16r(float x) { return blo(pack(x, 0.f)); }
__device__ __forceinline__ uint32_t hmul2(uint32_t a, uint32_t b) { uint32_t r; asm("mul.rn.bf16x2 %0, %1, %2;" : "=r"(r) : "r"(a), "r"(b)); return r; }
__device__ __forceinline__ uint32_t hadd2(uint32_t a, uint32_t b) { uint32_t r; asm("add.rn.bf16x2 %0, %1, %2;" : "=r"(r) : "r"(a), "r"(b)); return r; }
__device__ __forceinline__ uint32_t hfma2(uint32_t a, uint32_t b, uint32_t c) { uint32_t r; asm("fma.rn.bf16x2 %0, %1, %2, %3;" : "=r"(r) : "r"(a), "r"(b), "r"(c)); return r; }
__device__ __forceinline__ uint32_t packh(float lo, float hi) { uint32_t r; asm("cvt.rn.f16x2.f32 %0, %1, %2;" : "=r"(r) : "f"(hi), "f"(lo)); return r; }
__device__ __forceinline__ __half2 H2(uint32_t a) { return *reinterpret_cast<__half2*>(&a); }
__device__ __forceinline__ uint32_t U2(__half2 a) { return *reinterpret_cast<uint32_t*>(&a); }
__device__ __forceinline__ uint32_t fmul(uint32_t a, uint32_t b) { return U2(__hmul2(H2(a), H2(b))); }
__device__ __forceinline__ uint32_t ffma(uint32_t a, uint32_t b, uint32_t c) { return U2(__hfma2(H2(a), H2(b), H2(c))); }
__device__ __forceinline__ uint32_t fneg(uint32_t a) { return U2(__hneg2(H2(a))); }
__device__ __forceinline__ uint32_t amax2(uint32_t a, uint32_t b) { uint32_t r; asm("max.xorsign.abs.bf16x2 %0, %1, %2;" : "=r"(r) : "r"(a), "r"(b)); return r; }
__device__ __forceinline__ uint32_t prmt(uint32_t a, uint32_t b, uint32_t s) { return __byte_perm(a, b, s); }
__device__ __forceinline__ uint32_t ldraw(const __nv_bfloat16* p) { uint32_t v; asm volatile("ld.global.nc.u16 %0, [%1];" : "=r"(v) : "l"(p)); return v; }
__device__ __forceinline__ uint4 ldg128(const void* p) { uint4 v; asm volatile("ld.global.nc.v4.u32 {%0,%1,%2,%3}, [%4];" : "=r"(v.x), "=r"(v.y), "=r"(v.z), "=r"(v.w) : "l"(p)); return v; }
__device__ __forceinline__ void bar_sync(int id, int n) { asm volatile("bar.sync %0, %1;" :: "r"(id), "r"(n) : "memory"); }
__device__ __forceinline__ void bar_arrive(int id, int n) { asm volatile("bar.arrive %0, %1;" :: "r"(id), "r"(n) : "memory"); }
__device__ __forceinline__ void cluster_arrive() { asm volatile("barrier.cluster.arrive.relaxed.aligned;" ::: "memory"); }
__device__ __forceinline__ void cluster_wait() { asm volatile("barrier.cluster.wait.aligned;" ::: "memory"); }
__device__ __forceinline__ void fence_async() { asm volatile("fence.proxy.async.shared::cta;" ::: "memory"); }
__device__ __forceinline__ void fence_mbinit() { asm volatile("fence.mbarrier_init.release.cluster;" ::: "memory"); }
__device__ __forceinline__ uint32_t mapa(uint32_t a, uint32_t rank) { uint32_t r; asm("mapa.shared::cluster.u32 %0, %1, %2;" : "=r"(r) : "r"(a), "r"(rank)); return r; }
__device__ __forceinline__ void bulk_dsmem(uint32_t dst, uint32_t src, uint32_t mbar) {
  asm volatile("cp.async.bulk.shared::cluster.shared::cta.mbarrier::complete_tx::bytes [%0], [%1], 512, [%2];" :: "r"(dst), "r"(src), "r"(mbar) : "memory");
}
__device__ __forceinline__ void bulk_load(uint32_t dst, const void* src, uint32_t bytes, uint32_t mbar) {
  asm volatile("cp.async.bulk.shared::cluster.global.mbarrier::complete_tx::bytes [%0], [%1], %2, [%3];" :: "r"(dst), "l"(src), "r"(bytes), "r"(mbar) : "memory");
}
__device__ __forceinline__ void mbar_init(uint32_t m, uint32_t cnt) { asm volatile("mbarrier.init.shared::cta.b64 [%0], %1;" :: "r"(m), "r"(cnt) : "memory"); }
__device__ __forceinline__ void mbar_expect(uint32_t m, uint32_t bytes) { asm volatile("mbarrier.arrive.expect_tx.shared::cta.b64 _, [%0], %1;" :: "r"(m), "r"(bytes) : "memory"); }
__device__ __forceinline__ bool mbar_try(uint32_t m) {
  uint32_t done;
  asm volatile("{.reg .pred p; mbarrier.try_wait.parity.shared::cta.b64 p, [%1], 0; selp.u32 %0, 1, 0, p;}" : "=r"(done) : "r"(m) : "memory");
  return done;
}
__device__ __forceinline__ void mbar_wait(uint32_t m) {
  if (!mbar_try(m)) {
    int it = 0;
    while (!mbar_try(m) && ++it < (1 << 22)) {}
  }
}
__device__ __forceinline__ bool elect() {
  uint32_t e;
  asm volatile("{.reg .pred p; elect.sync _|p, 0xffffffff; selp.u32 %0, 1, 0, p;}" : "=r"(e));
  return e;
}
__device__ __forceinline__ void tma_load4(uint32_t dst, const CUtensorMap* tm, int c0, int c1, int c2, int c3, uint32_t mbar) {
  asm volatile("cp.async.bulk.tensor.4d.shared::cluster.global.mbarrier::complete_tx::bytes [%0], [%1, {%3, %4, %5, %6}], [%2];"
               :: "r"(dst), "l"(tm), "r"(mbar), "r"(c0), "r"(c1), "r"(c2), "r"(c3) : "memory");
}
__device__ __forceinline__ void tma_load3(uint32_t dst, const CUtensorMap* tm, int c0, int c1, int c2, uint32_t mbar) {
  asm volatile("cp.async.bulk.tensor.3d.shared::cluster.global.mbarrier::complete_tx::bytes [%0], [%1, {%3, %4, %5}], [%2];"
               :: "r"(dst), "l"(tm), "r"(mbar), "r"(c0), "r"(c1), "r"(c2) : "memory");
}
__device__ __forceinline__ void tma_store3(const CUtensorMap* tm, int c0, int c1, int c2, uint32_t src) {
  asm volatile("cp.async.bulk.tensor.3d.global.shared::cta.bulk_group [%0, {%2, %3, %4}], [%1];"
               :: "l"(tm), "r"(src), "r"(c0), "r"(c1), "r"(c2) : "memory");
}
__device__ __forceinline__ void wg_fence() { asm volatile("wgmma.fence.sync.aligned;" ::: "memory"); }
__device__ __forceinline__ void wg_commit() { asm volatile("wgmma.commit_group.sync.aligned;" ::: "memory"); }
template <int N> __device__ __forceinline__ void wg_wait() { asm volatile("wgmma.wait_group.sync.aligned %0;" :: "n"(N) : "memory"); }
template <int N> __device__ __forceinline__ void tie_all(uint32_t (&x)[N]) {
#pragma unroll
  for (int i = 0; i < N; i++) asm volatile("" : "+r"(x[i]) :: "memory");
}
template <int N> __device__ __forceinline__ void tie_all(float (&x)[N]) {
#pragma unroll
  for (int i = 0; i < N; i++) asm volatile("" : "+f"(x[i]) :: "memory");
}
#define R16(C, d) C(d[0]), C(d[1]), C(d[2]), C(d[3]), C(d[4]), C(d[5]), C(d[6]), C(d[7]), C(d[8]), C(d[9]), C(d[10]), C(d[11]), C(d[12]), C(d[13]), C(d[14]), C(d[15])
#define R32(C, d) R16(C, d), R16(C, (d + 16))
#define P16 "{%0,%1,%2,%3,%4,%5,%6,%7,%8,%9,%10,%11,%12,%13,%14,%15}"
#define P32 "{%0,%1,%2,%3,%4,%5,%6,%7,%8,%9,%10,%11,%12,%13,%14,%15,%16,%17,%18,%19,%20,%21,%22,%23,%24,%25,%26,%27,%28,%29,%30,%31}"
template <int SD, int TB, int OFF> __device__ __forceinline__ void rs64(float* d, const uint32_t* a, uint64_t db) {
  if (SD) asm volatile("{.reg .b64 db; add.s64 db, %36, %37; wgmma.mma_async.sync.aligned.m64n64k16.f32.bf16.bf16 " P32 ", {%32,%33,%34,%35}, db, 1, 1, 1, %38;}"
                       : R32("+f", d) : "r"(a[0]), "r"(a[1]), "r"(a[2]), "r"(a[3]), "l"(db), "n"(OFF), "n"(TB));
  else asm volatile("{.reg .b64 db; add.s64 db, %36, %37; wgmma.mma_async.sync.aligned.m64n64k16.f32.bf16.bf16 " P32 ", {%32,%33,%34,%35}, db, 0, 1, 1, %38;}"
                    : R32("=f", d) : "r"(a[0]), "r"(a[1]), "r"(a[2]), "r"(a[3]), "l"(db), "n"(OFF), "n"(TB));
}
template <int SD, int TB, int OFF> __device__ __forceinline__ void rs64h(uint32_t* d, const uint32_t* a, uint64_t db) {
  if (SD) asm volatile("{.reg .b64 db; add.s64 db, %20, %21; wgmma.mma_async.sync.aligned.m64n64k16.f16.f16.f16 " P16 ", {%16,%17,%18,%19}, db, 1, 1, 1, %22;}"
                       : R16("+r", d) : "r"(a[0]), "r"(a[1]), "r"(a[2]), "r"(a[3]), "l"(db), "n"(OFF), "n"(TB));
  else asm volatile("{.reg .b64 db; add.s64 db, %20, %21; wgmma.mma_async.sync.aligned.m64n64k16.f16.f16.f16 " P16 ", {%16,%17,%18,%19}, db, 0, 1, 1, %22;}"
                    : R16("=r", d) : "r"(a[0]), "r"(a[1]), "r"(a[2]), "r"(a[3]), "l"(db), "n"(OFF), "n"(TB));
}
template <int SD, int OFFA, int OFFB> __device__ __forceinline__ void ss32(float* d, uint64_t da, uint64_t db) {
  if (SD) asm volatile("{.reg .b64 da, db; add.s64 da, %16, %18; add.s64 db, %17, %19; wgmma.mma_async.sync.aligned.m64n32k16.f32.f16.f16 " P16 ", da, db, 1, 1, 1, 1, 1;}"
                       : R16("+f", d) : "l"(da), "l"(db), "n"(OFFA), "n"(OFFB));
  else asm volatile("{.reg .b64 da, db; add.s64 da, %16, %18; add.s64 db, %17, %19; wgmma.mma_async.sync.aligned.m64n32k16.f32.f16.f16 " P16 ", da, db, 0, 1, 1, 1, 1;}"
                    : R16("=f", d) : "l"(da), "l"(db), "n"(OFFA), "n"(OFFB));
}
#define KGEN_ASM(SD) "{.reg .b64 da, db; add.s64 da, %32, %33; add.s64 db, %32, %34;\n" \
  "wgmma.mma_async.sync.aligned.m64n64k16.f32.bf16.bf16 " P32 ", da, db, " SD ", 1, 1, 1, 1;}"
template <int KS> __device__ __forceinline__ void kgen_mma(float (&c)[32], uint64_t da) {
  if (KS) asm volatile(KGEN_ASM("1") : R32("+f", c) : "l"(da), "n"(8 * KS), "n"(8 * KS + 512));
  else asm volatile(KGEN_ASM("0") : R32("=f", c) : "l"(da), "n"(8 * KS), "n"(8 * KS + 512));
  if constexpr (KS < 7) kgen_mma<KS + 1>(c, da);
}
__device__ __forceinline__ uint64_t desc_lo(uint32_t a) { return (uint64_t)((a & 0x3FFFF) >> 4); }
__device__ __forceinline__ void stage1(float (&D)[32], const uint32_t (&A1)[8], uint32_t src) {
  const uint64_t du = desc_lo(src) | (128ull << 16) | (32ull << 32) | (2ull << 62);
  rs64<0, 1, 0>(D, A1, du); rs64<1, 1, 64>(D, A1 + 4, du);
}
template <int INV> __device__ __forceinline__ void stage2(uint32_t (&X)[16], const uint32_t (&F)[16], uint32_t cf) {
  constexpr int KS = INV ? 16 : 128, TB = INV ? 0 : 1;
  const uint64_t dc = desc_lo(cf) | (INV ? (8ull << 16) | (64ull << 32) : (64ull << 16) | (8ull << 32));
  rs64h<0, TB, 0>(X, F, dc); rs64h<1, TB, KS>(X, F + 4, dc); rs64h<1, TB, 2 * KS>(X, F + 8, dc); rs64h<1, TB, 3 * KS>(X, F + 12, dc);
}
__device__ __forceinline__ void fwd_mid(uint32_t (&F)[16], const float (&D)[32], const uint32_t (&tc)[4], const uint32_t (&ts)[4]) {
#pragma unroll
  for (int j = 0; j < 4; j++)
#pragma unroll
    for (int b = 0; b < 2; b++) {
      const int i = 4 * j + 16 * b;
      const uint32_t ar = packh(D[i], D[i + 1]), ai = packh(D[i + 2], D[i + 3]);
      F[2 * j + b] = ffma(ar, tc[j], fmul(ai, ts[j]));
      F[8 + 2 * j + b] = ffma(ai, tc[j], fneg(fmul(ar, ts[j])));
    }
}
__device__ __forceinline__ void put_exp(uint32_t a, uint32_t m, int lane) {
  m = __reduce_max_sync(0xffffffffu, max(m & 0x7f80u, (m >> 16) & 0x7f80u));
  if (lane == 0) sts32(a, m);
}
__device__ __forceinline__ uint32_t seq_mag(uint32_t a) {
  const uint4 x = lds128(a), y = lds128(a + 2048);
  return amax2(amax2(amax2(x.x, x.y), amax2(x.z, x.w)), amax2(amax2(y.x, y.y), amax2(y.z, y.w)));
}
__device__ __forceinline__ uint32_t get_exp(uint32_t a) { const uint4 v = lds128(a); return max(max(v.x, v.y), max(v.z, v.w)) >> 7; }
__device__ __forceinline__ void scale_a1(uint32_t (&As)[8], const uint32_t (&A1)[8], uint32_t field) {
#pragma unroll
  for (int i = 0; i < 8; i++) As[i] = hmul2(A1[i], field * 0x00800080u);
}

struct cf { float x, y; };
__device__ __forceinline__ cf cmul(cf a, cf b) { cf r; r.x = fmaf(a.x, b.x, -a.y * b.y); r.y = fmaf(a.x, b.y, a.y * b.x); return r; }
__device__ __forceinline__ cf cexp_p(float lr2, float lt, float p) {
  float m;
  asm("ex2.approx.ftz.f32 %0, %1;" : "=f"(m) : "f"(lr2 * p));
  float t = lt * p;
  t = (t - rintf(t)) * 6.283185307179586f;
  cf r; r.x = m * __cosf(t); r.y = m * __sinf(t); return r;
}
__device__ __forceinline__ void store8(uint32_t a, uint32_t b, const cf (&v)[8]) {
  sts128(a, pack(v[0].x, v[1].x), pack(v[2].x, v[3].x), pack(v[4].x, v[5].x), pack(v[6].x, v[7].x));
  sts128(b, pack(v[0].y, v[1].y), pack(v[2].y, v[3].y), pack(v[4].y, v[5].y), pack(v[6].y, v[7].y));
}
__device__ __forceinline__ void mbar_arrive(uint32_t m) { asm volatile("mbarrier.arrive.shared::cta.b64 _, [%0];" :: "r"(m) : "memory"); }
__device__ __forceinline__ float sigmoidf_(float s) { return __fdividef(1.f, 1.f + __expf(fminf(-s, 80.f))); }

__global__ void __cluster_dims__(CS, 1, 1) __launch_bounds__(NTHREADS, 1) fused_kernel(const __grid_constant__ Params p) {
  extern __shared__ __align__(1024) uint8_t smem[];
  TL_INIT();
  TL(31);
  const int wid = __shfl_sync(0xffffffffu, threadIdx.x >> 5, 0);
  const uint32_t sb = (uint32_t)__cvta_generic_to_shared(smem);
  const uint32_t mb = sb + OFF_MB;
  const int u = wid >> 2, w = wid & 3;
  const int tid = threadIdx.x & 127, lane = tid & 31, g = lane >> 2, t = lane & 3;
  const int cl = blockIdx.x >> 3, rank = blockIdx.x & 7;
  const int ch0 = cl * CPC;
  const int nu = min(5, (DCH - ch0) >> 3);
  const bool act = u < nu;

  uint32_t pla, pai, pcr, pci, pdt, tag = 0;
  auto load_params = [&]() {
    const int ch = act ? ch0 + 8 * u + rank : 0, o = ch * NMODE + tid;
    pla = ldraw(p.logA + o); pdt = ldraw(p.logdt + ch); pai = ldraw(p.Aim + o); pcr = ldraw(p.Cre + o); pci = ldraw(p.Cim + o);
  };
  if (u == 4) {
    const bool e = elect();
    if (e) {
#pragma unroll
      for (int i = 0; i < 5; i++) mbar_init(mb + 40 * w + 8 * i, 1);
      if (w == 3) { mbar_init(mb + 8 * MB_TH, 1); mbar_init(mb + 8 * MB_XQ, 21); mbar_init(mb + 8 * MB_KV, 1); }
      if (w == 2) { mbar_init(mb + 8 * MB_CF, 1); mbar_init(mb + 8 * MB_G, 16); }
      fence_mbinit();
    }
    __syncwarp();
    load_params();
    if (w == 0 && lane < 2) asm volatile("atom.relaxed.gpu.global.add.u32 %0, [%1], %2;" : "=r"(tag) : "l"(&p.cnt[rank * 32 + lane]), "r"(cl == 0 ? 16 - (NCL - 1) : 1) : "memory");
    if (e) {
      if (w == 3) {
        mbar_expect(mb + 8 * MB_TH, 8192 + 112 * nu);
        bulk_load(sb + OFF_YB, p.tab->thr, 8192, mb + 8 * MB_TH);
        bulk_load(sb + OFF_SP, p.gate_w + ch0, 16 * nu, mb + 8 * MB_TH);
        bulk_load(sb + OFF_SP + 80, p.Dskip + ch0, 16 * nu, mb + 8 * MB_TH);
        bulk_load(sb + OFF_SP + 160, p.ssm_D + ch0, 16 * nu, mb + 8 * MB_TH);
        bulk_load(sb + OFF_SP + 240, p.shift_k + 4 * ch0, 64 * nu, mb + 8 * MB_TH);
        asm volatile("cp.async.bulk.prefetch.L2.global [%0], 12288;" :: "l"(p.tab->mat) : "memory");
        mbar_expect(mb + 8 * MB_XQ, 20480);
        tma_load3(sb + OFF_TQ, &p.tq, ch0, 8 * rank, 0, mb + 8 * MB_XQ);
        TL(20);
        mbar_expect(mb + 8 * MB_KV, 2 * 20480 + 320);
        tma_load3(sb + OFF_TK, &p.tk, ch0, 8 * rank, 0, mb + 8 * MB_KV);
        tma_load3(sb + OFF_HALO, &p.tkh, ch0, 8 * rank - 1, 28, mb + 8 * MB_KV);
      }
      if (w == 2) mbar_expect(mb + 8 * MB_CF, 12288);
#pragma unroll
      for (int i = 0; i < 5; i++) mbar_expect(mb + 40 * w + 8 * i, w == 3 ? 4096 : w == 2 ? 7168 : 3584);
    }
    __syncwarp();
  } else {
    load_params();
  }
  cluster_arrive();
  TL(0);

  const uint32_t tab = sb + OFF_T + u * KTAB;
  const uint32_t toff = (64 * w + lane) * 80 + 16 * u;
  auto put = [&](uint32_t dst, const uint32_t (&a)[4], const uint32_t (&b)[4]) {
    const uint32_t s0 = (g & 1) ? 0x7632 : 0x5410, s1 = s0 ^ 0x2222;
    const uint32_t o = dst + 128 * t + 64 * (g & 1) + 16 * (w ^ t);
    sts128(o, prmt(a[0], a[1], s0), prmt(a[2], a[3], s0), prmt(b[0], b[1], s0), prmt(b[2], b[3], s0));
    sts128(o ^ 64, prmt(a[0], a[1], s1), prmt(a[2], a[3], s1), prmt(b[0], b[1], s1), prmt(b[2], b[3], s1));
  };
  const int d0 = rank ^ (2 * w), d1 = d0 ^ 1;
  const uint32_t rb0 = mapa(sb, d0), rb1 = mapa(sb, d1);
  auto send = [&](int stage, int dst, int mbar) {
    if (elect()) {
      if (w) bulk_dsmem(rb0 + dst, sb + stage + d0 * 512, rb0 + mbar);
      bulk_dsmem(rb1 + dst, sb + stage + d1 * 512, rb1 + mbar);
    }
    __syncwarp();
  };

  uint32_t A1[8], tc[4], ts[4];
  {
    const float dt = bf16r(expf(blo(pdt)));
    const float lr2 = (-bf16r(expf(blo(pla))) * dt) * 1.4426950408889634f;
    const float lt = (blo(pai) * dt) * 0.15915494309189535f;
    const uint32_t tim = sb + (u ? OFF_IM + (u - 1) * KTAB : OFF_UX);
    const uint32_t row = tab + tid * 16, rim = tim + tid * 16;
    const cf w1 = cexp_p(lr2, lt, 8.f);
    cf z1 = cexp_p(lr2, lt, 1.f), Z = cexp_p(lr2, lt, 256.f);
    if (lr2 != 123.f) TL(16);
    TL(12);
    {
      cf v[8];
      v[0].x = 1.f; v[0].y = 0.f; v[1] = w1; v[2] = cmul(w1, w1); v[3] = cmul(v[2], w1);
      const cf w4 = cmul(v[2], v[2]);
      v[4] = w4; v[5] = cmul(v[1], w4); v[6] = cmul(v[2], w4); v[7] = cmul(v[3], w4);
      const cf w8 = cmul(w4, w4);
      store8(row, rim, v);
#pragma unroll
      for (int k = 1; k < 4; k++) {
#pragma unroll
        for (int i = 0; i < 8; i++) v[i] = (k == 1 && i == 0) ? w8 : cmul(v[i], w8);
        store8(row + 2048 * k, rim + 2048 * k, v);
      }
    }
    cluster_wait();
    if (u) cluster_arrive();
    mbar_wait(mb + 8 * MB_TH);
    {
      const uint4 x = lds128(sb + OFF_YB + 16 * tid), y = lds128(sb + OFF_YB + 2048 + 16 * tid), a = lds128(sb + OFF_YB + 4096 + 16 * tid), b = lds128(sb + OFF_YB + 6144 + 16 * tid);
      A1[0] = x.x; A1[1] = x.y; A1[2] = x.z; A1[3] = x.w; A1[4] = y.x; A1[5] = y.y; A1[6] = y.z; A1[7] = y.w;
      tc[0] = a.x; tc[1] = a.y; tc[2] = a.z; tc[3] = a.w; ts[0] = b.x; ts[1] = b.y; ts[2] = b.z; ts[3] = b.w;
    }
    if (wid == 16 && lane == 0) sts32(mb + 8 * MB_TAG, tag);
    __syncwarp();
    if (lane == 0) mbar_arrive(mb + 8 * MB_XQ);
    if (u == 1) {
      float z0_ = 0.f, z1_ = 0.f, z2_ = 0.f, z3_ = 0.f;
      asm volatile("mma.sync.aligned.m16n8k8.row.col.f32.bf16.bf16.f32 {%0,%1,%2,%3}, {%4,%4}, {%4}, {%0,%1,%2,%3};"
                   : "+f"(z0_), "+f"(z1_), "+f"(z2_), "+f"(z3_) : "r"(pla >> 16));
      pcr += __float_as_uint(z0_);
      TL(8);
    }
    {
      z1.y = -z1.y; Z.y = -Z.y;
      const cf z2 = cmul(z1, z1);
      cf h[8], v[8];
      h[0].x = 2.f * blo(pcr) * dt; h[0].y = -2.f * blo(pci) * dt;
      h[1] = cmul(h[0], z1);
#pragma unroll
      for (int i = 2; i < 8; i++) h[i] = cmul(h[i - 2], z2);
      store8(row + 4 * 2048, rim + 4 * 2048, h);
      const cf h8 = cmul(h[6], z2);
      v[0] = cmul(h[0], Z); v[2] = cmul(h[2], Z); v[3] = cmul(h[4], Z); v[6] = cmul(h[6], Z); v[7] = cmul(h8, Z);
      v[1] = v[0]; v[4] = v[5] = v[3];
      store8(row + 5 * 2048, rim + 5 * 2048, v);
      h[0] = cmul(v[0], Z); h[1] = cmul(v[3], Z); h[3] = cmul(v[7], Z); h[4] = cmul(h[0], Z); h[5] = cmul(h[1], Z); h[7] = cmul(h[3], Z);
      h[2] = h[1]; h[6] = h[5];
      store8(row + 6 * 2048, rim + 6 * 2048, h);
      const cf Z2 = cmul(Z, Z);
      v[0] = cmul(h[0], Z2); v[1] = cmul(h[3], Z2); v[2] = cmul(h[4], Z2); v[3] = cmul(h[7], Z2);
#pragma unroll
      for (int i = 4; i < 8; i++) v[i] = cmul(v[i - 4], Z2);
      store8(row + 7 * 2048, rim + 7 * 2048, v);
    }
    TL(17);
    mbar_wait(mb + 8 * MB_XQ);
    TL(18);
    uint32_t x0[4], x1[4];
    ldsm4t(x0, sb + OFF_TQ + toff);
    ldsm4t(x1, sb + OFF_TQ + toff + 2560);
    put(sb + OFF_YB + u * 4096 + g * 512, x0, x1);
    TL(3);
    fence_async();
    if (u) bar_sync(NB_ORD + u - 1, 256); else bar_sync(NB_WG0, 128);
    TL(13);
    float c[32];
    wg_fence();
    kgen_mma<0>(c, desc_lo(tab) | ((uint64_t)((tim - tab) >> 4) << 16) | (64ull << 32));
    wg_commit();
    if (u < 4) bar_arrive(NB_ORD + u, 256);
    TL(14);
    wg_wait<0>(); tie_all(c);
    TL(26);
    if (u == 0) cluster_arrive();
    if (u == 1 || u == 2) bar_arrive(NB_V, 288);
    bar_sync(NB_WG0 + u, 128);
    if (wid == 4 && elect()) bulk_load(sb + OFF_CF, p.tab->mat, 12288, mb + 8 * MB_CF);
    __syncwarp();
    const uint32_t k0 = pack(c[0] + c[6], c[1] + c[7]), k1 = pack(c[8] + c[14], c[9] + c[15]);
    const uint32_t k2 = pack(c[16] + c[22], c[17] + c[23]), k3 = pack(c[24] + c[30], c[25] + c[31]);
    const uint32_t ka = tab + 16 * (8 * w + (g ^ w));
    sts32(ka + 4 * t, k0);
    sts32(ka + 512 + 4 * t, k1);
    sts64(ka + 1024 + 512 * (t >> 1) + 8 * (t & 1), prmt(k2, 0, 0x1010), (t & 1) ? prmt(k2, 0, 0x3232) : k2);
    const uint32_t lo = prmt(k3, 0, 0x1010), hi = prmt(k3, 0, 0x3232);
    sts128(ka + 2048 + 512 * t, lo, lo, (g & 1) ? hi : k3, hi);
    put_exp(sb + OFF_MX + u * 64 + 4 * w, amax2(amax2(k0, k1), amax2(k2, k3)), lane);
    cluster_wait();
    cluster_arrive();
    TL(4);
    send(OFF_YB + u * 4096, OFF_UX + u * 4096 + 512 * rank, OFF_MB + 8 * (MB_UX + u));
    if (wid == 16) {
      bar_sync(NB_V, 288);
      if (elect()) tma_load3(sb + OFF_TV, &p.tv, ch0, 8 * rank, 0, mb + 8 * MB_KV);
      __syncwarp();
    }
    if (g == rank) put(sb + OFF_UX + u * 4096 + 512 * rank, x0, x1);
    TL(15);
    fence_async();
    bar_sync(NB_WG0 + u, 128);
  }

#pragma unroll
  for (int isA = 0; isA < 2; isA++) {
    {
      TL(1 + isA);
      const uint32_t usrc = isA ? tab + T_UKV : sb + OFF_UX + u * 4096;
      const uint32_t mxa = sb + OFF_MX + u * 64 + 32 * isA;
      const uint32_t pd = lds16(sb + OFF_SP + 80 + 80 * isA + 16 * u + 2 * rank);
      float D[32];
      uint32_t As[8], F[16], H[16], X[16];
      const uint32_t eh = min(max((int)get_exp(mxa), (int)((pd >> 7) & 0xff) - 5), 240);
      scale_a1(As, A1, 248 - eh);
      wg_fence();
      stage1(D, As, isA ? tab + T_HA : tab);
      wg_commit();
      wg_wait<0>(); tie_all(D);
      fwd_mid(F, D, tc, ts);
      if (!isA) mbar_wait(mb + 8 * MB_CF);
      wg_fence();
      stage2<0>(H, F, sb + OFF_CF);
      wg_commit();
      if (!isA) {
        if (w == 2 && elect()) bulk_load(tab + T_HA, p.ssm_k + (size_t)(act ? ch0 + 8 * u + rank : 0) * SEQ, 4096, mb + 8 * (MB_HA + u));
        __syncwarp();
        if (u < 2) {
          float s0 = 0.f;
#pragma unroll
          for (int j = 0; j < 5; j++) {
            if (j >= 2 && j >= nu) break;
            const uint4 gw = lds128(sb + OFF_SP + 16 * j), x = lds128(sb + OFF_TQ + (tid + 128 * u) * 80 + 16 * j);
            const uint32_t m0 = hmul2(x.x, gw.x), m1 = hmul2(x.y, gw.y), m2 = hmul2(x.z, gw.z), m3 = hmul2(x.w, gw.w);
            s0 += ((blo(m0) + bhi(m0)) + (blo(m1) + bhi(m1))) + ((blo(m2) + bhi(m2)) + (blo(m3) + bhi(m3)));
          }
          tag = (lds64(mb + 8 * MB_TAG).x >> 4) + 1;
          asm volatile("st.relaxed.gpu.global.u64 [%0], %1;" :: "l"(p.part + cl * SEQ + rank * 256 + tid + 128 * u),
                       "l"(((uint64_t)tag << 32) | __float_as_uint(s0)) : "memory");
        }
        TL(7);
      }
      mbar_wait(mb + 8 * ((isA ? MB_UKV : MB_UX) + u));
      TL(5 + isA);
      put_exp(mxa + 16 + 4 * w, seq_mag(usrc + 16 * tid), lane);
      bar_sync(NB_WG0 + u, 128);
      const uint32_t eu = min(get_exp(mxa + 16), 240u);
      scale_a1(As, A1, 250 - eu);
      wg_wait<0>(); tie_all(H);
      wg_fence();
      stage1(D, As, usrc);
      wg_commit();
      wg_wait<0>(); tie_all(D);
      fwd_mid(F, D, tc, ts);
      wg_fence();
      stage2<0>(X, F, sb + OFF_CF);
      wg_commit();
      {
        const float dsk = blo(pd) * __uint_as_float((248 - eh) << 23);
        const uint32_t d2 = packh(dsk, dsk);
#pragma unroll
        for (int j = 0; j < 4; j++) H[2 * j] = U2(__hadd2(H2(H[2 * j]), H2(d2)));
      }
      wg_wait<0>(); tie_all(X);
#pragma unroll
      for (int j = 0; j < 4; j++) {
        const uint32_t h0r = H[2 * j], h1r = H[2 * j + 1], h0i = H[8 + 2 * j], h1i = H[9 + 2 * j];
        const uint32_t x0r = X[2 * j], x1r = X[2 * j + 1], x0i = X[8 + 2 * j], x1i = X[9 + 2 * j];
        F[2 * j] = ffma(x0r, h0r, fneg(fmul(x0i, h0i)));
        F[8 + 2 * j] = ffma(x0r, h0i, fmul(x0i, h0r));
        F[2 * j + 1] = ffma(x1r, h0r, ffma(fneg(x1i), h0i, ffma(x0r, h1r, fneg(ffma(x0i, h1i, F[8 + 2 * j])))));
        F[9 + 2 * j] = ffma(x1r, h0i, ffma(x1i, h0r, ffma(x0r, h1i, ffma(x0i, h1r, F[2 * j]))));
      }
      wg_fence();
      stage2<1>(H, F, sb + OFF_CF);
      wg_commit();
      wg_wait<0>(); tie_all(H);
      {
        const uint32_t va = tab + (16 * w + (lane & 15)) * 128;
        const int vx = (lane >> 4) ^ (lane & 7);
#pragma unroll
        for (int j = 0; j < 4; j++) {
          uint32_t V[4];
#pragma unroll
          for (int b = 0; b < 2; b++) {
            const uint32_t er = H[2 * j + b], ei = H[8 + 2 * j + b];
            V[2 * b] = ffma(er, tc[j], fneg(fmul(ei, ts[j])));
            V[2 * b + 1] = ffma(ei, tc[j], fmul(er, ts[j]));
          }
          stsm4(va + ((vx ^ (2 * j)) << 4), V);
        }
      }
      if (!isA) {
        uint64_t ga[4][2];
        const int slot = 64 * u + 16 * w + 2 * g;
        auto gload = [&]() {
#pragma unroll
          for (int k = 0; k < 4; k++)
            asm volatile("ld.relaxed.gpu.global.v2.u64 {%0,%1}, [%2];" : "=l"(ga[k][0]), "=l"(ga[k][1])
                         : "l"(p.part + min(t + 4 * k, NCL - 1) * SEQ + rank * 256 + slot) : "memory");
        };
        cluster_wait();
        if (u < 4) gload();
        mbar_wait(mb + 8 * MB_KV);
        TL(21);
        uint32_t K[3][4], V[2][4];
        const uint2 psw = lds64(sb + OFF_SP + 240 + 64 * u + 8 * g);
        ldsm4t(K[0], w ? sb + OFF_TK + toff - 2560 : (lane & 7) ? sb + OFF_TK + toff + 223 * 80 : sb + OFF_HALO + 10 * lane + 16 * u);
        ldsm4t(K[1], sb + OFF_TK + toff);
        ldsm4t(K[2], sb + OFF_TK + toff + 2560);
        ldsm4t(V[0], sb + OFF_TV + toff);
        ldsm4t(V[1], sb + OFF_TV + toff + 2560);
        mbar_wait(mb + 8 * (MB_HA + u));
        const uint4 hx = lds128(tab + T_HA + 16 * tid), hy = lds128(tab + T_HA + 2048 + 16 * tid);
        const uint32_t w0 = prmt(psw.x, 0, 0x1010), w1 = prmt(psw.x, 0, 0x3232), w2 = prmt(psw.y, 0, 0x1010), w3 = prmt(psw.y, 0, 0x3232);
#pragma unroll
        for (int m = 4; m < 12; m++)
          V[(m >> 2) - 1][m & 3] = hmul2(hfma2(K[m >> 2][m & 3], w0, hfma2(K[(m - 1) >> 2][(m - 1) & 3], w1,
                                         hfma2(K[(m - 2) >> 2][(m - 2) & 3], w2, hmul2(K[(m - 3) >> 2][(m - 3) & 3], w3)))), V[(m >> 2) - 1][m & 3]);
        put(g == rank ? tab + T_UKV + 512 * rank : sb + OFF_YA + u * 4096 + g * 512, V[0], V[1]);
        put_exp(mxa + 32 + 4 * w, amax2(amax2(amax2(hx.x, hx.y), amax2(hx.z, hx.w)), amax2(amax2(hy.x, hy.y), amax2(hy.z, hy.w))), lane);
        sts128(tab + T_HA + 16 * (tid ^ (lane >> 3)), hx.x, hx.y, hx.z, hx.w);
        sts128(tab + T_HA + 2048 + 16 * (tid ^ (lane >> 3)), hy.x, hy.y, hy.z, hy.w);
        if (u < 4) {
          tag = (lds64(mb + 8 * MB_TAG).x >> 4) + 1;
          bool ok;
#pragma unroll 1
          for (int it = 0;; it++) {
            ok = true;
#pragma unroll
            for (int k = 0; k < 4; k++) ok = ok && (uint32_t)(ga[k][0] >> 32) == tag && (uint32_t)(ga[k][1] >> 32) == tag;
            ok = __all_sync(0xffffffffu, ok);
            if (ok || it == 4000) break;
            gload();
          }
          float s0 = __uint_as_float((uint32_t)ga[0][0]) + __uint_as_float((uint32_t)ga[1][0]) + __uint_as_float((uint32_t)ga[2][0]);
          float s1 = __uint_as_float((uint32_t)ga[0][1]) + __uint_as_float((uint32_t)ga[1][1]) + __uint_as_float((uint32_t)ga[2][1]);
          if (t < 3) { s0 += __uint_as_float((uint32_t)ga[3][0]); s1 += __uint_as_float((uint32_t)ga[3][1]); }
          float s = ((t & 1) ? s1 : s0) + __shfl_xor_sync(0xffffffffu, (t & 1) ? s0 : s1, 1);
          s += __shfl_xor_sync(0xffffffffu, s, 2);
          const int sl = slot + (t & 1);
          if (!ok) {
            const uint32_t* xr = (const uint32_t*)(p.q + (size_t)(rank * 256 + 32 * (sl & 7) + (sl >> 3)) * DCH);
            const uint32_t* gr = (const uint32_t*)p.gate_w;
            s = 0.f;
#pragma unroll 1
            for (int k = 0; k < DCH / 2; k++) { const uint32_t m = hmul2(__ldg(xr + k), __ldg(gr + k)); s += blo(m) + bhi(m); }
          }
          const float g0 = bf16r(sigmoidf_(bf16r(s)));
          sts32(sb + OFF_GB + 8 * sl + (t & 2) * 2, (t & 2) ? pack(1.f - g0, 1.f - g0) : pack(g0, g0));
          __syncwarp();
          if (lane == 0) mbar_arrive(mb + 8 * MB_G);
        }
        TL(22);
      }
      fence_async();
      bar_sync(NB_WG0 + u, 128);
      float O[16];
      {
        const uint64_t dv = desc_lo(tab) | (1ull << 16) | (64ull << 32) | (1ull << 62);
        const uint64_t dl = desc_lo(sb + OFF_CL) | (32ull << 16) | (8ull << 32);
        wg_fence();
        ss32<0, 0, 0>(O, dv, dl); ss32<1, 128, 64>(O, dv, dl); ss32<1, 256, 128>(O, dv, dl); ss32<1, 384, 192>(O, dv, dl);
        wg_commit();
      }
      if (!isA) send(OFF_YA + u * 4096, OFF_T + u * KTAB + T_UKV + 512 * rank, OFF_MB + 8 * (MB_UKV + u));
      wg_wait<0>(); tie_all(O);
      {
        const uint32_t co = ((8 * w + g) ^ (2 * t) ^ rank) * 16;
        const int yo = (isA ? OFF_YA : OFF_YB) + (8 * u + rank) * 512, ym = OFF_MB + 8 * (MB_Y + u);
        const uint32_t us = min(max((int)(eu + eh) - 127, 0), 254) * 0x00800080u;
        const uint32_t a0 = hmul2(pack(O[0], O[1]), us), a1 = hmul2(pack(O[4], O[5]), us), a2 = hmul2(pack(O[8], O[9]), us), a3 = hmul2(pack(O[12], O[13]), us);
        const uint32_t b0 = hmul2(pack(O[2], O[3]), us), b1 = hmul2(pack(O[6], O[7]), us), b2 = hmul2(pack(O[10], O[11]), us), b3 = hmul2(pack(O[14], O[15]), us);
        sts128((t == rank ? sb + yo : usrc + t * 512) + co, a0, a1, a2, a3);
        sts128((t + 4 == rank ? sb + yo : usrc + t * 512 + 2048) + co, b0, b1, b2, b3);
        fence_async();
        bar_sync(NB_WG0 + u, 128);
        send(usrc - sb, yo, ym);
      }
      TL(9 + isA);
    }
  }

  {
    mbar_wait(mb + 8 * MB_G);
    uint2 gg[2][4];
    uint32_t qv[2][4];
#pragma unroll
    for (int hh = 0; hh < 2; hh++)
#pragma unroll
      for (int i = 0; i < 4; i++) gg[hh][i] = lds64(sb + OFF_GB + 8 * (64 * w + 32 * hh + 8 * i + g));
    const uint32_t qa = sb + OFF_TQ + toff;
    ldsm4(qv[0], qa);
    ldsm4(qv[1], qa + 2560);
    TL(24);
    mbar_wait(mb + 8 * (MB_Y + u));
    uint32_t ya[2][4], yb[2][4];
#pragma unroll
    for (int hh = 0; hh < 2; hh++) {
      const uint32_t yo = (8 * u + (lane & 7)) * 512 + ((8 * w + 4 * hh + (lane >> 3)) ^ (2 * (rank & 3)) ^ (lane & 7)) * 16;
      ldsm4t(ya[hh], sb + OFF_YA + yo); ldsm4t(yb[hh], sb + OFF_YB + yo);
    }
#pragma unroll
    for (int hh = 0; hh < 2; hh++) {
      uint32_t o[4];
#pragma unroll
      for (int i = 0; i < 4; i++) o[i] = hadd2(hmul2(gg[hh][i].x, hmul2(qv[hh][i], ya[hh][i])), hmul2(gg[hh][i].y, yb[hh][i]));
      stsm4(qa + 2560 * hh, o);
    }
    TL(25);
  }
  cluster_arrive();
  bar_sync(NB_ROW0 + w, 160);
  {
    uint4 v[2];
#pragma unroll
    for (int k = 0; k < 2; k++) {
      const int i = 64 * u + 32 * k + lane, sl = (i * 205) >> 10, cc = i - 5 * sl;
      v[k] = lds128(sb + OFF_TQ + (64 * w + 8 * (sl & 7) + (sl >> 3)) * 80 + cc * 16);
    }
#pragma unroll
    for (int k = 0; k < 2; k++) {
      const int i = 64 * u + 32 * k + lane, sl = (i * 205) >> 10, cc = i - 5 * sl;
      if (cc < nu)
        asm volatile("st.global.v4.u32 [%0], {%1,%2,%3,%4};" :: "l"(p.out + (size_t)(256 * rank + 32 * (sl >> 3) + 8 * w + (sl & 7)) * DCH + ch0 + 8 * cc),
                     "r"(v[k].x), "r"(v[k].y), "r"(v[k].z), "r"(v[k].w) : "memory");
    }
  }
  cluster_wait();
  TL(27);
  TL_DUMP();
}

typedef CUresult (*EncodeFn)(CUtensorMap*, CUtensorMapDataType, cuuint32_t, void*, const cuuint64_t*, const cuuint64_t*,
                             const cuuint32_t*, const cuuint32_t*, CUtensorMapInterleave, CUtensorMapSwizzle,
                             CUtensorMapL2promotion, CUtensorMapFloatOOBfill);

void encode(EncodeFn fn, CUtensorMap* tm, const void* ptr, int nd, const cuuint64_t* dims, const cuuint64_t* strides,
            const cuuint32_t* box, CUtensorMapSwizzle swz) {
  cuuint32_t es[4] = {1, 1, 1, 1};
  fn(tm, CU_TENSOR_MAP_DATA_TYPE_BFLOAT16, nd, const_cast<void*>(ptr), dims, strides, box, es, CU_TENSOR_MAP_INTERLEAVE_NONE,
     swz, CU_TENSOR_MAP_L2_PROMOTION_L2_128B, CU_TENSOR_MAP_FLOAT_OOB_FILL_NONE);
}
void make_map(EncodeFn fn, CUtensorMap* tm, const void* ptr, int ne, int nr) {
  const cuuint64_t dims[3] = {DCH, SEQ / 32, 32}, strides[2] = {32 * DCH * 2, DCH * 2};
  const cuuint32_t box[3] = {CPC, (cuuint32_t)ne, (cuuint32_t)nr};
  encode(fn, tm, ptr, 3, dims, strides, box, CU_TENSOR_MAP_SWIZZLE_NONE);
}

}

extern "C" void kernel_launch(void* const* d_in, const int* in_sizes, int n_in, void* d_out, int out_size) {
  (void)in_sizes; (void)n_in; (void)out_size;
  static EncodeFn fn = nullptr;
  static void *tab = nullptr, *cnt = nullptr, *part = nullptr;
  if (!fn) {
    cudaGetSymbolAddress(&tab, d_tab);
    cudaGetSymbolAddress(&cnt, g_cnt);
    cudaGetSymbolAddress(&part, g_part);
    cudaDriverEntryPointQueryResult qr;
    cudaGetDriverEntryPoint("cuTensorMapEncodeTiled", (void**)&fn, cudaEnableDefault, &qr);
    cudaFuncSetAttribute(fused_kernel, cudaFuncAttributeMaxDynamicSharedMemorySize, SMEM_BYTES);
  }
  Params p;
  make_map(fn, &p.tq, d_in[0], 8, 32);
  make_map(fn, &p.tk, d_in[1], 8, 32);
  make_map(fn, &p.tv, d_in[2], 8, 32);
  make_map(fn, &p.tkh, d_in[1], 1, 4);
  p.out = (__nv_bfloat16*)d_out;
  p.tab = (const Tables*)tab;
  p.cnt = (unsigned*)cnt;
  p.part = (uint2*)part;
  p.tl = nullptr;
  p.q = (const __nv_bfloat16*)d_in[0];
  p.ssm_k = (const __nv_bfloat16*)d_in[4];
  p.shift_k = (const __nv_bfloat16*)d_in[3];
  p.ssm_D = (const __nv_bfloat16*)d_in[5];
  p.logA = (const __nv_bfloat16*)d_in[7];
  p.Aim = (const __nv_bfloat16*)d_in[8];
  p.Cre = (const __nv_bfloat16*)d_in[9];
  p.Cim = (const __nv_bfloat16*)d_in[10];
  p.logdt = (const __nv_bfloat16*)d_in[11];
  p.Dskip = (const __nv_bfloat16*)d_in[12];
  p.gate_w = (const __nv_bfloat16*)d_in[13];
  fused_kernel<<<NCL * CS, NTHREADS, SMEM_BYTES, cudaStreamPerThread>>>(p);
}
```

```cpp
#include <cuda_runtime.h>
#include <cuda_bf16.h>
#include <cuda_fp16.h>
#include <cuda.h>
#include <stdint.h>

#define TIMELINE 0
#define TLHI 0

namespace {

constexpr int SEQ = 2048, DCH = 576, NMODE = 128;
constexpr int CS = 8, CPC = 40, NCL = 15, NTHREADS = 640;

constexpr int KTAB = 16384;
constexpr int OFF_T = 0;
constexpr int T_UKV = 8192, T_HA = 12288;
constexpr int OFF_UX = 5 * KTAB;
constexpr int OFF_IM = OFF_UX + 20480;
constexpr int OFF_CF = OFF_IM;
constexpr int OFF_CL = OFF_CF + 8192;
constexpr int OFF_TV = OFF_CL + 4096;
constexpr int OFF_YA = OFF_TV + 20480;
constexpr int OFF_GB = OFF_YA + 20480;
constexpr int OFF_YB = OFF_IM + 4 * KTAB;
constexpr int OFF_TQ = OFF_YB + 20480;
constexpr int OFF_TK = OFF_TQ + 20480;
constexpr int OFF_HALO = OFF_TK + 20480;
constexpr int OFF_MX = OFF_HALO + 320;
constexpr int OFF_SP = OFF_MX + 320;
constexpr int OFF_MB = OFF_SP + 560;
constexpr int OFF_TL = OFF_MB + 28 * 8;
constexpr int SMEM_BYTES = OFF_TL + (TIMELINE ? 1280 : 0);
static_assert(SMEM_BYTES <= 232448 && OFF_YA == OFF_IM + 2 * KTAB && OFF_GB + 2048 <= OFF_YB, "smem");
static_assert((OFF_MB & 7) == 0 && (OFF_MX & 15) == 0 && (OFF_SP & 15) == 0, "align");

enum { MB_UX = 0, MB_UKV = 5, MB_Y = 10, MB_HA = 15, MB_XQ = 20, MB_KV = 21, MB_CF = 22, MB_G = 23, MB_TH = 24, MB_TAG = 25 };
enum { NB_WG0 = 1, NB_ROW0 = 6, NB_ORD = 6, NB_V = 10 };

constexpr double cos_turn(int m, int n) {
  m &= n - 1;
  if (m > n / 2) m = n - m;
  double sgn = 1.0;
  if (m > n / 4) { m = n / 2 - m; sgn = -1.0; }
  if (m == n / 4) return 0.0;
  const double x = 6.283185307179586476925 * m / n;
  double term = 1.0, sum = 1.0;
  for (int k = 1; k < 14; k++) { term *= -x * x / ((2 * k - 1) * (2 * k)); sum += term; }
  return sgn * sum;
}
constexpr uint32_t bf16_bits(double v) {
  if (v == 0.0) return 0;
  uint32_t sgn = 0;
  if (v < 0) { sgn = 0x8000; v = -v; }
  int e = 127;
  while (v < 1.0) { v *= 2.0; e--; }
  while (v >= 2.0) { v *= 0.5; e++; }
  const double f = v * 128.0;
  int m = (int)f;
  if (f - m > 0.5 || (f - m == 0.5 && (m & 1))) m++;
  return sgn | (uint32_t)((e << 7) + (m - 128));
}
constexpr uint32_t f16_bits(double v) {
  if (v == 0.0) return 0;
  uint32_t sgn = 0;
  if (v < 0) { sgn = 0x8000; v = -v; }
  int e = 15;
  while (v < 1.0) { v *= 2.0; e--; }
  const double f = v * 1024.0;
  int m = (int)f;
  if (f - m > 0.5 || (f - m == 0.5 && (m & 1))) m++;
  return sgn | (uint32_t)((e << 10) + (m - 1024));
}
constexpr uint32_t pair_bits(double lo, double hi) { return bf16_bits(lo) | (bf16_bits(hi) << 16); }
constexpr uint32_t pair_h(double lo, double hi) { return f16_bits(lo) | (f16_bits(hi) << 16); }
struct alignas(128) Tables {
  uint32_t mat[3072];
  uint32_t thr[4][128][4];
};
constexpr Tables make_tables() {
  Tables T{};
  for (int q = 0; q < 768; q++) {
    int m0 = 0, d0 = 0, d1 = 0;
    if (q < 512) {
      const int r = (q >> 6) * 8 + (q & 7), cc = (q >> 3) & 7;
      d0 = 4 * (r & 31); d1 = 2 * d0;
      m0 = 8 * (cc & 3) * d0 + ((r >> 5) == (cc >> 2) ? 0 : (r >> 5) ? 96 : 32);
    } else {
      const int r = ((q - 512) >> 5) * 8 + (q & 7), pc = (q >> 3) & 3;
      d0 = 4 * (8 * (r >> 4) + (r & 7)) + 1; d1 = 8 * d0;
      m0 = 2 * pc * d0 + ((r & 8) ? 32 : 0);
    }
    for (int e = 0; e < 4; e++) T.mat[4 * q + e] = pair_h(cos_turn(m0 + e * d1, 128), cos_turn(m0 + e * d1 + d0, 128));
  }
  for (int tid = 0; tid < 128; tid++) {
    const int kk = 4 * (tid >> 2) + 1, t = tid & 3;
    for (int q = 0; q < 4; q++) {
      const int m = (8 * q + 2 * t) * kk;
      T.thr[q >> 1][tid][2 * (q & 1)] = pair_bits(cos_turn(m, 128), cos_turn(m + kk, 128));
      T.thr[q >> 1][tid][2 * (q & 1) + 1] = pair_bits(cos_turn(m + 32, 128), cos_turn(m + kk + 32, 128));
      T.thr[2][tid][q] = pair_h(cos_turn(m, 4096), cos_turn(m + kk, 4096));
      T.thr[3][tid][q] = pair_h(cos_turn(m + 3072, 4096), cos_turn(m + kk + 3072, 4096));
    }
  }
  return T;
}
__device__ const Tables d_tab = make_tables();

struct Params {
  const __nv_bfloat16 *logA, *Aim, *Cre, *Cim, *logdt;
  const Tables* tab;
  unsigned* cnt;
  const __nv_bfloat16 *Dskip, *shift_k, *ssm_D, *gate_w, *q, *ssm_k;
  uint2* part;
  __nv_bfloat16* out;
  unsigned* tl;
  CUtensorMap tq, tk, tv, tkh;
};

__device__ uint2 g_part[NCL * SEQ];
__device__ unsigned g_cnt[CS * 32];
#define TL(i) do {} while (0)
#define TL_INIT() do {} while (0)
#define TL_DUMP() do {} while (0)

__device__ __forceinline__ uint32_t lds16(uint32_t a) { uint32_t v; asm volatile("ld.shared.u16 %0, [%1];" : "=r"(v) : "r"(a) : "memory"); return v; }
__device__ __forceinline__ uint2 lds64(uint32_t a) { uint2 v; asm volatile("ld.shared.v2.u32 {%0,%1}, [%2];" : "=r"(v.x), "=r"(v.y) : "r"(a) : "memory"); return v; }
__device__ __forceinline__ uint4 lds128(uint32_t a) { uint4 v; asm volatile("ld.shared.v4.u32 {%0,%1,%2,%3}, [%4];" : "=r"(v.x), "=r"(v.y), "=r"(v.z), "=r"(v.w) : "r"(a) : "memory"); return v; }
__device__ __forceinline__ void sts16(uint32_t a, uint32_t v) { asm volatile("st.shared.u16 [%0], %1;" :: "r"(a), "r"(v) : "memory"); }
__device__ __forceinline__ void sts32(uint32_t a, uint32_t v) { asm volatile("st.shared.u32 [%0], %1;" :: "r"(a), "r"(v) : "memory"); }
__device__ __forceinline__ void sts64(uint32_t a, uint32_t x, uint32_t y) { asm volatile("st.shared.v2.u32 [%0], {%1,%2};" :: "r"(a), "r"(x), "r"(y) : "memory"); }
__device__ __forceinline__ void sts128(uint32_t a, uint32_t x, uint32_t y, uint32_t z, uint32_t w) { asm volatile("st.shared.v4.u32 [%0], {%1,%2,%3,%4};" :: "r"(a), "r"(x), "r"(y), "r"(z), "r"(w) : "memory"); }
__device__ __forceinline__ void ldsm4t(uint32_t (&r)[4], uint32_t a) { asm volatile("ldmatrix.sync.aligned.m8n8.x4.trans.shared.b16 {%0,%1,%2,%3}, [%4];" : "=r"(r[0]), "=r"(r[1]), "=r"(r[2]), "=r"(r[3]) : "r"(a) : "memory"); }
__device__ __forceinline__ void ldsm2t(uint32_t& r0, uint32_t& r1, uint32_t a) { asm volatile("ldmatrix.sync.aligned.m8n8.x2.trans.shared.b16 {%0,%1}, [%2];" : "=r"(r0), "=r"(r1) : "r"(a) : "memory"); }
__device__ __forceinline__ void ldsm4(uint32_t (&r)[4], uint32_t a) { asm volatile("ldmatrix.sync.aligned.m8n8.x4.shared.b16 {%0,%1,%2,%3}, [%4];" : "=r"(r[0]), "=r"(r[1]), "=r"(r[2]), "=r"(r[3]) : "r"(a) : "memory"); }
__device__ __forceinline__ void stsm4(uint32_t a, const uint32_t (&r)[4]) { asm volatile("stmatrix.sync.aligned.m8n8.x4.shared.b16 [%0], {%1,%2,%3,%4};" :: "r"(a), "r"(r[0]), "r"(r[1]), "r"(r[2]), "r"(r[3]) : "memory"); }
__device__ __forceinline__ uint32_t pack(float lo, float hi) { uint32_t r; asm("cvt.rn.bf16x2.f32 %0, %1, %2;" : "=r"(r) : "f"(hi), "f"(lo)); return r; }
__device__ __forceinline__ float blo(uint32_t v) { return __uint_as_float(v << 16); }
__device__ __forceinline__ float bhi(uint32_t v) { return __uint_as_float(v & 0xffff0000u); }
__device__ __forceinline__ float bf16r(float x) { return blo(pack(x, 0.f)); }
__device__ __forceinline__ uint32_t hmul2(uint32_t a, uint32_t b) { uint32_t r; asm("mul.rn.bf16x2 %0, %1, %2;" : "=r"(r) : "r"(a), "r"(b)); return r; }
__device__ __forceinline__ uint32_t hadd2(uint32_t a, uint32_t b) { uint32_t r; asm("add.rn.bf16x2 %0, %1, %2;" : "=r"(r) : "r"(a), "r"(b)); return r; }
__device__ __forceinline__ uint32_t hfma2(uint32_t a, uint32_t b, uint32_t c) { uint32_t r; asm("fma.rn.bf16x2 %0, %1, %2, %3;" : "=r"(r) : "r"(a), "r"(b), "r"(c)); return r; }
__device__ __forceinline__ uint32_t packh(float lo, float hi) { uint32_t r; asm("cvt.rn.f16x2.f32 %0, %1, %2;" : "=r"(r) : "f"(hi), "f"(lo)); return r; }
__device__ __forceinline__ __half2 H2(uint32_t a) { return *reinterpret_cast<__half2*>(&a); }
__device__ __forceinline__ uint32_t U2(__half2 a) { return *reinterpret_cast<uint32_t*>(&a); }
__device__ __forceinline__ uint32_t fmul(uint32_t a, uint32_t b) { return U2(__hmul2(H2(a), H2(b))); }
__device__ __forceinline__ uint32_t ffma(uint32_t a, uint32_t b, uint32_t c) { return U2(__hfma2(H2(a), H2(b), H2(c))); }
__device__ __forceinline__ uint32_t fneg(uint32_t a) { return U2(__hneg2(H2(a))); }
__device__ __forceinline__ uint32_t amax2(uint32_t a, uint32_t b) { uint32_t r; asm("max.xorsign.abs.bf16x2 %0, %1, %2;" : "=r"(r) : "r"(a), "r"(b)); return r; }
__device__ __forceinline__ uint32_t prmt(uint32_t a, uint32_t b, uint32_t s) { return __byte_perm(a, b, s); }
__device__ __forceinline__ uint32_t ldraw(const __nv_bfloat16* p) { uint32_t v; asm volatile("ld.global.nc.u16 %0, [%1];" : "=r"(v) : "l"(p)); return v; }
__device__ __forceinline__ uint4 ldg128(const void* p) { uint4 v; asm volatile("ld.global.nc.v4.u32 {%0,%1,%2,%3}, [%4];" : "=r"(v.x), "=r"(v.y), "=r"(v.z), "=r"(v.w) : "l"(p)); return v; }
__device__ __forceinline__ void bar_sync(int id, int n) { asm volatile("bar.sync %0, %1;" :: "r"(id), "r"(n) : "memory"); }
__device__ __forceinline__ void bar_arrive(int id, int n) { asm volatile("bar.arrive %0, %1;" :: "r"(id), "r"(n) : "memory"); }
__device__ __forceinline__ void cluster_arrive() { asm volatile("barrier.cluster.arrive.relaxed.aligned;" ::: "memory"); }
__device__ __forceinline__ void cluster_wait() { asm volatile("barrier.cluster.wait.aligned;" ::: "memory"); }
__device__ __forceinline__ void fence_async() { asm volatile("fence.proxy.async.shared::cta;" ::: "memory"); }
__device__ __forceinline__ void fence_mbinit() { asm volatile("fence.mbarrier_init.release.cluster;" ::: "memory"); }
__device__ __forceinline__ uint32_t mapa(uint32_t a, uint32_t rank) { uint32_t r; asm("mapa.shared::cluster.u32 %0, %1, %2;" : "=r"(r) : "r"(a), "r"(rank)); return r; }
__device__ __forceinline__ void bulk_dsmem(uint32_t dst, uint32_t src, uint32_t mbar) {
  asm volatile("cp.async.bulk.shared::cluster.shared::cta.mbarrier::complete_tx::bytes [%0], [%1], 512, [%2];" :: "r"(dst), "r"(src), "r"(mbar) : "memory");
}
__device__ __forceinline__ void bulk_load(uint32_t dst, const void* src, uint32_t bytes, uint32_t mbar) {
  asm volatile("cp.async.bulk.shared::cluster.global.mbarrier::complete_tx::bytes [%0], [%1], %2, [%3];" :: "r"(dst), "l"(src), "r"(bytes), "r"(mbar) : "memory");
}
__device__ __forceinline__ void mbar_init(uint32_t m, uint32_t cnt) { asm volatile("mbarrier.init.shared::cta.b64 [%0], %1;" :: "r"(m), "r"(cnt) : "memory"); }
__device__ __forceinline__ void mbar_expect(uint32_t m, uint32_t bytes) { asm volatile("mbarrier.arrive.expect_tx.shared::cta.b64 _, [%0], %1;" :: "r"(m), "r"(bytes) : "memory"); }
__device__ __forceinline__ bool mbar_try(uint32_t m) {
  uint32_t done;
  asm volatile("{.reg .pred p; mbarrier.try_wait.parity.shared::cta.b64 p, [%1], 0; selp.u32 %0, 1, 0, p;}" : "=r"(done) : "r"(m) : "memory");
  return done;
}
__device__ __forceinline__ void mbar_wait(uint32_t m) {
  if (!mbar_try(m)) {
    int it = 0;
    while (!mbar_try(m) && ++it < (1 << 22)) {}
  }
}
__device__ __forceinline__ bool elect() {
  uint32_t e;
  asm volatile("{.reg .pred p; elect.sync _|p, 0xffffffff; selp.u32 %0, 1, 0, p;}" : "=r"(e));
  return e;
}
__device__ __forceinline__ void tma_load4(uint32_t dst, const CUtensorMap* tm, int c0, int c1, int c2, int c3, uint32_t mbar) {
  asm volatile("cp.async.bulk.tensor.4d.shared::cluster.global.mbarrier::complete_tx::bytes [%0], [%1, {%3, %4, %5, %6}], [%2];"
               :: "r"(dst), "l"(tm), "r"(mbar), "r"(c0), "r"(c1), "r"(c2), "r"(c3) : "memory");
}
__device__ __forceinline__ void tma_load3(uint32_t dst, const CUtensorMap* tm, int c0, int c1, int c2, uint32_t mbar) {
  asm volatile("cp.async.bulk.tensor.3d.shared::cluster.global.mbarrier::complete_tx::bytes [%0], [%1, {%3, %4, %5}], [%2];"
               :: "r"(dst), "l"(tm), "r"(mbar), "r"(c0), "r"(c1), "r"(c2) : "memory");
}
__device__ __forceinline__ void tma_store3(const CUtensorMap* tm, int c0, int c1, int c2, uint32_t src) {
  asm volatile("cp.async.bulk.tensor.3d.global.shared::cta.bulk_group [%0, {%2, %3, %4}], [%1];"
               :: "l"(tm), "r"(src), "r"(c0), "r"(c1), "r"(c2) : "memory");
}
__device__ __forceinline__ void wg_fence() { asm volatile("wgmma.fence.sync.aligned;" ::: "memory"); }
__device__ __forceinline__ void wg_commit() { asm volatile("wgmma.commit_group.sync.aligned;" ::: "memory"); }
template <int N> __device__ __forceinline__ void wg_wait() { asm volatile("wgmma.wait_group.sync.aligned %0;" :: "n"(N) : "memory"); }
template <int N> __device__ __forceinline__ void tie_all(uint32_t (&x)[N]) {
#pragma unroll
  for (int i = 0; i < N; i++) asm volatile("" : "+r"(x[i]) :: "memory");
}
template <int N> __device__ __forceinline__ void tie_all(float (&x)[N]) {
#pragma unroll
  for (int i = 0; i < N; i++) asm volatile("" : "+f"(x[i]) :: "memory");
}
#define R16(C, d) C(d[0]), C(d[1]), C(d[2]), C(d[3]), C(d[4]), C(d[5]), C(d[6]), C(d[7]), C(d[8]), C(d[9]), C(d[10]), C(d[11]), C(d[12]), C(d[13]), C(d[14]), C(d[15])
#define R32(C, d) R16(C, d), R16(C, (d + 16))
#define P16 "{%0,%1,%2,%3,%4,%5,%6,%7,%8,%9,%10,%11,%12,%13,%14,%15}"
#define P32 "{%0,%1,%2,%3,%4,%5,%6,%7,%8,%9,%10,%11,%12,%13,%14,%15,%16,%17,%18,%19,%20,%21,%22,%23,%24,%25,%26,%27,%28,%29,%30,%31}"
template <int SD, int TB, int OFF> __device__ __forceinline__ void rs64(float* d, const uint32_t* a, uint64_t db) {
  if (SD) asm volatile("{.reg .b64 db; add.s64 db, %36, %37; wgmma.mma_async.sync.aligned.m64n64k16.f32.bf16.bf16 " P32 ", {%32,%33,%34,%35}, db, 1, 1, 1, %38;}"
                       : R32("+f", d) : "r"(a[0]), "r"(a[1]), "r"(a[2]), "r"(a[3]), "l"(db), "n"(OFF), "n"(TB));
  else asm volatile("{.reg .b64 db; add.s64 db, %36, %37; wgmma.mma_async.sync.aligned.m64n64k16.f32.bf16.bf16 " P32 ", {%32,%33,%34,%35}, db, 0, 1, 1, %38;}"
                    : R32("=f", d) : "r"(a[0]), "r"(a[1]), "r"(a[2]), "r"(a[3]), "l"(db), "n"(OFF), "n"(TB));
}
template <int SD, int TB, int OFF> __device__ __forceinline__ void rs64h(uint32_t* d, const uint32_t* a, uint64_t db) {
  if (SD) asm volatile("{.reg .b64 db; add.s64 db, %20, %21; wgmma.mma_async.sync.aligned.m64n64k16.f16.f16.f16 " P16 ", {%16,%17,%18,%19}, db, 1, 1, 1, %22;}"
                       : R16("+r", d) : "r"(a[0]), "r"(a[1]), "r"(a[2]), "r"(a[3]), "l"(db), "n"(OFF), "n"(TB));
  else asm volatile("{.reg .b64 db; add.s64 db, %20, %21; wgmma.mma_async.sync.aligned.m64n64k16.f16.f16.f16 " P16 ", {%16,%17,%18,%19}, db, 0, 1, 1, %22;}"
                    : R16("=r", d) : "r"(a[0]), "r"(a[1]), "r"(a[2]), "r"(a[3]), "l"(db), "n"(OFF), "n"(TB));
}
template <int SD, int OFFA, int OFFB> __device__ __forceinline__ void ss32(float* d, uint64_t da, uint64_t db) {
  if (SD) asm volatile("{.reg .b64 da, db; add.s64 da, %16, %18; add.s64 db, %17, %19; wgmma.mma_async.sync.aligned.m64n32k16.f32.f16.f16 " P16 ", da, db, 1, 1, 1, 1, 1;}"
                       : R16("+f", d) : "l"(da), "l"(db), "n"(OFFA), "n"(OFFB));
  else asm volatile("{.reg .b64 da, db; add.s64 da, %16, %18; add.s64 db, %17, %19; wgmma.mma_async.sync.aligned.m64n32k16.f32.f16.f16 " P16 ", da, db, 0, 1, 1, 1, 1;}"
                    : R16("=f", d) : "l"(da), "l"(db), "n"(OFFA), "n"(OFFB));
}
#define KGEN_ASM(SD) "{.reg .b64 da, db; add.s64 da, %32, %33; add.s64 db, %32, %34;\n" \
  "wgmma.mma_async.sync.aligned.m64n64k16.f32.bf16.bf16 " P32 ", da, db, " SD ", 1, 1, 1, 1;}"
template <int KS> __device__ __forceinline__ void kgen_mma(float (&c)[32], uint64_t da) {
  if (KS) asm volatile(KGEN_ASM("1") : R32("+f", c) : "l"(da), "n"(8 * KS), "n"(8 * KS + 512));
  else asm volatile(KGEN_ASM("0") : R32("=f", c) : "l"(da), "n"(8 * KS), "n"(8 * KS + 512));
  if constexpr (KS < 7) kgen_mma<KS + 1>(c, da);
}
__device__ __forceinline__ uint64_t desc_lo(uint32_t a) { return (uint64_t)((a & 0x3FFFF) >> 4); }
__device__ __forceinline__ void stage1(float (&D)[32], const uint32_t (&A1)[8], uint32_t src) {
  const uint64_t du = desc_lo(src) | (128ull << 16) | (32ull << 32) | (2ull << 62);
  rs64<0, 1, 0>(D, A1, du); rs64<1, 1, 64>(D, A1 + 4, du);
}
template <int INV> __device__ __forceinline__ void stage2(uint32_t (&X)[16], const uint32_t (&F)[16], uint32_t cf) {
  constexpr int KS = INV ? 16 : 128, TB = INV ? 0 : 1;
  const uint64_t dc = desc_lo(cf) | (INV ? (8ull << 16) | (64ull << 32) : (64ull << 16) | (8ull << 32));
  rs64h<0, TB, 0>(X, F, dc); rs64h<1, TB, KS>(X, F + 4, dc); rs64h<1, TB, 2 * KS>(X, F + 8, dc); rs64h<1, TB, 3 * KS>(X, F + 12, dc);
}
__device__ __forceinline__ void fwd_mid(uint32_t (&F)[16], const float (&D)[32], const uint32_t (&tc)[4], const uint32_t (&ts)[4]) {
#pragma unroll
  for (int j = 0; j < 4; j++)
#pragma unroll
    for (int b = 0; b < 2; b++) {
      const int i = 4 * j + 16 * b;
      const uint32_t ar = packh(D[i], D[i + 1]), ai = packh(D[i + 2], D[i + 3]);
      F[2 * j + b] = ffma(ar, tc[j], fmul(ai, ts[j]));
      F[8 + 2 * j + b] = ffma(ai, tc[j], fneg(fmul(ar, ts[j])));
    }
}
__device__ __forceinline__ void put_exp(uint32_t a, uint32_t m, int lane) {
  m = __reduce_max_sync(0xffffffffu, max(m & 0x7f80u, (m >> 16) & 0x7f80u));
  if (lane == 0) sts32(a, m);
}
__device__ __forceinline__ uint32_t seq_mag(uint32_t a) {
  const uint4 x = lds128(a), y = lds128(a + 2048);
  return amax2(amax2(amax2(x.x, x.y), amax2(x.z, x.w)), amax2(amax2(y.x, y.y), amax2(y.z, y.w)));
}
__device__ __forceinline__ uint32_t get_exp(uint32_t a) { const uint4 v = lds128(a); return max(max(v.x, v.y), max(v.z, v.w)) >> 7; }
__device__ __forceinline__ void scale_a1(uint32_t (&As)[8], const uint32_t (&A1)[8], uint32_t field) {
#pragma unroll
  for (int i = 0; i < 8; i++) As[i] = hmul2(A1[i], field * 0x00800080u);
}

struct cf { float x, y; };
__device__ __forceinline__ cf cmul(cf a, cf b) { cf r; r.x = fmaf(a.x, b.x, -a.y * b.y); r.y = fmaf(a.x, b.y, a.y * b.x); return r; }
__device__ __forceinline__ cf cexp_p(float lr2, float lt, float p) {
  float m;
  asm("ex2.approx.ftz.f32 %0, %1;" : "=f"(m) : "f"(lr2 * p));
  float t = lt * p;
  t = (t - rintf(t)) * 6.283185307179586f;
  cf r; r.x = m * __cosf(t); r.y = m * __sinf(t); return r;
}
__device__ __forceinline__ void store8(uint32_t a, uint32_t b, const cf (&v)[8]) {
  sts128(a, pack(v[0].x, v[1].x), pack(v[2].x, v[3].x), pack(v[4].x, v[5].x), pack(v[6].x, v[7].x));
  sts128(b, pack(v[0].y, v[1].y), pack(v[2].y, v[3].y), pack(v[4].y, v[5].y), pack(v[6].y, v[7].y));
}
__device__ __forceinline__ void mbar_arrive(uint32_t m) { asm volatile("mbarrier.arrive.shared::cta.b64 _, [%0];" :: "r"(m) : "memory"); }
__device__ __forceinline__ float sigmoidf_(float s) { return __fdividef(1.f, 1.f + __expf(fminf(-s, 80.f))); }

__global__ void __cluster_dims__(CS, 1, 1) __launch_bounds__(NTHREADS, 1) fused_kernel(const __grid_constant__ Params p) {
  extern __shared__ __align__(1024) uint8_t smem[];
  TL_INIT();
  TL(31);
  const int wid = __shfl_sync(0xffffffffu, threadIdx.x >> 5, 0);
  const uint32_t sb = (uint32_t)__cvta_generic_to_shared(smem);
  const uint32_t mb = sb + OFF_MB;
  const int u = wid >> 2, w = wid & 3;
  const int tid = threadIdx.x & 127, lane = tid & 31, g = lane >> 2, t = lane & 3;
  const int cl = blockIdx.x >> 3, rank = blockIdx.x & 7;
  const int ch0 = cl * CPC;
  const int nu = min(5, (DCH - ch0) >> 3);
  const bool act = u < nu;

  uint32_t pla, pai, pcr, pci, pdt, tag = 0;
  auto load_params = [&]() {
    const int ch = act ? ch0 + 8 * u + rank : 0, o = ch * NMODE + tid;
    pla = ldraw(p.logA + o); pdt = ldraw(p.logdt + ch); pai = ldraw(p.Aim + o); pcr = ldraw(p.Cre + o); pci = ldraw(p.Cim + o);
  };
  if (u == 4) {
    const bool e = elect();
    if (e) {
#pragma unroll
      for (int i = 0; i < 5; i++) mbar_init(mb + 40 * w + 8 * i, 1);
      if (w == 3) { mbar_init(mb + 8 * MB_TH, 1); mbar_init(mb + 8 * MB_XQ, 21); mbar_init(mb + 8 * MB_KV, 1); }
      if (w == 2) { mbar_init(mb + 8 * MB_CF, 1); mbar_init(mb + 8 * MB_G, 16); }
      fence_mbinit();
    }
    __syncwarp();
    load_params();
    if (w == 0 && lane < 2) asm volatile("atom.relaxed.gpu.global.add.u32 %0, [%1], %2;" : "=r"(tag) : "l"(&p.cnt[rank * 32 + lane]), "r"(cl == 0 ? 16 - (NCL - 1) : 1) : "memory");
    if (e) {
      if (w == 3) {
        mbar_expect(mb + 8 * MB_TH, 8192 + 112 * nu);
        bulk_load(sb + OFF_YB, p.tab->thr, 8192, mb + 8 * MB_TH);
        bulk_load(sb + OFF_SP, p.gate_w + ch0, 16 * nu, mb + 8 * MB_TH);
        bulk_load(sb + OFF_SP + 80, p.Dskip + ch0, 16 * nu, mb + 8 * MB_TH);
        bulk_load(sb + OFF_SP + 160, p.ssm_D + ch0, 16 * nu, mb + 8 * MB_TH);
        bulk_load(sb + OFF_SP + 240, p.shift_k + 4 * ch0, 64 * nu, mb + 8 * MB_TH);
        asm volatile("cp.async.bulk.prefetch.L2.global [%0], 12288;" :: "l"(p.tab->mat) : "memory");
        mbar_expect(mb + 8 * MB_XQ, 20480);
        tma_load3(sb + OFF_TQ, &p.tq, ch0, 8 * rank, 0, mb + 8 * MB_XQ);
        TL(20);
        mbar_expect(mb + 8 * MB_KV, 2 * 20480 + 320);
        tma_load3(sb + OFF_TK, &p.tk, ch0, 8 * rank, 0, mb + 8 * MB_KV);
        tma_load3(sb + OFF_HALO, &p.tkh, ch0, 8 * rank - 1, 28, mb + 8 * MB_KV);
      }
      if (w == 2) mbar_expect(mb + 8 * MB_CF, 12288);
#pragma unroll
      for (int i = 0; i < 5; i++) mbar_expect(mb + 40 * w + 8 * i, w == 3 ? 4096 : w == 2 ? 7168 : 3584);
    }
    __syncwarp();
  } else {
    load_params();
  }
  cluster_arrive();
  TL(0);

  const uint32_t tab = sb + OFF_T + u * KTAB;
  const uint32_t toff = (64 * w + lane) * 80 + 16 * u;
  auto put = [&](uint32_t dst, const uint32_t (&a)[4], const uint32_t (&b)[4]) {
    const uint32_t s0 = (g & 1) ? 0x7632 : 0x5410, s1 = s0 ^ 0x2222;
    const uint32_t o = dst + 128 * t + 64 * (g & 1) + 16 * (w ^ t);
    sts128(o, prmt(a[0], a[1], s0), prmt(a[2], a[3], s0), prmt(b[0], b[1], s0), prmt(b[2], b[3], s0));
    sts128(o ^ 64, prmt(a[0], a[1], s1), prmt(a[2], a[3], s1), prmt(b[0], b[1], s1), prmt(b[2], b[3], s1));
  };
  const int d0 = rank ^ (2 * w), d1 = d0 ^ 1;
  const uint32_t rb0 = mapa(sb, d0), rb1 = mapa(sb, d1);
  auto send = [&](int stage, int dst, int mbar) {
    if (elect()) {
      if (w) bulk_dsmem(rb0 + dst, sb + stage + d0 * 512, rb0 + mbar);
      bulk_dsmem(rb1 + dst, sb + stage + d1 * 512, rb1 + mbar);
    }
    __syncwarp();
  };

  uint32_t A1[8], tc[4], ts[4];
  {
    const float dt = bf16r(expf(blo(pdt)));
    const float lr2 = (-bf16r(expf(blo(pla))) * dt) * 1.4426950408889634f;
    const float lt = (blo(pai) * dt) * 0.15915494309189535f;
    const uint32_t tim = sb + (u ? OFF_IM + (u - 1) * KTAB : OFF_UX);
    const uint32_t row = tab + tid * 16, rim = tim + tid * 16;
    const cf w1 = cexp_p(lr2, lt, 8.f);
    cf z1 = cexp_p(lr2, lt, 1.f), Z = cexp_p(lr2, lt, 256.f);
    if (lr2 != 123.f) TL(16);
    TL(12);
    {
      cf v[8];
      v[0].x = 1.f; v[0].y = 0.f; v[1] = w1; v[2] = cmul(w1, w1); v[3] = cmul(v[2], w1);
      const cf w4 = cmul(v[2], v[2]);
      v[4] = w4; v[5] = cmul(v[1], w4); v[6] = cmul(v[2], w4); v[7] = cmul(v[3], w4);
      const cf w8 = cmul(w4, w4);
      store8(row, rim, v);
#pragma unroll
      for (int k = 1; k < 4; k++) {
#pragma unroll
        for (int i = 0; i < 8; i++) v[i] = (k == 1 && i == 0) ? w8 : cmul(v[i], w8);
        store8(row + 2048 * k, rim + 2048 * k, v);
      }
    }
    cluster_wait();
    if (u) cluster_arrive();
    mbar_wait(mb + 8 * MB_TH);
    {
      const uint4 x = lds128(sb + OFF_YB + 16 * tid), y = lds128(sb + OFF_YB + 2048 + 16 * tid), a = lds128(sb + OFF_YB + 4096 + 16 * tid), b = lds128(sb + OFF_YB + 6144 + 16 * tid);
      A1[0] = x.x; A1[1] = x.y; A1[2] = x.z; A1[3] = x.w; A1[4] = y.x; A1[5] = y.y; A1[6] = y.z; A1[7] = y.w;
      tc[0] = a.x; tc[1] = a.y; tc[2] = a.z; tc[3] = a.w; ts[0] = b.x; ts[1] = b.y; ts[2] = b.z; ts[3] = b.w;
    }
    if (wid == 16 && lane == 0) sts32(mb + 8 * MB_TAG, tag);
    __syncwarp();
    if (lane == 0) mbar_arrive(mb + 8 * MB_XQ);
    if (u == 1) {
      float z0_ = 0.f, z1_ = 0.f, z2_ = 0.f, z3_ = 0.f;
      asm volatile("mma.sync.aligned.m16n8k8.row.col.f32.bf16.bf16.f32 {%0,%1,%2,%3}, {%4,%4}, {%4}, {%0,%1,%2,%3};"
                   : "+f"(z0_), "+f"(z1_), "+f"(z2_), "+f"(z3_) : "r"(pla >> 16));
      pcr += __float_as_uint(z0_);
      TL(8);
    }
    {
      z1.y = -z1.y; Z.y = -Z.y;
      const cf z2 = cmul(z1, z1);
      cf h[8], v[8];
      h[0].x = 2.f * blo(pcr) * dt; h[0].y = -2.f * blo(pci) * dt;
      h[1] = cmul(h[0], z1);
#pragma unroll
      for (int i = 2; i < 8; i++) h[i] = cmul(h[i - 2], z2);
      store8(row + 4 * 2048, rim + 4 * 2048, h);
      const cf h8 = cmul(h[6], z2);
      v[0] = cmul(h[0], Z); v[2] = cmul(h[2], Z); v[3] = cmul(h[4], Z); v[6] = cmul(h[6], Z); v[7] = cmul(h8, Z);
      v[1] = v[0]; v[4] = v[5] = v[3];
      store8(row + 5 * 2048, rim + 5 * 2048, v);
      h[0] = cmul(v[0], Z); h[1] = cmul(v[3], Z); h[3] = cmul(v[7], Z); h[4] = cmul(h[0], Z); h[5] = cmul(h[1], Z); h[7] = cmul(h[3], Z);
      h[2] = h[1]; h[6] = h[5];
      store8(row + 6 * 2048, rim + 6 * 2048, h);
      const cf Z2 = cmul(Z, Z);
      v[0] = cmul(h[0], Z2); v[1] = cmul(h[3], Z2); v[2] = cmul(h[4], Z2); v[3] = cmul(h[7], Z2);
#pragma unroll
      for (int i = 4; i < 8; i++) v[i] = cmul(v[i - 4], Z2);
      store8(row + 7 * 2048, rim + 7 * 2048, v);
    }
    TL(17);
    fence_async();
    if (u) bar_sync(NB_ORD + u - 1, 256); else bar_sync(NB_WG0, 128);
    TL(13);
    float c[32];
    wg_fence();
    kgen_mma<0>(c, desc_lo(tab) | ((uint64_t)((tim - tab) >> 4) << 16) | (64ull << 32));
    wg_commit();
    if (u < 4) bar_arrive(NB_ORD + u, 256);
    TL(14);
    mbar_wait(mb + 8 * MB_XQ);
    TL(18);
    uint32_t x0[4], x1[4];
    ldsm4t(x0, sb + OFF_TQ + toff);
    ldsm4t(x1, sb + OFF_TQ + toff + 2560);
    wg_wait<0>(); tie_all(c);
    TL(26);
    if (u == 0) cluster_arrive();
    if (u == 1 || u == 2) bar_arrive(NB_V, 288);
    bar_sync(NB_WG0 + u, 128);
    if (wid == 4 && elect()) bulk_load(sb + OFF_CF, p.tab->mat, 12288, mb + 8 * MB_CF);
    __syncwarp();
    const uint32_t k0 = pack(c[0] + c[6], c[1] + c[7]), k1 = pack(c[8] + c[14], c[9] + c[15]);
    const uint32_t k2 = pack(c[16] + c[22], c[17] + c[23]), k3 = pack(c[24] + c[30], c[25] + c[31]);
    const uint32_t ka = tab + 16 * (8 * w + (g ^ w));
    sts32(ka + 4 * t, k0);
    sts32(ka + 512 + 4 * t, k1);
    sts64(ka + 1024 + 512 * (t >> 1) + 8 * (t & 1), prmt(k2, 0, 0x1010), (t & 1) ? prmt(k2, 0, 0x3232) : k2);
    const uint32_t lo = prmt(k3, 0, 0x1010), hi = prmt(k3, 0, 0x3232);
    sts128(ka + 2048 + 512 * t, lo, lo, (g & 1) ? hi : k3, hi);
    put_exp(sb + OFF_MX + u * 64 + 4 * w, amax2(amax2(k0, k1), amax2(k2, k3)), lane);
    cluster_wait();
    cluster_arrive();
    put(sb + u * 4096 + g * 512 + (g == rank ? OFF_UX : OFF_YB), x0, x1);
    TL(15);
    fence_async();
    bar_sync(NB_WG0 + u, 128);
    send(OFF_YB + u * 4096, OFF_UX + u * 4096 + 512 * rank, OFF_MB + 8 * (MB_UX + u));
    if (wid == 16) {
      bar_sync(NB_V, 288);
      if (elect()) tma_load3(sb + OFF_TV, &p.tv, ch0, 8 * rank, 0, mb + 8 * MB_KV);
      __syncwarp();
    }
  }

#pragma unroll
  for (int isA = 0; isA < 2; isA++) {
    {
      TL(1 + isA);
      const uint32_t usrc = isA ? tab + T_UKV : sb + OFF_UX + u * 4096;
      const uint32_t mxa = sb + OFF_MX + u * 64 + 32 * isA;
      const uint32_t pd = lds16(sb + OFF_SP + 80 + 80 * isA + 16 * u + 2 * rank);
      float D[32];
      uint32_t As[8], F[16], H[16], X[16];
      const uint32_t eh = min(max((int)get_exp(mxa), (int)((pd >> 7) & 0xff) - 5), 240);
      scale_a1(As, A1, 248 - eh);
      wg_fence();
      stage1(D, As, isA ? tab + T_HA : tab);
      wg_commit();
      wg_wait<0>(); tie_all(D);
      fwd_mid(F, D, tc, ts);
      if (!isA) mbar_wait(mb + 8 * MB_CF);
      wg_fence();
      stage2<0>(H, F, sb + OFF_CF);
      wg_commit();
      if (!isA) {
        if (w == 2 && elect()) bulk_load(tab + T_HA, p.ssm_k + (size_t)(act ? ch0 + 8 * u + rank : 0) * SEQ, 4096, mb + 8 * (MB_HA + u));
        __syncwarp();
        if (u < 2) {
          float s0 = 0.f;
#pragma unroll
          for (int j = 0; j < 5; j++) {
            if (j >= 2 && j >= nu) break;
            const uint4 gw = lds128(sb + OFF_SP + 16 * j), x = lds128(sb + OFF_TQ + (tid + 128 * u) * 80 + 16 * j);
            const uint32_t m0 = hmul2(x.x, gw.x), m1 = hmul2(x.y, gw.y), m2 = hmul2(x.z, gw.z), m3 = hmul2(x.w, gw.w);
            s0 += ((blo(m0) + bhi(m0)) + (blo(m1) + bhi(m1))) + ((blo(m2) + bhi(m2)) + (blo(m3) + bhi(m3)));
          }
          tag = (lds64(mb + 8 * MB_TAG).x >> 4) + 1;
          asm volatile("st.relaxed.gpu.global.u64 [%0], %1;" :: "l"(p.part + cl * SEQ + rank * 256 + tid + 128 * u),
                       "l"(((uint64_t)tag << 32) | __float_as_uint(s0)) : "memory");
        }
        TL(7);
      }
      mbar_wait(mb + 8 * ((isA ? MB_UKV : MB_UX) + u));
      TL(5 + isA);
      put_exp(mxa + 16 + 4 * w, seq_mag(usrc + 16 * tid), lane);
      bar_sync(NB_WG0 + u, 128);
      const uint32_t eu = min(get_exp(mxa + 16), 240u);
      scale_a1(As, A1, 250 - eu);
      wg_wait<0>(); tie_all(H);
      wg_fence();
      stage1(D, As, usrc);
      wg_commit();
      wg_wait<0>(); tie_all(D);
      fwd_mid(F, D, tc, ts);
      wg_fence();
      stage2<0>(X, F, sb + OFF_CF);
      wg_commit();
      {
        const float dsk = blo(pd) * __uint_as_float((248 - eh) << 23);
        const uint32_t d2 = packh(dsk, dsk);
#pragma unroll
        for (int j = 0; j < 4; j++) H[2 * j] = U2(__hadd2(H2(H[2 * j]), H2(d2)));
      }
      wg_wait<0>(); tie_all(X);
#pragma unroll
      for (int j = 0; j < 4; j++) {
        const uint32_t h0r = H[2 * j], h1r = H[2 * j + 1], h0i = H[8 + 2 * j], h1i = H[9 + 2 * j];
        const uint32_t x0r = X[2 * j], x1r = X[2 * j + 1], x0i = X[8 + 2 * j], x1i = X[9 + 2 * j];
        F[2 * j] = ffma(x0r, h0r, fneg(fmul(x0i, h0i)));
        F[8 + 2 * j] = ffma(x0r, h0i, fmul(x0i, h0r));
        F[2 * j + 1] = ffma(x1r, h0r, ffma(fneg(x1i), h0i, ffma(x0r, h1r, fneg(ffma(x0i, h1i, F[8 + 2 * j])))));
        F[9 + 2 * j] = ffma(x1r, h0i, ffma(x1i, h0r, ffma(x0r, h1i, ffma(x0i, h1r, F[2 * j]))));
      }
      wg_fence();
      stage2<1>(H, F, sb + OFF_CF);
      wg_commit();
      uint64_t ga[4][2];
      const int slot = 64 * u + 16 * w + 2 * g;
      auto gload = [&]() {
#pragma unroll
        for (int k = 0; k < 4; k++)
          asm volatile("ld.relaxed.gpu.global.v2.u64 {%0,%1}, [%2];" : "=l"(ga[k][0]), "=l"(ga[k][1])
                       : "l"(p.part + min(t + 4 * k, NCL - 1) * SEQ + rank * 256 + slot) : "memory");
      };
      if (isA && u < 4) gload();
      wg_wait<0>(); tie_all(H);
      {
        const uint32_t va = tab + (16 * w + (lane & 15)) * 128;
        const int vx = (lane >> 4) ^ (lane & 7);
#pragma unroll
        for (int j = 0; j < 4; j++) {
          uint32_t V[4];
#pragma unroll
          for (int b = 0; b < 2; b++) {
            const uint32_t er = H[2 * j + b], ei = H[8 + 2 * j + b];
            V[2 * b] = ffma(er, tc[j], fneg(fmul(ei, ts[j])));
            V[2 * b + 1] = ffma(ei, tc[j], fmul(er, ts[j]));
          }
          stsm4(va + ((vx ^ (2 * j)) << 4), V);
        }
      }
      if (!isA) {
        cluster_wait();
        mbar_wait(mb + 8 * MB_KV);
        TL(21);
        uint32_t K[3][4], V[2][4];
        const uint2 psw = lds64(sb + OFF_SP + 240 + 64 * u + 8 * g);
        ldsm4t(K[0], w ? sb + OFF_TK + toff - 2560 : (lane & 7) ? sb + OFF_TK + toff + 223 * 80 : sb + OFF_HALO + 10 * lane + 16 * u);
        ldsm4t(K[1], sb + OFF_TK + toff);
        ldsm4t(K[2], sb + OFF_TK + toff + 2560);
        ldsm4t(V[0], sb + OFF_TV + toff);
        ldsm4t(V[1], sb + OFF_TV + toff + 2560);
        mbar_wait(mb + 8 * (MB_HA + u));
        const uint4 hx = lds128(tab + T_HA + 16 * tid), hy = lds128(tab + T_HA + 2048 + 16 * tid);
        const uint32_t w0 = prmt(psw.x, 0, 0x1010), w1 = prmt(psw.x, 0, 0x3232), w2 = prmt(psw.y, 0, 0x1010), w3 = prmt(psw.y, 0, 0x3232);
#pragma unroll
        for (int m = 4; m < 12; m++)
          V[(m >> 2) - 1][m & 3] = hmul2(hfma2(K[m >> 2][m & 3], w0, hfma2(K[(m - 1) >> 2][(m - 1) & 3], w1,
                                         hfma2(K[(m - 2) >> 2][(m - 2) & 3], w2, hmul2(K[(m - 3) >> 2][(m - 3) & 3], w3)))), V[(m >> 2) - 1][m & 3]);
        put(g == rank ? tab + T_UKV + 512 * rank : sb + OFF_YA + u * 4096 + g * 512, V[0], V[1]);
        put_exp(mxa + 32 + 4 * w, amax2(amax2(amax2(hx.x, hx.y), amax2(hx.z, hx.w)), amax2(amax2(hy.x, hy.y), amax2(hy.z, hy.w))), lane);
        sts128(tab + T_HA + 16 * (tid ^ (lane >> 3)), hx.x, hx.y, hx.z, hx.w);
        sts128(tab + T_HA + 2048 + 16 * (tid ^ (lane >> 3)), hy.x, hy.y, hy.z, hy.w);
        TL(22);
      }
      fence_async();
      bar_sync(NB_WG0 + u, 128);
      float O[16];
      {
        const uint64_t dv = desc_lo(tab) | (1ull << 16) | (64ull << 32) | (1ull << 62);
        const uint64_t dl = desc_lo(sb + OFF_CL) | (32ull << 16) | (8ull << 32);
        wg_fence();
        ss32<0, 0, 0>(O, dv, dl); ss32<1, 128, 64>(O, dv, dl); ss32<1, 256, 128>(O, dv, dl); ss32<1, 384, 192>(O, dv, dl);
        wg_commit();
      }
      if (!isA) send(OFF_YA + u * 4096, OFF_T + u * KTAB + T_UKV + 512 * rank, OFF_MB + 8 * (MB_UKV + u));
      if (isA && u < 4) {
        tag = (lds64(mb + 8 * MB_TAG).x >> 4) + 1;
        bool ok;
#pragma unroll 1
        for (int it = 0;; it++) {
          ok = true;
#pragma unroll
          for (int k = 0; k < 4; k++) ok = ok && (uint32_t)(ga[k][0] >> 32) == tag && (uint32_t)(ga[k][1] >> 32) == tag;
          ok = __all_sync(0xffffffffu, ok);
          if (ok || it == 4000) break;
          gload();
        }
        float s0 = __uint_as_float((uint32_t)ga[0][0]) + __uint_as_float((uint32_t)ga[1][0]) + __uint_as_float((uint32_t)ga[2][0]);
        float s1 = __uint_as_float((uint32_t)ga[0][1]) + __uint_as_float((uint32_t)ga[1][1]) + __uint_as_float((uint32_t)ga[2][1]);
        if (t < 3) { s0 += __uint_as_float((uint32_t)ga[3][0]); s1 += __uint_as_float((uint32_t)ga[3][1]); }
        float s = ((t & 1) ? s1 : s0) + __shfl_xor_sync(0xffffffffu, (t & 1) ? s0 : s1, 1);
        s += __shfl_xor_sync(0xffffffffu, s, 2);
        const int sl = slot + (t & 1);
        if (!ok) {
          const uint32_t* xr = (const uint32_t*)(p.q + (size_t)(rank * 256 + 32 * (sl & 7) + (sl >> 3)) * DCH);
          const uint32_t* gr = (const uint32_t*)p.gate_w;
          s = 0.f;
#pragma unroll 1
          for (int k = 0; k < DCH / 2; k++) { const uint32_t m = hmul2(__ldg(xr + k), __ldg(gr + k)); s += blo(m) + bhi(m); }
        }
        const float g0 = bf16r(sigmoidf_(bf16r(s)));
        sts32(sb + OFF_GB + 8 * sl + (t & 2) * 2, (t & 2) ? pack(1.f - g0, 1.f - g0) : pack(g0, g0));
        __syncwarp();
        if (lane == 0) mbar_arrive(mb + 8 * MB_G);
      }
      wg_wait<0>(); tie_all(O);
      {
        const uint32_t co = ((8 * w + g) ^ (2 * t) ^ rank) * 16;
        const int yo = (isA ? OFF_YA : OFF_YB) + (8 * u + rank) * 512, ym = OFF_MB + 8 * (MB_Y + u);
        const uint32_t us = min(max((int)(eu + eh) - 127, 0), 254) * 0x00800080u;
        const uint32_t a0 = hmul2(pack(O[0], O[1]), us), a1 = hmul2(pack(O[4], O[5]), us), a2 = hmul2(pack(O[8], O[9]), us), a3 = hmul2(pack(O[12], O[13]), us);
        const uint32_t b0 = hmul2(pack(O[2], O[3]), us), b1 = hmul2(pack(O[6], O[7]), us), b2 = hmul2(pack(O[10], O[11]), us), b3 = hmul2(pack(O[14], O[15]), us);
        sts128((t == rank ? sb + yo : usrc + t * 512) + co, a0, a1, a2, a3);
        sts128((t + 4 == rank ? sb + yo : usrc + t * 512 + 2048) + co, b0, b1, b2, b3);
        fence_async();
        bar_sync(NB_WG0 + u, 128);
        send(usrc - sb, yo, ym);
      }
      TL(9 + isA);
    }
  }

  {
    mbar_wait(mb + 8 * MB_G);
    uint2 gg[2][4];
    uint32_t qv[2][4];
#pragma unroll
    for (int hh = 0; hh < 2; hh++)
#pragma unroll
      for (int i = 0; i < 4; i++) gg[hh][i] = lds64(sb + OFF_GB + 8 * (64 * w + 32 * hh + 8 * i + g));
    const uint32_t qa = sb + OFF_TQ + toff;
    ldsm4(qv[0], qa);
    ldsm4(qv[1], qa + 2560);
    TL(24);
    mbar_wait(mb + 8 * (MB_Y + u));
    uint32_t ya[2][4], yb[2][4];
#pragma unroll
    for (int hh = 0; hh < 2; hh++) {
      const uint32_t yo = (8 * u + (lane & 7)) * 512 + ((8 * w + 4 * hh + (lane >> 3)) ^ (2 * (rank & 3)) ^ (lane & 7)) * 16;
      ldsm4t(ya[hh], sb + OFF_YA + yo); ldsm4t(yb[hh], sb + OFF_YB + yo);
    }
#pragma unroll
    for (int hh = 0; hh < 2; hh++) {
      uint32_t o[4];
#pragma unroll
      for (int i = 0; i < 4; i++) o[i] = hadd2(hmul2(gg[hh][i].x, hmul2(qv[hh][i], ya[hh][i])), hmul2(gg[hh][i].y, yb[hh][i]));
      stsm4(qa + 2560 * hh, o);
    }
    TL(25);
  }
  cluster_arrive();
  bar_sync(NB_ROW0 + w, 160);
  {
    uint4 v[2];
#pragma unroll
    for (int k = 0; k < 2; k++) {
      const int i = 64 * u + 32 * k + lane, sl = (i * 205) >> 10, cc = i - 5 * sl;
      v[k] = lds128(sb + OFF_TQ + (64 * w + 8 * (sl & 7) + (sl >> 3)) * 80 + cc * 16);
    }
#pragma unroll
    for (int k = 0; k < 2; k++) {
      const int i = 64 * u + 32 * k + lane, sl = (i * 205) >> 10, cc = i - 5 * sl;
      if (cc < nu)
        asm volatile("st.global.v4.u32 [%0], {%1,%2,%3,%4};" :: "l"(p.out + (size_t)(256 * rank + 32 * (sl >> 3) + 8 * w + (sl & 7)) * DCH + ch0 + 8 * cc),
                     "r"(v[k].x), "r"(v[k].y), "r"(v[k].z), "r"(v[k].w) : "memory");
    }
  }
  cluster_wait();
  TL(27);
  TL_DUMP();
}

typedef CUresult (*EncodeFn)(CUtensorMap*, CUtensorMapDataType, cuuint32_t, void*, const cuuint64_t*, const cuuint64_t*,
                             const cuuint32_t*, const cuuint32_t*, CUtensorMapInterleave, CUtensorMapSwizzle,
                             CUtensorMapL2promotion, CUtensorMapFloatOOBfill);

void encode(EncodeFn fn, CUtensorMap* tm, const void* ptr, int nd, const cuuint64_t* dims, const cuuint64_t* strides,
            const cuuint32_t* box, CUtensorMapSwizzle swz) {
  cuuint32_t es[4] = {1, 1, 1, 1};
  fn(tm, CU_TENSOR_MAP_DATA_TYPE_BFLOAT16, nd, const_cast<void*>(ptr), dims, strides, box, es, CU_TENSOR_MAP_INTERLEAVE_NONE,
     swz, CU_TENSOR_MAP_L2_PROMOTION_L2_128B, CU_TENSOR_MAP_FLOAT_OOB_FILL_NONE);
}
void make_map(EncodeFn fn, CUtensorMap* tm, const void* ptr, int ne, int nr) {
  const cuuint64_t dims[3] = {DCH, SEQ / 32, 32}, strides[2] = {32 * DCH * 2, DCH * 2};
  const cuuint32_t box[3] = {CPC, (cuuint32_t)ne, (cuuint32_t)nr};
  encode(fn, tm, ptr, 3, dims, strides, box, CU_TENSOR_MAP_SWIZZLE_NONE);
}

}

extern "C" void kernel_launch(void* const* d_in, const int* in_sizes, int n_in, void* d_out, int out_size) {
  (void)in_sizes; (void)n_in; (void)out_size;
  static EncodeFn fn = nullptr;
  static void *tab = nullptr, *cnt = nullptr, *part = nullptr;
  if (!fn) {
    cudaGetSymbolAddress(&tab, d_tab);
    cudaGetSymbolAddress(&cnt, g_cnt);
    cudaGetSymbolAddress(&part, g_part);
    cudaDriverEntryPointQueryResult qr;
    cudaGetDriverEntryPoint("cuTensorMapEncodeTiled", (void**)&fn, cudaEnableDefault, &qr);
    cudaFuncSetAttribute(fused_kernel, cudaFuncAttributeMaxDynamicSharedMemorySize, SMEM_BYTES);
  }
  Params p;
  make_map(fn, &p.tq, d_in[0], 8, 32);
  make_map(fn, &p.tk, d_in[1], 8, 32);
  make_map(fn, &p.tv, d_in[2], 8, 32);
  make_map(fn, &p.tkh, d_in[1], 1, 4);
  p.out = (__nv_bfloat16*)d_out;
  p.tab = (const Tables*)tab;
  p.cnt = (unsigned*)cnt;
  p.part = (uint2*)part;
  p.tl = nullptr;
  p.q = (const __nv_bfloat16*)d_in[0];
  p.ssm_k = (const __nv_bfloat16*)d_in[4];
  p.shift_k = (const __nv_bfloat16*)d_in[3];
  p.ssm_D = (const __nv_bfloat16*)d_in[5];
  p.logA = (const __nv_bfloat16*)d_in[7];
  p.Aim = (const __nv_bfloat16*)d_in[8];
  p.Cre = (const __nv_bfloat16*)d_in[9];
  p.Cim = (const __nv_bfloat16*)d_in[10];
  p.logdt = (const __nv_bfloat16*)d_in[11];
  p.Dskip = (const __nv_bfloat16*)d_in[12];
  p.gate_w = (const __nv_bfloat16*)d_in[13];
  fused_kernel<<<NCL * CS, NTHREADS, SMEM_BYTES, cudaStreamPerThread>>>(p);
}
```

```cpp
#include <cuda_runtime.h>
#include <cuda_bf16.h>
#include <cuda_fp16.h>
#include <cuda.h>
#include <stdint.h>

#define TIMELINE 0
#define TLHI 0

namespace {

constexpr int SEQ = 2048, DCH = 576, NMODE = 128;
constexpr int CS = 8, CPC = 40, NCL = 15, NTHREADS = 640;

constexpr int KTAB = 16384;
constexpr int OFF_T = 0;
constexpr int T_UKV = 8192, T_HA = 12288;
constexpr int OFF_UX = 5 * KTAB;
constexpr int OFF_IM = OFF_UX + 20480;
constexpr int OFF_CF = OFF_IM;
constexpr int OFF_CL = OFF_CF + 8192;
constexpr int OFF_TV = OFF_CL + 4096;
constexpr int OFF_YA = OFF_TV + 20480;
constexpr int OFF_GB = OFF_YA + 20480;
constexpr int OFF_YB = OFF_IM + 4 * KTAB;
constexpr int OFF_TQ = OFF_YB + 20480;
constexpr int OFF_TK = OFF_TQ + 20480;
constexpr int OFF_HALO = OFF_TK + 20480;
constexpr int OFF_MX = OFF_HALO + 320;
constexpr int OFF_SP = OFF_MX + 320;
constexpr int OFF_MB = OFF_SP + 560;
constexpr int OFF_TL = OFF_MB + 28 * 8;
constexpr int SMEM_BYTES = OFF_TL + (TIMELINE ? 1280 : 0);
static_assert(SMEM_BYTES <= 232448 && OFF_YA == OFF_IM + 2 * KTAB && OFF_GB + 2048 <= OFF_YB, "smem");
static_assert((OFF_MB & 7) == 0 && (OFF_MX & 15) == 0 && (OFF_SP & 15) == 0, "align");

enum { MB_UX = 0, MB_UKV = 5, MB_Y = 10, MB_HA = 15, MB_XQ = 20, MB_KV = 21, MB_CF = 22, MB_G = 23, MB_TH = 24, MB_TAG = 25 };
enum { NB_WG0 = 1, NB_ROW0 = 6, NB_ORD = 6, NB_V = 10 };

constexpr double cos_turn(int m, int n) {
  m &= n - 1;
  if (m > n / 2) m = n - m;
  double sgn = 1.0;
  if (m > n / 4) { m = n / 2 - m; sgn = -1.0; }
  if (m == n / 4) return 0.0;
  const double x = 6.283185307179586476925 * m / n;
  double term = 1.0, sum = 1.0;
  for (int k = 1; k < 14; k++) { term *= -x * x / ((2 * k - 1) * (2 * k)); sum += term; }
  return sgn * sum;
}
constexpr uint32_t bf16_bits(double v) {
  if (v == 0.0) return 0;
  uint32_t sgn = 0;
  if (v < 0) { sgn = 0x8000; v = -v; }
  int e = 127;
  while (v < 1.0) { v *= 2.0; e--; }
  while (v >= 2.0) { v *= 0.5; e++; }
  const double f = v * 128.0;
  int m = (int)f;
  if (f - m > 0.5 || (f - m == 0.5 && (m & 1))) m++;
  return sgn | (uint32_t)((e << 7) + (m - 128));
}
constexpr uint32_t f16_bits(double v) {
  if (v == 0.0) return 0;
  uint32_t sgn = 0;
  if (v < 0) { sgn = 0x8000; v = -v; }
  int e = 15;
  while (v < 1.0) { v *= 2.0; e--; }
  const double f = v * 1024.0;
  int m = (int)f;
  if (f - m > 0.5 || (f - m == 0.5 && (m & 1))) m++;
  return sgn | (uint32_t)((e << 10) + (m - 1024));
}
constexpr uint32_t pair_bits(double lo, double hi) { return bf16_bits(lo) | (bf16_bits(hi) << 16); }
constexpr uint32_t pair_h(double lo, double hi) { return f16_bits(lo) | (f16_bits(hi) << 16); }
struct alignas(128) Tables {
  uint32_t mat[3072];
  uint32_t thr[4][128][4];
};
constexpr Tables make_tables() {
  Tables T{};
  for (int q = 0; q < 768; q++) {
    int m0 = 0, d0 = 0, d1 = 0;
    if (q < 512) {
      const int r = (q >> 6) * 8 + (q & 7), cc = (q >> 3) & 7;
      d0 = 4 * (r & 31); d1 = 2 * d0;
      m0 = 8 * (cc & 3) * d0 + ((r >> 5) == (cc >> 2) ? 0 : (r >> 5) ? 96 : 32);
    } else {
      const int r = ((q - 512) >> 5) * 8 + (q & 7), pc = (q >> 3) & 3;
      d0 = 4 * (8 * (r >> 4) + (r & 7)) + 1; d1 = 8 * d0;
      m0 = 2 * pc * d0 + ((r & 8) ? 32 : 0);
    }
    for (int e = 0; e < 4; e++) T.mat[4 * q + e] = pair_h(cos_turn(m0 + e * d1, 128), cos_turn(m0 + e * d1 + d0, 128));
  }
  for (int tid = 0; tid < 128; tid++) {
    const int kk = 4 * (tid >> 2) + 1, t = tid & 3;
    for (int q = 0; q < 4; q++) {
      const int m = (8 * q + 2 * t) * kk;
      T.thr[q >> 1][tid][2 * (q & 1)] = pair_bits(cos_turn(m, 128), cos_turn(m + kk, 128));
      T.thr[q >> 1][tid][2 * (q & 1) + 1] = pair_bits(cos_turn(m + 32, 128), cos_turn(m + kk + 32, 128));
      T.thr[2][tid][q] = pair_h(cos_turn(m, 4096), cos_turn(m + kk, 4096));
      T.thr[3][tid][q] = pair_h(cos_turn(m + 3072, 4096), cos_turn(m + kk + 3072, 4096));
    }
  }
  return T;
}
__device__ const Tables d_tab = make_tables();

struct Params {
  const __nv_bfloat16 *logA, *Aim, *Cre, *Cim, *logdt;
  const Tables* tab;
  unsigned* cnt;
  const __nv_bfloat16 *Dskip, *shift_k, *ssm_D, *gate_w, *q, *ssm_k;
  uint2* part;
  __nv_bfloat16* out;
  unsigned* tl;
  CUtensorMap tq, tk, tv, tkh;
};

__device__ uint2 g_part[NCL * SEQ];
__device__ unsigned g_cnt[CS * 32];
#define TL(i) do {} while (0)
#define TL_INIT() do {} while (0)
#define TL_DUMP() do {} while (0)

__device__ __forceinline__ uint32_t lds16(uint32_t a) { uint32_t v; asm volatile("ld.shared.u16 %0, [%1];" : "=r"(v) : "r"(a) : "memory"); return v; }
__device__ __forceinline__ uint2 lds64(uint32_t a) { uint2 v; asm volatile("ld.shared.v2.u32 {%0,%1}, [%2];" : "=r"(v.x), "=r"(v.y) : "r"(a) : "memory"); return v; }
__device__ __forceinline__ uint4 lds128(uint32_t a) { uint4 v; asm volatile("ld.shared.v4.u32 {%0,%1,%2,%3}, [%4];" : "=r"(v.x), "=r"(v.y), "=r"(v.z), "=r"(v.w) : "r"(a) : "memory"); return v; }
__device__ __forceinline__ void sts16(uint32_t a, uint32_t v) { asm volatile("st.shared.u16 [%0], %1;" :: "r"(a), "r"(v) : "memory"); }
__device__ __forceinline__ void sts32(uint32_t a, uint32_t v) { asm volatile("st.shared.u32 [%0], %1;" :: "r"(a), "r"(v) : "memory"); }
__device__ __forceinline__ void sts64(uint32_t a, uint32_t x, uint32_t y) { asm volatile("st.shared.v2.u32 [%0], {%1,%2};" :: "r"(a), "r"(x), "r"(y) : "memory"); }
__device__ __forceinline__ void sts128(uint32_t a, uint32_t x, uint32_t y, uint32_t z, uint32_t w) { asm volatile("st.shared.v4.u32 [%0], {%1,%2,%3,%4};" :: "r"(a), "r"(x), "r"(y), "r"(z), "r"(w) : "memory"); }
__device__ __forceinline__ void ldsm4t(uint32_t (&r)[4], uint32_t a) { asm volatile("ldmatrix.sync.aligned.m8n8.x4.trans.shared.b16 {%0,%1,%2,%3}, [%4];" : "=r"(r[0]), "=r"(r[1]), "=r"(r[2]), "=r"(r[3]) : "r"(a) : "memory"); }
__device__ __forceinline__ void ldsm2t(uint32_t& r0, uint32_t& r1, uint32_t a) { asm volatile("ldmatrix.sync.aligned.m8n8.x2.trans.shared.b16 {%0,%1}, [%2];" : "=r"(r0), "=r"(r1) : "r"(a) : "memory"); }
__device__ __forceinline__ void ldsm4(uint32_t (&r)[4], uint32_t a) { asm volatile("ldmatrix.sync.aligned.m8n8.x4.shared.b16 {%0,%1,%2,%3}, [%4];" : "=r"(r[0]), "=r"(r[1]), "=r"(r[2]), "=r"(r[3]) : "r"(a) : "memory"); }
__device__ __forceinline__ void stsm4(uint32_t a, const uint32_t (&r)[4]) { asm volatile("stmatrix.sync.aligned.m8n8.x4.shared.b16 [%0], {%1,%2,%3,%4};" :: "r"(a), "r"(r[0]), "r"(r[1]), "r"(r[2]), "r"(r[3]) : "memory"); }
__device__ __forceinline__ uint32_t pack(float lo, float hi) { uint32_t r; asm("cvt.rn.bf16x2.f32 %0, %1, %2;" : "=r"(r) : "f"(hi), "f"(lo)); return r; }
__device__ __forceinline__ float blo(uint32_t v) { return __uint_as_float(v << 16); }
__device__ __forceinline__ float bhi(uint32_t v) { return __uint_as_float(v & 0xffff0000u); }
__device__ __forceinline__ float bf16r(float x) { return blo(pack(x, 0.f)); }
__device__ __forceinline__ uint32_t hmul2(uint32_t a, uint32_t b) { uint32_t r; asm("mul.rn.bf16x2 %0, %1, %2;" : "=r"(r) : "r"(a), "r"(b)); return r; }
__device__ __forceinline__ uint32_t hadd2(uint32_t a, uint32_t b) { uint32_t r; asm("add.rn.bf16x2 %0, %1, %2;" : "=r"(r) : "r"(a), "r"(b)); return r; }
__device__ __forceinline__ uint32_t hfma2(uint32_t a, uint32_t b, uint32_t c) { uint32_t r; asm("fma.rn.bf16x2 %0, %1, %2, %3;" : "=r"(r) : "r"(a), "r"(b), "r"(c)); return r; }
__device__ __forceinline__ uint32_t packh(float lo, float hi) { uint32_t r; asm("cvt.rn.f16x2.f32 %0, %1, %2;" : "=r"(r) : "f"(hi), "f"(lo)); return r; }
__device__ __forceinline__ __half2 H2(uint32_t a) { return *reinterpret_cast<__half2*>(&a); }
__device__ __forceinline__ uint32_t U2(__half2 a) { return *reinterpret_cast<uint32_t*>(&a); }
__device__ __forceinline__ uint32_t fmul(uint32_t a, uint32_t b) { return U2(__hmul2(H2(a), H2(b))); }
__device__ __forceinline__ uint32_t ffma(uint32_t a, uint32_t b, uint32_t c) { return U2(__hfma2(H2(a), H2(b), H2(c))); }
__device__ __forceinline__ uint32_t fneg(uint32_t a) { return U2(__hneg2(H2(a))); }
__device__ __forceinline__ uint32_t amax2(uint32_t a, uint32_t b) { uint32_t r; asm("max.xorsign.abs.bf16x2 %0, %1, %2;" : "=r"(r) : "r"(a), "r"(b)); return r; }
__device__ __forceinline__ uint32_t prmt(uint32_t a, uint32_t b, uint32_t s) { return __byte_perm(a, b, s); }
__device__ __forceinline__ uint32_t ldraw(const __nv_bfloat16* p) { uint32_t v; asm volatile("ld.global.nc.u16 %0, [%1];" : "=r"(v) : "l"(p)); return v; }
__device__ __forceinline__ uint4 ldg128(const void* p) { uint4 v; asm volatile("ld.global.nc.v4.u32 {%0,%1,%2,%3}, [%4];" : "=r"(v.x), "=r"(v.y), "=r"(v.z), "=r"(v.w) : "l"(p)); return v; }
__device__ __forceinline__ void bar_sync(int id, int n) { asm volatile("bar.sync %0, %1;" :: "r"(id), "r"(n) : "memory"); }
__device__ __forceinline__ void bar_arrive(int id, int n) { asm volatile("bar.arrive %0, %1;" :: "r"(id), "r"(n) : "memory"); }
__device__ __forceinline__ void cluster_arrive() { asm volatile("barrier.cluster.arrive.relaxed.aligned;" ::: "memory"); }
__device__ __forceinline__ void cluster_wait() { asm volatile("barrier.cluster.wait.aligned;" ::: "memory"); }
__device__ __forceinline__ void fence_async() { asm volatile("fence.proxy.async.shared::cta;" ::: "memory"); }
__device__ __forceinline__ void fence_mbinit() { asm volatile("fence.mbarrier_init.release.cluster;" ::: "memory"); }
__device__ __forceinline__ uint32_t mapa(uint32_t a, uint32_t rank) { uint32_t r; asm("mapa.shared::cluster.u32 %0, %1, %2;" : "=r"(r) : "r"(a), "r"(rank)); return r; }
__device__ __forceinline__ void bulk_dsmem(uint32_t dst, uint32_t src, uint32_t mbar) {
  asm volatile("cp.async.bulk.shared::cluster.shared::cta.mbarrier::complete_tx::bytes [%0], [%1], 512, [%2];" :: "r"(dst), "r"(src), "r"(mbar) : "memory");
}
__device__ __forceinline__ void bulk_load(uint32_t dst, const void* src, uint32_t bytes, uint32_t mbar) {
  asm volatile("cp.async.bulk.shared::cluster.global.mbarrier::complete_tx::bytes [%0], [%1], %2, [%3];" :: "r"(dst), "l"(src), "r"(bytes), "r"(mbar) : "memory");
}
__device__ __forceinline__ void mbar_init(uint32_t m, uint32_t cnt) { asm volatile("mbarrier.init.shared::cta.b64 [%0], %1;" :: "r"(m), "r"(cnt) : "memory"); }
__device__ __forceinline__ void mbar_expect(uint32_t m, uint32_t bytes) { asm volatile("mbarrier.arrive.expect_tx.shared::cta.b64 _, [%0], %1;" :: "r"(m), "r"(bytes) : "memory"); }
__device__ __forceinline__ bool mbar_try(uint32_t m) {
  uint32_t done;
  asm volatile("{.reg .pred p; mbarrier.try_wait.parity.shared::cta.b64 p, [%1], 0; selp.u32 %0, 1, 0, p;}" : "=r"(done) : "r"(m) : "memory");
  return done;
}
__device__ __forceinline__ void mbar_wait(uint32_t m) {
  if (!mbar_try(m)) {
    int it = 0;
    while (!mbar_try(m) && ++it < (1 << 22)) {}
  }
}
__device__ __forceinline__ bool elect() {
  uint32_t e;
  asm volatile("{.reg .pred p; elect.sync _|p, 0xffffffff; selp.u32 %0, 1, 0, p;}" : "=r"(e));
  return e;
}
__device__ __forceinline__ void tma_load4(uint32_t dst, const CUtensorMap* tm, int c0, int c1, int c2, int c3, uint32_t mbar) {
  asm volatile("cp.async.bulk.tensor.4d.shared::cluster.global.mbarrier::complete_tx::bytes [%0], [%1, {%3, %4, %5, %6}], [%2];"
               :: "r"(dst), "l"(tm), "r"(mbar), "r"(c0), "r"(c1), "r"(c2), "r"(c3) : "memory");
}
__device__ __forceinline__ void tma_load3(uint32_t dst, const CUtensorMap* tm, int c0, int c1, int c2, uint32_t mbar) {
  asm volatile("cp.async.bulk.tensor.3d.shared::cluster.global.mbarrier::complete_tx::bytes [%0], [%1, {%3, %4, %5}], [%2];"
               :: "r"(dst), "l"(tm), "r"(mbar), "r"(c0), "r"(c1), "r"(c2) : "memory");
}
__device__ __forceinline__ void tma_store3(const CUtensorMap* tm, int c0, int c1, int c2, uint32_t src) {
  asm volatile("cp.async.bulk.tensor.3d.global.shared::cta.bulk_group [%0, {%2, %3, %4}], [%1];"
               :: "l"(tm), "r"(src), "r"(c0), "r"(c1), "r"(c2) : "memory");
}
__device__ __forceinline__ void mma1688(float (&c)[4], uint32_t a0, uint32_t a1, uint32_t b) {
  asm volatile("mma.sync.aligned.m16n8k8.row.col.f32.bf16.bf16.f32 {%0,%1,%2,%3}, {%4,%5}, {%6}, {%0,%1,%2,%3};"
               : "+f"(c[0]), "+f"(c[1]), "+f"(c[2]), "+f"(c[3]) : "r"(a0), "r"(a1), "r"(b));
}
__device__ __forceinline__ void wg_fence() { asm volatile("wgmma.fence.sync.aligned;" ::: "memory"); }
__device__ __forceinline__ void wg_commit() { asm volatile("wgmma.commit_group.sync.aligned;" ::: "memory"); }
template <int N> __device__ __forceinline__ void wg_wait() { asm volatile("wgmma.wait_group.sync.aligned %0;" :: "n"(N) : "memory"); }
template <int N> __device__ __forceinline__ void tie_all(uint32_t (&x)[N]) {
#pragma unroll
  for (int i = 0; i < N; i++) asm volatile("" : "+r"(x[i]) :: "memory");
}
template <int N> __device__ __forceinline__ void tie_all(float (&x)[N]) {
#pragma unroll
  for (int i = 0; i < N; i++) asm volatile("" : "+f"(x[i]) :: "memory");
}
#define R16(C, d) C(d[0]), C(d[1]), C(d[2]), C(d[3]), C(d[4]), C(d[5]), C(d[6]), C(d[7]), C(d[8]), C(d[9]), C(d[10]), C(d[11]), C(d[12]), C(d[13]), C(d[14]), C(d[15])
#define R32(C, d) R16(C, d), R16(C, (d + 16))
#define P16 "{%0,%1,%2,%3,%4,%5,%6,%7,%8,%9,%10,%11,%12,%13,%14,%15}"
#define P32 "{%0,%1,%2,%3,%4,%5,%6,%7,%8,%9,%10,%11,%12,%13,%14,%15,%16,%17,%18,%19,%20,%21,%22,%23,%24,%25,%26,%27,%28,%29,%30,%31}"
template <int SD, int TB, int OFF> __device__ __forceinline__ void rs64(float* d, const uint32_t* a, uint64_t db) {
  if (SD) asm volatile("{.reg .b64 db; add.s64 db, %36, %37; wgmma.mma_async.sync.aligned.m64n64k16.f32.bf16.bf16 " P32 ", {%32,%33,%34,%35}, db, 1, 1, 1, %38;}"
                       : R32("+f", d) : "r"(a[0]), "r"(a[1]), "r"(a[2]), "r"(a[3]), "l"(db), "n"(OFF), "n"(TB));
  else asm volatile("{.reg .b64 db; add.s64 db, %36, %37; wgmma.mma_async.sync.aligned.m64n64k16.f32.bf16.bf16 " P32 ", {%32,%33,%34,%35}, db, 0, 1, 1, %38;}"
                    : R32("=f", d) : "r"(a[0]), "r"(a[1]), "r"(a[2]), "r"(a[3]), "l"(db), "n"(OFF), "n"(TB));
}
template <int SD, int TB, int OFF> __device__ __forceinline__ void rs64h(uint32_t* d, const uint32_t* a, uint64_t db) {
  if (SD) asm volatile("{.reg .b64 db; add.s64 db, %20, %21; wgmma.mma_async.sync.aligned.m64n64k16.f16.f16.f16 " P16 ", {%16,%17,%18,%19}, db, 1, 1, 1, %22;}"
                       : R16("+r", d) : "r"(a[0]), "r"(a[1]), "r"(a[2]), "r"(a[3]), "l"(db), "n"(OFF), "n"(TB));
  else asm volatile("{.reg .b64 db; add.s64 db, %20, %21; wgmma.mma_async.sync.aligned.m64n64k16.f16.f16.f16 " P16 ", {%16,%17,%18,%19}, db, 0, 1, 1, %22;}"
                    : R16("=r", d) : "r"(a[0]), "r"(a[1]), "r"(a[2]), "r"(a[3]), "l"(db), "n"(OFF), "n"(TB));
}
template <int SD, int OFFA, int OFFB> __device__ __forceinline__ void ss32(float* d, uint64_t da, uint64_t db) {
  if (SD) asm volatile("{.reg .b64 da, db; add.s64 da, %16, %18; add.s64 db, %17, %19; wgmma.mma_async.sync.aligned.m64n32k16.f32.f16.f16 " P16 ", da, db, 1, 1, 1, 1, 1;}"
                       : R16("+f", d) : "l"(da), "l"(db), "n"(OFFA), "n"(OFFB));
  else asm volatile("{.reg .b64 da, db; add.s64 da, %16, %18; add.s64 db, %17, %19; wgmma.mma_async.sync.aligned.m64n32k16.f32.f16.f16 " P16 ", da, db, 0, 1, 1, 1, 1;}"
                    : R16("=f", d) : "l"(da), "l"(db), "n"(OFFA), "n"(OFFB));
}
#define KGEN_ASM(SD) "{.reg .b64 da, db; add.s64 da, %32, %33; add.s64 db, %32, %34;\n" \
  "wgmma.mma_async.sync.aligned.m64n64k16.f32.bf16.bf16 " P32 ", da, db, " SD ", 1, 1, 1, 1;}"
template <int KS> __device__ __forceinline__ void kgen_mma(float (&c)[32], uint64_t da) {
  if (KS) asm volatile(KGEN_ASM("1") : R32("+f", c) : "l"(da), "n"(8 * KS), "n"(8 * KS + 512));
  else asm volatile(KGEN_ASM("0") : R32("=f", c) : "l"(da), "n"(8 * KS), "n"(8 * KS + 512));
  if constexpr (KS < 7) kgen_mma<KS + 1>(c, da);
}
__device__ __forceinline__ uint64_t desc_lo(uint32_t a) { return (uint64_t)((a & 0x3FFFF) >> 4); }
__device__ __forceinline__ void stage1(float (&D)[32], const uint32_t (&A1)[8], uint32_t src) {
  const uint64_t du = desc_lo(src) | (128ull << 16) | (32ull << 32) | (2ull << 62);
  rs64<0, 1, 0>(D, A1, du); rs64<1, 1, 64>(D, A1 + 4, du);
}
template <int INV> __device__ __forceinline__ void stage2(uint32_t (&X)[16], const uint32_t (&F)[16], uint32_t cf) {
  constexpr int KS = INV ? 16 : 128, TB = INV ? 0 : 1;
  const uint64_t dc = desc_lo(cf) | (INV ? (8ull << 16) | (64ull << 32) : (64ull << 16) | (8ull << 32));
  rs64h<0, TB, 0>(X, F, dc); rs64h<1, TB, KS>(X, F + 4, dc); rs64h<1, TB, 2 * KS>(X, F + 8, dc); rs64h<1, TB, 3 * KS>(X, F + 12, dc);
}
__device__ __forceinline__ void fwd_mid(uint32_t (&F)[16], const float (&D)[32], const uint32_t (&tc)[4], const uint32_t (&ts)[4]) {
#pragma unroll
  for (int j = 0; j < 4; j++)
#pragma unroll
    for (int b = 0; b < 2; b++) {
      const int i = 4 * j + 16 * b;
      const uint32_t ar = packh(D[i], D[i + 1]), ai = packh(D[i + 2], D[i + 3]);
      F[2 * j + b] = ffma(ar, tc[j], fmul(ai, ts[j]));
      F[8 + 2 * j + b] = ffma(ai, tc[j], fneg(fmul(ar, ts[j])));
    }
}
__device__ __forceinline__ void put_exp(uint32_t a, uint32_t m, int lane) {
  m = __reduce_max_sync(0xffffffffu, max(m & 0x7f80u, (m >> 16) & 0x7f80u));
  if (lane == 0) sts32(a, m);
}
__device__ __forceinline__ uint32_t seq_mag(uint32_t a) {
  const uint4 x = lds128(a), y = lds128(a + 2048);
  return amax2(amax2(amax2(x.x, x.y), amax2(x.z, x.w)), amax2(amax2(y.x, y.y), amax2(y.z, y.w)));
}
__device__ __forceinline__ uint32_t get_exp(uint32_t a) { const uint4 v = lds128(a); return max(max(v.x, v.y), max(v.z, v.w)) >> 7; }
__device__ __forceinline__ void scale_a1(uint32_t (&As)[8], const uint32_t (&A1)[8], uint32_t field) {
#pragma unroll
  for (int i = 0; i < 8; i++) As[i] = hmul2(A1[i], field * 0x00800080u);
}

struct cf { float x, y; };
__device__ __forceinline__ cf cmul(cf a, cf b) { cf r; r.x = fmaf(a.x, b.x, -a.y * b.y); r.y = fmaf(a.x, b.y, a.y * b.x); return r; }
__device__ __forceinline__ cf cexp_p(float lr2, float lt, float p) {
  float m;
  asm("ex2.approx.ftz.f32 %0, %1;" : "=f"(m) : "f"(lr2 * p));
  float t = lt * p;
  t = (t - rintf(t)) * 6.283185307179586f;
  cf r; r.x = m * __cosf(t); r.y = m * __sinf(t); return r;
}
__device__ __forceinline__ void store8(uint32_t a, uint32_t b, const cf (&v)[8]) {
  sts128(a, pack(v[0].x, v[1].x), pack(v[2].x, v[3].x), pack(v[4].x, v[5].x), pack(v[6].x, v[7].x));
  sts128(b, pack(v[0].y, v[1].y), pack(v[2].y, v[3].y), pack(v[4].y, v[5].y), pack(v[6].y, v[7].y));
}
__device__ __forceinline__ void mbar_arrive(uint32_t m) { asm volatile("mbarrier.arrive.shared::cta.b64 _, [%0];" :: "r"(m) : "memory"); }
__device__ __forceinline__ float sigmoidf_(float s) { return __fdividef(1.f, 1.f + __expf(fminf(-s, 80.f))); }

__global__ void __cluster_dims__(CS, 1, 1) __launch_bounds__(NTHREADS, 1) fused_kernel(const __grid_constant__ Params p) {
  extern __shared__ __align__(1024) uint8_t smem[];
  TL_INIT();
  TL(31);
  const int wid = __shfl_sync(0xffffffffu, threadIdx.x >> 5, 0);
  const uint32_t sb = (uint32_t)__cvta_generic_to_shared(smem);
  const uint32_t mb = sb + OFF_MB;
  const int u = wid >> 2, w = wid & 3;
  const int tid = threadIdx.x & 127, lane = tid & 31, g = lane >> 2, t = lane & 3;
  const int cl = blockIdx.x >> 3, rank = blockIdx.x & 7;
  const int ch0 = cl * CPC;
  const int nu = min(5, (DCH - ch0) >> 3);
  const bool act = u < nu;

  uint32_t pla, pai, pcr, pci, pdt, tag = 0;
  auto load_params = [&]() {
    const int ch = act ? ch0 + 8 * u + rank : 0, o = ch * NMODE + tid;
    pla = ldraw(p.logA + o); pdt = ldraw(p.logdt + ch); pai = ldraw(p.Aim + o); pcr = ldraw(p.Cre + o); pci = ldraw(p.Cim + o);
  };
  if (u == 4) {
    const bool e = elect();
    if (e) {
#pragma unroll
      for (int i = 0; i < 5; i++) mbar_init(mb + 40 * w + 8 * i, 1);
      if (w == 3) { mbar_init(mb + 8 * MB_TH, 1); mbar_init(mb + 8 * MB_XQ, 21); mbar_init(mb + 8 * MB_KV, 1); }
      if (w == 2) { mbar_init(mb + 8 * MB_CF, 1); mbar_init(mb + 8 * MB_G, 16); }
      fence_mbinit();
    }
    __syncwarp();
    load_params();
    if (w == 0 && lane < 2) asm volatile("atom.relaxed.gpu.global.add.u32 %0, [%1], %2;" : "=r"(tag) : "l"(&p.cnt[rank * 32 + lane]), "r"(cl == 0 ? 16 - (NCL - 1) : 1) : "memory");
    if (e) {
      if (w == 3) {
        mbar_expect(mb + 8 * MB_TH, 8192 + 112 * nu);
        bulk_load(sb + OFF_YB, p.tab->thr, 8192, mb + 8 * MB_TH);
        bulk_load(sb + OFF_SP, p.gate_w + ch0, 16 * nu, mb + 8 * MB_TH);
        bulk_load(sb + OFF_SP + 80, p.Dskip + ch0, 16 * nu, mb + 8 * MB_TH);
        bulk_load(sb + OFF_SP + 160, p.ssm_D + ch0, 16 * nu, mb + 8 * MB_TH);
        bulk_load(sb + OFF_SP + 240, p.shift_k + 4 * ch0, 64 * nu, mb + 8 * MB_TH);
        asm volatile("cp.async.bulk.prefetch.L2.global [%0], 12288;" :: "l"(p.tab->mat) : "memory");
        mbar_expect(mb + 8 * MB_XQ, 20480);
        tma_load3(sb + OFF_TQ, &p.tq, ch0, 8 * rank, 0, mb + 8 * MB_XQ);
        TL(20);
        mbar_expect(mb + 8 * MB_KV, 2 * 20480 + 320);
        tma_load3(sb + OFF_TK, &p.tk, ch0, 8 * rank, 0, mb + 8 * MB_KV);
        tma_load3(sb + OFF_HALO, &p.tkh, ch0, 8 * rank - 1, 28, mb + 8 * MB_KV);
      }
      if (w == 2) mbar_expect(mb + 8 * MB_CF, 12288);
#pragma unroll
      for (int i = 0; i < 5; i++) mbar_expect(mb + 40 * w + 8 * i, w == 3 ? 4096 : w == 2 ? 7168 : 3584);
    }
    __syncwarp();
  } else {
    load_params();
  }
  cluster_arrive();
  TL(0);

  const uint32_t tab = sb + OFF_T + u * KTAB;
  const uint32_t toff = (64 * w + lane) * 80 + 16 * u;
  auto put = [&](uint32_t dst, const uint32_t (&a)[4], const uint32_t (&b)[4]) {
    const uint32_t s0 = (g & 1) ? 0x7632 : 0x5410, s1 = s0 ^ 0x2222;
    const uint32_t o = dst + 128 * t + 64 * (g & 1) + 16 * (w ^ t);
    sts128(o, prmt(a[0], a[1], s0), prmt(a[2], a[3], s0), prmt(b[0], b[1], s0), prmt(b[2], b[3], s0));
    sts128(o ^ 64, prmt(a[0], a[1], s1), prmt(a[2], a[3], s1), prmt(b[0], b[1], s1), prmt(b[2], b[3], s1));
  };
  const int d0 = rank ^ (2 * w), d1 = d0 ^ 1;
  const uint32_t rb0 = mapa(sb, d0), rb1 = mapa(sb, d1);
  auto send = [&](int stage, int dst, int mbar) {
    if (elect()) {
      if (w) bulk_dsmem(rb0 + dst, sb + stage + d0 * 512, rb0 + mbar);
      bulk_dsmem(rb1 + dst, sb + stage + d1 * 512, rb1 + mbar);
    }
    __syncwarp();
  };

  uint32_t A1[8], tc[4], ts[4];
  {
    const float dt = bf16r(expf(blo(pdt)));
    const float lr2 = (-bf16r(expf(blo(pla))) * dt) * 1.4426950408889634f;
    const float lt = (blo(pai) * dt) * 0.15915494309189535f;
    const uint32_t tim = sb + (u ? OFF_IM + (u - 1) * KTAB : OFF_UX);
    const uint32_t row = tab + tid * 16, rim = tim + tid * 16;
    const cf w1 = cexp_p(lr2, lt, 8.f);
    cf z1 = cexp_p(lr2, lt, 1.f), Z = cexp_p(lr2, lt, 256.f);
    if (lr2 != 123.f) TL(16);
    TL(12);
    {
      cf v[8];
      v[0].x = 1.f; v[0].y = 0.f; v[1] = w1; v[2] = cmul(w1, w1); v[3] = cmul(v[2], w1);
      const cf w4 = cmul(v[2], v[2]);
      v[4] = w4; v[5] = cmul(v[1], w4); v[6] = cmul(v[2], w4); v[7] = cmul(v[3], w4);
      const cf w8 = cmul(w4, w4);
      store8(row, rim, v);
#pragma unroll
      for (int k = 1; k < 4; k++) {
#pragma unroll
        for (int i = 0; i < 8; i++) v[i] = (k == 1 && i == 0) ? w8 : cmul(v[i], w8);
        store8(row + 2048 * k, rim + 2048 * k, v);
      }
    }
    cluster_wait();
    if (u) cluster_arrive();
    mbar_wait(mb + 8 * MB_TH);
    {
      const uint4 x = lds128(sb + OFF_YB + 16 * tid), y = lds128(sb + OFF_YB + 2048 + 16 * tid), a = lds128(sb + OFF_YB + 4096 + 16 * tid), b = lds128(sb + OFF_YB + 6144 + 16 * tid);
      A1[0] = x.x; A1[1] = x.y; A1[2] = x.z; A1[3] = x.w; A1[4] = y.x; A1[5] = y.y; A1[6] = y.z; A1[7] = y.w;
      tc[0] = a.x; tc[1] = a.y; tc[2] = a.z; tc[3] = a.w; ts[0] = b.x; ts[1] = b.y; ts[2] = b.z; ts[3] = b.w;
    }
    if (wid == 16 && lane == 0) sts32(mb + 8 * MB_TAG, tag);
    __syncwarp();
    if (lane == 0) mbar_arrive(mb + 8 * MB_XQ);
    if (u == 1) {
      float z0_ = 0.f, z1_ = 0.f, z2_ = 0.f, z3_ = 0.f;
      asm volatile("mma.sync.aligned.m16n8k8.row.col.f32.bf16.bf16.f32 {%0,%1,%2,%3}, {%4,%4}, {%4}, {%0,%1,%2,%3};"
                   : "+f"(z0_), "+f"(z1_), "+f"(z2_), "+f"(z3_) : "r"(pla >> 16));
      pcr += __float_as_uint(z0_);
      TL(8);
    }
    {
      z1.y = -z1.y; Z.y = -Z.y;
      const cf z2 = cmul(z1, z1);
      cf h[8], v[8];
      h[0].x = 2.f * blo(pcr) * dt; h[0].y = -2.f * blo(pci) * dt;
      h[1] = cmul(h[0], z1);
#pragma unroll
      for (int i = 2; i < 8; i++) h[i] = cmul(h[i - 2], z2);
      store8(row + 4 * 2048, rim + 4 * 2048, h);
      const cf h8 = cmul(h[6], z2);
      v[0] = cmul(h[0], Z); v[2] = cmul(h[2], Z); v[3] = cmul(h[4], Z); v[6] = cmul(h[6], Z); v[7] = cmul(h8, Z);
      v[1] = v[0]; v[4] = v[5] = v[3];
      store8(row + 5 * 2048, rim + 5 * 2048, v);
      h[0] = cmul(v[0], Z); h[1] = cmul(v[3], Z); h[3] = cmul(v[7], Z); h[4] = cmul(h[0], Z); h[5] = cmul(h[1], Z); h[7] = cmul(h[3], Z);
      h[2] = h[1]; h[6] = h[5];
      store8(row + 6 * 2048, rim + 6 * 2048, h);
      const cf Z2 = cmul(Z, Z);
      v[0] = cmul(h[0], Z2); v[1] = cmul(h[3], Z2); v[2] = cmul(h[4], Z2); v[3] = cmul(h[7], Z2);
#pragma unroll
      for (int i = 4; i < 8; i++) v[i] = cmul(v[i - 4], Z2);
      store8(row + 7 * 2048, rim + 7 * 2048, v);
    }
    TL(17);
    fence_async();
    if (u) bar_sync(NB_ORD + u - 1, 256); else bar_sync(NB_WG0, 128);
    TL(13);
    float c[32];
    wg_fence();
    kgen_mma<0>(c, desc_lo(tab) | ((uint64_t)((tim - tab) >> 4) << 16) | (64ull << 32));
    wg_commit();
    if (u < 4) bar_arrive(NB_ORD + u, 256);
    TL(14);
    mbar_wait(mb + 8 * MB_XQ);
    TL(18);
    uint32_t x0[4], x1[4];
    ldsm4t(x0, sb + OFF_TQ + toff);
    ldsm4t(x1, sb + OFF_TQ + toff + 2560);
    wg_wait<0>(); tie_all(c);
    TL(26);
    if (u == 0) cluster_arrive();
    if (u == 1 || u == 2) bar_arrive(NB_V, 288);
    bar_sync(NB_WG0 + u, 128);
    if (wid == 4 && elect()) bulk_load(sb + OFF_CF, p.tab->mat, 12288, mb + 8 * MB_CF);
    __syncwarp();
    const uint32_t k0 = pack(c[0] + c[6], c[1] + c[7]), k1 = pack(c[8] + c[14], c[9] + c[15]);
    const uint32_t k2 = pack(c[16] + c[22], c[17] + c[23]), k3 = pack(c[24] + c[30], c[25] + c[31]);
    const uint32_t ka = tab + 16 * (8 * w + (g ^ w));
    sts32(ka + 4 * t, k0);
    sts32(ka + 512 + 4 * t, k1);
    sts64(ka + 1024 + 512 * (t >> 1) + 8 * (t & 1), prmt(k2, 0, 0x1010), (t & 1) ? prmt(k2, 0, 0x3232) : k2);
    const uint32_t lo = prmt(k3, 0, 0x1010), hi = prmt(k3, 0, 0x3232);
    sts128(ka + 2048 + 512 * t, lo, lo, (g & 1) ? hi : k3, hi);
    put_exp(sb + OFF_MX + u * 64 + 4 * w, amax2(amax2(k0, k1), amax2(k2, k3)), lane);
    cluster_wait();
    cluster_arrive();
    put(sb + u * 4096 + g * 512 + (g == rank ? OFF_UX : OFF_YB), x0, x1);
    TL(15);
    fence_async();
    bar_sync(NB_WG0 + u, 128);
    send(OFF_YB + u * 4096, OFF_UX + u * 4096 + 512 * rank, OFF_MB + 8 * (MB_UX + u));
    if (wid == 16) {
      bar_sync(NB_V, 288);
      if (elect()) tma_load3(sb + OFF_TV, &p.tv, ch0, 8 * rank, 0, mb + 8 * MB_KV);
      __syncwarp();
    }
  }
  if (u == 0) {
    float ga[4][4];
#pragma unroll
    for (int i = 0; i < 4; i++) ga[i][0] = ga[i][1] = ga[i][2] = ga[i][3] = 0.f;
#pragma unroll
    for (int j = 0; j < 5; j++) {
      uint32_t a0[4], a1[4], b;
      ldsm4(a0, sb + OFF_TQ + toff + 16 * j);
      ldsm4(a1, sb + OFF_TQ + toff + 2560 + 16 * j);
      asm volatile("ld.shared.u32 %0, [%1];" : "=r"(b) : "r"(sb + OFF_SP + 16 * j + 4 * t) : "memory");
      if (j >= 2 && j >= nu) b = 0;
      mma1688(ga[0], a0[0], a0[1], b); mma1688(ga[1], a0[2], a0[3], b); mma1688(ga[2], a1[0], a1[1], b); mma1688(ga[3], a1[2], a1[3], b);
    }
    const float s0 = t == 0 ? ga[0][0] : t == 1 ? ga[1][0] : t == 2 ? ga[2][0] : ga[3][0];
    const float s1 = t == 0 ? ga[0][2] : t == 1 ? ga[1][2] : t == 2 ? ga[2][2] : ga[3][2];
    tag = (lds64(mb + 8 * MB_TAG).x >> 4) + 1;
    uint2* gp = p.part + cl * SEQ + rank * 256 + 64 * w + 16 * t + g;
    asm volatile("st.relaxed.gpu.global.u64 [%0], %1;" :: "l"(gp), "l"(((uint64_t)tag << 32) | __float_as_uint(s0)) : "memory");
    asm volatile("st.relaxed.gpu.global.u64 [%0], %1;" :: "l"(gp + 8), "l"(((uint64_t)tag << 32) | __float_as_uint(s1)) : "memory");
  }

  auto gload = [&]() {
    const uint2* gp = p.part + t * SEQ + rank * 256 + 64 * u + 16 * w + 2 * g;
#pragma unroll
    for (int k = 0; k < 4; k++)
      asm volatile("cp.async.cg.shared.global [%0], [%1], 16;" :: "r"(tab + 2048 * w + 512 * k + 16 * lane), "l"(gp + (k == 3 && t == 3 ? 8 : 4 * k) * SEQ) : "memory");
  };
#pragma unroll
  for (int isA = 0; isA < 2; isA++) {
    {
      TL(1 + isA);
      const uint32_t usrc = isA ? tab + T_UKV : sb + OFF_UX + u * 4096;
      const uint32_t mxa = sb + OFF_MX + u * 64 + 32 * isA;
      const uint32_t pd = lds16(sb + OFF_SP + 80 + 80 * isA + 16 * u + 2 * rank);
      float D[32];
      uint32_t As[8], F[16], H[16], X[16];
      const uint32_t eh = min(max((int)get_exp(mxa), (int)((pd >> 7) & 0xff) - 5), 240);
      scale_a1(As, A1, 248 - eh);
      wg_fence();
      stage1(D, As, isA ? tab + T_HA : tab);
      wg_commit();
      wg_wait<0>(); tie_all(D);
      fwd_mid(F, D, tc, ts);
      if (!isA) mbar_wait(mb + 8 * MB_CF);
      wg_fence();
      stage2<0>(H, F, sb + OFF_CF);
      wg_commit();
      if (!isA) {
        if (w == 2 && elect()) bulk_load(tab + T_HA, p.ssm_k + (size_t)(act ? ch0 + 8 * u + rank : 0) * SEQ, 4096, mb + 8 * (MB_HA + u));
        __syncwarp();
        TL(7);
      }
      if (isA) fence_async();
      mbar_wait(mb + 8 * ((isA ? MB_UKV : MB_UX) + u));
      TL(5 + isA);
      put_exp(mxa + 16 + 4 * w, seq_mag(usrc + 16 * tid), lane);
      bar_sync(NB_WG0 + u, 128);
      if (isA) {
        send(OFF_UX + u * 4096, OFF_YB + (8 * u + rank) * 512, OFF_MB + 8 * (MB_Y + u));
        if (u < 4) gload();
      }
      const uint32_t eu = min(get_exp(mxa + 16), 240u);
      scale_a1(As, A1, 250 - eu);
      wg_wait<0>(); tie_all(H);
      wg_fence();
      stage1(D, As, usrc);
      wg_commit();
      wg_wait<0>(); tie_all(D);
      fwd_mid(F, D, tc, ts);
      wg_fence();
      stage2<0>(X, F, sb + OFF_CF);
      wg_commit();
      {
        const float dsk = blo(pd) * __uint_as_float((248 - eh) << 23);
        const uint32_t d2 = packh(dsk, dsk);
#pragma unroll
        for (int j = 0; j < 4; j++) H[2 * j] = U2(__hadd2(H2(H[2 * j]), H2(d2)));
      }
      wg_wait<0>(); tie_all(X);
#pragma unroll
      for (int j = 0; j < 4; j++) {
        const uint32_t h0r = H[2 * j], h1r = H[2 * j + 1], h0i = H[8 + 2 * j], h1i = H[9 + 2 * j];
        const uint32_t x0r = X[2 * j], x1r = X[2 * j + 1], x0i = X[8 + 2 * j], x1i = X[9 + 2 * j];
        F[2 * j] = ffma(x0r, h0r, fneg(fmul(x0i, h0i)));
        F[8 + 2 * j] = ffma(x0r, h0i, fmul(x0i, h0r));
        F[2 * j + 1] = ffma(x1r, h0r, ffma(fneg(x1i), h0i, ffma(x0r, h1r, fneg(ffma(x0i, h1i, F[8 + 2 * j])))));
        F[9 + 2 * j] = ffma(x1r, h0i, ffma(x1i, h0r, ffma(x0r, h1i, ffma(x0i, h1r, F[2 * j]))));
      }
      wg_fence();
      stage2<1>(H, F, sb + OFF_CF);
      wg_commit();
      if (isA && u < 4) {
        tag = (lds64(mb + 8 * MB_TAG).x >> 4) + 1;
        uint4 ga[4];
        bool ok;
#pragma unroll 1
        for (int it = 0;; it++) {
          asm volatile("cp.async.wait_all;" ::: "memory");
#pragma unroll
          for (int k = 0; k < 4; k++) ga[k] = lds128(tab + 2048 * w + 512 * k + 16 * lane);
          ok = __all_sync(0xffffffffu, ((ga[0].y ^ tag) | (ga[0].w ^ tag) | (ga[1].y ^ tag) | (ga[1].w ^ tag) | (ga[2].y ^ tag) | (ga[2].w ^ tag) | (ga[3].y ^ tag) | (ga[3].w ^ tag)) == 0);
          if (ok || it == 4000) break;
          gload();
        }
        float s0 = __uint_as_float(ga[0].x) + __uint_as_float(ga[1].x) + __uint_as_float(ga[2].x);
        float s1 = __uint_as_float(ga[0].z) + __uint_as_float(ga[1].z) + __uint_as_float(ga[2].z);
        if (t < 3) { s0 += __uint_as_float(ga[3].x); s1 += __uint_as_float(ga[3].z); }
        float s = ((t & 1) ? s1 : s0) + __shfl_xor_sync(0xffffffffu, (t & 1) ? s0 : s1, 1);
        s += __shfl_xor_sync(0xffffffffu, s, 2);
        const int sl = 64 * u + 16 * w + 2 * g + (t & 1);
        if (!ok) {
          const uint32_t* xr = (const uint32_t*)(p.q + (size_t)(rank * 256 + 32 * (sl & 7) + (sl >> 3)) * DCH);
          const uint32_t* gr = (const uint32_t*)p.gate_w;
          s = 0.f;
#pragma unroll 1
          for (int k = 0; k < DCH / 2; k++) { const uint32_t x = __ldg(xr + k), y = __ldg(gr + k); s = fmaf(blo(x), blo(y), fmaf(bhi(x), bhi(y), s)); }
        }
        float g0 = bf16r(sigmoidf_(bf16r(s)));
        if (t & 2) g0 = 1.f - g0;
        sts32(sb + OFF_GB + 8 * sl + (t & 2) * 2, pack(g0, g0));
        __syncwarp();
        if (lane == 0) mbar_arrive(mb + 8 * MB_G);
      }
      wg_wait<0>(); tie_all(H);
      {
        const uint32_t va = tab + (16 * w + (lane & 15)) * 128;
        const int vx = (lane >> 4) ^ (lane & 7);
#pragma unroll
        for (int j = 0; j < 4; j++) {
          uint32_t V[4];
#pragma unroll
          for (int b = 0; b < 2; b++) {
            const uint32_t er = H[2 * j + b], ei = H[8 + 2 * j + b];
            V[2 * b] = ffma(er, tc[j], fneg(fmul(ei, ts[j])));
            V[2 * b + 1] = ffma(ei, tc[j], fmul(er, ts[j]));
          }
          stsm4(va + ((vx ^ (2 * j)) << 4), V);
        }
      }
      if (!isA) {
        cluster_wait();
        mbar_wait(mb + 8 * MB_KV);
        TL(21);
        uint32_t K[3][4], V[2][4];
        const uint2 psw = lds64(sb + OFF_SP + 240 + 64 * u + 8 * g);
        ldsm4t(K[0], w ? sb + OFF_TK + toff - 2560 : (lane & 7) ? sb + OFF_TK + toff + 223 * 80 : sb + OFF_HALO + 10 * lane + 16 * u);
        ldsm4t(K[1], sb + OFF_TK + toff);
        ldsm4t(K[2], sb + OFF_TK + toff + 2560);
        ldsm4t(V[0], sb + OFF_TV + toff);
        ldsm4t(V[1], sb + OFF_TV + toff + 2560);
        mbar_wait(mb + 8 * (MB_HA + u));
        const uint4 hx = lds128(tab + T_HA + 16 * tid), hy = lds128(tab + T_HA + 2048 + 16 * tid);
        const uint32_t w0 = prmt(psw.x, 0, 0x1010), w1 = prmt(psw.x, 0, 0x3232), w2 = prmt(psw.y, 0, 0x1010), w3 = prmt(psw.y, 0, 0x3232);
#pragma unroll
        for (int m = 4; m < 12; m++)
          V[(m >> 2) - 1][m & 3] = hmul2(hfma2(K[m >> 2][m & 3], w0, hfma2(K[(m - 1) >> 2][(m - 1) & 3], w1,
                                         hfma2(K[(m - 2) >> 2][(m - 2) & 3], w2, hmul2(K[(m - 3) >> 2][(m - 3) & 3], w3)))), V[(m >> 2) - 1][m & 3]);
        put(g == rank ? tab + T_UKV + 512 * rank : sb + OFF_YA + u * 4096 + g * 512, V[0], V[1]);
        put_exp(mxa + 32 + 4 * w, amax2(amax2(amax2(hx.x, hx.y), amax2(hx.z, hx.w)), amax2(amax2(hy.x, hy.y), amax2(hy.z, hy.w))), lane);
        sts128(tab + T_HA + 16 * (tid ^ (lane >> 3)), hx.x, hx.y, hx.z, hx.w);
        sts128(tab + T_HA + 2048 + 16 * (tid ^ (lane >> 3)), hy.x, hy.y, hy.z, hy.w);
        TL(22);
      }
      fence_async();
      bar_sync(NB_WG0 + u, 128);
      float O[16];
      {
        const uint64_t dv = desc_lo(tab) | (1ull << 16) | (64ull << 32) | (1ull << 62);
        const uint64_t dl = desc_lo(sb + OFF_CL) | (32ull << 16) | (8ull << 32);
        wg_fence();
        ss32<0, 0, 0>(O, dv, dl); ss32<1, 128, 64>(O, dv, dl); ss32<1, 256, 128>(O, dv, dl); ss32<1, 384, 192>(O, dv, dl);
        wg_commit();
      }
      if (!isA) send(OFF_YA + u * 4096, OFF_T + u * KTAB + T_UKV + 512 * rank, OFF_MB + 8 * (MB_UKV + u));
      wg_wait<0>(); tie_all(O);
      {
        const uint32_t co = ((8 * w + g) ^ (2 * t) ^ rank) * 16;
        const int yo = (isA ? OFF_YA : OFF_YB) + (8 * u + rank) * 512, ym = OFF_MB + 8 * (MB_Y + u);
        const uint32_t us = min(max((int)(eu + eh) - 127, 0), 254) * 0x00800080u;
        const uint32_t a0 = hmul2(pack(O[0], O[1]), us), a1 = hmul2(pack(O[4], O[5]), us), a2 = hmul2(pack(O[8], O[9]), us), a3 = hmul2(pack(O[12], O[13]), us);
        const uint32_t b0 = hmul2(pack(O[2], O[3]), us), b1 = hmul2(pack(O[6], O[7]), us), b2 = hmul2(pack(O[10], O[11]), us), b3 = hmul2(pack(O[14], O[15]), us);
        sts128((t == rank ? sb + yo : usrc + t * 512) + co, a0, a1, a2, a3);
        sts128((t + 4 == rank ? sb + yo : usrc + t * 512 + 2048) + co, b0, b1, b2, b3);
        if (isA) {
          fence_async();
          bar_sync(NB_WG0 + u, 128);
          send(usrc - sb, yo, ym);
        }
      }
      TL(9 + isA);
    }
  }

  {
    mbar_wait(mb + 8 * MB_G);
    uint2 gg[2][4];
    uint32_t qv[2][4];
#pragma unroll
    for (int hh = 0; hh < 2; hh++)
#pragma unroll
      for (int i = 0; i < 4; i++) gg[hh][i] = lds64(sb + OFF_GB + 8 * (64 * w + 32 * hh + 8 * i + g));
    const uint32_t qa = sb + OFF_TQ + toff;
    ldsm4(qv[0], qa);
    ldsm4(qv[1], qa + 2560);
    TL(24);
    mbar_wait(mb + 8 * (MB_Y + u));
    uint32_t ya[2][4], yb[2][4];
#pragma unroll
    for (int hh = 0; hh < 2; hh++) {
      const uint32_t yo = (8 * u + (lane & 7)) * 512 + ((8 * w + 4 * hh + (lane >> 3)) ^ (2 * (rank & 3)) ^ (lane & 7)) * 16;
      ldsm4t(ya[hh], sb + OFF_YA + yo); ldsm4t(yb[hh], sb + OFF_YB + yo);
    }
#pragma unroll
    for (int hh = 0; hh < 2; hh++) {
      uint32_t o[4];
#pragma unroll
      for (int i = 0; i < 4; i++) o[i] = hadd2(hmul2(gg[hh][i].x, hmul2(qv[hh][i], ya[hh][i])), hmul2(gg[hh][i].y, yb[hh][i]));
      stsm4(qa + 2560 * hh, o);
    }
    TL(25);
  }
  cluster_arrive();
  bar_sync(NB_ROW0 + w, 160);
  {
    uint4 v[2];
#pragma unroll
    for (int k = 0; k < 2; k++) {
      const int i = 64 * u + 32 * k + lane, sl = (i * 205) >> 10, cc = i - 5 * sl;
      v[k] = lds128(sb + OFF_TQ + (64 * w + 8 * (sl & 7) + (sl >> 3)) * 80 + cc * 16);
    }
#pragma unroll
    for (int k = 0; k < 2; k++) {
      const int i = 64 * u + 32 * k + lane, sl = (i * 205) >> 10, cc = i - 5 * sl;
      if (cc < nu)
        asm volatile("st.global.v4.u32 [%0], {%1,%2,%3,%4};" :: "l"(p.out + (size_t)(256 * rank + 32 * (sl >> 3) + 8 * w + (sl & 7)) * DCH + ch0 + 8 * cc),
                     "r"(v[k].x), "r"(v[k].y), "r"(v[k].z), "r"(v[k].w) : "memory");
    }
  }
  cluster_wait();
  TL(27);
  TL_DUMP();
}

typedef CUresult (*EncodeFn)(CUtensorMap*, CUtensorMapDataType, cuuint32_t, void*, const cuuint64_t*, const cuuint64_t*,
                             const cuuint32_t*, const cuuint32_t*, CUtensorMapInterleave, CUtensorMapSwizzle,
                             CUtensorMapL2promotion, CUtensorMapFloatOOBfill);

void encode(EncodeFn fn, CUtensorMap* tm, const void* ptr, int nd, const cuuint64_t* dims, const cuuint64_t* strides,
            const cuuint32_t* box, CUtensorMapSwizzle swz) {
  cuuint32_t es[4] = {1, 1, 1, 1};
  fn(tm, CU_TENSOR_MAP_DATA_TYPE_BFLOAT16, nd, const_cast<void*>(ptr), dims, strides, box, es, CU_TENSOR_MAP_INTERLEAVE_NONE,
     swz, CU_TENSOR_MAP_L2_PROMOTION_L2_128B, CU_TENSOR_MAP_FLOAT_OOB_FILL_NONE);
}
void make_map(EncodeFn fn, CUtensorMap* tm, const void* ptr, int ne, int nr) {
  const cuuint64_t dims[3] = {DCH, SEQ / 32, 32}, strides[2] = {32 * DCH * 2, DCH * 2};
  const cuuint32_t box[3] = {CPC, (cuuint32_t)ne, (cuuint32_t)nr};
  encode(fn, tm, ptr, 3, dims, strides, box, CU_TENSOR_MAP_SWIZZLE_NONE);
}

}

extern "C" void kernel_launch(void* const* d_in, const int* in_sizes, int n_in, void* d_out, int out_size) {
  (void)in_sizes; (void)n_in; (void)out_size;
  static EncodeFn fn = nullptr;
  static void *tab = nullptr, *cnt = nullptr, *part = nullptr;
  if (!fn) {
    cudaGetSymbolAddress(&tab, d_tab);
    cudaGetSymbolAddress(&cnt, g_cnt);
    cudaGetSymbolAddress(&part, g_part);
    cudaDriverEntryPointQueryResult qr;
    cudaGetDriverEntryPoint("cuTensorMapEncodeTiled", (void**)&fn, cudaEnableDefault, &qr);
    cudaFuncSetAttribute(fused_kernel, cudaFuncAttributeMaxDynamicSharedMemorySize, SMEM_BYTES);
  }
  Params p;
  make_map(fn, &p.tq, d_in[0], 8, 32);
  make_map(fn, &p.tk, d_in[1], 8, 32);
  make_map(fn, &p.tv, d_in[2], 8, 32);
  make_map(fn, &p.tkh, d_in[1], 1, 4);
  p.out = (__nv_bfloat16*)d_out;
  p.tab = (const Tables*)tab;
  p.cnt = (unsigned*)cnt;
  p.part = (uint2*)part;
  p.tl = nullptr;
  p.q = (const __nv_bfloat16*)d_in[0];
  p.ssm_k = (const __nv_bfloat16*)d_in[4];
  p.shift_k = (const __nv_bfloat16*)d_in[3];
  p.ssm_D = (const __nv_bfloat16*)d_in[5];
  p.logA = (const __nv_bfloat16*)d_in[7];
  p.Aim = (const __nv_bfloat16*)d_in[8];
  p.Cre = (const __nv_bfloat16*)d_in[9];
  p.Cim = (const __nv_bfloat16*)d_in[10];
  p.logdt = (const __nv_bfloat16*)d_in[11];
  p.Dskip = (const __nv_bfloat16*)d_in[12];
  p.gate_w = (const __nv_bfloat16*)d_in[13];
  fused_kernel<<<NCL * CS, NTHREADS, SMEM_BYTES, cudaStreamPerThread>>>(p);
}
```

```cpp
#include <cuda_runtime.h>
#include <cuda_bf16.h>
#include <cuda_fp16.h>
#include <cuda.h>
#include <stdint.h>

#define TIMELINE 0
#define TLHI 0

namespace {

constexpr int SEQ = 2048, DCH = 576, NMODE = 128;
constexpr int CS = 8, CPC = 40, NCL = 15, NTHREADS = 640;

constexpr int KTAB = 16384;
constexpr int OFF_T = 0;
constexpr int T_UKV = 8192, T_HA = 12288;
constexpr int OFF_UX = 5 * KTAB;
constexpr int OFF_IM = OFF_UX + 20480;
constexpr int OFF_CF = OFF_IM;
constexpr int OFF_CL = OFF_CF + 8192;
constexpr int OFF_TV = OFF_CL + 4096;
constexpr int OFF_YA = OFF_TV + 20480;
constexpr int OFF_GB = OFF_YA + 20480;
constexpr int OFF_YB = OFF_IM + 4 * KTAB;
constexpr int OFF_TQ = OFF_YB + 20480;
constexpr int OFF_TK = OFF_TQ + 20480;
constexpr int OFF_HALO = OFF_TK + 20480;
constexpr int OFF_MX = OFF_HALO + 320;
constexpr int OFF_SP = OFF_MX + 320;
constexpr int OFF_MB = OFF_SP + 560;
constexpr int OFF_TL = OFF_MB + 28 * 8;
constexpr int SMEM_BYTES = OFF_TL + (TIMELINE ? 1280 : 0);
static_assert(SMEM_BYTES <= 232448 && OFF_YA == OFF_IM + 2 * KTAB && OFF_GB + 2048 <= OFF_YB, "smem");
static_assert((OFF_MB & 7) == 0 && (OFF_MX & 15) == 0 && (OFF_SP & 15) == 0, "align");

enum { MB_UX = 0, MB_UKV = 5, MB_Y = 10, MB_HA = 15, MB_XQ = 20, MB_KV = 21, MB_CF = 22, MB_G = 23, MB_TH = 24, MB_TAG = 25 };
enum { NB_WG0 = 1, NB_ROW0 = 6, NB_ORD = 6, NB_V = 10 };

constexpr double cos_turn(int m, int n) {
  m &= n - 1;
  if (m > n / 2) m = n - m;
  double sgn = 1.0;
  if (m > n / 4) { m = n / 2 - m; sgn = -1.0; }
  if (m == n / 4) return 0.0;
  const double x = 6.283185307179586476925 * m / n;
  double term = 1.0, sum = 1.0;
  for (int k = 1; k < 14; k++) { term *= -x * x / ((2 * k - 1) * (2 * k)); sum += term; }
  return sgn * sum;
}
constexpr uint32_t bf16_bits(double v) {
  if (v == 0.0) return 0;
  uint32_t sgn = 0;
  if (v < 0) { sgn = 0x8000; v = -v; }
  int e = 127;
  while (v < 1.0) { v *= 2.0; e--; }
  while (v >= 2.0) { v *= 0.5; e++; }
  const double f = v * 128.0;
  int m = (int)f;
  if (f - m > 0.5 || (f - m == 0.5 && (m & 1))) m++;
  return sgn | (uint32_t)((e << 7) + (m - 128));
}
constexpr uint32_t f16_bits(double v) {
  if (v == 0.0) return 0;
  uint32_t sgn = 0;
  if (v < 0) { sgn = 0x8000; v = -v; }
  int e = 15;
  while (v < 1.0) { v *= 2.0; e--; }
  const double f = v * 1024.0;
  int m = (int)f;
  if (f - m > 0.5 || (f - m == 0.5 && (m & 1))) m++;
  return sgn | (uint32_t)((e << 10) + (m - 1024));
}
constexpr uint32_t pair_bits(double lo, double hi) { return bf16_bits(lo) | (bf16_bits(hi) << 16); }
constexpr uint32_t pair_h(double lo, double hi) { return f16_bits(lo) | (f16_bits(hi) << 16); }
struct alignas(128) Tables {
  uint32_t mat[3072];
  uint32_t thr[4][128][4];
};
constexpr Tables make_tables() {
  Tables T{};
  for (int q = 0; q < 768; q++) {
    int m0 = 0, d0 = 0, d1 = 0;
    if (q < 512) {
      const int r = (q >> 6) * 8 + (q & 7), cc = (q >> 3) & 7;
      d0 = 4 * (r & 31); d1 = 2 * d0;
      m0 = 8 * (cc & 3) * d0 + ((r >> 5) == (cc >> 2) ? 0 : (r >> 5) ? 96 : 32);
    } else {
      const int r = ((q - 512) >> 5) * 8 + (q & 7), pc = (q >> 3) & 3;
      d0 = 4 * (8 * (r >> 4) + (r & 7)) + 1; d1 = 8 * d0;
      m0 = 2 * pc * d0 + ((r & 8) ? 32 : 0);
    }
    for (int e = 0; e < 4; e++) T.mat[4 * q + e] = pair_h(cos_turn(m0 + e * d1, 128), cos_turn(m0 + e * d1 + d0, 128));
  }
  for (int tid = 0; tid < 128; tid++) {
    const int kk = 4 * (tid >> 2) + 1, t = tid & 3;
    for (int q = 0; q < 4; q++) {
      const int m = (8 * q + 2 * t) * kk;
      T.thr[q >> 1][tid][2 * (q & 1)] = pair_bits(cos_turn(m, 128), cos_turn(m + kk, 128));
      T.thr[q >> 1][tid][2 * (q & 1) + 1] = pair_bits(cos_turn(m + 32, 128), cos_turn(m + kk + 32, 128));
      T.thr[2][tid][q] = pair_h(cos_turn(m, 4096), cos_turn(m + kk, 4096));
      T.thr[3][tid][q] = pair_h(cos_turn(m + 3072, 4096), cos_turn(m + kk + 3072, 4096));
    }
  }
  return T;
}
__device__ const Tables d_tab = make_tables();

struct Params {
  const __nv_bfloat16 *logA, *Aim, *Cre, *Cim, *logdt;
  const Tables* tab;
  unsigned* cnt;
  const __nv_bfloat16 *Dskip, *shift_k, *ssm_D, *gate_w, *q, *ssm_k;
  uint2* part;
  __nv_bfloat16* out;
  unsigned* tl;
  CUtensorMap tq, tk, tv, tkh;
};

__device__ uint2 g_part[(NCL + 1) * SEQ];
__device__ unsigned g_cnt[CS * 32];
#define TL(i) do {} while (0)
#define TL_INIT() do {} while (0)
#define TL_DUMP() do {} while (0)

__device__ __forceinline__ uint32_t lds16(uint32_t a) { uint32_t v; asm volatile("ld.shared.u16 %0, [%1];" : "=r"(v) : "r"(a) : "memory"); return v; }
__device__ __forceinline__ uint2 lds64(uint32_t a) { uint2 v; asm volatile("ld.shared.v2.u32 {%0,%1}, [%2];" : "=r"(v.x), "=r"(v.y) : "r"(a) : "memory"); return v; }
__device__ __forceinline__ uint4 lds128(uint32_t a) { uint4 v; asm volatile("ld.shared.v4.u32 {%0,%1,%2,%3}, [%4];" : "=r"(v.x), "=r"(v.y), "=r"(v.z), "=r"(v.w) : "r"(a) : "memory"); return v; }
__device__ __forceinline__ void sts16(uint32_t a, uint32_t v) { asm volatile("st.shared.u16 [%0], %1;" :: "r"(a), "r"(v) : "memory"); }
__device__ __forceinline__ void sts32(uint32_t a, uint32_t v) { asm volatile("st.shared.u32 [%0], %1;" :: "r"(a), "r"(v) : "memory"); }
__device__ __forceinline__ void sts64(uint32_t a, uint32_t x, uint32_t y) { asm volatile("st.shared.v2.u32 [%0], {%1,%2};" :: "r"(a), "r"(x), "r"(y) : "memory"); }
__device__ __forceinline__ void sts128(uint32_t a, uint32_t x, uint32_t y, uint32_t z, uint32_t w) { asm volatile("st.shared.v4.u32 [%0], {%1,%2,%3,%4};" :: "r"(a), "r"(x), "r"(y), "r"(z), "r"(w) : "memory"); }
__device__ __forceinline__ void ldsm4t(uint32_t (&r)[4], uint32_t a) { asm volatile("ldmatrix.sync.aligned.m8n8.x4.trans.shared.b16 {%0,%1,%2,%3}, [%4];" : "=r"(r[0]), "=r"(r[1]), "=r"(r[2]), "=r"(r[3]) : "r"(a) : "memory"); }
__device__ __forceinline__ void ldsm2t(uint32_t& r0, uint32_t& r1, uint32_t a) { asm volatile("ldmatrix.sync.aligned.m8n8.x2.trans.shared.b16 {%0,%1}, [%2];" : "=r"(r0), "=r"(r1) : "r"(a) : "memory"); }
__device__ __forceinline__ void ldsm4(uint32_t (&r)[4], uint32_t a) { asm volatile("ldmatrix.sync.aligned.m8n8.x4.shared.b16 {%0,%1,%2,%3}, [%4];" : "=r"(r[0]), "=r"(r[1]), "=r"(r[2]), "=r"(r[3]) : "r"(a) : "memory"); }
__device__ __forceinline__ void stsm4(uint32_t a, const uint32_t (&r)[4]) { asm volatile("stmatrix.sync.aligned.m8n8.x4.shared.b16 [%0], {%1,%2,%3,%4};" :: "r"(a), "r"(r[0]), "r"(r[1]), "r"(r[2]), "r"(r[3]) : "memory"); }
__device__ __forceinline__ uint32_t pack(float lo, float hi) { uint32_t r; asm("cvt.rn.bf16x2.f32 %0, %1, %2;" : "=r"(r) : "f"(hi), "f"(lo)); return r; }
__device__ __forceinline__ float blo(uint32_t v) { return __uint_as_float(v << 16); }
__device__ __forceinline__ float bhi(uint32_t v) { return __uint_as_float(v & 0xffff0000u); }
__device__ __forceinline__ float bf16r(float x) { return blo(pack(x, 0.f)); }
__device__ __forceinline__ uint32_t hmul2(uint32_t a, uint32_t b) { uint32_t r; asm("mul.rn.bf16x2 %0, %1, %2;" : "=r"(r) : "r"(a), "r"(b)); return r; }
__device__ __forceinline__ uint32_t hadd2(uint32_t a, uint32_t b) { uint32_t r; asm("add.rn.bf16x2 %0, %1, %2;" : "=r"(r) : "r"(a), "r"(b)); return r; }
__device__ __forceinline__ uint32_t hfma2(uint32_t a, uint32_t b, uint32_t c) { uint32_t r; asm("fma.rn.bf16x2 %0, %1, %2, %3;" : "=r"(r) : "r"(a), "r"(b), "r"(c)); return r; }
__device__ __forceinline__ uint32_t packh(float lo, float hi) { uint32_t r; asm("cvt.rn.f16x2.f32 %0, %1, %2;" : "=r"(r) : "f"(hi), "f"(lo)); return r; }
__device__ __forceinline__ __half2 H2(uint32_t a) { return *reinterpret_cast<__half2*>(&a); }
__device__ __forceinline__ uint32_t U2(__half2 a) { return *reinterpret_cast<uint32_t*>(&a); }
__device__ __forceinline__ uint32_t fmul(uint32_t a, uint32_t b) { return U2(__hmul2(H2(a), H2(b))); }
__device__ __forceinline__ uint32_t ffma(uint32_t a, uint32_t b, uint32_t c) { return U2(__hfma2(H2(a), H2(b), H2(c))); }
__device__ __forceinline__ uint32_t fneg(uint32_t a) { return U2(__hneg2(H2(a))); }
__device__ __forceinline__ uint32_t amax2(uint32_t a, uint32_t b) { uint32_t r; asm("max.xorsign.abs.bf16x2 %0, %1, %2;" : "=r"(r) : "r"(a), "r"(b)); return r; }
__device__ __forceinline__ uint32_t prmt(uint32_t a, uint32_t b, uint32_t s) { return __byte_perm(a, b, s); }
__device__ __forceinline__ uint32_t ldraw(const __nv_bfloat16* p) { uint32_t v; asm volatile("ld.global.nc.u16 %0, [%1];" : "=r"(v) : "l"(p)); return v; }
__device__ __forceinline__ uint4 ldg128(const void* p) { uint4 v; asm volatile("ld.global.nc.v4.u32 {%0,%1,%2,%3}, [%4];" : "=r"(v.x), "=r"(v.y), "=r"(v.z), "=r"(v.w) : "l"(p)); return v; }
__device__ __forceinline__ void bar_sync(int id, int n) { asm volatile("bar.sync %0, %1;" :: "r"(id), "r"(n) : "memory"); }
__device__ __forceinline__ void bar_arrive(int id, int n) { asm volatile("bar.arrive %0, %1;" :: "r"(id), "r"(n) : "memory"); }
__device__ __forceinline__ void cluster_arrive() { asm volatile("barrier.cluster.arrive.relaxed.aligned;" ::: "memory"); }
__device__ __forceinline__ void cluster_wait() { asm volatile("barrier.cluster.wait.aligned;" ::: "memory"); }
__device__ __forceinline__ void fence_async() { asm volatile("fence.proxy.async.shared::cta;" ::: "memory"); }
__device__ __forceinline__ void fence_mbinit() { asm volatile("fence.mbarrier_init.release.cluster;" ::: "memory"); }
__device__ __forceinline__ uint32_t mapa(uint32_t a, uint32_t rank) { uint32_t r; asm("mapa.shared::cluster.u32 %0, %1, %2;" : "=r"(r) : "r"(a), "r"(rank)); return r; }
__device__ __forceinline__ void bulk_dsmem(uint32_t dst, uint32_t src, uint32_t mbar) {
  asm volatile("cp.async.bulk.shared::cluster.shared::cta.mbarrier::complete_tx::bytes [%0], [%1], 512, [%2];" :: "r"(dst), "r"(src), "r"(mbar) : "memory");
}
__device__ __forceinline__ void bulk_load(uint32_t dst, const void* src, uint32_t bytes, uint32_t mbar) {
  asm volatile("cp.async.bulk.shared::cluster.global.mbarrier::complete_tx::bytes [%0], [%1], %2, [%3];" :: "r"(dst), "l"(src), "r"(bytes), "r"(mbar) : "memory");
}
__device__ __forceinline__ void mbar_init(uint32_t m, uint32_t cnt) { asm volatile("mbarrier.init.shared::cta.b64 [%0], %1;" :: "r"(m), "r"(cnt) : "memory"); }
__device__ __forceinline__ void mbar_expect(uint32_t m, uint32_t bytes) { asm volatile("mbarrier.arrive.expect_tx.shared::cta.b64 _, [%0], %1;" :: "r"(m), "r"(bytes) : "memory"); }
__device__ __forceinline__ bool mbar_try(uint32_t m) {
  uint32_t done;
  asm volatile("{.reg .pred p; mbarrier.try_wait.parity.shared::cta.b64 p, [%1], 0; selp.u32 %0, 1, 0, p;}" : "=r"(done) : "r"(m) : "memory");
  return done;
}
__device__ __forceinline__ void mbar_wait(uint32_t m) {
  if (!mbar_try(m)) {
    int it = 0;
    while (!mbar_try(m) && ++it < (1 << 22)) {}
  }
}
__device__ __forceinline__ bool elect() {
  uint32_t e;
  asm volatile("{.reg .pred p; elect.sync _|p, 0xffffffff; selp.u32 %0, 1, 0, p;}" : "=r"(e));
  return e;
}
__device__ __forceinline__ void tma_load4(uint32_t dst, const CUtensorMap* tm, int c0, int c1, int c2, int c3, uint32_t mbar) {
  asm volatile("cp.async.bulk.tensor.4d.shared::cluster.global.mbarrier::complete_tx::bytes [%0], [%1, {%3, %4, %5, %6}], [%2];"
               :: "r"(dst), "l"(tm), "r"(mbar), "r"(c0), "r"(c1), "r"(c2), "r"(c3) : "memory");
}
__device__ __forceinline__ void tma_load3(uint32_t dst, const CUtensorMap* tm, int c0, int c1, int c2, uint32_t mbar) {
  asm volatile("cp.async.bulk.tensor.3d.shared::cluster.global.mbarrier::complete_tx::bytes [%0], [%1, {%3, %4, %5}], [%2];"
               :: "r"(dst), "l"(tm), "r"(mbar), "r"(c0), "r"(c1), "r"(c2) : "memory");
}
__device__ __forceinline__ void tma_store3(const CUtensorMap* tm, int c0, int c1, int c2, uint32_t src) {
  asm volatile("cp.async.bulk.tensor.3d.global.shared::cta.bulk_group [%0, {%2, %3, %4}], [%1];"
               :: "l"(tm), "r"(src), "r"(c0), "r"(c1), "r"(c2) : "memory");
}
__device__ __forceinline__ void mma1688(float (&c)[4], uint32_t a0, uint32_t a1, uint32_t b) {
  asm volatile("mma.sync.aligned.m16n8k8.row.col.f32.bf16.bf16.f32 {%0,%1,%2,%3}, {%4,%5}, {%6}, {%0,%1,%2,%3};"
               : "+f"(c[0]), "+f"(c[1]), "+f"(c[2]), "+f"(c[3]) : "r"(a0), "r"(a1), "r"(b));
}
__device__ __forceinline__ void wg_fence() { asm volatile("wgmma.fence.sync.aligned;" ::: "memory"); }
__device__ __forceinline__ void wg_commit() { asm volatile("wgmma.commit_group.sync.aligned;" ::: "memory"); }
template <int N> __device__ __forceinline__ void wg_wait() { asm volatile("wgmma.wait_group.sync.aligned %0;" :: "n"(N) : "memory"); }
template <int N> __device__ __forceinline__ void tie_all(uint32_t (&x)[N]) {
#pragma unroll
  for (int i = 0; i < N; i++) asm volatile("" : "+r"(x[i]) :: "memory");
}
template <int N> __device__ __forceinline__ void tie_all(float (&x)[N]) {
#pragma unroll
  for (int i = 0; i < N; i++) asm volatile("" : "+f"(x[i]) :: "memory");
}
#define R16(C, d) C(d[0]), C(d[1]), C(d[2]), C(d[3]), C(d[4]), C(d[5]), C(d[6]), C(d[7]), C(d[8]), C(d[9]), C(d[10]), C(d[11]), C(d[12]), C(d[13]), C(d[14]), C(d[15])
#define R32(C, d) R16(C, d), R16(C, (d + 16))
#define P16 "{%0,%1,%2,%3,%4,%5,%6,%7,%8,%9,%10,%11,%12,%13,%14,%15}"
#define P32 "{%0,%1,%2,%3,%4,%5,%6,%7,%8,%9,%10,%11,%12,%13,%14,%15,%16,%17,%18,%19,%20,%21,%22,%23,%24,%25,%26,%27,%28,%29,%30,%31}"
template <int SD, int TB, int OFF> __device__ __forceinline__ void rs64(float* d, const uint32_t* a, uint64_t db) {
  if (SD) asm volatile("{.reg .b64 db; add.s64 db, %36, %37; wgmma.mma_async.sync.aligned.m64n64k16.f32.bf16.bf16 " P32 ", {%32,%33,%34,%35}, db, 1, 1, 1, %38;}"
                       : R32("+f", d) : "r"(a[0]), "r"(a[1]), "r"(a[2]), "r"(a[3]), "l"(db), "n"(OFF), "n"(TB));
  else asm volatile("{.reg .b64 db; add.s64 db, %36, %37; wgmma.mma_async.sync.aligned.m64n64k16.f32.bf16.bf16 " P32 ", {%32,%33,%34,%35}, db, 0, 1, 1, %38;}"
                    : R32("=f", d) : "r"(a[0]), "r"(a[1]), "r"(a[2]), "r"(a[3]), "l"(db), "n"(OFF), "n"(TB));
}
template <int SD, int TB, int OFF> __device__ __forceinline__ void rs64h(uint32_t* d, const uint32_t* a, uint64_t db) {
  if (SD) asm volatile("{.reg .b64 db; add.s64 db, %20, %21; wgmma.mma_async.sync.aligned.m64n64k16.f16.f16.f16 " P16 ", {%16,%17,%18,%19}, db, 1, 1, 1, %22;}"
                       : R16("+r", d) : "r"(a[0]), "r"(a[1]), "r"(a[2]), "r"(a[3]), "l"(db), "n"(OFF), "n"(TB));
  else asm volatile("{.reg .b64 db; add.s64 db, %20, %21; wgmma.mma_async.sync.aligned.m64n64k16.f16.f16.f16 " P16 ", {%16,%17,%18,%19}, db, 0, 1, 1, %22;}"
                    : R16("=r", d) : "r"(a[0]), "r"(a[1]), "r"(a[2]), "r"(a[3]), "l"(db), "n"(OFF), "n"(TB));
}
template <int SD, int OFFA, int OFFB> __device__ __forceinline__ void ss32(float* d, uint64_t da, uint64_t db) {
  if (SD) asm volatile("{.reg .b64 da, db; add.s64 da, %16, %18; add.s64 db, %17, %19; wgmma.mma_async.sync.aligned.m64n32k16.f32.f16.f16 " P16 ", da, db, 1, 1, 1, 1, 1;}"
                       : R16("+f", d) : "l"(da), "l"(db), "n"(OFFA), "n"(OFFB));
  else asm volatile("{.reg .b64 da, db; add.s64 da, %16, %18; add.s64 db, %17, %19; wgmma.mma_async.sync.aligned.m64n32k16.f32.f16.f16 " P16 ", da, db, 0, 1, 1, 1, 1;}"
                    : R16("=f", d) : "l"(da), "l"(db), "n"(OFFA), "n"(OFFB));
}
#define KGEN_ASM(SD) "{.reg .b64 da, db; add.s64 da, %32, %33; add.s64 db, %32, %34;\n" \
  "wgmma.mma_async.sync.aligned.m64n64k16.f32.bf16.bf16 " P32 ", da, db, " SD ", 1, 1, 1, 1;}"
template <int KS> __device__ __forceinline__ void kgen_mma(float (&c)[32], uint64_t da) {
  if (KS) asm volatile(KGEN_ASM("1") : R32("+f", c) : "l"(da), "n"(8 * KS), "n"(8 * KS + 512));
  else asm volatile(KGEN_ASM("0") : R32("=f", c) : "l"(da), "n"(8 * KS), "n"(8 * KS + 512));
  if constexpr (KS < 7) kgen_mma<KS + 1>(c, da);
}
__device__ __forceinline__ uint64_t desc_lo(uint32_t a) { return (uint64_t)((a & 0x3FFFF) >> 4); }
__device__ __forceinline__ void stage1(float (&D)[32], const uint32_t (&A1)[8], uint32_t src) {
  const uint64_t du = desc_lo(src) | (128ull << 16) | (32ull << 32) | (2ull << 62);
  rs64<0, 1, 0>(D, A1, du); rs64<1, 1, 64>(D, A1 + 4, du);
}
template <int INV> __device__ __forceinline__ void stage2(uint32_t (&X)[16], const uint32_t (&F)[16], uint32_t cf) {
  constexpr int KS = INV ? 16 : 128, TB = INV ? 0 : 1;
  const uint64_t dc = desc_lo(cf) | (INV ? (8ull << 16) | (64ull << 32) : (64ull << 16) | (8ull << 32));
  rs64h<0, TB, 0>(X, F, dc); rs64h<1, TB, KS>(X, F + 4, dc); rs64h<1, TB, 2 * KS>(X, F + 8, dc); rs64h<1, TB, 3 * KS>(X, F + 12, dc);
}
__device__ __forceinline__ void fwd_mid(uint32_t (&F)[16], const float (&D)[32], const uint32_t (&tc)[4], const uint32_t (&ts)[4]) {
#pragma unroll
  for (int j = 0; j < 4; j++)
#pragma unroll
    for (int b = 0; b < 2; b++) {
      const int i = 4 * j + 16 * b;
      const uint32_t ar = packh(D[i], D[i + 1]), ai = packh(D[i + 2], D[i + 3]);
      F[2 * j + b] = ffma(ar, tc[j], fmul(ai, ts[j]));
      F[8 + 2 * j + b] = ffma(ai, tc[j], fneg(fmul(ar, ts[j])));
    }
}
__device__ __forceinline__ void put_exp(uint32_t a, uint32_t m, int lane) {
  m = __reduce_max_sync(0xffffffffu, max(m & 0x7f80u, (m >> 16) & 0x7f80u));
  if (lane == 0) sts32(a, m);
}
__device__ __forceinline__ uint32_t seq_mag(uint32_t a) {
  const uint4 x = lds128(a), y = lds128(a + 2048);
  return amax2(amax2(amax2(x.x, x.y), amax2(x.z, x.w)), amax2(amax2(y.x, y.y), amax2(y.z, y.w)));
}
__device__ __forceinline__ uint32_t get_exp(uint32_t a) { const uint4 v = lds128(a); return max(max(v.x, v.y), max(v.z, v.w)) >> 7; }
__device__ __forceinline__ void scale_a1(uint32_t (&As)[8], const uint32_t (&A1)[8], uint32_t field) {
#pragma unroll
  for (int i = 0; i < 8; i++) As[i] = hmul2(A1[i], field * 0x00800080u);
}

struct cf { float x, y; };
__device__ __forceinline__ cf cmul(cf a, cf b) { cf r; r.x = fmaf(a.x, b.x, -a.y * b.y); r.y = fmaf(a.x, b.y, a.y * b.x); return r; }
__device__ __forceinline__ cf cexp_p(float lr2, float lt, float p) {
  float m;
  asm("ex2.approx.ftz.f32 %0, %1;" : "=f"(m) : "f"(lr2 * p));
  float t = lt * p;
  t = (t - rintf(t)) * 6.283185307179586f;
  cf r; r.x = m * __cosf(t); r.y = m * __sinf(t); return r;
}
__device__ __forceinline__ void store8(uint32_t a, uint32_t b, const cf (&v)[8]) {
  sts128(a, pack(v[0].x, v[1].x), pack(v[2].x, v[3].x), pack(v[4].x, v[5].x), pack(v[6].x, v[7].x));
  sts128(b, pack(v[0].y, v[1].y), pack(v[2].y, v[3].y), pack(v[4].y, v[5].y), pack(v[6].y, v[7].y));
}
__device__ __forceinline__ void mbar_arrive(uint32_t m) { asm volatile("mbarrier.arrive.shared::cta.b64 _, [%0];" :: "r"(m) : "memory"); }
__device__ __forceinline__ float sigmoidf_(float s) { return __fdividef(1.f, 1.f + __expf(fminf(-s, 80.f))); }

__global__ void __cluster_dims__(CS, 1, 1) __launch_bounds__(NTHREADS, 1) fused_kernel(const __grid_constant__ Params p) {
  extern __shared__ __align__(1024) uint8_t smem[];
  TL_INIT();
  TL(31);
  const int wid = __shfl_sync(0xffffffffu, threadIdx.x >> 5, 0);
  const uint32_t sb = (uint32_t)__cvta_generic_to_shared(smem);
  const uint32_t mb = sb + OFF_MB;
  const int u = wid >> 2, w = wid & 3;
  const int tid = threadIdx.x & 127, lane = tid & 31, g = lane >> 2, t = lane & 3;
  const int cl = blockIdx.x >> 3, rank = blockIdx.x & 7;
  const int ch0 = cl * CPC;
  const int nu = min(5, (DCH - ch0) >> 3);
  const bool act = u < nu;

  uint32_t pla, pai, pcr, pci, pdt, tag = 0;
  auto load_params = [&]() {
    const int ch = act ? ch0 + 8 * u + rank : 0, o = ch * NMODE + tid;
    pla = ldraw(p.logA + o); pdt = ldraw(p.logdt + ch); pai = ldraw(p.Aim + o); pcr = ldraw(p.Cre + o); pci = ldraw(p.Cim + o);
  };
  if (u == 4) {
    const bool e = elect();
    if (e) {
#pragma unroll
      for (int i = 0; i < 5; i++) mbar_init(mb + 40 * w + 8 * i, 1);
      if (w == 3) { mbar_init(mb + 8 * MB_TH, 1); mbar_init(mb + 8 * MB_XQ, 21); mbar_init(mb + 8 * MB_KV, 1); }
      if (w == 2) { mbar_init(mb + 8 * MB_CF, 1); mbar_init(mb + 8 * MB_G, 8); }
      fence_mbinit();
    }
    __syncwarp();
    load_params();
    if (w == 0 && lane < 2) asm volatile("atom.relaxed.gpu.global.add.u32 %0, [%1], %2;" : "=r"(tag) : "l"(&p.cnt[rank * 32 + lane]), "r"(cl == 0 ? 16 - (NCL - 1) : 1) : "memory");
    if (e) {
      if (w == 3) {
        mbar_expect(mb + 8 * MB_TH, 8192 + 112 * nu);
        bulk_load(sb + OFF_YB, p.tab->thr, 8192, mb + 8 * MB_TH);
        bulk_load(sb + OFF_SP, p.gate_w + ch0, 16 * nu, mb + 8 * MB_TH);
        bulk_load(sb + OFF_SP + 80, p.Dskip + ch0, 16 * nu, mb + 8 * MB_TH);
        bulk_load(sb + OFF_SP + 160, p.ssm_D + ch0, 16 * nu, mb + 8 * MB_TH);
        bulk_load(sb + OFF_SP + 240, p.shift_k + 4 * ch0, 64 * nu, mb + 8 * MB_TH);
        asm volatile("cp.async.bulk.prefetch.L2.global [%0], 12288;" :: "l"(p.tab->mat) : "memory");
        mbar_expect(mb + 8 * MB_XQ, 20480);
        tma_load3(sb + OFF_TQ, &p.tq, ch0, 8 * rank, 0, mb + 8 * MB_XQ);
        TL(20);
        mbar_expect(mb + 8 * MB_KV, 2 * 20480 + 320);
        tma_load3(sb + OFF_TK, &p.tk, ch0, 8 * rank, 0, mb + 8 * MB_KV);
        tma_load3(sb + OFF_HALO, &p.tkh, ch0, 8 * rank - 1, 28, mb + 8 * MB_KV);
      }
      if (w == 2) mbar_expect(mb + 8 * MB_CF, 12288);
#pragma unroll
      for (int i = 0; i < 5; i++) mbar_expect(mb + 40 * w + 8 * i, w == 3 ? 4096 : w == 2 ? 7168 : 3584);
    }
    __syncwarp();
  } else {
    load_params();
  }
  cluster_arrive();
  TL(0);

  const uint32_t tab = sb + OFF_T + u * KTAB;
  const uint32_t toff = (64 * w + lane) * 80 + 16 * u;
  auto put = [&](uint32_t dst, const uint32_t (&a)[4], const uint32_t (&b)[4]) {
    const uint32_t s0 = (g & 1) ? 0x7632 : 0x5410, s1 = s0 ^ 0x2222;
    const uint32_t o = dst + 128 * t + 64 * (g & 1) + 16 * (w ^ t);
    sts128(o, prmt(a[0], a[1], s0), prmt(a[2], a[3], s0), prmt(b[0], b[1], s0), prmt(b[2], b[3], s0));
    sts128(o ^ 64, prmt(a[0], a[1], s1), prmt(a[2], a[3], s1), prmt(b[0], b[1], s1), prmt(b[2], b[3], s1));
  };
  const int d0 = rank ^ (2 * w), d1 = d0 ^ 1;
  const uint32_t rb0 = mapa(sb, d0), rb1 = mapa(sb, d1);
  auto send = [&](int stage, int dst, int mbar) {
    if (elect()) {
      if (w) bulk_dsmem(rb0 + dst, sb + stage + d0 * 512, rb0 + mbar);
      bulk_dsmem(rb1 + dst, sb + stage + d1 * 512, rb1 + mbar);
    }
    __syncwarp();
  };

  uint32_t A1[8], tc[4], ts[4];
  {
    const float dt = bf16r(expf(blo(pdt)));
    const float lr2 = (-bf16r(expf(blo(pla))) * dt) * 1.4426950408889634f;
    const float lt = (blo(pai) * dt) * 0.15915494309189535f;
    const uint32_t tim = sb + (u ? OFF_IM + (u - 1) * KTAB : OFF_UX);
    const uint32_t row = tab + tid * 16, rim = tim + tid * 16;
    const cf w1 = cexp_p(lr2, lt, 8.f);
    cf z1 = cexp_p(lr2, lt, 1.f), Z = cexp_p(lr2, lt, 256.f);
    if (lr2 != 123.f) TL(16);
    TL(12);
    {
      cf v[8];
      v[0].x = 1.f; v[0].y = 0.f; v[1] = w1; v[2] = cmul(w1, w1); v[3] = cmul(v[2], w1);
      const cf w4 = cmul(v[2], v[2]);
      v[4] = w4; v[5] = cmul(v[1], w4); v[6] = cmul(v[2], w4); v[7] = cmul(v[3], w4);
      const cf w8 = cmul(w4, w4);
      store8(row, rim, v);
#pragma unroll
      for (int k = 1; k < 4; k++) {
#pragma unroll
        for (int i = 0; i < 8; i++) v[i] = (k == 1 && i == 0) ? w8 : cmul(v[i], w8);
        store8(row + 2048 * k, rim + 2048 * k, v);
      }
    }
    cluster_wait();
    if (u) cluster_arrive();
    mbar_wait(mb + 8 * MB_TH);
    {
      const uint4 x = lds128(sb + OFF_YB + 16 * tid), y = lds128(sb + OFF_YB + 2048 + 16 * tid), a = lds128(sb + OFF_YB + 4096 + 16 * tid), b = lds128(sb + OFF_YB + 6144 + 16 * tid);
      A1[0] = x.x; A1[1] = x.y; A1[2] = x.z; A1[3] = x.w; A1[4] = y.x; A1[5] = y.y; A1[6] = y.z; A1[7] = y.w;
      tc[0] = a.x; tc[1] = a.y; tc[2] = a.z; tc[3] = a.w; ts[0] = b.x; ts[1] = b.y; ts[2] = b.z; ts[3] = b.w;
    }
    if (wid == 16 && lane == 0) sts32(mb + 8 * MB_TAG, tag);
    __syncwarp();
    if (lane == 0) mbar_arrive(mb + 8 * MB_XQ);
    if (u == 1) {
      float z0_ = 0.f, z1_ = 0.f, z2_ = 0.f, z3_ = 0.f;
      asm volatile("mma.sync.aligned.m16n8k8.row.col.f32.bf16.bf16.f32 {%0,%1,%2,%3}, {%4,%4}, {%4}, {%0,%1,%2,%3};"
                   : "+f"(z0_), "+f"(z1_), "+f"(z2_), "+f"(z3_) : "r"(pla >> 16));
      pcr += __float_as_uint(z0_);
      TL(8);
    }
    {
      z1.y = -z1.y; Z.y = -Z.y;
      const cf z2 = cmul(z1, z1);
      cf h[8], v[8];
      h[0].x = 2.f * blo(pcr) * dt; h[0].y = -2.f * blo(pci) * dt;
      h[1] = cmul(h[0], z1);
#pragma unroll
      for (int i = 2; i < 8; i++) h[i] = cmul(h[i - 2], z2);
      store8(row + 4 * 2048, rim + 4 * 2048, h);
      const cf h8 = cmul(h[6], z2);
      v[0] = cmul(h[0], Z); v[2] = cmul(h[2], Z); v[3] = cmul(h[4], Z); v[6] = cmul(h[6], Z); v[7] = cmul(h8, Z);
      v[1] = v[0]; v[4] = v[5] = v[3];
      store8(row + 5 * 2048, rim + 5 * 2048, v);
      h[0] = cmul(v[0], Z); h[1] = cmul(v[3], Z); h[3] = cmul(v[7], Z); h[4] = cmul(h[0], Z); h[5] = cmul(h[1], Z); h[7] = cmul(h[3], Z);
      h[2] = h[1]; h[6] = h[5];
      store8(row + 6 * 2048, rim + 6 * 2048, h);
      const cf Z2 = cmul(Z, Z);
      v[0] = cmul(h[0], Z2); v[1] = cmul(h[3], Z2); v[2] = cmul(h[4], Z2); v[3] = cmul(h[7], Z2);
#pragma unroll
      for (int i = 4; i < 8; i++) v[i] = cmul(v[i - 4], Z2);
      store8(row + 7 * 2048, rim + 7 * 2048, v);
    }
    TL(17);
    fence_async();
    if (u) bar_sync(NB_ORD + u - 1, 256); else bar_sync(NB_WG0, 128);
    TL(13);
    float c[32];
    wg_fence();
    kgen_mma<0>(c, desc_lo(tab) | ((uint64_t)((tim - tab) >> 4) << 16) | (64ull << 32));
    wg_commit();
    if (u < 4) bar_arrive(NB_ORD + u, 256);
    TL(14);
    mbar_wait(mb + 8 * MB_XQ);
    TL(18);
    uint32_t x0[4], x1[4];
    ldsm4t(x0, sb + OFF_TQ + toff);
    ldsm4t(x1, sb + OFF_TQ + toff + 2560);
    wg_wait<0>(); tie_all(c);
    TL(26);
    if (u == 0) cluster_arrive();
    if (u == 1 || u == 2) bar_arrive(NB_V, 288);
    bar_sync(NB_WG0 + u, 128);
    if (wid == 4 && elect()) bulk_load(sb + OFF_CF, p.tab->mat, 12288, mb + 8 * MB_CF);
    __syncwarp();
    const uint32_t k0 = pack(c[0] + c[6], c[1] + c[7]), k1 = pack(c[8] + c[14], c[9] + c[15]);
    const uint32_t k2 = pack(c[16] + c[22], c[17] + c[23]), k3 = pack(c[24] + c[30], c[25] + c[31]);
    const uint32_t ka = tab + 16 * (8 * w + (g ^ w));
    sts32(ka + 4 * t, k0);
    sts32(ka + 512 + 4 * t, k1);
    sts64(ka + 1024 + 512 * (t >> 1) + 8 * (t & 1), prmt(k2, 0, 0x1010), (t & 1) ? prmt(k2, 0, 0x3232) : k2);
    const uint32_t lo = prmt(k3, 0, 0x1010), hi = prmt(k3, 0, 0x3232);
    sts128(ka + 2048 + 512 * t, lo, lo, (g & 1) ? hi : k3, hi);
    put_exp(sb + OFF_MX + u * 64 + 4 * w, amax2(amax2(k0, k1), amax2(k2, k3)), lane);
    cluster_wait();
    cluster_arrive();
    put(sb + u * 4096 + g * 512 + (g == rank ? OFF_UX : OFF_YB), x0, x1);
    TL(15);
    fence_async();
    bar_sync(NB_WG0 + u, 128);
    send(OFF_YB + u * 4096, OFF_UX + u * 4096 + 512 * rank, OFF_MB + 8 * (MB_UX + u));
    if (wid == 16) {
      bar_sync(NB_V, 288);
      if (elect()) tma_load3(sb + OFF_TV, &p.tv, ch0, 8 * rank, 0, mb + 8 * MB_KV);
      __syncwarp();
    }
  }
  if (u == 0) {
    float ga[4][4];
#pragma unroll
    for (int i = 0; i < 4; i++) ga[i][0] = ga[i][1] = ga[i][2] = ga[i][3] = 0.f;
#pragma unroll
    for (int j = 0; j < 5; j++) {
      uint32_t a0[4], a1[4], b;
      ldsm4(a0, sb + OFF_TQ + toff + 16 * j);
      ldsm4(a1, sb + OFF_TQ + toff + 2560 + 16 * j);
      asm volatile("ld.shared.u32 %0, [%1];" : "=r"(b) : "r"(sb + OFF_SP + 16 * j + 4 * t) : "memory");
      if (j >= 2 && j >= nu) b = 0;
      mma1688(ga[0], a0[0], a0[1], b); mma1688(ga[1], a0[2], a0[3], b); mma1688(ga[2], a1[0], a1[1], b); mma1688(ga[3], a1[2], a1[3], b);
    }
    const float s0 = t == 0 ? ga[0][0] : t == 1 ? ga[1][0] : t == 2 ? ga[2][0] : ga[3][0];
    const float s1 = t == 0 ? ga[0][2] : t == 1 ? ga[1][2] : t == 2 ? ga[2][2] : ga[3][2];
    tag = (lds64(mb + 8 * MB_TAG).x >> 4) + 1;
    uint2* gp = p.part + cl * SEQ + rank * 256 + 64 * w + 16 * t + g;
    asm volatile("st.relaxed.gpu.global.u64 [%0], %1;" :: "l"(gp), "l"(((uint64_t)tag << 32) | __float_as_uint(s0)) : "memory");
    asm volatile("st.relaxed.gpu.global.u64 [%0], %1;" :: "l"(gp + 8), "l"(((uint64_t)tag << 32) | __float_as_uint(s1)) : "memory");
  }

#pragma unroll
  for (int isA = 0; isA < 2; isA++) {
    {
      TL(1 + isA);
      const uint32_t usrc = isA ? tab + T_UKV : sb + OFF_UX + u * 4096;
      const uint32_t mxa = sb + OFF_MX + u * 64 + 32 * isA;
      const uint32_t pd = lds16(sb + OFF_SP + 80 + 80 * isA + 16 * u + 2 * rank);
      float D[32];
      uint32_t As[8], F[16], H[16], X[16];
      const uint32_t eh = min(max((int)get_exp(mxa), (int)((pd >> 7) & 0xff) - 5), 240);
      scale_a1(As, A1, 248 - eh);
      wg_fence();
      stage1(D, As, isA ? tab + T_HA : tab);
      wg_commit();
      wg_wait<0>(); tie_all(D);
      fwd_mid(F, D, tc, ts);
      if (!isA) mbar_wait(mb + 8 * MB_CF);
      wg_fence();
      stage2<0>(H, F, sb + OFF_CF);
      wg_commit();
      if (!isA) {
        if (w == 2 && elect()) bulk_load(tab + T_HA, p.ssm_k + (size_t)(act ? ch0 + 8 * u + rank : 0) * SEQ, 4096, mb + 8 * (MB_HA + u));
        __syncwarp();
        TL(7);
      }
      if (isA) fence_async();
      mbar_wait(mb + 8 * ((isA ? MB_UKV : MB_UX) + u));
      TL(5 + isA);
      put_exp(mxa + 16 + 4 * w, seq_mag(usrc + 16 * tid), lane);
      bar_sync(NB_WG0 + u, 128);
      if (isA) {
        send(OFF_UX + u * 4096, OFF_YB + (8 * u + rank) * 512, OFF_MB + 8 * (MB_Y + u));
      }
      const uint32_t eu = min(get_exp(mxa + 16), 240u);
      scale_a1(As, A1, 250 - eu);
      wg_wait<0>(); tie_all(H);
      wg_fence();
      stage1(D, As, usrc);
      wg_commit();
      wg_wait<0>(); tie_all(D);
      fwd_mid(F, D, tc, ts);
      wg_fence();
      stage2<0>(X, F, sb + OFF_CF);
      wg_commit();
      {
        const float dsk = blo(pd) * __uint_as_float((248 - eh) << 23);
        const uint32_t d2 = packh(dsk, dsk);
#pragma unroll
        for (int j = 0; j < 4; j++) H[2 * j] = U2(__hadd2(H2(H[2 * j]), H2(d2)));
      }
      wg_wait<0>(); tie_all(X);
#pragma unroll
      for (int j = 0; j < 4; j++) {
        const uint32_t h0r = H[2 * j], h1r = H[2 * j + 1], h0i = H[8 + 2 * j], h1i = H[9 + 2 * j];
        const uint32_t x0r = X[2 * j], x1r = X[2 * j + 1], x0i = X[8 + 2 * j], x1i = X[9 + 2 * j];
        F[2 * j] = ffma(x0r, h0r, fneg(fmul(x0i, h0i)));
        F[8 + 2 * j] = ffma(x0r, h0i, fmul(x0i, h0r));
        F[2 * j + 1] = ffma(x1r, h0r, ffma(fneg(x1i), h0i, ffma(x0r, h1r, fneg(ffma(x0i, h1i, F[8 + 2 * j])))));
        F[9 + 2 * j] = ffma(x1r, h0i, ffma(x1i, h0r, ffma(x0r, h1i, ffma(x0i, h1r, F[2 * j]))));
      }
      wg_fence();
      stage2<1>(H, F, sb + OFF_CF);
      wg_commit();
      uint64_t ga[4];
      const int sl2 = min(18 * cl + min(8 * w + g, 17), 255), sl3 = tid + 128 * (u & 1);
      auto gload = [&]() {
        if (isA) {
          asm volatile("ld.relaxed.gpu.global.u64 %0, [%1];" : "=l"(ga[0]) : "l"(p.part + NCL * SEQ + rank * 256 + sl3) : "memory");
        } else {
#pragma unroll
          for (int k = 0; k < 4; k++)
            asm volatile("ld.relaxed.gpu.global.u64 %0, [%1];" : "=l"(ga[k]) : "l"(p.part + (t + (k == 3 && t == 3 ? 8 : 4 * k)) * SEQ + rank * 256 + sl2) : "memory");
        }
      };
      if (isA ? (u & 6) == 2 : u == 1) gload();
      if (isA) TL(23);
      wg_wait<0>(); tie_all(H);
      {
        const uint32_t va = tab + (16 * w + (lane & 15)) * 128;
        const int vx = (lane >> 4) ^ (lane & 7);
#pragma unroll
        for (int j = 0; j < 4; j++) {
          uint32_t V[4];
#pragma unroll
          for (int b = 0; b < 2; b++) {
            const uint32_t er = H[2 * j + b], ei = H[8 + 2 * j + b];
            V[2 * b] = ffma(er, tc[j], fneg(fmul(ei, ts[j])));
            V[2 * b + 1] = ffma(ei, tc[j], fmul(er, ts[j]));
          }
          stsm4(va + ((vx ^ (2 * j)) << 4), V);
        }
      }
      if (!isA) {
        cluster_wait();
        mbar_wait(mb + 8 * MB_KV);
        TL(21);
        uint32_t K[3][4], V[2][4];
        const uint2 psw = lds64(sb + OFF_SP + 240 + 64 * u + 8 * g);
        ldsm4t(K[0], w ? sb + OFF_TK + toff - 2560 : (lane & 7) ? sb + OFF_TK + toff + 223 * 80 : sb + OFF_HALO + 10 * lane + 16 * u);
        ldsm4t(K[1], sb + OFF_TK + toff);
        ldsm4t(K[2], sb + OFF_TK + toff + 2560);
        ldsm4t(V[0], sb + OFF_TV + toff);
        ldsm4t(V[1], sb + OFF_TV + toff + 2560);
        mbar_wait(mb + 8 * (MB_HA + u));
        const uint4 hx = lds128(tab + T_HA + 16 * tid), hy = lds128(tab + T_HA + 2048 + 16 * tid);
        const uint32_t w0 = prmt(psw.x, 0, 0x1010), w1 = prmt(psw.x, 0, 0x3232), w2 = prmt(psw.y, 0, 0x1010), w3 = prmt(psw.y, 0, 0x3232);
#pragma unroll
        for (int m = 4; m < 12; m++)
          V[(m >> 2) - 1][m & 3] = hmul2(hfma2(K[m >> 2][m & 3], w0, hfma2(K[(m - 1) >> 2][(m - 1) & 3], w1,
                                         hfma2(K[(m - 2) >> 2][(m - 2) & 3], w2, hmul2(K[(m - 3) >> 2][(m - 3) & 3], w3)))), V[(m >> 2) - 1][m & 3]);
        put(g == rank ? tab + T_UKV + 512 * rank : sb + OFF_YA + u * 4096 + g * 512, V[0], V[1]);
        put_exp(mxa + 32 + 4 * w, amax2(amax2(amax2(hx.x, hx.y), amax2(hx.z, hx.w)), amax2(amax2(hy.x, hy.y), amax2(hy.z, hy.w))), lane);
        sts128(tab + T_HA + 16 * (tid ^ (lane >> 3)), hx.x, hx.y, hx.z, hx.w);
        sts128(tab + T_HA + 2048 + 16 * (tid ^ (lane >> 3)), hy.x, hy.y, hy.z, hy.w);
        TL(22);
      }
      fence_async();
      bar_sync(NB_WG0 + u, 128);
      float O[16];
      {
        const uint64_t dv = desc_lo(tab) | (1ull << 16) | (64ull << 32) | (1ull << 62);
        const uint64_t dl = desc_lo(sb + OFF_CL) | (32ull << 16) | (8ull << 32);
        wg_fence();
        ss32<0, 0, 0>(O, dv, dl); ss32<1, 128, 64>(O, dv, dl); ss32<1, 256, 128>(O, dv, dl); ss32<1, 384, 192>(O, dv, dl);
        wg_commit();
      }
      if (!isA) send(OFF_YA + u * 4096, OFF_T + u * KTAB + T_UKV + 512 * rank, OFF_MB + 8 * (MB_UKV + u));
      if (isA ? (u & 6) == 2 : u == 1) {
        tag = (lds64(mb + 8 * MB_TAG).x >> 4) + 1;
        bool ok;
#pragma unroll 1
        for (int it = 0;; it++) {
          ok = (uint32_t)(ga[0] >> 32) == tag;
          if (!isA) ok = ok && (uint32_t)(ga[1] >> 32) == tag && (uint32_t)(ga[2] >> 32) == tag && (uint32_t)(ga[3] >> 32) == tag;
          ok = __all_sync(0xffffffffu, ok);
          if (ok || it == (isA ? 8000 : 2000)) break;
          gload();
        }
        if (!isA) {
          float s = __uint_as_float((uint32_t)ga[0]) + __uint_as_float((uint32_t)ga[1]) + __uint_as_float((uint32_t)ga[2]);
          if (t < 3) s += __uint_as_float((uint32_t)ga[3]);
          s += __shfl_xor_sync(0xffffffffu, s, 1);
          s += __shfl_xor_sync(0xffffffffu, s, 2);
          const float g0 = bf16r(sigmoidf_(bf16r(s)));
          if (ok && t == 0)
            asm volatile("st.relaxed.gpu.global.u64 [%0], %1;" :: "l"(p.part + NCL * SEQ + rank * 256 + sl2), "l"(((uint64_t)tag << 32) | pack(g0, 1.f - g0)) : "memory");
        } else {
          uint32_t gv = (uint32_t)ga[0];
          if (!ok) {
            const uint32_t* xr = (const uint32_t*)(p.q + (size_t)(rank * 256 + 32 * (sl3 & 7) + (sl3 >> 3)) * DCH);
            const uint32_t* gr = (const uint32_t*)p.gate_w;
            float s = 0.f;
#pragma unroll 1
            for (int k = 0; k < DCH / 2; k++) { const uint32_t x = __ldg(xr + k), y = __ldg(gr + k); s = fmaf(blo(x), blo(y), fmaf(bhi(x), bhi(y), s)); }
            const float g0 = bf16r(sigmoidf_(bf16r(s)));
            gv = pack(g0, 1.f - g0);
          }
          sts64(sb + OFF_GB + 8 * sl3, prmt(gv, 0, 0x1010), prmt(gv, 0, 0x3232));
          __syncwarp();
          if (lane == 0) mbar_arrive(mb + 8 * MB_G);
        }
      }
      if (isA) TL(28);
      wg_wait<0>(); tie_all(O);
      {
        const uint32_t co = ((8 * w + g) ^ (2 * t) ^ rank) * 16;
        const int yo = (isA ? OFF_YA : OFF_YB) + (8 * u + rank) * 512, ym = OFF_MB + 8 * (MB_Y + u);
        const uint32_t us = min(max((int)(eu + eh) - 127, 0), 254) * 0x00800080u;
        const uint32_t a0 = hmul2(pack(O[0], O[1]), us), a1 = hmul2(pack(O[4], O[5]), us), a2 = hmul2(pack(O[8], O[9]), us), a3 = hmul2(pack(O[12], O[13]), us);
        const uint32_t b0 = hmul2(pack(O[2], O[3]), us), b1 = hmul2(pack(O[6], O[7]), us), b2 = hmul2(pack(O[10], O[11]), us), b3 = hmul2(pack(O[14], O[15]), us);
        sts128((t == rank ? sb + yo : usrc + t * 512) + co, a0, a1, a2, a3);
        sts128((t + 4 == rank ? sb + yo : usrc + t * 512 + 2048) + co, b0, b1, b2, b3);
        if (isA) {
          fence_async();
          bar_sync(NB_WG0 + u, 128);
          send(usrc - sb, yo, ym);
        }
      }
      TL(9 + isA);
    }
  }

  {
    mbar_wait(mb + 8 * MB_G);
    uint2 gg[2][4];
    uint32_t qv[2][4];
#pragma unroll
    for (int hh = 0; hh < 2; hh++)
#pragma unroll
      for (int i = 0; i < 4; i++) gg[hh][i] = lds64(sb + OFF_GB + 8 * (64 * w + 32 * hh + 8 * i + g));
    const uint32_t qa = sb + OFF_TQ + toff;
    ldsm4(qv[0], qa);
    ldsm4(qv[1], qa + 2560);
    TL(24);
    mbar_wait(mb + 8 * (MB_Y + u));
    uint32_t ya[2][4], yb[2][4];
#pragma unroll
    for (int hh = 0; hh < 2; hh++) {
      const uint32_t yo = (8 * u + (lane & 7)) * 512 + ((8 * w + 4 * hh + (lane >> 3)) ^ (2 * (rank & 3)) ^ (lane & 7)) * 16;
      ldsm4t(ya[hh], sb + OFF_YA + yo); ldsm4t(yb[hh], sb + OFF_YB + yo);
    }
#pragma unroll
    for (int hh = 0; hh < 2; hh++) {
      uint32_t o[4];
#pragma unroll
      for (int i = 0; i < 4; i++) o[i] = hadd2(hmul2(gg[hh][i].x, hmul2(qv[hh][i], ya[hh][i])), hmul2(gg[hh][i].y, yb[hh][i]));
      stsm4(qa + 2560 * hh, o);
    }
    TL(25);
  }
  cluster_arrive();
  bar_sync(NB_ROW0 + w, 160);
  {
    uint4 v[2];
#pragma unroll
    for (int k = 0; k < 2; k++) {
      const int i = 64 * u + 32 * k + lane, sl = (i * 205) >> 10, cc = i - 5 * sl;
      v[k] = lds128(sb + OFF_TQ + (64 * w + 8 * (sl & 7) + (sl >> 3)) * 80 + cc * 16);
    }
#pragma unroll
    for (int k = 0; k < 2; k++) {
      const int i = 64 * u + 32 * k + lane, sl = (i * 205) >> 10, cc = i - 5 * sl;
      if (cc < nu)
        asm volatile("st.global.v4.u32 [%0], {%1,%2,%3,%4};" :: "l"(p.out + (size_t)(256 * rank + 32 * (sl >> 3) + 8 * w + (sl & 7)) * DCH + ch0 + 8 * cc),
                     "r"(v[k].x), "r"(v[k].y), "r"(v[k].z), "r"(v[k].w) : "memory");
    }
  }
  cluster_wait();
  TL(27);
  TL_DUMP();
}

typedef CUresult (*EncodeFn)(CUtensorMap*, CUtensorMapDataType, cuuint32_t, void*, const cuuint64_t*, const cuuint64_t*,
                             const cuuint32_t*, const cuuint32_t*, CUtensorMapInterleave, CUtensorMapSwizzle,
                             CUtensorMapL2promotion, CUtensorMapFloatOOBfill);

void encode(EncodeFn fn, CUtensorMap* tm, const void* ptr, int nd, const cuuint64_t* dims, const cuuint64_t* strides,
            const cuuint32_t* box, CUtensorMapSwizzle swz) {
  cuuint32_t es[4] = {1, 1, 1, 1};
  fn(tm, CU_TENSOR_MAP_DATA_TYPE_BFLOAT16, nd, const_cast<void*>(ptr), dims, strides, box, es, CU_TENSOR_MAP_INTERLEAVE_NONE,
     swz, CU_TENSOR_MAP_L2_PROMOTION_L2_128B, CU_TENSOR_MAP_FLOAT_OOB_FILL_NONE);
}
void make_map(EncodeFn fn, CUtensorMap* tm, const void* ptr, int ne, int nr) {
  const cuuint64_t dims[3] = {DCH, SEQ / 32, 32}, strides[2] = {32 * DCH * 2, DCH * 2};
  const cuuint32_t box[3] = {CPC, (cuuint32_t)ne, (cuuint32_t)nr};
  encode(fn, tm, ptr, 3, dims, strides, box, CU_TENSOR_MAP_SWIZZLE_NONE);
}

}

extern "C" void kernel_launch(void* const* d_in, const int* in_sizes, int n_in, void* d_out, int out_size) {
  (void)in_sizes; (void)n_in; (void)out_size;
  static EncodeFn fn = nullptr;
  static void *tab = nullptr, *cnt = nullptr, *part = nullptr;
  if (!fn) {
    cudaGetSymbolAddress(&tab, d_tab);
    cudaGetSymbolAddress(&cnt, g_cnt);
    cudaGetSymbolAddress(&part, g_part);
    cudaDriverEntryPointQueryResult qr;
    cudaGetDriverEntryPoint("cuTensorMapEncodeTiled", (void**)&fn, cudaEnableDefault, &qr);
    cudaFuncSetAttribute(fused_kernel, cudaFuncAttributeMaxDynamicSharedMemorySize, SMEM_BYTES);
  }
  Params p;
  make_map(fn, &p.tq, d_in[0], 8, 32);
  make_map(fn, &p.tk, d_in[1], 8, 32);
  make_map(fn, &p.tv, d_in[2], 8, 32);
  make_map(fn, &p.tkh, d_in[1], 1, 4);
  p.out = (__nv_bfloat16*)d_out;
  p.tab = (const Tables*)tab;
  p.cnt = (unsigned*)cnt;
  p.part = (uint2*)part;
  p.tl = nullptr;
  p.q = (const __nv_bfloat16*)d_in[0];
  p.ssm_k = (const __nv_bfloat16*)d_in[4];
  p.shift_k = (const __nv_bfloat16*)d_in[3];
  p.ssm_D = (const __nv_bfloat16*)d_in[5];
  p.logA = (const __nv_bfloat16*)d_in[7];
  p.Aim = (const __nv_bfloat16*)d_in[8];
  p.Cre = (const __nv_bfloat16*)d_in[9];
  p.Cim = (const __nv_bfloat16*)d_in[10];
  p.logdt = (const __nv_bfloat16*)d_in[11];
  p.Dskip = (const __nv_bfloat16*)d_in[12];
  p.gate_w = (const __nv_bfloat16*)d_in[13];
  fused_kernel<<<NCL * CS, NTHREADS, SMEM_BYTES, cudaStreamPerThread>>>(p);
}
```

```cpp
#include <cuda_runtime.h>
#include <cuda_bf16.h>
#include <cuda_fp16.h>
#include <cuda.h>
#include <stdint.h>

#define TIMELINE 0
#define STAGGER 1
#define TLHI 0

namespace {

constexpr int SEQ = 2048, DCH = 576, NMODE = 128;
constexpr int CS = 8, CPC = 40, NCL = 15, NTHREADS = 640;

constexpr int KTAB = 16384;
constexpr int OFF_T = 0;
constexpr int T_UKV = 8192, T_HA = 12288;
constexpr int OFF_UX = 5 * KTAB;
constexpr int OFF_IM = OFF_UX + 20480;
constexpr int OFF_CF = OFF_IM;
constexpr int OFF_CL = OFF_CF + 8192;
constexpr int OFF_TV = OFF_CL + 4096;
constexpr int OFF_YA = OFF_TV + 20480;
constexpr int OFF_GB = OFF_YA + 20480;
constexpr int OFF_YB = OFF_IM + 4 * KTAB;
constexpr int OFF_TQ = OFF_YB + 20480;
constexpr int OFF_TK = OFF_TQ + 20480;
constexpr int OFF_HALO = OFF_TK + 20480;
constexpr int OFF_MX = OFF_HALO + 320;
constexpr int OFF_SP = OFF_MX + 320;
constexpr int OFF_MB = OFF_SP + 560;
constexpr int OFF_TL = OFF_MB + 28 * 8;
constexpr int SMEM_BYTES = OFF_TL + (TIMELINE ? 1280 : 0);
static_assert(SMEM_BYTES <= 232448 && OFF_YA == OFF_IM + 2 * KTAB && OFF_GB + 2048 <= OFF_YB, "smem");
static_assert((OFF_MB & 7) == 0 && (OFF_MX & 15) == 0 && (OFF_SP & 15) == 0, "align");

enum { MB_UX = 0, MB_UKV = 5, MB_Y = 10, MB_HA = 15, MB_XQ = 20, MB_KV = 21, MB_CF = 22, MB_G = 23, MB_TH = 24, MB_TAG = 25 };
enum { NB_WG0 = 1, NB_ROW0 = 6, NB_ORD = 6, NB_V = 10, NB_ST = 11 };

constexpr double cos_turn(int m, int n) {
  m &= n - 1;
  if (m > n / 2) m = n - m;
  double sgn = 1.0;
  if (m > n / 4) { m = n / 2 - m; sgn = -1.0; }
  if (m == n / 4) return 0.0;
  const double x = 6.283185307179586476925 * m / n;
  double term = 1.0, sum = 1.0;
  for (int k = 1; k < 14; k++) { term *= -x * x / ((2 * k - 1) * (2 * k)); sum += term; }
  return sgn * sum;
}
constexpr uint32_t bf16_bits(double v) {
  if (v == 0.0) return 0;
  uint32_t sgn = 0;
  if (v < 0) { sgn = 0x8000; v = -v; }
  int e = 127;
  while (v < 1.0) { v *= 2.0; e--; }
  while (v >= 2.0) { v *= 0.5; e++; }
  const double f = v * 128.0;
  int m = (int)f;
  if (f - m > 0.5 || (f - m == 0.5 && (m & 1))) m++;
  return sgn | (uint32_t)((e << 7) + (m - 128));
}
constexpr uint32_t f16_bits(double v) {
  if (v == 0.0) return 0;
  uint32_t sgn = 0;
  if (v < 0) { sgn = 0x8000; v = -v; }
  int e = 15;
  while (v < 1.0) { v *= 2.0; e--; }
  const double f = v * 1024.0;
  int m = (int)f;
  if (f - m > 0.5 || (f - m == 0.5 && (m & 1))) m++;
  return sgn | (uint32_t)((e << 10) + (m - 1024));
}
constexpr uint32_t pair_bits(double lo, double hi) { return bf16_bits(lo) | (bf16_bits(hi) << 16); }
constexpr uint32_t pair_h(double lo, double hi) { return f16_bits(lo) | (f16_bits(hi) << 16); }
struct alignas(128) Tables {
  uint32_t mat[3072];
  uint32_t thr[4][128][4];
};
constexpr Tables make_tables() {
  Tables T{};
  for (int q = 0; q < 768; q++) {
    int m0 = 0, d0 = 0, d1 = 0;
    if (q < 512) {
      const int r = (q >> 6) * 8 + (q & 7), cc = (q >> 3) & 7;
      d0 = 4 * (r & 31); d1 = 2 * d0;
      m0 = 8 * (cc & 3) * d0 + ((r >> 5) == (cc >> 2) ? 0 : (r >> 5) ? 96 : 32);
    } else {
      const int r = ((q - 512) >> 5) * 8 + (q & 7), pc = (q >> 3) & 3;
      d0 = 4 * (8 * (r >> 4) + (r & 7)) + 1; d1 = 8 * d0;
      m0 = 2 * pc * d0 + ((r & 8) ? 32 : 0);
    }
    for (int e = 0; e < 4; e++) T.mat[4 * q + e] = pair_h(cos_turn(m0 + e * d1, 128), cos_turn(m0 + e * d1 + d0, 128));
  }
  for (int tid = 0; tid < 128; tid++) {
    const int kk = 4 * (tid >> 2) + 1, t = tid & 3;
    for (int q = 0; q < 4; q++) {
      const int m = (8 * q + 2 * t) * kk;
      T.thr[q >> 1][tid][2 * (q & 1)] = pair_bits(cos_turn(m, 128), cos_turn(m + kk, 128));
      T.thr[q >> 1][tid][2 * (q & 1) + 1] = pair_bits(cos_turn(m + 32, 128), cos_turn(m + kk + 32, 128));
      T.thr[2][tid][q] = pair_h(cos_turn(m, 4096), cos_turn(m + kk, 4096));
      T.thr[3][tid][q] = pair_h(cos_turn(m + 3072, 4096), cos_turn(m + kk + 3072, 4096));
    }
  }
  return T;
}
__device__ const Tables d_tab = make_tables();

struct Params {
  const __nv_bfloat16 *logA, *Aim, *Cre, *Cim, *logdt;
  const Tables* tab;
  unsigned* cnt;
  const __nv_bfloat16 *Dskip, *shift_k, *ssm_D, *gate_w, *q, *v, *ssm_k;
  uint2* part;
  __nv_bfloat16* out;
  unsigned* tl;
  CUtensorMap tq, tk, tv, tkh;
};

__device__ uint2 g_part[(NCL + 1) * SEQ];
__device__ unsigned g_cnt[CS * 32];
#define TL(i) do {} while (0)
#define TL_INIT() do {} while (0)
#define TL_DUMP() do {} while (0)

__device__ __forceinline__ uint32_t lds16(uint32_t a) { uint32_t v; asm volatile("ld.shared.u16 %0, [%1];" : "=r"(v) : "r"(a) : "memory"); return v; }
__device__ __forceinline__ uint2 lds64(uint32_t a) { uint2 v; asm volatile("ld.shared.v2.u32 {%0,%1}, [%2];" : "=r"(v.x), "=r"(v.y) : "r"(a) : "memory"); return v; }
__device__ __forceinline__ uint4 lds128(uint32_t a) { uint4 v; asm volatile("ld.shared.v4.u32 {%0,%1,%2,%3}, [%4];" : "=r"(v.x), "=r"(v.y), "=r"(v.z), "=r"(v.w) : "r"(a) : "memory"); return v; }
__device__ __forceinline__ void sts16(uint32_t a, uint32_t v) { asm volatile("st.shared.u16 [%0], %1;" :: "r"(a), "r"(v) : "memory"); }
__device__ __forceinline__ void sts32(uint32_t a, uint32_t v) { asm volatile("st.shared.u32 [%0], %1;" :: "r"(a), "r"(v) : "memory"); }
__device__ __forceinline__ void sts64(uint32_t a, uint32_t x, uint32_t y) { asm volatile("st.shared.v2.u32 [%0], {%1,%2};" :: "r"(a), "r"(x), "r"(y) : "memory"); }
__device__ __forceinline__ void sts128(uint32_t a, uint32_t x, uint32_t y, uint32_t z, uint32_t w) { asm volatile("st.shared.v4.u32 [%0], {%1,%2,%3,%4};" :: "r"(a), "r"(x), "r"(y), "r"(z), "r"(w) : "memory"); }
__device__ __forceinline__ void ldsm4t(uint32_t (&r)[4], uint32_t a) { asm volatile("ldmatrix.sync.aligned.m8n8.x4.trans.shared.b16 {%0,%1,%2,%3}, [%4];" : "=r"(r[0]), "=r"(r[1]), "=r"(r[2]), "=r"(r[3]) : "r"(a) : "memory"); }
__device__ __forceinline__ void ldsm2t(uint32_t& r0, uint32_t& r1, uint32_t a) { asm volatile("ldmatrix.sync.aligned.m8n8.x2.trans.shared.b16 {%0,%1}, [%2];" : "=r"(r0), "=r"(r1) : "r"(a) : "memory"); }
__device__ __forceinline__ void ldsm4(uint32_t (&r)[4], uint32_t a) { asm volatile("ldmatrix.sync.aligned.m8n8.x4.shared.b16 {%0,%1,%2,%3}, [%4];" : "=r"(r[0]), "=r"(r[1]), "=r"(r[2]), "=r"(r[3]) : "r"(a) : "memory"); }
__device__ __forceinline__ void stsm4(uint32_t a, const uint32_t (&r)[4]) { asm volatile("stmatrix.sync.aligned.m8n8.x4.shared.b16 [%0], {%1,%2,%3,%4};" :: "r"(a), "r"(r[0]), "r"(r[1]), "r"(r[2]), "r"(r[3]) : "memory"); }
__device__ __forceinline__ uint32_t pack(float lo, float hi) { uint32_t r; asm("cvt.rn.bf16x2.f32 %0, %1, %2;" : "=r"(r) : "f"(hi), "f"(lo)); return r; }
__device__ __forceinline__ float blo(uint32_t v) { return __uint_as_float(v << 16); }
__device__ __forceinline__ float bhi(uint32_t v) { return __uint_as_float(v & 0xffff0000u); }
__device__ __forceinline__ float bf16r(float x) { return blo(pack(x, 0.f)); }
__device__ __forceinline__ uint32_t hmul2(uint32_t a, uint32_t b) { uint32_t r; asm("mul.rn.bf16x2 %0, %1, %2;" : "=r"(r) : "r"(a), "r"(b)); return r; }
__device__ __forceinline__ uint32_t hadd2(uint32_t a, uint32_t b) { uint32_t r; asm("add.rn.bf16x2 %0, %1, %2;" : "=r"(r) : "r"(a), "r"(b)); return r; }
__device__ __forceinline__ uint32_t hfma2(uint32_t a, uint32_t b, uint32_t c) { uint32_t r; asm("fma.rn.bf16x2 %0, %1, %2, %3;" : "=r"(r) : "r"(a), "r"(b), "r"(c)); return r; }
__device__ __forceinline__ uint32_t packh(float lo, float hi) { uint32_t r; asm("cvt.rn.f16x2.f32 %0, %1, %2;" : "=r"(r) : "f"(hi), "f"(lo)); return r; }
__device__ __forceinline__ __half2 H2(uint32_t a) { return *reinterpret_cast<__half2*>(&a); }
__device__ __forceinline__ uint32_t U2(__half2 a) { return *reinterpret_cast<uint32_t*>(&a); }
__device__ __forceinline__ uint32_t fmul(uint32_t a, uint32_t b) { return U2(__hmul2(H2(a), H2(b))); }
__device__ __forceinline__ uint32_t ffma(uint32_t a, uint32_t b, uint32_t c) { return U2(__hfma2(H2(a), H2(b), H2(c))); }
__device__ __forceinline__ uint32_t fneg(uint32_t a) { return U2(__hneg2(H2(a))); }
__device__ __forceinline__ uint32_t amax2(uint32_t a, uint32_t b) { uint32_t r; asm("max.xorsign.abs.bf16x2 %0, %1, %2;" : "=r"(r) : "r"(a), "r"(b)); return r; }
__device__ __forceinline__ uint32_t prmt(uint32_t a, uint32_t b, uint32_t s) { return __byte_perm(a, b, s); }
__device__ __forceinline__ uint32_t ldraw(const __nv_bfloat16* p) { uint32_t v; asm volatile("ld.global.nc.u16 %0, [%1];" : "=r"(v) : "l"(p)); return v; }
__device__ __forceinline__ uint4 ldg128(const void* p) { uint4 v; asm volatile("ld.global.nc.v4.u32 {%0,%1,%2,%3}, [%4];" : "=r"(v.x), "=r"(v.y), "=r"(v.z), "=r"(v.w) : "l"(p)); return v; }
__device__ __forceinline__ void bar_sync(int id, int n) { asm volatile("bar.sync %0, %1;" :: "r"(id), "r"(n) : "memory"); }
__device__ __forceinline__ void bar_arrive(int id, int n) { asm volatile("bar.arrive %0, %1;" :: "r"(id), "r"(n) : "memory"); }
__device__ __forceinline__ void cluster_arrive() { asm volatile("barrier.cluster.arrive.relaxed.aligned;" ::: "memory"); }
__device__ __forceinline__ void cluster_wait() { asm volatile("barrier.cluster.wait.aligned;" ::: "memory"); }
__device__ __forceinline__ void fence_async() { asm volatile("fence.proxy.async.shared::cta;" ::: "memory"); }
__device__ __forceinline__ void fence_mbinit() { asm volatile("fence.mbarrier_init.release.cluster;" ::: "memory"); }
__device__ __forceinline__ uint32_t mapa(uint32_t a, uint32_t rank) { uint32_t r; asm("mapa.shared::cluster.u32 %0, %1, %2;" : "=r"(r) : "r"(a), "r"(rank)); return r; }
__device__ __forceinline__ void bulk_dsmem(uint32_t dst, uint32_t src, uint32_t mbar) {
  asm volatile("cp.async.bulk.shared::cluster.shared::cta.mbarrier::complete_tx::bytes [%0], [%1], 512, [%2];" :: "r"(dst), "r"(src), "r"(mbar) : "memory");
}
__device__ __forceinline__ void bulk_load(uint32_t dst, const void* src, uint32_t bytes, uint32_t mbar) {
  asm volatile("cp.async.bulk.shared::cluster.global.mbarrier::complete_tx::bytes [%0], [%1], %2, [%3];" :: "r"(dst), "l"(src), "r"(bytes), "r"(mbar) : "memory");
}
__device__ __forceinline__ void mbar_init(uint32_t m, uint32_t cnt) { asm volatile("mbarrier.init.shared::cta.b64 [%0], %1;" :: "r"(m), "r"(cnt) : "memory"); }
__device__ __forceinline__ void mbar_expect(uint32_t m, uint32_t bytes) { asm volatile("mbarrier.arrive.expect_tx.shared::cta.b64 _, [%0], %1;" :: "r"(m), "r"(bytes) : "memory"); }
__device__ __forceinline__ bool mbar_try(uint32_t m) {
  uint32_t done;
  asm volatile("{.reg .pred p; mbarrier.try_wait.parity.shared::cta.b64 p, [%1], 0; selp.u32 %0, 1, 0, p;}" : "=r"(done) : "r"(m) : "memory");
  return done;
}
__device__ __forceinline__ void mbar_wait(uint32_t m) {
  if (!mbar_try(m)) {
    int it = 0;
    while (!mbar_try(m) && ++it < (1 << 22)) {}
  }
}
__device__ __forceinline__ bool elect() {
  uint32_t e;
  asm volatile("{.reg .pred p; elect.sync _|p, 0xffffffff; selp.u32 %0, 1, 0, p;}" : "=r"(e));
  return e;
}
__device__ __forceinline__ void tma_load4(uint32_t dst, const CUtensorMap* tm, int c0, int c1, int c2, int c3, uint32_t mbar) {
  asm volatile("cp.async.bulk.tensor.4d.shared::cluster.global.mbarrier::complete_tx::bytes [%0], [%1, {%3, %4, %5, %6}], [%2];"
               :: "r"(dst), "l"(tm), "r"(mbar), "r"(c0), "r"(c1), "r"(c2), "r"(c3) : "memory");
}
__device__ __forceinline__ void tma_load3(uint32_t dst, const CUtensorMap* tm, int c0, int c1, int c2, uint32_t mbar) {
  asm volatile("cp.async.bulk.tensor.3d.shared::cluster.global.mbarrier::complete_tx::bytes [%0], [%1, {%3, %4, %5}], [%2];"
               :: "r"(dst), "l"(tm), "r"(mbar), "r"(c0), "r"(c1), "r"(c2) : "memory");
}
__device__ __forceinline__ void tma_store3(const CUtensorMap* tm, int c0, int c1, int c2, uint32_t src) {
  asm volatile("cp.async.bulk.tensor.3d.global.shared::cta.bulk_group [%0, {%2, %3, %4}], [%1];"
               :: "l"(tm), "r"(src), "r"(c0), "r"(c1), "r"(c2) : "memory");
}
__device__ __forceinline__ void mma1688(float (&c)[4], uint32_t a0, uint32_t a1, uint32_t b) {
  asm volatile("mma.sync.aligned.m16n8k8.row.col.f32.bf16.bf16.f32 {%0,%1,%2,%3}, {%4,%5}, {%6}, {%0,%1,%2,%3};"
               : "+f"(c[0]), "+f"(c[1]), "+f"(c[2]), "+f"(c[3]) : "r"(a0), "r"(a1), "r"(b));
}
__device__ __forceinline__ void wg_fence() { asm volatile("wgmma.fence.sync.aligned;" ::: "memory"); }
__device__ __forceinline__ void wg_commit() { asm volatile("wgmma.commit_group.sync.aligned;" ::: "memory"); }
template <int N> __device__ __forceinline__ void wg_wait() { asm volatile("wgmma.wait_group.sync.aligned %0;" :: "n"(N) : "memory"); }
template <int N> __device__ __forceinline__ void tie_all(uint32_t (&x)[N]) {
#pragma unroll
  for (int i = 0; i < N; i++) asm volatile("" : "+r"(x[i]) :: "memory");
}
template <int N> __device__ __forceinline__ void tie_all(float (&x)[N]) {
#pragma unroll
  for (int i = 0; i < N; i++) asm volatile("" : "+f"(x[i]) :: "memory");
}
#define R16(C, d) C(d[0]), C(d[1]), C(d[2]), C(d[3]), C(d[4]), C(d[5]), C(d[6]), C(d[7]), C(d[8]), C(d[9]), C(d[10]), C(d[11]), C(d[12]), C(d[13]), C(d[14]), C(d[15])
#define R32(C, d) R16(C, d), R16(C, (d + 16))
#define P16 "{%0,%1,%2,%3,%4,%5,%6,%7,%8,%9,%10,%11,%12,%13,%14,%15}"
#define P32 "{%0,%1,%2,%3,%4,%5,%6,%7,%8,%9,%10,%11,%12,%13,%14,%15,%16,%17,%18,%19,%20,%21,%22,%23,%24,%25,%26,%27,%28,%29,%30,%31}"
template <int SD, int TB, int OFF> __device__ __forceinline__ void rs64(float* d, const uint32_t* a, uint64_t db) {
  if (SD) asm volatile("{.reg .b64 db; add.s64 db, %36, %37; wgmma.mma_async.sync.aligned.m64n64k16.f32.bf16.bf16 " P32 ", {%32,%33,%34,%35}, db, 1, 1, 1, %38;}"
                       : R32("+f", d) : "r"(a[0]), "r"(a[1]), "r"(a[2]), "r"(a[3]), "l"(db), "n"(OFF), "n"(TB));
  else asm volatile("{.reg .b64 db; add.s64 db, %36, %37; wgmma.mma_async.sync.aligned.m64n64k16.f32.bf16.bf16 " P32 ", {%32,%33,%34,%35}, db, 0, 1, 1, %38;}"
                    : R32("=f", d) : "r"(a[0]), "r"(a[1]), "r"(a[2]), "r"(a[3]), "l"(db), "n"(OFF), "n"(TB));
}
template <int SD, int TB, int OFF> __device__ __forceinline__ void rs64h(uint32_t* d, const uint32_t* a, uint64_t db) {
  if (SD) asm volatile("{.reg .b64 db; add.s64 db, %20, %21; wgmma.mma_async.sync.aligned.m64n64k16.f16.f16.f16 " P16 ", {%16,%17,%18,%19}, db, 1, 1, 1, %22;}"
                       : R16("+r", d) : "r"(a[0]), "r"(a[1]), "r"(a[2]), "r"(a[3]), "l"(db), "n"(OFF), "n"(TB));
  else asm volatile("{.reg .b64 db; add.s64 db, %20, %21; wgmma.mma_async.sync.aligned.m64n64k16.f16.f16.f16 " P16 ", {%16,%17,%18,%19}, db, 0, 1, 1, %22;}"
                    : R16("=r", d) : "r"(a[0]), "r"(a[1]), "r"(a[2]), "r"(a[3]), "l"(db), "n"(OFF), "n"(TB));
}
template <int SD, int OFFA, int OFFB> __device__ __forceinline__ void ss32(float* d, uint64_t da, uint64_t db) {
  if (SD) asm volatile("{.reg .b64 da, db; add.s64 da, %16, %18; add.s64 db, %17, %19; wgmma.mma_async.sync.aligned.m64n32k16.f32.f16.f16 " P16 ", da, db, 1, 1, 1, 1, 1;}"
                       : R16("+f", d) : "l"(da), "l"(db), "n"(OFFA), "n"(OFFB));
  else asm volatile("{.reg .b64 da, db; add.s64 da, %16, %18; add.s64 db, %17, %19; wgmma.mma_async.sync.aligned.m64n32k16.f32.f16.f16 " P16 ", da, db, 0, 1, 1, 1, 1;}"
                    : R16("=f", d) : "l"(da), "l"(db), "n"(OFFA), "n"(OFFB));
}
#define KGEN_ASM(SD) "{.reg .b64 da, db; add.s64 da, %32, %33; add.s64 db, %32, %34;\n" \
  "wgmma.mma_async.sync.aligned.m64n64k16.f32.bf16.bf16 " P32 ", da, db, " SD ", 1, 1, 1, 1;}"
template <int KS> __device__ __forceinline__ void kgen_mma(float (&c)[32], uint64_t da) {
  if (KS) asm volatile(KGEN_ASM("1") : R32("+f", c) : "l"(da), "n"(8 * KS), "n"(8 * KS + 512));
  else asm volatile(KGEN_ASM("0") : R32("=f", c) : "l"(da), "n"(8 * KS), "n"(8 * KS + 512));
  if constexpr (KS < 7) kgen_mma<KS + 1>(c, da);
}
__device__ __forceinline__ uint64_t desc_lo(uint32_t a) { return (uint64_t)((a & 0x3FFFF) >> 4); }
__device__ __forceinline__ void stage1(float (&D)[32], const uint32_t (&A1)[8], uint32_t src) {
  const uint64_t du = desc_lo(src) | (128ull << 16) | (32ull << 32) | (2ull << 62);
  rs64<0, 1, 0>(D, A1, du); rs64<1, 1, 64>(D, A1 + 4, du);
}
template <int INV> __device__ __forceinline__ void stage2(uint32_t (&X)[16], const uint32_t (&F)[16], uint32_t cf) {
  constexpr int KS = INV ? 16 : 128, TB = INV ? 0 : 1;
  const uint64_t dc = desc_lo(cf) | (INV ? (8ull << 16) | (64ull << 32) : (64ull << 16) | (8ull << 32));
  rs64h<0, TB, 0>(X, F, dc); rs64h<1, TB, KS>(X, F + 4, dc); rs64h<1, TB, 2 * KS>(X, F + 8, dc); rs64h<1, TB, 3 * KS>(X, F + 12, dc);
}
__device__ __forceinline__ void fwd_mid(uint32_t (&F)[16], const float (&D)[32], const uint32_t (&tc)[4], const uint32_t (&ts)[4]) {
#pragma unroll
  for (int j = 0; j < 4; j++)
#pragma unroll
    for (int b = 0; b < 2; b++) {
      const int i = 4 * j + 16 * b;
      const uint32_t ar = packh(D[i], D[i + 1]), ai = packh(D[i + 2], D[i + 3]);
      F[2 * j + b] = ffma(ar, tc[j], fmul(ai, ts[j]));
      F[8 + 2 * j + b] = ffma(ai, tc[j], fneg(fmul(ar, ts[j])));
    }
}
__device__ __forceinline__ void put_exp(uint32_t a, uint32_t m, int lane) {
  m = __reduce_max_sync(0xffffffffu, max(m & 0x7f80u, (m >> 16) & 0x7f80u));
  if (lane == 0) sts32(a, m);
}
__device__ __forceinline__ uint32_t seq_mag(uint32_t a) {
  const uint4 x = lds128(a), y = lds128(a + 2048);
  return amax2(amax2(amax2(x.x, x.y), amax2(x.z, x.w)), amax2(amax2(y.x, y.y), amax2(y.z, y.w)));
}
__device__ __forceinline__ uint32_t get_exp(uint32_t a) { const uint4 v = lds128(a); return max(max(v.x, v.y), max(v.z, v.w)) >> 7; }
__device__ __forceinline__ void scale_a1(uint32_t (&As)[8], const uint32_t (&A1)[8], uint32_t field) {
#pragma unroll
  for (int i = 0; i < 8; i++) As[i] = hmul2(A1[i], field * 0x00800080u);
}

struct cf { float x, y; };
__device__ __forceinline__ cf cmul(cf a, cf b) { cf r; r.x = fmaf(a.x, b.x, -a.y * b.y); r.y = fmaf(a.x, b.y, a.y * b.x); return r; }
__device__ __forceinline__ cf cexp_p(float lr2, float lt, float p) {
  float m;
  asm("ex2.approx.ftz.f32 %0, %1;" : "=f"(m) : "f"(lr2 * p));
  float t = lt * p;
  t = (t - rintf(t)) * 6.283185307179586f;
  cf r; r.x = m * __cosf(t); r.y = m * __sinf(t); return r;
}
__device__ __forceinline__ void store8(uint32_t a, uint32_t b, const cf (&v)[8]) {
  sts128(a, pack(v[0].x, v[1].x), pack(v[2].x, v[3].x), pack(v[4].x, v[5].x), pack(v[6].x, v[7].x));
  sts128(b, pack(v[0].y, v[1].y), pack(v[2].y, v[3].y), pack(v[4].y, v[5].y), pack(v[6].y, v[7].y));
}
__device__ __forceinline__ void mbar_arrive(uint32_t m) { asm volatile("mbarrier.arrive.shared::cta.b64 _, [%0];" :: "r"(m) : "memory"); }
__device__ __forceinline__ float sigmoidf_(float s) { return __fdividef(1.f, 1.f + __expf(fminf(-s, 80.f))); }

__global__ void __cluster_dims__(CS, 1, 1) __launch_bounds__(NTHREADS, 1) fused_kernel(const __grid_constant__ Params p) {
  extern __shared__ __align__(1024) uint8_t smem[];
  TL_INIT();
  TL(31);
  const int wid = __shfl_sync(0xffffffffu, threadIdx.x >> 5, 0);
  const uint32_t sb = (uint32_t)__cvta_generic_to_shared(smem);
  const uint32_t mb = sb + OFF_MB;
  const int u = wid >> 2, w = wid & 3;
  const int tid = threadIdx.x & 127, lane = tid & 31, g = lane >> 2, t = lane & 3;
  const int cl = blockIdx.x >> 3, rank = blockIdx.x & 7;
  const int ch0 = cl * CPC;
  const int nu = min(5, (DCH - ch0) >> 3);
  const bool act = u < nu;

  uint32_t pla, pai, pcr, pci, pdt, tag = 0;
  auto load_params = [&]() {
    const int ch = act ? ch0 + 8 * u + rank : 0, o = ch * NMODE + tid;
    pla = ldraw(p.logA + o); pdt = ldraw(p.logdt + ch); pai = ldraw(p.Aim + o); pcr = ldraw(p.Cre + o); pci = ldraw(p.Cim + o);
  };
  if (u == 4) {
    const bool e = elect();
    if (e) {
#pragma unroll
      for (int i = 0; i < 5; i++) mbar_init(mb + 40 * w + 8 * i, 1);
      if (w == 3) { mbar_init(mb + 8 * MB_TH, 1); mbar_init(mb + 8 * MB_XQ, 21); mbar_init(mb + 8 * MB_KV, 1); }
      if (w == 2) { mbar_init(mb + 8 * MB_CF, 1); mbar_init(mb + 8 * MB_G, 8); }
      fence_mbinit();
    }
    __syncwarp();
    load_params();
    if (w == 0 && lane < 2) asm volatile("atom.relaxed.gpu.global.add.u32 %0, [%1], %2;" : "=r"(tag) : "l"(&p.cnt[rank * 32 + lane]), "r"(cl == 0 ? 16 - (NCL - 1) : 1) : "memory");
    if (e) {
      if (w == 3) {
        mbar_expect(mb + 8 * MB_TH, 8192 + 112 * nu);
        bulk_load(sb + OFF_YB, p.tab->thr, 8192, mb + 8 * MB_TH);
        bulk_load(sb + OFF_SP, p.gate_w + ch0, 16 * nu, mb + 8 * MB_TH);
        bulk_load(sb + OFF_SP + 80, p.Dskip + ch0, 16 * nu, mb + 8 * MB_TH);
        bulk_load(sb + OFF_SP + 160, p.ssm_D + ch0, 16 * nu, mb + 8 * MB_TH);
        bulk_load(sb + OFF_SP + 240, p.shift_k + 4 * ch0, 64 * nu, mb + 8 * MB_TH);
        asm volatile("cp.async.bulk.prefetch.L2.global [%0], 12288;" :: "l"(p.tab->mat) : "memory");
        mbar_expect(mb + 8 * MB_XQ, 20480);
        tma_load3(sb + OFF_TQ, &p.tq, ch0, 8 * rank, 0, mb + 8 * MB_XQ);
        TL(20);
        mbar_expect(mb + 8 * MB_KV, 2 * 20480 + 320);
        tma_load3(sb + OFF_TK, &p.tk, ch0, 8 * rank, 0, mb + 8 * MB_KV);
        tma_load3(sb + OFF_HALO, &p.tkh, ch0, 8 * rank - 1, 28, mb + 8 * MB_KV);
      }
      if (w == 2) mbar_expect(mb + 8 * MB_CF, 12288);
#pragma unroll
      for (int i = 0; i < 5; i++) mbar_expect(mb + 40 * w + 8 * i, w == 3 ? 4096 : w == 2 ? 7168 : 3584);
    }
    __syncwarp();
  } else {
    load_params();
  }
  cluster_arrive();
  TL(0);

  const uint32_t tab = sb + OFF_T + u * KTAB;
  const uint32_t toff = (64 * w + lane) * 80 + 16 * u;
  auto put = [&](uint32_t dst, const uint32_t (&a)[4], const uint32_t (&b)[4]) {
    const uint32_t s0 = (g & 1) ? 0x7632 : 0x5410, s1 = s0 ^ 0x2222;
    const uint32_t o = dst + 128 * t + 64 * (g & 1) + 16 * (w ^ t);
    sts128(o, prmt(a[0], a[1], s0), prmt(a[2], a[3], s0), prmt(b[0], b[1], s0), prmt(b[2], b[3], s0));
    sts128(o ^ 64, prmt(a[0], a[1], s1), prmt(a[2], a[3], s1), prmt(b[0], b[1], s1), prmt(b[2], b[3], s1));
  };
  const int d0 = rank ^ (2 * w), d1 = d0 ^ 1;
  const uint32_t rb0 = mapa(sb, d0), rb1 = mapa(sb, d1);
  auto send = [&](int stage, int dst, int mbar) {
    if (elect()) {
      if (w) bulk_dsmem(rb0 + dst, sb + stage + d0 * 512, rb0 + mbar);
      bulk_dsmem(rb1 + dst, sb + stage + d1 * 512, rb1 + mbar);
    }
    __syncwarp();
  };

  uint32_t A1[8], tc[4], ts[4];
  {
    const float dt = bf16r(expf(blo(pdt)));
    const float lr2 = (-bf16r(expf(blo(pla))) * dt) * 1.4426950408889634f;
    const float lt = (blo(pai) * dt) * 0.15915494309189535f;
    const uint32_t tim = sb + (u ? OFF_IM + (u - 1) * KTAB : OFF_UX);
    const uint32_t row = tab + tid * 16, rim = tim + tid * 16;
    const cf w1 = cexp_p(lr2, lt, 8.f);
    cf z1 = cexp_p(lr2, lt, 1.f), Z = cexp_p(lr2, lt, 256.f);
    if (lr2 != 123.f) TL(16);
    if (u == 3) {
      float z0_ = 0.f, z1_ = 0.f, z2_ = 0.f, z3_ = 0.f;
      asm volatile("mma.sync.aligned.m16n8k8.row.col.f32.bf16.bf16.f32 {%0,%1,%2,%3}, {%4,%4}, {%4}, {%0,%1,%2,%3};"
                   : "+f"(z0_), "+f"(z1_), "+f"(z2_), "+f"(z3_) : "r"(pla >> 16));
      pcr += __float_as_uint(z0_);
      TL(8);
    }
    if (u >= 2) bar_sync(NB_ST + u - 2, 256);
    TL(12);
    {
      cf v[8];
      v[0].x = 1.f; v[0].y = 0.f; v[1] = w1; v[2] = cmul(w1, w1); v[3] = cmul(v[2], w1);
      const cf w4 = cmul(v[2], v[2]);
      v[4] = w4; v[5] = cmul(v[1], w4); v[6] = cmul(v[2], w4); v[7] = cmul(v[3], w4);
      const cf w8 = cmul(w4, w4);
      store8(row, rim, v);
#pragma unroll
      for (int k = 1; k < 4; k++) {
#pragma unroll
        for (int i = 0; i < 8; i++) v[i] = (k == 1 && i == 0) ? w8 : cmul(v[i], w8);
        store8(row + 2048 * k, rim + 2048 * k, v);
      }
    }
    cluster_wait();
    if (u) cluster_arrive();
    mbar_wait(mb + 8 * MB_TH);
    {
      const uint4 x = lds128(sb + OFF_YB + 16 * tid), y = lds128(sb + OFF_YB + 2048 + 16 * tid), a = lds128(sb + OFF_YB + 4096 + 16 * tid), b = lds128(sb + OFF_YB + 6144 + 16 * tid);
      A1[0] = x.x; A1[1] = x.y; A1[2] = x.z; A1[3] = x.w; A1[4] = y.x; A1[5] = y.y; A1[6] = y.z; A1[7] = y.w;
      tc[0] = a.x; tc[1] = a.y; tc[2] = a.z; tc[3] = a.w; ts[0] = b.x; ts[1] = b.y; ts[2] = b.z; ts[3] = b.w;
    }
    if (wid == 16 && lane == 0) sts32(mb + 8 * MB_TAG, tag);
    __syncwarp();
    if (lane == 0) mbar_arrive(mb + 8 * MB_XQ);
    if (wid == 8 && elect()) {
      const uint32_t o = blockIdx.x * 9856u, n = min(9856u, SEQ * DCH - o) * 2;
      asm volatile("cp.async.bulk.prefetch.L2.global [%0], %1;" :: "l"(p.v + o), "r"(n) : "memory");
      asm volatile("cp.async.bulk.prefetch.L2.global [%0], %1;" :: "l"(p.ssm_k + o), "r"(n) : "memory");
    }
    __syncwarp();
    {
      z1.y = -z1.y; Z.y = -Z.y;
      const cf z2 = cmul(z1, z1);
      cf h[8], v[8];
      h[0].x = 2.f * blo(pcr) * dt; h[0].y = -2.f * blo(pci) * dt;
      h[1] = cmul(h[0], z1);
#pragma unroll
      for (int i = 2; i < 8; i++) h[i] = cmul(h[i - 2], z2);
      store8(row + 4 * 2048, rim + 4 * 2048, h);
      const cf h8 = cmul(h[6], z2);
      v[0] = cmul(h[0], Z); v[2] = cmul(h[2], Z); v[3] = cmul(h[4], Z); v[6] = cmul(h[6], Z); v[7] = cmul(h8, Z);
      v[1] = v[0]; v[4] = v[5] = v[3];
      store8(row + 5 * 2048, rim + 5 * 2048, v);
      h[0] = cmul(v[0], Z); h[1] = cmul(v[3], Z); h[3] = cmul(v[7], Z); h[4] = cmul(h[0], Z); h[5] = cmul(h[1], Z); h[7] = cmul(h[3], Z);
      h[2] = h[1]; h[6] = h[5];
      store8(row + 6 * 2048, rim + 6 * 2048, h);
      const cf Z2 = cmul(Z, Z);
      v[0] = cmul(h[0], Z2); v[1] = cmul(h[3], Z2); v[2] = cmul(h[4], Z2); v[3] = cmul(h[7], Z2);
#pragma unroll
      for (int i = 4; i < 8; i++) v[i] = cmul(v[i - 4], Z2);
      store8(row + 7 * 2048, rim + 7 * 2048, v);
    }
    TL(17);
    if (u < 3) bar_arrive(NB_ST + u, 256);
    fence_async();
    if (u) bar_sync(NB_ORD + u - 1, 256); else bar_sync(NB_WG0, 128);
    TL(13);
    float c[32];
    wg_fence();
    kgen_mma<0>(c, desc_lo(tab) | ((uint64_t)((tim - tab) >> 4) << 16) | (64ull << 32));
    wg_commit();
    if (u < 4) bar_arrive(NB_ORD + u, 256);
    TL(14);
    mbar_wait(mb + 8 * MB_XQ);
    TL(18);
    uint32_t x0[4], x1[4];
    ldsm4t(x0, sb + OFF_TQ + toff);
    ldsm4t(x1, sb + OFF_TQ + toff + 2560);
    wg_wait<0>(); tie_all(c);
    TL(26);
    if (u == 0) cluster_arrive();
    if (u == 1 || u == 2) bar_arrive(NB_V, 288);
    bar_sync(NB_WG0 + u, 128);
    if (wid == 4 && elect()) bulk_load(sb + OFF_CF, p.tab->mat, 12288, mb + 8 * MB_CF);
    __syncwarp();
    const uint32_t k0 = pack(c[0] + c[6], c[1] + c[7]), k1 = pack(c[8] + c[14], c[9] + c[15]);
    const uint32_t k2 = pack(c[16] + c[22], c[17] + c[23]), k3 = pack(c[24] + c[30], c[25] + c[31]);
    const uint32_t ka = tab + 16 * (8 * w + (g ^ w));
    sts32(ka + 4 * t, k0);
    sts32(ka + 512 + 4 * t, k1);
    sts64(ka + 1024 + 512 * (t >> 1) + 8 * (t & 1), prmt(k2, 0, 0x1010), (t & 1) ? prmt(k2, 0, 0x3232) : k2);
    const uint32_t lo = prmt(k3, 0, 0x1010), hi = prmt(k3, 0, 0x3232);
    sts128(ka + 2048 + 512 * t, lo, lo, (g & 1) ? hi : k3, hi);
    put_exp(sb + OFF_MX + u * 64 + 4 * w, amax2(amax2(k0, k1), amax2(k2, k3)), lane);
    cluster_wait();
    cluster_arrive();
    put(sb + u * 4096 + g * 512 + (g == rank ? OFF_UX : OFF_YB), x0, x1);
    TL(15);
    fence_async();
    bar_sync(NB_WG0 + u, 128);
    send(OFF_YB + u * 4096, OFF_UX + u * 4096 + 512 * rank, OFF_MB + 8 * (MB_UX + u));
    if (wid == 16) {
      bar_sync(NB_V, 288);
      if (elect()) tma_load3(sb + OFF_TV, &p.tv, ch0, 8 * rank, 0, mb + 8 * MB_KV);
      __syncwarp();
    }
  }
  if (u == 0) {
    float ga[4][4];
#pragma unroll
    for (int i = 0; i < 4; i++) ga[i][0] = ga[i][1] = ga[i][2] = ga[i][3] = 0.f;
#pragma unroll
    for (int j = 0; j < 5; j++) {
      uint32_t a0[4], a1[4], b;
      ldsm4(a0, sb + OFF_TQ + toff + 16 * j);
      ldsm4(a1, sb + OFF_TQ + toff + 2560 + 16 * j);
      asm volatile("ld.shared.u32 %0, [%1];" : "=r"(b) : "r"(sb + OFF_SP + 16 * j + 4 * t) : "memory");
      if (j >= 2 && j >= nu) b = 0;
      mma1688(ga[0], a0[0], a0[1], b); mma1688(ga[1], a0[2], a0[3], b); mma1688(ga[2], a1[0], a1[1], b); mma1688(ga[3], a1[2], a1[3], b);
    }
    const float s0 = t == 0 ? ga[0][0] : t == 1 ? ga[1][0] : t == 2 ? ga[2][0] : ga[3][0];
    const float s1 = t == 0 ? ga[0][2] : t == 1 ? ga[1][2] : t == 2 ? ga[2][2] : ga[3][2];
    tag = (lds64(mb + 8 * MB_TAG).x >> 4) + 1;
    uint2* gp = p.part + cl * SEQ + rank * 256 + 64 * w + 16 * t + g;
    asm volatile("st.relaxed.gpu.global.u64 [%0], %1;" :: "l"(gp), "l"(((uint64_t)tag << 32) | __float_as_uint(s0)) : "memory");
    asm volatile("st.relaxed.gpu.global.u64 [%0], %1;" :: "l"(gp + 8), "l"(((uint64_t)tag << 32) | __float_as_uint(s1)) : "memory");
  }

#pragma unroll
  for (int isA = 0; isA < 2; isA++) {
    {
      TL(1 + isA);
      const uint32_t usrc = isA ? tab + T_UKV : sb + OFF_UX + u * 4096;
      const uint32_t mxa = sb + OFF_MX + u * 64 + 32 * isA;
      const uint32_t pd = lds16(sb + OFF_SP + 80 + 80 * isA + 16 * u + 2 * rank);
      float D[32];
      uint32_t As[8], F[16], H[16], X[16];
      const uint32_t eh = min(max((int)get_exp(mxa), (int)((pd >> 7) & 0xff) - 5), 240);
      scale_a1(As, A1, 248 - eh);
      wg_fence();
      stage1(D, As, isA ? tab + T_HA : tab);
      wg_commit();
      wg_wait<0>(); tie_all(D);
      fwd_mid(F, D, tc, ts);
      if (!isA) mbar_wait(mb + 8 * MB_CF);
      wg_fence();
      stage2<0>(H, F, sb + OFF_CF);
      wg_commit();
      if (!isA) {
        if (w == 2 && elect()) bulk_load(tab + T_HA, p.ssm_k + (size_t)(act ? ch0 + 8 * u + rank : 0) * SEQ, 4096, mb + 8 * (MB_HA + u));
        __syncwarp();
        TL(7);
      }
      if (isA) fence_async();
      mbar_wait(mb + 8 * ((isA ? MB_UKV : MB_UX) + u));
      TL(5 + isA);
      put_exp(mxa + 16 + 4 * w, seq_mag(usrc + 16 * tid), lane);
      bar_sync(NB_WG0 + u, 128);
      if (isA) {
        send(OFF_UX + u * 4096, OFF_YB + (8 * u + rank) * 512, OFF_MB + 8 * (MB_Y + u));
      }
      const uint32_t eu = min(get_exp(mxa + 16), 240u);
      scale_a1(As, A1, 250 - eu);
      wg_wait<0>(); tie_all(H);
      wg_fence();
      stage1(D, As, usrc);
      wg_commit();
      wg_wait<0>(); tie_all(D);
      fwd_mid(F, D, tc, ts);
      wg_fence();
      stage2<0>(X, F, sb + OFF_CF);
      wg_commit();
      {
        const float dsk = blo(pd) * __uint_as_float((248 - eh) << 23);
        const uint32_t d2 = packh(dsk, dsk);
#pragma unroll
        for (int j = 0; j < 4; j++) H[2 * j] = U2(__hadd2(H2(H[2 * j]), H2(d2)));
      }
      wg_wait<0>(); tie_all(X);
#pragma unroll
      for (int j = 0; j < 4; j++) {
        const uint32_t h0r = H[2 * j], h1r = H[2 * j + 1], h0i = H[8 + 2 * j], h1i = H[9 + 2 * j];
        const uint32_t x0r = X[2 * j], x1r = X[2 * j + 1], x0i = X[8 + 2 * j], x1i = X[9 + 2 * j];
        F[2 * j] = ffma(x0r, h0r, fneg(fmul(x0i, h0i)));
        F[8 + 2 * j] = ffma(x0r, h0i, fmul(x0i, h0r));
        F[2 * j + 1] = ffma(x1r, h0r, ffma(fneg(x1i), h0i, ffma(x0r, h1r, fneg(ffma(x0i, h1i, F[8 + 2 * j])))));
        F[9 + 2 * j] = ffma(x1r, h0i, ffma(x1i, h0r, ffma(x0r, h1i, ffma(x0i, h1r, F[2 * j]))));
      }
      wg_fence();
      stage2<1>(H, F, sb + OFF_CF);
      wg_commit();
      uint64_t ga[4];
      const int sl2 = min(18 * cl + min(8 * w + g, 17), 255), sl3 = tid + 128 * (u & 1);
      auto gload = [&]() {
        if (isA) {
          asm volatile("ld.relaxed.gpu.global.u64 %0, [%1];" : "=l"(ga[0]) : "l"(p.part + NCL * SEQ + rank * 256 + sl3) : "memory");
        } else {
#pragma unroll
          for (int k = 0; k < 4; k++)
            asm volatile("ld.relaxed.gpu.global.u64 %0, [%1];" : "=l"(ga[k]) : "l"(p.part + (t + (k == 3 && t == 3 ? 8 : 4 * k)) * SEQ + rank * 256 + sl2) : "memory");
        }
      };
      if (isA ? (u & 6) == 2 : u == 1) gload();
      if (isA) TL(23);
      wg_wait<0>(); tie_all(H);
      {
        const uint32_t va = tab + (16 * w + (lane & 15)) * 128;
        const int vx = (lane >> 4) ^ (lane & 7);
#pragma unroll
        for (int j = 0; j < 4; j++) {
          uint32_t V[4];
#pragma unroll
          for (int b = 0; b < 2; b++) {
            const uint32_t er = H[2 * j + b], ei = H[8 + 2 * j + b];
            V[2 * b] = ffma(er, tc[j], fneg(fmul(ei, ts[j])));
            V[2 * b + 1] = ffma(ei, tc[j], fmul(er, ts[j]));
          }
          stsm4(va + ((vx ^ (2 * j)) << 4), V);
        }
      }
      if (!isA) {
        cluster_wait();
        mbar_wait(mb + 8 * MB_KV);
        TL(21);
        uint32_t K[3][4], V[2][4];
        const uint2 psw = lds64(sb + OFF_SP + 240 + 64 * u + 8 * g);
        ldsm4t(K[0], w ? sb + OFF_TK + toff - 2560 : (lane & 7) ? sb + OFF_TK + toff + 223 * 80 : sb + OFF_HALO + 10 * lane + 16 * u);
        ldsm4t(K[1], sb + OFF_TK + toff);
        ldsm4t(K[2], sb + OFF_TK + toff + 2560);
        ldsm4t(V[0], sb + OFF_TV + toff);
        ldsm4t(V[1], sb + OFF_TV + toff + 2560);
        mbar_wait(mb + 8 * (MB_HA + u));
        const uint4 hx = lds128(tab + T_HA + 16 * tid), hy = lds128(tab + T_HA + 2048 + 16 * tid);
        const uint32_t w0 = prmt(psw.x, 0, 0x1010), w1 = prmt(psw.x, 0, 0x3232), w2 = prmt(psw.y, 0, 0x1010), w3 = prmt(psw.y, 0, 0x3232);
#pragma unroll
        for (int m = 4; m < 12; m++)
          V[(m >> 2) - 1][m & 3] = hmul2(hfma2(K[m >> 2][m & 3], w0, hfma2(K[(m - 1) >> 2][(m - 1) & 3], w1,
                                         hfma2(K[(m - 2) >> 2][(m - 2) & 3], w2, hmul2(K[(m - 3) >> 2][(m - 3) & 3], w3)))), V[(m >> 2) - 1][m & 3]);
        put(g == rank ? tab + T_UKV + 512 * rank : sb + OFF_YA + u * 4096 + g * 512, V[0], V[1]);
        put_exp(mxa + 32 + 4 * w, amax2(amax2(amax2(hx.x, hx.y), amax2(hx.z, hx.w)), amax2(amax2(hy.x, hy.y), amax2(hy.z, hy.w))), lane);
        sts128(tab + T_HA + 16 * (tid ^ (lane >> 3)), hx.x, hx.y, hx.z, hx.w);
        sts128(tab + T_HA + 2048 + 16 * (tid ^ (lane >> 3)), hy.x, hy.y, hy.z, hy.w);
        TL(22);
      }
      fence_async();
      bar_sync(NB_WG0 + u, 128);
      float O[16];
      {
        const uint64_t dv = desc_lo(tab) | (1ull << 16) | (64ull << 32) | (1ull << 62);
        const uint64_t dl = desc_lo(sb + OFF_CL) | (32ull << 16) | (8ull << 32);
        wg_fence();
        ss32<0, 0, 0>(O, dv, dl); ss32<1, 128, 64>(O, dv, dl); ss32<1, 256, 128>(O, dv, dl); ss32<1, 384, 192>(O, dv, dl);
        wg_commit();
      }
      if (!isA) send(OFF_YA + u * 4096, OFF_T + u * KTAB + T_UKV + 512 * rank, OFF_MB + 8 * (MB_UKV + u));
      if (isA ? (u & 6) == 2 : u == 1) {
        tag = (lds64(mb + 8 * MB_TAG).x >> 4) + 1;
        bool ok;
#pragma unroll 1
        for (int it = 0;; it++) {
          ok = (uint32_t)(ga[0] >> 32) == tag;
          if (!isA) ok = ok && (uint32_t)(ga[1] >> 32) == tag && (uint32_t)(ga[2] >> 32) == tag && (uint32_t)(ga[3] >> 32) == tag;
          ok = __all_sync(0xffffffffu, ok);
          if (ok || it == (isA ? 8000 : 2000)) break;
          gload();
        }
        if (!isA) {
          float s = __uint_as_float((uint32_t)ga[0]) + __uint_as_float((uint32_t)ga[1]) + __uint_as_float((uint32_t)ga[2]);
          if (t < 3) s += __uint_as_float((uint32_t)ga[3]);
          s += __shfl_xor_sync(0xffffffffu, s, 1);
          s += __shfl_xor_sync(0xffffffffu, s, 2);
          const float g0 = bf16r(sigmoidf_(bf16r(s)));
          if (ok && t == 0)
            asm volatile("st.relaxed.gpu.global.u64 [%0], %1;" :: "l"(p.part + NCL * SEQ + rank * 256 + sl2), "l"(((uint64_t)tag << 32) | pack(g0, 1.f - g0)) : "memory");
        } else {
          uint32_t gv = (uint32_t)ga[0];
          if (!ok) {
            const uint32_t* xr = (const uint32_t*)(p.q + (size_t)(rank * 256 + 32 * (sl3 & 7) + (sl3 >> 3)) * DCH);
            const uint32_t* gr = (const uint32_t*)p.gate_w;
            float s = 0.f;
#pragma unroll 1
            for (int k = 0; k < DCH / 2; k++) { const uint32_t x = __ldg(xr + k), y = __ldg(gr + k); s = fmaf(blo(x), blo(y), fmaf(bhi(x), bhi(y), s)); }
            const float g0 = bf16r(sigmoidf_(bf16r(s)));
            gv = pack(g0, 1.f - g0);
          }
          sts64(sb + OFF_GB + 8 * sl3, prmt(gv, 0, 0x1010), prmt(gv, 0, 0x3232));
          __syncwarp();
          if (lane == 0) mbar_arrive(mb + 8 * MB_G);
        }
      }
      if (isA) TL(28);
      wg_wait<0>(); tie_all(O);
      {
        const uint32_t co = ((8 * w + g) ^ (2 * t) ^ rank) * 16;
        const int yo = (isA ? OFF_YA : OFF_YB) + (8 * u + rank) * 512, ym = OFF_MB + 8 * (MB_Y + u);
        const uint32_t us = min(max((int)(eu + eh) - 127, 0), 254) * 0x00800080u;
        const uint32_t a0 = hmul2(pack(O[0], O[1]), us), a1 = hmul2(pack(O[4], O[5]), us), a2 = hmul2(pack(O[8], O[9]), us), a3 = hmul2(pack(O[12], O[13]), us);
        const uint32_t b0 = hmul2(pack(O[2], O[3]), us), b1 = hmul2(pack(O[6], O[7]), us), b2 = hmul2(pack(O[10], O[11]), us), b3 = hmul2(pack(O[14], O[15]), us);
        sts128((t == rank ? sb + yo : usrc + t * 512) + co, a0, a1, a2, a3);
        sts128((t + 4 == rank ? sb + yo : usrc + t * 512 + 2048) + co, b0, b1, b2, b3);
        if (isA) {
          fence_async();
          bar_sync(NB_WG0 + u, 128);
          send(usrc - sb, yo, ym);
        }
      }
      TL(9 + isA);
    }
  }

  {
    mbar_wait(mb + 8 * MB_G);
    uint2 gg[2][4];
    uint32_t qv[2][4];
#pragma unroll
    for (int hh = 0; hh < 2; hh++)
#pragma unroll
      for (int i = 0; i < 4; i++) gg[hh][i] = lds64(sb + OFF_GB + 8 * (64 * w + 32 * hh + 8 * i + g));
    const uint32_t qa = sb + OFF_TQ + toff;
    ldsm4(qv[0], qa);
    ldsm4(qv[1], qa + 2560);
    TL(24);
    mbar_wait(mb + 8 * (MB_Y + u));
    uint32_t ya[2][4], yb[2][4];
#pragma unroll
    for (int hh = 0; hh < 2; hh++) {
      const uint32_t yo = (8 * u + (lane & 7)) * 512 + ((8 * w + 4 * hh + (lane >> 3)) ^ (2 * (rank & 3)) ^ (lane & 7)) * 16;
      ldsm4t(ya[hh], sb + OFF_YA + yo); ldsm4t(yb[hh], sb + OFF_YB + yo);
    }
#pragma unroll
    for (int hh = 0; hh < 2; hh++) {
      uint32_t o[4];
#pragma unroll
      for (int i = 0; i < 4; i++) o[i] = hadd2(hmul2(gg[hh][i].x, hmul2(qv[hh][i], ya[hh][i])), hmul2(gg[hh][i].y, yb[hh][i]));
      stsm4(qa + 2560 * hh, o);
    }
    TL(25);
  }
  cluster_arrive();
  bar_sync(NB_ROW0 + w, 160);
  {
    uint4 v[2];
#pragma unroll
    for (int k = 0; k < 2; k++) {
      const int i = 64 * u + 32 * k + lane, sl = (i * 205) >> 10, cc = i - 5 * sl;
      v[k] = lds128(sb + OFF_TQ + (64 * w + 8 * (sl & 7) + (sl >> 3)) * 80 + cc * 16);
    }
#pragma unroll
    for (int k = 0; k < 2; k++) {
      const int i = 64 * u + 32 * k + lane, sl = (i * 205) >> 10, cc = i - 5 * sl;
      if (cc < nu)
        asm volatile("st.global.v4.u32 [%0], {%1,%2,%3,%4};" :: "l"(p.out + (size_t)(256 * rank + 32 * (sl >> 3) + 8 * w + (sl & 7)) * DCH + ch0 + 8 * cc),
                     "r"(v[k].x), "r"(v[k].y), "r"(v[k].z), "r"(v[k].w) : "memory");
    }
  }
  cluster_wait();
  TL(27);
  TL_DUMP();
}

typedef CUresult (*EncodeFn)(CUtensorMap*, CUtensorMapDataType, cuuint32_t, void*, const cuuint64_t*, const cuuint64_t*,
                             const cuuint32_t*, const cuuint32_t*, CUtensorMapInterleave, CUtensorMapSwizzle,
                             CUtensorMapL2promotion, CUtensorMapFloatOOBfill);

void encode(EncodeFn fn, CUtensorMap* tm, const void* ptr, int nd, const cuuint64_t* dims, const cuuint64_t* strides,
            const cuuint32_t* box, CUtensorMapSwizzle swz) {
  cuuint32_t es[4] = {1, 1, 1, 1};
  fn(tm, CU_TENSOR_MAP_DATA_TYPE_BFLOAT16, nd, const_cast<void*>(ptr), dims, strides, box, es, CU_TENSOR_MAP_INTERLEAVE_NONE,
     swz, CU_TENSOR_MAP_L2_PROMOTION_L2_128B, CU_TENSOR_MAP_FLOAT_OOB_FILL_NONE);
}
void make_map(EncodeFn fn, CUtensorMap* tm, const void* ptr, int ne, int nr) {
  const cuuint64_t dims[3] = {DCH, SEQ / 32, 32}, strides[2] = {32 * DCH * 2, DCH * 2};
  const cuuint32_t box[3] = {CPC, (cuuint32_t)ne, (cuuint32_t)nr};
  encode(fn, tm, ptr, 3, dims, strides, box, CU_TENSOR_MAP_SWIZZLE_NONE);
}

}

extern "C" void kernel_launch(void* const* d_in, const int* in_sizes, int n_in, void* d_out, int out_size) {
  (void)in_sizes; (void)n_in; (void)out_size;
  static EncodeFn fn = nullptr;
  static void *tab = nullptr, *cnt = nullptr, *part = nullptr;
  if (!fn) {
    cudaGetSymbolAddress(&tab, d_tab);
    cudaGetSymbolAddress(&cnt, g_cnt);
    cudaGetSymbolAddress(&part, g_part);
    cudaDriverEntryPointQueryResult qr;
    cudaGetDriverEntryPoint("cuTensorMapEncodeTiled", (void**)&fn, cudaEnableDefault, &qr);
    cudaFuncSetAttribute(fused_kernel, cudaFuncAttributeMaxDynamicSharedMemorySize, SMEM_BYTES);
  }
  Params p;
  make_map(fn, &p.tq, d_in[0], 8, 32);
  make_map(fn, &p.tk, d_in[1], 8, 32);
  make_map(fn, &p.tv, d_in[2], 8, 32);
  make_map(fn, &p.tkh, d_in[1], 1, 4);
  p.out = (__nv_bfloat16*)d_out;
  p.tab = (const Tables*)tab;
  p.cnt = (unsigned*)cnt;
  p.part = (uint2*)part;
  p.tl = nullptr;
  p.q = (const __nv_bfloat16*)d_in[0];
  p.v = (const __nv_bfloat16*)d_in[2];
  p.ssm_k = (const __nv_bfloat16*)d_in[4];
  p.shift_k = (const __nv_bfloat16*)d_in[3];
  p.ssm_D = (const __nv_bfloat16*)d_in[5];
  p.logA = (const __nv_bfloat16*)d_in[7];
  p.Aim = (const __nv_bfloat16*)d_in[8];
  p.Cre = (const __nv_bfloat16*)d_in[9];
  p.Cim = (const __nv_bfloat16*)d_in[10];
  p.logdt = (const __nv_bfloat16*)d_in[11];
  p.Dskip = (const __nv_bfloat16*)d_in[12];
  p.gate_w = (const __nv_bfloat16*)d_in[13];
  fused_kernel<<<NCL * CS, NTHREADS, SMEM_BYTES, cudaStreamPerThread>>>(p);
}
```

```cpp
#include <cuda_runtime.h>
#include <cuda_bf16.h>
#include <cuda_fp16.h>
#include <cuda.h>
#include <stdint.h>

#define TIMELINE 0
#define STAGGER 0
#define PREFETCH 1
#define TLHI 0

namespace {

constexpr int SEQ = 2048, DCH = 576, NMODE = 128;
constexpr int CS = 8, CPC = 40, NCL = 15, NTHREADS = 640;

constexpr int KTAB = 16384;
constexpr int OFF_T = 0;
constexpr int T_UKV = 8192, T_HA = 12288;
constexpr int OFF_UX = 5 * KTAB;
constexpr int OFF_IM = OFF_UX + 20480;
constexpr int OFF_CF = OFF_IM;
constexpr int OFF_CL = OFF_CF + 8192;
constexpr int OFF_TV = OFF_CL + 4096;
constexpr int OFF_YA = OFF_TV + 20480;
constexpr int OFF_GB = OFF_YA + 20480;
constexpr int OFF_YB = OFF_IM + 4 * KTAB;
constexpr int OFF_TQ = OFF_YB + 20480;
constexpr int OFF_TK = OFF_TQ + 20480;
constexpr int OFF_HALO = OFF_TK + 20480;
constexpr int OFF_MX = OFF_HALO + 320;
constexpr int OFF_SP = OFF_MX + 320;
constexpr int OFF_MB = OFF_SP + 560;
constexpr int OFF_TL = OFF_MB + 28 * 8;
constexpr int SMEM_BYTES = OFF_TL + (TIMELINE ? 1280 : 0);
static_assert(SMEM_BYTES <= 232448 && OFF_YA == OFF_IM + 2 * KTAB && OFF_GB + 2048 <= OFF_YB, "smem");
static_assert((OFF_MB & 7) == 0 && (OFF_MX & 15) == 0 && (OFF_SP & 15) == 0, "align");

enum { MB_UX = 0, MB_UKV = 5, MB_Y = 10, MB_HA = 15, MB_XQ = 20, MB_KV = 21, MB_CF = 22, MB_G = 23, MB_TH = 24, MB_TAG = 25 };
enum { NB_WG0 = 1, NB_ROW0 = 6, NB_ORD = 6, NB_V = 10, NB_ST = 11 };

constexpr uint32_t SB0 = 1024;
constexpr uint64_t mkdesc(uint32_t off, uint32_t lbo, uint32_t sbo, uint32_t swz) {
  return (uint64_t)((SB0 + off) >> 4) | ((uint64_t)(lbo >> 4) << 16) | ((uint64_t)(sbo >> 4) << 32) | ((uint64_t)swz << 62);
}

constexpr double cos_turn(int m, int n) {
  m &= n - 1;
  if (m > n / 2) m = n - m;
  double sgn = 1.0;
  if (m > n / 4) { m = n / 2 - m; sgn = -1.0; }
  if (m == n / 4) return 0.0;
  const double x = 6.283185307179586476925 * m / n;
  double term = 1.0, sum = 1.0;
  for (int k = 1; k < 14; k++) { term *= -x * x / ((2 * k - 1) * (2 * k)); sum += term; }
  return sgn * sum;
}
constexpr uint32_t bf16_bits(double v) {
  if (v == 0.0) return 0;
  uint32_t sgn = 0;
  if (v < 0) { sgn = 0x8000; v = -v; }
  int e = 127;
  while (v < 1.0) { v *= 2.0; e--; }
  while (v >= 2.0) { v *= 0.5; e++; }
  const double f = v * 128.0;
  int m = (int)f;
  if (f - m > 0.5 || (f - m == 0.5 && (m & 1))) m++;
  return sgn | (uint32_t)((e << 7) + (m - 128));
}
constexpr uint32_t f16_bits(double v) {
  if (v == 0.0) return 0;
  uint32_t sgn = 0;
  if (v < 0) { sgn = 0x8000; v = -v; }
  int e = 15;
  while (v < 1.0) { v *= 2.0; e--; }
  const double f = v * 1024.0;
  int m = (int)f;
  if (f - m > 0.5 || (f - m == 0.5 && (m & 1))) m++;
  return sgn | (uint32_t)((e << 10) + (m - 1024));
}
constexpr uint32_t pair_bits(double lo, double hi) { return bf16_bits(lo) | (bf16_bits(hi) << 16); }
constexpr uint32_t pair_h(double lo, double hi) { return f16_bits(lo) | (f16_bits(hi) << 16); }
struct alignas(128) Tables {
  uint32_t mat[3072];
  uint32_t thr[4][128][4];
};
constexpr Tables make_tables() {
  Tables T{};
  for (int q = 0; q < 768; q++) {
    int m0 = 0, d0 = 0, d1 = 0;
    if (q < 512) {
      const int r = (q >> 6) * 8 + (q & 7), cc = (q >> 3) & 7;
      d0 = 4 * (r & 31); d1 = 2 * d0;
      m0 = 8 * (cc & 3) * d0 + ((r >> 5) == (cc >> 2) ? 0 : (r >> 5) ? 96 : 32);
    } else {
      const int r = ((q - 512) >> 5) * 8 + (q & 7), pc = (q >> 3) & 3;
      d0 = 4 * (8 * (r >> 4) + (r & 7)) + 1; d1 = 8 * d0;
      m0 = 2 * pc * d0 + ((r & 8) ? 32 : 0);
    }
    for (int e = 0; e < 4; e++) T.mat[4 * q + e] = pair_h(cos_turn(m0 + e * d1, 128), cos_turn(m0 + e * d1 + d0, 128));
  }
  for (int tid = 0; tid < 128; tid++) {
    const int kk = 4 * (tid >> 2) + 1, t = tid & 3;
    for (int q = 0; q < 4; q++) {
      const int m = (8 * q + 2 * t) * kk;
      T.thr[q >> 1][tid][2 * (q & 1)] = pair_bits(cos_turn(m, 128), cos_turn(m + kk, 128));
      T.thr[q >> 1][tid][2 * (q & 1) + 1] = pair_bits(cos_turn(m + 32, 128), cos_turn(m + kk + 32, 128));
      T.thr[2][tid][q] = pair_h(cos_turn(m, 4096), cos_turn(m + kk, 4096));
      T.thr[3][tid][q] = pair_h(cos_turn(m + 3072, 4096), cos_turn(m + kk + 3072, 4096));
    }
  }
  return T;
}
__device__ const Tables d_tab = make_tables();

struct Params {
  const __nv_bfloat16 *logA, *Aim, *Cre, *Cim, *logdt;
  const Tables* tab;
  unsigned* cnt;
  const __nv_bfloat16 *Dskip, *shift_k, *ssm_D, *gate_w, *q, *v, *ssm_k;
  uint2* part;
  __nv_bfloat16* out;
  unsigned* tl;
  uint64_t dfwd, dinv, dlast, dk[5], dt[5], dx[5], dv[5];
  CUtensorMap tq, tk, tv, tkh;
};

__device__ uint2 g_part[(NCL + 1) * SEQ];
__device__ unsigned g_cnt[CS * 32];
#define TL(i) do {} while (0)
#define TL_INIT() do {} while (0)
#define TL_DUMP() do {} while (0)

__device__ __forceinline__ uint32_t lds16(uint32_t a) { uint32_t v; asm volatile("ld.shared.u16 %0, [%1];" : "=r"(v) : "r"(a) : "memory"); return v; }
__device__ __forceinline__ uint2 lds64(uint32_t a) { uint2 v; asm volatile("ld.shared.v2.u32 {%0,%1}, [%2];" : "=r"(v.x), "=r"(v.y) : "r"(a) : "memory"); return v; }
__device__ __forceinline__ uint4 lds128(uint32_t a) { uint4 v; asm volatile("ld.shared.v4.u32 {%0,%1,%2,%3}, [%4];" : "=r"(v.x), "=r"(v.y), "=r"(v.z), "=r"(v.w) : "r"(a) : "memory"); return v; }
__device__ __forceinline__ void sts16(uint32_t a, uint32_t v) { asm volatile("st.shared.u16 [%0], %1;" :: "r"(a), "r"(v) : "memory"); }
__device__ __forceinline__ void sts32(uint32_t a, uint32_t v) { asm volatile("st.shared.u32 [%0], %1;" :: "r"(a), "r"(v) : "memory"); }
__device__ __forceinline__ void sts64(uint32_t a, uint32_t x, uint32_t y) { asm volatile("st.shared.v2.u32 [%0], {%1,%2};" :: "r"(a), "r"(x), "r"(y) : "memory"); }
__device__ __forceinline__ void sts128(uint32_t a, uint32_t x, uint32_t y, uint32_t z, uint32_t w) { asm volatile("st.shared.v4.u32 [%0], {%1,%2,%3,%4};" :: "r"(a), "r"(x), "r"(y), "r"(z), "r"(w) : "memory"); }
__device__ __forceinline__ void ldsm4t(uint32_t (&r)[4], uint32_t a) { asm volatile("ldmatrix.sync.aligned.m8n8.x4.trans.shared.b16 {%0,%1,%2,%3}, [%4];" : "=r"(r[0]), "=r"(r[1]), "=r"(r[2]), "=r"(r[3]) : "r"(a) : "memory"); }
__device__ __forceinline__ void ldsm2t(uint32_t& r0, uint32_t& r1, uint32_t a) { asm volatile("ldmatrix.sync.aligned.m8n8.x2.trans.shared.b16 {%0,%1}, [%2];" : "=r"(r0), "=r"(r1) : "r"(a) : "memory"); }
__device__ __forceinline__ void ldsm4(uint32_t (&r)[4], uint32_t a) { asm volatile("ldmatrix.sync.aligned.m8n8.x4.shared.b16 {%0,%1,%2,%3}, [%4];" : "=r"(r[0]), "=r"(r[1]), "=r"(r[2]), "=r"(r[3]) : "r"(a) : "memory"); }
__device__ __forceinline__ void stsm4(uint32_t a, const uint32_t (&r)[4]) { asm volatile("stmatrix.sync.aligned.m8n8.x4.shared.b16 [%0], {%1,%2,%3,%4};" :: "r"(a), "r"(r[0]), "r"(r[1]), "r"(r[2]), "r"(r[3]) : "memory"); }
__device__ __forceinline__ uint32_t pack(float lo, float hi) { uint32_t r; asm("cvt.rn.bf16x2.f32 %0, %1, %2;" : "=r"(r) : "f"(hi), "f"(lo)); return r; }
__device__ __forceinline__ float blo(uint32_t v) { return __uint_as_float(v << 16); }
__device__ __forceinline__ float bhi(uint32_t v) { return __uint_as_float(v & 0xffff0000u); }
__device__ __forceinline__ float bf16r(float x) { return blo(pack(x, 0.f)); }
__device__ __forceinline__ uint32_t hmul2(uint32_t a, uint32_t b) { uint32_t r; asm("mul.rn.bf16x2 %0, %1, %2;" : "=r"(r) : "r"(a), "r"(b)); return r; }
__device__ __forceinline__ uint32_t hadd2(uint32_t a, uint32_t b) { uint32_t r; asm("add.rn.bf16x2 %0, %1, %2;" : "=r"(r) : "r"(a), "r"(b)); return r; }
__device__ __forceinline__ uint32_t hfma2(uint32_t a, uint32_t b, uint32_t c) { uint32_t r; asm("fma.rn.bf16x2 %0, %1, %2, %3;" : "=r"(r) : "r"(a), "r"(b), "r"(c)); return r; }
__device__ __forceinline__ uint32_t packh(float lo, float hi) { uint32_t r; asm("cvt.rn.f16x2.f32 %0, %1, %2;" : "=r"(r) : "f"(hi), "f"(lo)); return r; }
__device__ __forceinline__ __half2 H2(uint32_t a) { return *reinterpret_cast<__half2*>(&a); }
__device__ __forceinline__ uint32_t U2(__half2 a) { return *reinterpret_cast<uint32_t*>(&a); }
__device__ __forceinline__ uint32_t fmul(uint32_t a, uint32_t b) { return U2(__hmul2(H2(a), H2(b))); }
__device__ __forceinline__ uint32_t ffma(uint32_t a, uint32_t b, uint32_t c) { return U2(__hfma2(H2(a), H2(b), H2(c))); }
__device__ __forceinline__ uint32_t fneg(uint32_t a) { return U2(__hneg2(H2(a))); }
__device__ __forceinline__ uint32_t amax2(uint32_t a, uint32_t b) { uint32_t r; asm("max.xorsign.abs.bf16x2 %0, %1, %2;" : "=r"(r) : "r"(a), "r"(b)); return r; }
__device__ __forceinline__ uint32_t prmt(uint32_t a, uint32_t b, uint32_t s) { return __byte_perm(a, b, s); }
__device__ __forceinline__ uint32_t ldraw(const __nv_bfloat16* p) { uint32_t v; asm volatile("ld.global.nc.u16 %0, [%1];" : "=r"(v) : "l"(p)); return v; }
__device__ __forceinline__ uint4 ldg128(const void* p) { uint4 v; asm volatile("ld.global.nc.v4.u32 {%0,%1,%2,%3}, [%4];" : "=r"(v.x), "=r"(v.y), "=r"(v.z), "=r"(v.w) : "l"(p)); return v; }
__device__ __forceinline__ void bar_sync(int id, int n) { asm volatile("bar.sync %0, %1;" :: "r"(id), "r"(n) : "memory"); }
__device__ __forceinline__ void bar_arrive(int id, int n) { asm volatile("bar.arrive %0, %1;" :: "r"(id), "r"(n) : "memory"); }
__device__ __forceinline__ void cluster_arrive() { asm volatile("barrier.cluster.arrive.relaxed.aligned;" ::: "memory"); }
__device__ __forceinline__ void cluster_wait() { asm volatile("barrier.cluster.wait.aligned;" ::: "memory"); }
__device__ __forceinline__ void fence_async() { asm volatile("fence.proxy.async.shared::cta;" ::: "memory"); }
__device__ __forceinline__ void fence_mbinit() { asm volatile("fence.mbarrier_init.release.cluster;" ::: "memory"); }
__device__ __forceinline__ uint32_t mapa(uint32_t a, uint32_t rank) { uint32_t r; asm("mapa.shared::cluster.u32 %0, %1, %2;" : "=r"(r) : "r"(a), "r"(rank)); return r; }
__device__ __forceinline__ void bulk_dsmem(uint32_t dst, uint32_t src, uint32_t mbar) {
  asm volatile("cp.async.bulk.shared::cluster.shared::cta.mbarrier::complete_tx::bytes [%0], [%1], 512, [%2];" :: "r"(dst), "r"(src), "r"(mbar) : "memory");
}
__device__ __forceinline__ void bulk_load(uint32_t dst, const void* src, uint32_t bytes, uint32_t mbar) {
  asm volatile("cp.async.bulk.shared::cluster.global.mbarrier::complete_tx::bytes [%0], [%1], %2, [%3];" :: "r"(dst), "l"(src), "r"(bytes), "r"(mbar) : "memory");
}
__device__ __forceinline__ void mbar_init(uint32_t m, uint32_t cnt) { asm volatile("mbarrier.init.shared::cta.b64 [%0], %1;" :: "r"(m), "r"(cnt) : "memory"); }
__device__ __forceinline__ void mbar_expect(uint32_t m, uint32_t bytes) { asm volatile("mbarrier.arrive.expect_tx.shared::cta.b64 _, [%0], %1;" :: "r"(m), "r"(bytes) : "memory"); }
__device__ __forceinline__ bool mbar_try(uint32_t m) {
  uint32_t done;
  asm volatile("{.reg .pred p; mbarrier.try_wait.parity.shared::cta.b64 p, [%1], 0; selp.u32 %0, 1, 0, p;}" : "=r"(done) : "r"(m) : "memory");
  return done;
}
__device__ __forceinline__ void mbar_wait(uint32_t m) {
  if (!mbar_try(m)) {
    int it = 0;
    while (!mbar_try(m) && ++it < (1 << 22)) {}
  }
}
__device__ __forceinline__ bool elect() {
  uint32_t e;
  asm volatile("{.reg .pred p; elect.sync _|p, 0xffffffff; selp.u32 %0, 1, 0, p;}" : "=r"(e));
  return e;
}
__device__ __forceinline__ void tma_load4(uint32_t dst, const CUtensorMap* tm, int c0, int c1, int c2, int c3, uint32_t mbar) {
  asm volatile("cp.async.bulk.tensor.4d.shared::cluster.global.mbarrier::complete_tx::bytes [%0], [%1, {%3, %4, %5, %6}], [%2];"
               :: "r"(dst), "l"(tm), "r"(mbar), "r"(c0), "r"(c1), "r"(c2), "r"(c3) : "memory");
}
__device__ __forceinline__ void tma_load3(uint32_t dst, const CUtensorMap* tm, int c0, int c1, int c2, uint32_t mbar) {
  asm volatile("cp.async.bulk.tensor.3d.shared::cluster.global.mbarrier::complete_tx::bytes [%0], [%1, {%3, %4, %5}], [%2];"
               :: "r"(dst), "l"(tm), "r"(mbar), "r"(c0), "r"(c1), "r"(c2) : "memory");
}
__device__ __forceinline__ void tma_store3(const CUtensorMap* tm, int c0, int c1, int c2, uint32_t src) {
  asm volatile("cp.async.bulk.tensor.3d.global.shared::cta.bulk_group [%0, {%2, %3, %4}], [%1];"
               :: "l"(tm), "r"(src), "r"(c0), "r"(c1), "r"(c2) : "memory");
}
__device__ __forceinline__ void mma1688(float (&c)[4], uint32_t a0, uint32_t a1, uint32_t b) {
  asm volatile("mma.sync.aligned.m16n8k8.row.col.f32.bf16.bf16.f32 {%0,%1,%2,%3}, {%4,%5}, {%6}, {%0,%1,%2,%3};"
               : "+f"(c[0]), "+f"(c[1]), "+f"(c[2]), "+f"(c[3]) : "r"(a0), "r"(a1), "r"(b));
}
__device__ __forceinline__ void wg_fence() { asm volatile("wgmma.fence.sync.aligned;" ::: "memory"); }
__device__ __forceinline__ void wg_commit() { asm volatile("wgmma.commit_group.sync.aligned;" ::: "memory"); }
template <int N> __device__ __forceinline__ void wg_wait() { asm volatile("wgmma.wait_group.sync.aligned %0;" :: "n"(N) : "memory"); }
template <int N> __device__ __forceinline__ void tie_all(uint32_t (&x)[N]) {
#pragma unroll
  for (int i = 0; i < N; i++) asm volatile("" : "+r"(x[i]) :: "memory");
}
template <int N> __device__ __forceinline__ void tie_all(float (&x)[N]) {
#pragma unroll
  for (int i = 0; i < N; i++) asm volatile("" : "+f"(x[i]) :: "memory");
}
#define R16(C, d) C(d[0]), C(d[1]), C(d[2]), C(d[3]), C(d[4]), C(d[5]), C(d[6]), C(d[7]), C(d[8]), C(d[9]), C(d[10]), C(d[11]), C(d[12]), C(d[13]), C(d[14]), C(d[15])
#define R32(C, d) R16(C, d), R16(C, (d + 16))
#define P16 "{%0,%1,%2,%3,%4,%5,%6,%7,%8,%9,%10,%11,%12,%13,%14,%15}"
#define P32 "{%0,%1,%2,%3,%4,%5,%6,%7,%8,%9,%10,%11,%12,%13,%14,%15,%16,%17,%18,%19,%20,%21,%22,%23,%24,%25,%26,%27,%28,%29,%30,%31}"
template <int SD, int OFF> __device__ __forceinline__ void rs64(float* d, const uint32_t* a, uint64_t db) {
  if (SD) asm volatile("{.reg .b64 db; add.s64 db, %36, %37; wgmma.mma_async.sync.aligned.m64n64k16.f32.bf16.bf16 " P32 ", {%32,%33,%34,%35}, db, 1, 1, 1, 1;}"
                       : R32("+f", d) : "r"(a[0]), "r"(a[1]), "r"(a[2]), "r"(a[3]), "l"(db), "n"(OFF));
  else asm volatile("{.reg .b64 db; add.s64 db, %36, %37; wgmma.mma_async.sync.aligned.m64n64k16.f32.bf16.bf16 " P32 ", {%32,%33,%34,%35}, db, 0, 1, 1, 1;}"
                    : R32("=f", d) : "r"(a[0]), "r"(a[1]), "r"(a[2]), "r"(a[3]), "l"(db), "n"(OFF));
}
template <int SD, int TB, int OFF> __device__ __forceinline__ void rs64h(uint32_t* d, const uint32_t* a, uint64_t db) {
  if (SD) asm volatile("{.reg .b64 db; add.s64 db, %20, %21; wgmma.mma_async.sync.aligned.m64n64k16.f16.f16.f16 " P16 ", {%16,%17,%18,%19}, db, 1, 1, 1, %22;}"
                       : R16("+r", d) : "r"(a[0]), "r"(a[1]), "r"(a[2]), "r"(a[3]), "l"(db), "n"(OFF), "n"(TB));
  else asm volatile("{.reg .b64 db; add.s64 db, %20, %21; wgmma.mma_async.sync.aligned.m64n64k16.f16.f16.f16 " P16 ", {%16,%17,%18,%19}, db, 0, 1, 1, %22;}"
                    : R16("=r", d) : "r"(a[0]), "r"(a[1]), "r"(a[2]), "r"(a[3]), "l"(db), "n"(OFF), "n"(TB));
}
template <int SD, int OFFA, int OFFB> __device__ __forceinline__ void ss32(float* d, uint64_t da, uint64_t db) {
  if (SD) asm volatile("{.reg .b64 da, db; add.s64 da, %16, %18; add.s64 db, %17, %19; wgmma.mma_async.sync.aligned.m64n32k16.f32.f16.f16 " P16 ", da, db, 1, 1, 1, 1, 1;}"
                       : R16("+f", d) : "l"(da), "l"(db), "n"(OFFA), "n"(OFFB));
  else asm volatile("{.reg .b64 da, db; add.s64 da, %16, %18; add.s64 db, %17, %19; wgmma.mma_async.sync.aligned.m64n32k16.f32.f16.f16 " P16 ", da, db, 0, 1, 1, 1, 1;}"
                    : R16("=f", d) : "l"(da), "l"(db), "n"(OFFA), "n"(OFFB));
}
#define KGEN_ASM(SD) "{.reg .b64 da, db; add.s64 da, %32, %33; add.s64 db, %32, %34;\n" \
  "wgmma.mma_async.sync.aligned.m64n64k16.f32.bf16.bf16 " P32 ", da, db, " SD ", 1, 1, 1, 1;}"
template <int KS> __device__ __forceinline__ void kgen_mma(float (&c)[32], uint64_t da) {
  if (KS) asm volatile(KGEN_ASM("1") : R32("+f", c) : "l"(da), "n"(8 * KS), "n"(8 * KS + 512));
  else asm volatile(KGEN_ASM("0") : R32("=f", c) : "l"(da), "n"(8 * KS), "n"(8 * KS + 512));
  if constexpr (KS < 7) kgen_mma<KS + 1>(c, da);
}
template <int OFF> __device__ __forceinline__ void stage1(float (&D)[32], const uint32_t (&A1)[8], uint64_t d) {
  rs64<0, OFF>(D, A1, d); rs64<1, OFF + 64>(D, A1 + 4, d);
}
template <int INV> __device__ __forceinline__ void stage2(uint32_t (&X)[16], const uint32_t (&F)[16], uint64_t dc) {
  constexpr int KS = INV ? 16 : 128, TB = INV ? 0 : 1;
  rs64h<0, TB, 0>(X, F, dc); rs64h<1, TB, KS>(X, F + 4, dc); rs64h<1, TB, 2 * KS>(X, F + 8, dc); rs64h<1, TB, 3 * KS>(X, F + 12, dc);
}
__device__ __forceinline__ void fwd_mid(uint32_t (&F)[16], const float (&D)[32], const uint32_t (&tc)[4], const uint32_t (&ts)[4]) {
#pragma unroll
  for (int j = 0; j < 4; j++)
#pragma unroll
    for (int b = 0; b < 2; b++) {
      const int i = 4 * j + 16 * b;
      const uint32_t ar = packh(D[i], D[i + 1]), ai = packh(D[i + 2], D[i + 3]);
      F[2 * j + b] = ffma(ar, tc[j], fmul(ai, ts[j]));
      F[8 + 2 * j + b] = ffma(ai, tc[j], fneg(fmul(ar, ts[j])));
    }
}
__device__ __forceinline__ void put_exp(uint32_t a, uint32_t m, int lane) {
  m = __reduce_max_sync(0xffffffffu, max(m & 0x7f80u, (m >> 16) & 0x7f80u));
  if (lane == 0) sts32(a, m);
}
__device__ __forceinline__ uint32_t seq_mag(uint32_t a) {
  const uint4 x = lds128(a), y = lds128(a + 2048);
  return amax2(amax2(amax2(x.x, x.y), amax2(x.z, x.w)), amax2(amax2(y.x, y.y), amax2(y.z, y.w)));
}
__device__ __forceinline__ uint32_t get_exp(uint32_t a) { const uint4 v = lds128(a); return max(max(v.x, v.y), max(v.z, v.w)) >> 7; }
__device__ __forceinline__ void scale_a1(uint32_t (&As)[8], const uint32_t (&A1)[8], uint32_t field) {
#pragma unroll
  for (int i = 0; i < 8; i++) As[i] = hmul2(A1[i], field * 0x00800080u);
}

struct cf { float x, y; };
__device__ __forceinline__ cf cmul(cf a, cf b) { cf r; r.x = fmaf(a.x, b.x, -a.y * b.y); r.y = fmaf(a.x, b.y, a.y * b.x); return r; }
__device__ __forceinline__ cf cexp_p(float lr2, float lt, float p) {
  float m;
  asm("ex2.approx.ftz.f32 %0, %1;" : "=f"(m) : "f"(lr2 * p));
  float t = lt * p;
  t = (t - rintf(t)) * 6.283185307179586f;
  cf r; r.x = m * __cosf(t); r.y = m * __sinf(t); return r;
}
__device__ __forceinline__ void store8(uint32_t a, uint32_t b, const cf (&v)[8]) {
  sts128(a, pack(v[0].x, v[1].x), pack(v[2].x, v[3].x), pack(v[4].x, v[5].x), pack(v[6].x, v[7].x));
  sts128(b, pack(v[0].y, v[1].y), pack(v[2].y, v[3].y), pack(v[4].y, v[5].y), pack(v[6].y, v[7].y));
}
__device__ __forceinline__ void mbar_arrive(uint32_t m) { asm volatile("mbarrier.arrive.shared::cta.b64 _, [%0];" :: "r"(m) : "memory"); }
__device__ __forceinline__ float sigmoidf_(float s) { return __fdividef(1.f, 1.f + __expf(fminf(-s, 80.f))); }

__global__ void __cluster_dims__(CS, 1, 1) __launch_bounds__(NTHREADS, 1) fused_kernel(const __grid_constant__ Params p) {
  extern __shared__ __align__(1024) uint8_t smem[];
  TL_INIT();
  TL(31);
  const int wid = __shfl_sync(0xffffffffu, threadIdx.x >> 5, 0);
  const uint32_t sb = (uint32_t)__cvta_generic_to_shared(smem);
  const uint32_t mb = sb + OFF_MB;
  const int u = wid >> 2, w = wid & 3;
  const int tid = threadIdx.x & 127, lane = tid & 31, g = lane >> 2, t = lane & 3;
  const int cl = blockIdx.x >> 3, rank = blockIdx.x & 7;
  const int ch0 = cl * CPC;
  const int nu = min(5, (DCH - ch0) >> 3);
  const bool act = u < nu;

  uint32_t pla, pai, pcr, pci, pdt, tag = 0;
  auto load_params = [&]() {
    const int ch = act ? ch0 + 8 * u + rank : 0, o = ch * NMODE + tid;
    pla = ldraw(p.logA + o); pdt = ldraw(p.logdt + ch); pai = ldraw(p.Aim + o); pcr = ldraw(p.Cre + o); pci = ldraw(p.Cim + o);
  };
  if (u == 4) {
    const bool e = elect();
    if (e) {
#pragma unroll
      for (int i = 0; i < 5; i++) mbar_init(mb + 40 * w + 8 * i, 1);
      if (w == 3) { mbar_init(mb + 8 * MB_TH, 1); mbar_init(mb + 8 * MB_XQ, 21); mbar_init(mb + 8 * MB_KV, 1); }
      if (w == 2) { mbar_init(mb + 8 * MB_CF, 1); mbar_init(mb + 8 * MB_G, 8); }
      fence_mbinit();
      if ((sb & 0xffffffu) != SB0) __trap();
    }
    __syncwarp();
    load_params();
    if (w == 0 && lane < 2) asm volatile("atom.relaxed.gpu.global.add.u32 %0, [%1], %2;" : "=r"(tag) : "l"(&p.cnt[rank * 32 + lane]), "r"(cl == 0 ? 16 - (NCL - 1) : 1) : "memory");
    if (e) {
      if (w == 3) {
        mbar_expect(mb + 8 * MB_TH, 8192 + 112 * nu);
        bulk_load(sb + OFF_YB, p.tab->thr, 8192, mb + 8 * MB_TH);
        bulk_load(sb + OFF_SP, p.gate_w + ch0, 16 * nu, mb + 8 * MB_TH);
        bulk_load(sb + OFF_SP + 80, p.Dskip + ch0, 16 * nu, mb + 8 * MB_TH);
        bulk_load(sb + OFF_SP + 160, p.ssm_D + ch0, 16 * nu, mb + 8 * MB_TH);
        bulk_load(sb + OFF_SP + 240, p.shift_k + 4 * ch0, 64 * nu, mb + 8 * MB_TH);
        asm volatile("cp.async.bulk.prefetch.L2.global [%0], 12288;" :: "l"(p.tab->mat) : "memory");
        mbar_expect(mb + 8 * MB_XQ, 20480);
        tma_load3(sb + OFF_TQ, &p.tq, ch0, 8 * rank, 0, mb + 8 * MB_XQ);
        TL(20);
        mbar_expect(mb + 8 * MB_KV, 2 * 20480 + 320);
        tma_load3(sb + OFF_TK, &p.tk, ch0, 8 * rank, 0, mb + 8 * MB_KV);
        tma_load3(sb + OFF_HALO, &p.tkh, ch0, 8 * rank - 1, 28, mb + 8 * MB_KV);
      }
      if (w == 2) mbar_expect(mb + 8 * MB_CF, 12288);
#pragma unroll
      for (int i = 0; i < 5; i++) mbar_expect(mb + 40 * w + 8 * i, w == 3 ? 4096 : w == 2 ? 7168 : 3584);
    }
    __syncwarp();
  } else {
    load_params();
  }
  cluster_arrive();
  TL(0);

  const uint32_t tab = sb + OFF_T + u * KTAB;
  const uint32_t toff = (64 * w + lane) * 80 + 16 * u;
  auto put = [&](uint32_t dst, const uint32_t (&a)[4], const uint32_t (&b)[4]) {
    const uint32_t s0 = (g & 1) ? 0x7632 : 0x5410, s1 = s0 ^ 0x2222;
    const uint32_t o = dst + 128 * t + 64 * (g & 1) + 16 * (w ^ t);
    sts128(o, prmt(a[0], a[1], s0), prmt(a[2], a[3], s0), prmt(b[0], b[1], s0), prmt(b[2], b[3], s0));
    sts128(o ^ 64, prmt(a[0], a[1], s1), prmt(a[2], a[3], s1), prmt(b[0], b[1], s1), prmt(b[2], b[3], s1));
  };
  const int d0 = rank ^ (2 * w), d1 = d0 ^ 1;
  const uint32_t rb0 = mapa(sb, d0), rb1 = mapa(sb, d1);
  auto send = [&](int stage, int dst, int mbar) {
    if (elect()) {
      if (w) bulk_dsmem(rb0 + dst, sb + stage + d0 * 512, rb0 + mbar);
      bulk_dsmem(rb1 + dst, sb + stage + d1 * 512, rb1 + mbar);
    }
    __syncwarp();
  };

  uint32_t A1[8], tc[4], ts[4];
  {
    const float dt = bf16r(expf(blo(pdt)));
    const float lr2 = (-bf16r(expf(blo(pla))) * dt) * 1.4426950408889634f;
    const float lt = (blo(pai) * dt) * 0.15915494309189535f;
    const uint32_t tim = sb + (u ? OFF_IM + (u - 1) * KTAB : OFF_UX);
    const uint32_t row = tab + tid * 16, rim = tim + tid * 16;
    const cf w1 = cexp_p(lr2, lt, 8.f);
    cf z1 = cexp_p(lr2, lt, 1.f), Z = cexp_p(lr2, lt, 256.f);
    if (lr2 != 123.f) TL(16);
    TL(12);
    {
      cf v[8];
      v[0].x = 1.f; v[0].y = 0.f; v[1] = w1; v[2] = cmul(w1, w1); v[3] = cmul(v[2], w1);
      const cf w4 = cmul(v[2], v[2]);
      v[4] = w4; v[5] = cmul(v[1], w4); v[6] = cmul(v[2], w4); v[7] = cmul(v[3], w4);
      const cf w8 = cmul(w4, w4);
      store8(row, rim, v);
#pragma unroll
      for (int k = 1; k < 4; k++) {
#pragma unroll
        for (int i = 0; i < 8; i++) v[i] = (k == 1 && i == 0) ? w8 : cmul(v[i], w8);
        store8(row + 2048 * k, rim + 2048 * k, v);
      }
    }
    cluster_wait();
    if (u) cluster_arrive();
    mbar_wait(mb + 8 * MB_TH);
    {
      const uint4 x = lds128(sb + OFF_YB + 16 * tid), y = lds128(sb + OFF_YB + 2048 + 16 * tid), a = lds128(sb + OFF_YB + 4096 + 16 * tid), b = lds128(sb + OFF_YB + 6144 + 16 * tid);
      A1[0] = x.x; A1[1] = x.y; A1[2] = x.z; A1[3] = x.w; A1[4] = y.x; A1[5] = y.y; A1[6] = y.z; A1[7] = y.w;
      tc[0] = a.x; tc[1] = a.y; tc[2] = a.z; tc[3] = a.w; ts[0] = b.x; ts[1] = b.y; ts[2] = b.z; ts[3] = b.w;
    }
    if (wid == 16 && lane == 0) sts32(mb + 8 * MB_TAG, tag);
    __syncwarp();
    if (lane == 0) mbar_arrive(mb + 8 * MB_XQ);
    if (PREFETCH && wid == 8 && elect()) {
      const uint32_t o = blockIdx.x * 9856u, n = min(9856u, SEQ * DCH - o) * 2;
      asm volatile("cp.async.bulk.prefetch.L2.global [%0], %1;" :: "l"(p.v + o), "r"(n) : "memory");
      asm volatile("cp.async.bulk.prefetch.L2.global [%0], %1;" :: "l"(p.ssm_k + o), "r"(n) : "memory");
    }
    __syncwarp();
    if (u == 1) {
      float z0_ = 0.f, z1_ = 0.f, z2_ = 0.f, z3_ = 0.f;
      asm volatile("mma.sync.aligned.m16n8k8.row.col.f32.bf16.bf16.f32 {%0,%1,%2,%3}, {%4,%4}, {%4}, {%0,%1,%2,%3};"
                   : "+f"(z0_), "+f"(z1_), "+f"(z2_), "+f"(z3_) : "r"(pla >> 16));
      pcr += __float_as_uint(z0_);
      TL(8);
    }
    {
      z1.y = -z1.y; Z.y = -Z.y;
      const cf z2 = cmul(z1, z1);
      cf h[8], v[8];
      h[0].x = 2.f * blo(pcr) * dt; h[0].y = -2.f * blo(pci) * dt;
      h[1] = cmul(h[0], z1);
#pragma unroll
      for (int i = 2; i < 8; i++) h[i] = cmul(h[i - 2], z2);
      store8(row + 4 * 2048, rim + 4 * 2048, h);
      const cf h8 = cmul(h[6], z2);
      v[0] = cmul(h[0], Z); v[2] = cmul(h[2], Z); v[3] = cmul(h[4], Z); v[6] = cmul(h[6], Z); v[7] = cmul(h8, Z);
      v[1] = v[0]; v[4] = v[5] = v[3];
      store8(row + 5 * 2048, rim + 5 * 2048, v);
      h[0] = cmul(v[0], Z); h[1] = cmul(v[3], Z); h[3] = cmul(v[7], Z); h[4] = cmul(h[0], Z); h[5] = cmul(h[1], Z); h[7] = cmul(h[3], Z);
      h[2] = h[1]; h[6] = h[5];
      store8(row + 6 * 2048, rim + 6 * 2048, h);
      const cf Z2 = cmul(Z, Z);
      v[0] = cmul(h[0], Z2); v[1] = cmul(h[3], Z2); v[2] = cmul(h[4], Z2); v[3] = cmul(h[7], Z2);
#pragma unroll
      for (int i = 4; i < 8; i++) v[i] = cmul(v[i - 4], Z2);
      store8(row + 7 * 2048, rim + 7 * 2048, v);
    }
    TL(17);
    fence_async();
    if (u) bar_sync(NB_ORD + u - 1, 256); else bar_sync(NB_WG0, 128);
    TL(13);
    float c[32];
    wg_fence();
    kgen_mma<0>(c, p.dk[u]);
    wg_commit();
    if (u < 4) bar_arrive(NB_ORD + u, 256);
    TL(14);
    mbar_wait(mb + 8 * MB_XQ);
    TL(18);
    uint32_t x0[4], x1[4];
    ldsm4t(x0, sb + OFF_TQ + toff);
    ldsm4t(x1, sb + OFF_TQ + toff + 2560);
    wg_wait<0>(); tie_all(c);
    TL(26);
    if (u == 0) cluster_arrive();
    if (u == 1 || u == 2) bar_arrive(NB_V, 288);
    bar_sync(NB_WG0 + u, 128);
    if (wid == 4 && elect()) bulk_load(sb + OFF_CF, p.tab->mat, 12288, mb + 8 * MB_CF);
    __syncwarp();
    const uint32_t k0 = pack(c[0] + c[6], c[1] + c[7]), k1 = pack(c[8] + c[14], c[9] + c[15]);
    const uint32_t k2 = pack(c[16] + c[22], c[17] + c[23]), k3 = pack(c[24] + c[30], c[25] + c[31]);
    const uint32_t ka = tab + 16 * (8 * w + (g ^ w));
    sts32(ka + 4 * t, k0);
    sts32(ka + 512 + 4 * t, k1);
    sts64(ka + 1024 + 512 * (t >> 1) + 8 * (t & 1), prmt(k2, 0, 0x1010), (t & 1) ? prmt(k2, 0, 0x3232) : k2);
    const uint32_t lo = prmt(k3, 0, 0x1010), hi = prmt(k3, 0, 0x3232);
    sts128(ka + 2048 + 512 * t, lo, lo, (g & 1) ? hi : k3, hi);
    put_exp(sb + OFF_MX + u * 64 + 4 * w, amax2(amax2(k0, k1), amax2(k2, k3)), lane);
    cluster_wait();
    cluster_arrive();
    put(sb + u * 4096 + g * 512 + (g == rank ? OFF_UX : OFF_YB), x0, x1);
    TL(15);
    fence_async();
    bar_sync(NB_WG0 + u, 128);
    send(OFF_YB + u * 4096, OFF_UX + u * 4096 + 512 * rank, OFF_MB + 8 * (MB_UX + u));
    if (wid == 16) {
      bar_sync(NB_V, 288);
      if (elect()) tma_load3(sb + OFF_TV, &p.tv, ch0, 8 * rank, 0, mb + 8 * MB_KV);
      __syncwarp();
    }
  }
  if (u == 0) {
    float ga[4][4];
#pragma unroll
    for (int i = 0; i < 4; i++) ga[i][0] = ga[i][1] = ga[i][2] = ga[i][3] = 0.f;
#pragma unroll
    for (int j = 0; j < 5; j++) {
      uint32_t a0[4], a1[4], b;
      ldsm4(a0, sb + OFF_TQ + toff + 16 * j);
      ldsm4(a1, sb + OFF_TQ + toff + 2560 + 16 * j);
      asm volatile("ld.shared.u32 %0, [%1];" : "=r"(b) : "r"(sb + OFF_SP + 16 * j + 4 * t) : "memory");
      if (j >= 2 && j >= nu) b = 0;
      mma1688(ga[0], a0[0], a0[1], b); mma1688(ga[1], a0[2], a0[3], b); mma1688(ga[2], a1[0], a1[1], b); mma1688(ga[3], a1[2], a1[3], b);
    }
    const float s0 = t == 0 ? ga[0][0] : t == 1 ? ga[1][0] : t == 2 ? ga[2][0] : ga[3][0];
    const float s1 = t == 0 ? ga[0][2] : t == 1 ? ga[1][2] : t == 2 ? ga[2][2] : ga[3][2];
    tag = (lds64(mb + 8 * MB_TAG).x >> 4) + 1;
    uint2* gp = p.part + cl * SEQ + rank * 256 + 64 * w + 16 * t + g;
    asm volatile("st.relaxed.gpu.global.u64 [%0], %1;" :: "l"(gp), "l"(((uint64_t)tag << 32) | __float_as_uint(s0)) : "memory");
    asm volatile("st.relaxed.gpu.global.u64 [%0], %1;" :: "l"(gp + 8), "l"(((uint64_t)tag << 32) | __float_as_uint(s1)) : "memory");
  }

#pragma unroll
  for (int isA = 0; isA < 2; isA++) {
    {
      TL(1 + isA);
      const uint32_t usrc = isA ? tab + T_UKV : sb + OFF_UX + u * 4096;
      const uint32_t mxa = sb + OFF_MX + u * 64 + 32 * isA;
      const uint32_t pd = lds16(sb + OFF_SP + 80 + 80 * isA + 16 * u + 2 * rank);
      float D[32];
      uint32_t As[8], F[16], H[16], X[16];
      const uint32_t eh = min(max((int)get_exp(mxa), (int)((pd >> 7) & 0xff) - 5), 240);
      scale_a1(As, A1, 248 - eh);
      wg_fence();
      if (isA) stage1<T_HA / 16>(D, As, p.dt[u]); else stage1<0>(D, As, p.dt[u]);
      wg_commit();
      wg_wait<0>(); tie_all(D);
      fwd_mid(F, D, tc, ts);
      if (!isA) mbar_wait(mb + 8 * MB_CF);
      wg_fence();
      stage2<0>(H, F, p.dfwd);
      wg_commit();
      if (!isA) {
        if (w == 2 && elect()) bulk_load(tab + T_HA, p.ssm_k + (size_t)(act ? ch0 + 8 * u + rank : 0) * SEQ, 4096, mb + 8 * (MB_HA + u));
        __syncwarp();
        TL(7);
      }
      if (isA) fence_async();
      mbar_wait(mb + 8 * ((isA ? MB_UKV : MB_UX) + u));
      TL(5 + isA);
      put_exp(mxa + 16 + 4 * w, seq_mag(usrc + 16 * tid), lane);
      bar_sync(NB_WG0 + u, 128);
      if (isA) {
        send(OFF_UX + u * 4096, OFF_YB + (8 * u + rank) * 512, OFF_MB + 8 * (MB_Y + u));
      }
      const uint32_t eu = min(get_exp(mxa + 16), 240u);
      scale_a1(As, A1, 250 - eu);
      wg_wait<0>(); tie_all(H);
      wg_fence();
      if (isA) stage1<T_UKV / 16>(D, As, p.dt[u]); else stage1<0>(D, As, p.dx[u]);
      wg_commit();
      wg_wait<0>(); tie_all(D);
      fwd_mid(F, D, tc, ts);
      wg_fence();
      stage2<0>(X, F, p.dfwd);
      wg_commit();
      {
        const float dsk = blo(pd) * __uint_as_float((248 - eh) << 23);
        const uint32_t d2 = packh(dsk, dsk);
#pragma unroll
        for (int j = 0; j < 4; j++) H[2 * j] = U2(__hadd2(H2(H[2 * j]), H2(d2)));
      }
      wg_wait<0>(); tie_all(X);
#pragma unroll
      for (int j = 0; j < 4; j++) {
        const uint32_t h0r = H[2 * j], h1r = H[2 * j + 1], h0i = H[8 + 2 * j], h1i = H[9 + 2 * j];
        const uint32_t x0r = X[2 * j], x1r = X[2 * j + 1], x0i = X[8 + 2 * j], x1i = X[9 + 2 * j];
        F[2 * j] = ffma(x0r, h0r, fneg(fmul(x0i, h0i)));
        F[8 + 2 * j] = ffma(x0r, h0i, fmul(x0i, h0r));
        F[2 * j + 1] = ffma(x1r, h0r, ffma(fneg(x1i), h0i, ffma(x0r, h1r, fneg(ffma(x0i, h1i, F[8 + 2 * j])))));
        F[9 + 2 * j] = ffma(x1r, h0i, ffma(x1i, h0r, ffma(x0r, h1i, ffma(x0i, h1r, F[2 * j]))));
      }
      wg_fence();
      stage2<1>(H, F, p.dinv);
      wg_commit();
      uint64_t ga[4];
      const int sl2 = min(18 * cl + min(8 * w + g, 17), 255), sl3 = tid + 128 * (u & 1);
      auto gload = [&]() {
        if (isA) {
          asm volatile("ld.relaxed.gpu.global.u64 %0, [%1];" : "=l"(ga[0]) : "l"(p.part + NCL * SEQ + rank * 256 + sl3) : "memory");
        } else {
#pragma unroll
          for (int k = 0; k < 4; k++)
            asm volatile("ld.relaxed.gpu.global.u64 %0, [%1];" : "=l"(ga[k]) : "l"(p.part + (t + (k == 3 && t == 3 ? 8 : 4 * k)) * SEQ + rank * 256 + sl2) : "memory");
        }
      };
      if (isA ? (u & 6) == 2 : u == 1) gload();
      if (isA) TL(23);
      wg_wait<0>(); tie_all(H);
      {
        const uint32_t va = tab + (16 * w + (lane & 15)) * 128;
        const int vx = (lane >> 4) ^ (lane & 7);
#pragma unroll
        for (int j = 0; j < 4; j++) {
          uint32_t V[4];
#pragma unroll
          for (int b = 0; b < 2; b++) {
            const uint32_t er = H[2 * j + b], ei = H[8 + 2 * j + b];
            V[2 * b] = ffma(er, tc[j], fneg(fmul(ei, ts[j])));
            V[2 * b + 1] = ffma(ei, tc[j], fmul(er, ts[j]));
          }
          stsm4(va + ((vx ^ (2 * j)) << 4), V);
        }
      }
      if (!isA) {
        cluster_wait();
        mbar_wait(mb + 8 * MB_KV);
        TL(21);
        uint32_t K[3][4], V[2][4];
        const uint2 psw = lds64(sb + OFF_SP + 240 + 64 * u + 8 * g);
        ldsm4t(K[0], w ? sb + OFF_TK + toff - 2560 : (lane & 7) ? sb + OFF_TK + toff + 223 * 80 : sb + OFF_HALO + 10 * lane + 16 * u);
        ldsm4t(K[1], sb + OFF_TK + toff);
        ldsm4t(K[2], sb + OFF_TK + toff + 2560);
        ldsm4t(V[0], sb + OFF_TV + toff);
        ldsm4t(V[1], sb + OFF_TV + toff + 2560);
        mbar_wait(mb + 8 * (MB_HA + u));
        const uint4 hx = lds128(tab + T_HA + 16 * tid), hy = lds128(tab + T_HA + 2048 + 16 * tid);
        const uint32_t w0 = prmt(psw.x, 0, 0x1010), w1 = prmt(psw.x, 0, 0x3232), w2 = prmt(psw.y, 0, 0x1010), w3 = prmt(psw.y, 0, 0x3232);
#pragma unroll
        for (int m = 4; m < 12; m++)
          V[(m >> 2) - 1][m & 3] = hmul2(hfma2(K[m >> 2][m & 3], w0, hfma2(K[(m - 1) >> 2][(m - 1) & 3], w1,
                                         hfma2(K[(m - 2) >> 2][(m - 2) & 3], w2, hmul2(K[(m - 3) >> 2][(m - 3) & 3], w3)))), V[(m >> 2) - 1][m & 3]);
        put(g == rank ? tab + T_UKV + 512 * rank : sb + OFF_YA + u * 4096 + g * 512, V[0], V[1]);
        put_exp(mxa + 32 + 4 * w, amax2(amax2(amax2(hx.x, hx.y), amax2(hx.z, hx.w)), amax2(amax2(hy.x, hy.y), amax2(hy.z, hy.w))), lane);
        sts128(tab + T_HA + 16 * (tid ^ (lane >> 3)), hx.x, hx.y, hx.z, hx.w);
        sts128(tab + T_HA + 2048 + 16 * (tid ^ (lane >> 3)), hy.x, hy.y, hy.z, hy.w);
        TL(22);
      }
      fence_async();
      bar_sync(NB_WG0 + u, 128);
      float O[16];
      {
        const uint64_t dv = p.dv[u], dl = p.dlast;
        wg_fence();
        ss32<0, 0, 0>(O, dv, dl); ss32<1, 128, 64>(O, dv, dl); ss32<1, 256, 128>(O, dv, dl); ss32<1, 384, 192>(O, dv, dl);
        wg_commit();
      }
      if (!isA) send(OFF_YA + u * 4096, OFF_T + u * KTAB + T_UKV + 512 * rank, OFF_MB + 8 * (MB_UKV + u));
      if (isA ? (u & 6) == 2 : u == 1) {
        tag = (lds64(mb + 8 * MB_TAG).x >> 4) + 1;
        bool ok;
#pragma unroll 1
        for (int it = 0;; it++) {
          ok = (uint32_t)(ga[0] >> 32) == tag;
          if (!isA) ok = ok && (uint32_t)(ga[1] >> 32) == tag && (uint32_t)(ga[2] >> 32) == tag && (uint32_t)(ga[3] >> 32) == tag;
          ok = __all_sync(0xffffffffu, ok);
          if (ok || it == (isA ? 8000 : 2000)) break;
          gload();
        }
        if (!isA) {
          float s = __uint_as_float((uint32_t)ga[0]) + __uint_as_float((uint32_t)ga[1]) + __uint_as_float((uint32_t)ga[2]);
          if (t < 3) s += __uint_as_float((uint32_t)ga[3]);
          s += __shfl_xor_sync(0xffffffffu, s, 1);
          s += __shfl_xor_sync(0xffffffffu, s, 2);
          const float g0 = bf16r(sigmoidf_(bf16r(s)));
          if (ok && t == 0)
            asm volatile("st.relaxed.gpu.global.u64 [%0], %1;" :: "l"(p.part + NCL * SEQ + rank * 256 + sl2), "l"(((uint64_t)tag << 32) | pack(g0, 1.f - g0)) : "memory");
        } else {
          uint32_t gv = (uint32_t)ga[0];
          if (!ok) {
            const uint32_t* xr = (const uint32_t*)(p.q + (size_t)(rank * 256 + 32 * (sl3 & 7) + (sl3 >> 3)) * DCH);
            const uint32_t* gr = (const uint32_t*)p.gate_w;
            float s = 0.f;
#pragma unroll 1
            for (int k = 0; k < DCH / 2; k++) { const uint32_t x = __ldg(xr + k), y = __ldg(gr + k); s = fmaf(blo(x), blo(y), fmaf(bhi(x), bhi(y), s)); }
            const float g0 = bf16r(sigmoidf_(bf16r(s)));
            gv = pack(g0, 1.f - g0);
          }
          sts64(sb + OFF_GB + 8 * sl3, prmt(gv, 0, 0x1010), prmt(gv, 0, 0x3232));
          __syncwarp();
          if (lane == 0) mbar_arrive(mb + 8 * MB_G);
        }
      }
      if (isA) TL(28);
      wg_wait<0>(); tie_all(O);
      {
        const uint32_t co = ((8 * w + g) ^ (2 * t) ^ rank) * 16;
        const int yo = (isA ? OFF_YA : OFF_YB) + (8 * u + rank) * 512, ym = OFF_MB + 8 * (MB_Y + u);
        const uint32_t us = min(max((int)(eu + eh) - 127, 0), 254) * 0x00800080u;
        const uint32_t a0 = hmul2(pack(O[0], O[1]), us), a1 = hmul2(pack(O[4], O[5]), us), a2 = hmul2(pack(O[8], O[9]), us), a3 = hmul2(pack(O[12], O[13]), us);
        const uint32_t b0 = hmul2(pack(O[2], O[3]), us), b1 = hmul2(pack(O[6], O[7]), us), b2 = hmul2(pack(O[10], O[11]), us), b3 = hmul2(pack(O[14], O[15]), us);
        sts128((t == rank ? sb + yo : usrc + t * 512) + co, a0, a1, a2, a3);
        sts128((t + 4 == rank ? sb + yo : usrc + t * 512 + 2048) + co, b0, b1, b2, b3);
        if (isA) {
          fence_async();
          bar_sync(NB_WG0 + u, 128);
          send(usrc - sb, yo, ym);
        }
      }
      TL(9 + isA);
    }
  }

  {
    mbar_wait(mb + 8 * MB_G);
    uint2 gg[2][4];
    uint32_t qv[2][4];
#pragma unroll
    for (int hh = 0; hh < 2; hh++)
#pragma unroll
      for (int i = 0; i < 4; i++) gg[hh][i] = lds64(sb + OFF_GB + 8 * (64 * w + 32 * hh + 8 * i + g));
    const uint32_t qa = sb + OFF_TQ + toff;
    ldsm4(qv[0], qa);
    ldsm4(qv[1], qa + 2560);
    TL(24);
    mbar_wait(mb + 8 * (MB_Y + u));
    uint32_t ya[2][4], yb[2][4];
#pragma unroll
    for (int hh = 0; hh < 2; hh++) {
      const uint32_t yo = (8 * u + (lane & 7)) * 512 + ((8 * w + 4 * hh + (lane >> 3)) ^ (2 * (rank & 3)) ^ (lane & 7)) * 16;
      ldsm4t(ya[hh], sb + OFF_YA + yo); ldsm4t(yb[hh], sb + OFF_YB + yo);
    }
#pragma unroll
    for (int hh = 0; hh < 2; hh++) {
      uint32_t o[4];
#pragma unroll
      for (int i = 0; i < 4; i++) o[i] = hadd2(hmul2(gg[hh][i].x, hmul2(qv[hh][i], ya[hh][i])), hmul2(gg[hh][i].y, yb[hh][i]));
      stsm4(qa + 2560 * hh, o);
    }
    TL(25);
  }
  cluster_arrive();
  bar_sync(NB_ROW0 + w, 160);
  {
    uint4 v[2];
#pragma unroll
    for (int k = 0; k < 2; k++) {
      const int i = 64 * u + 32 * k + lane, sl = (i * 205) >> 10, cc = i - 5 * sl;
      v[k] = lds128(sb + OFF_TQ + (64 * w + 8 * (sl & 7) + (sl >> 3)) * 80 + cc * 16);
    }
#pragma unroll
    for (int k = 0; k < 2; k++) {
      const int i = 64 * u + 32 * k + lane, sl = (i * 205) >> 10, cc = i - 5 * sl;
      if (cc < nu)
        asm volatile("st.global.v4.u32 [%0], {%1,%2,%3,%4};" :: "l"(p.out + (size_t)(256 * rank + 32 * (sl >> 3) + 8 * w + (sl & 7)) * DCH + ch0 + 8 * cc),
                     "r"(v[k].x), "r"(v[k].y), "r"(v[k].z), "r"(v[k].w) : "memory");
    }
  }
  cluster_wait();
  TL(27);
  TL_DUMP();
}

typedef CUresult (*EncodeFn)(CUtensorMap*, CUtensorMapDataType, cuuint32_t, void*, const cuuint64_t*, const cuuint64_t*,
                             const cuuint32_t*, const cuuint32_t*, CUtensorMapInterleave, CUtensorMapSwizzle,
                             CUtensorMapL2promotion, CUtensorMapFloatOOBfill);

void encode(EncodeFn fn, CUtensorMap* tm, const void* ptr, int nd, const cuuint64_t* dims, const cuuint64_t* strides,
            const cuuint32_t* box, CUtensorMapSwizzle swz) {
  cuuint32_t es[4] = {1, 1, 1, 1};
  fn(tm, CU_TENSOR_MAP_DATA_TYPE_BFLOAT16, nd, const_cast<void*>(ptr), dims, strides, box, es, CU_TENSOR_MAP_INTERLEAVE_NONE,
     swz, CU_TENSOR_MAP_L2_PROMOTION_L2_128B, CU_TENSOR_MAP_FLOAT_OOB_FILL_NONE);
}
void make_map(EncodeFn fn, CUtensorMap* tm, const void* ptr, int ne, int nr) {
  const cuuint64_t dims[3] = {DCH, SEQ / 32, 32}, strides[2] = {32 * DCH * 2, DCH * 2};
  const cuuint32_t box[3] = {CPC, (cuuint32_t)ne, (cuuint32_t)nr};
  encode(fn, tm, ptr, 3, dims, strides, box, CU_TENSOR_MAP_SWIZZLE_NONE);
}

}

extern "C" void kernel_launch(void* const* d_in, const int* in_sizes, int n_in, void* d_out, int out_size) {
  (void)in_sizes; (void)n_in; (void)out_size;
  static EncodeFn fn = nullptr;
  static void *tab = nullptr, *cnt = nullptr, *part = nullptr;
  if (!fn) {
    cudaGetSymbolAddress(&tab, d_tab);
    cudaGetSymbolAddress(&cnt, g_cnt);
    cudaGetSymbolAddress(&part, g_part);
    cudaDriverEntryPointQueryResult qr;
    cudaGetDriverEntryPoint("cuTensorMapEncodeTiled", (void**)&fn, cudaEnableDefault, &qr);
    cudaFuncSetAttribute(fused_kernel, cudaFuncAttributeMaxDynamicSharedMemorySize, SMEM_BYTES);
  }
  Params p;
  make_map(fn, &p.tq, d_in[0], 8, 32);
  make_map(fn, &p.tk, d_in[1], 8, 32);
  make_map(fn, &p.tv, d_in[2], 8, 32);
  make_map(fn, &p.tkh, d_in[1], 1, 4);
  p.out = (__nv_bfloat16*)d_out;
  p.dfwd = mkdesc(OFF_CF, 1024, 128, 0);
  p.dinv = mkdesc(OFF_CF, 128, 1024, 0);
  p.dlast = mkdesc(OFF_CL, 512, 128, 0);
  for (int u = 0; u < 5; u++) {
    p.dk[u] = mkdesc(OFF_T + u * KTAB, u ? OFF_IM - KTAB - OFF_T : OFF_UX - OFF_T, 1024, 0);
    p.dt[u] = mkdesc(OFF_T + u * KTAB, 2048, 512, 2);
    p.dx[u] = mkdesc(OFF_UX + u * 4096, 2048, 512, 2);
    p.dv[u] = mkdesc(OFF_T + u * KTAB, 16, 1024, 1);
  }
  p.tab = (const Tables*)tab;
  p.cnt = (unsigned*)cnt;
  p.part = (uint2*)part;
  p.tl = nullptr;
  p.q = (const __nv_bfloat16*)d_in[0];
  p.v = (const __nv_bfloat16*)d_in[2];
  p.ssm_k = (const __nv_bfloat16*)d_in[4];
  p.shift_k = (const __nv_bfloat16*)d_in[3];
  p.ssm_D = (const __nv_bfloat16*)d_in[5];
  p.logA = (const __nv_bfloat16*)d_in[7];
  p.Aim = (const __nv_bfloat16*)d_in[8];
  p.Cre = (const __nv_bfloat16*)d_in[9];
  p.Cim = (const __nv_bfloat16*)d_in[10];
  p.logdt = (const __nv_bfloat16*)d_in[11];
  p.Dskip = (const __nv_bfloat16*)d_in[12];
  p.gate_w = (const __nv_bfloat16*)d_in[13];
  fused_kernel<<<NCL * CS, NTHREADS, SMEM_BYTES, cudaStreamPerThread>>>(p);
}
```

```cpp
#include <cuda_runtime.h>
#include <cuda_bf16.h>
#include <cuda_fp16.h>
#include <cuda.h>
#include <stdint.h>

#define TIMELINE 0
#define STAGGER 0
#define PREFETCH 1
#define TLHI 0

namespace {

constexpr int SEQ = 2048, DCH = 576, NMODE = 128;
constexpr int CS = 8, CPC = 40, NCL = 15, NTHREADS = 640;

constexpr int KTAB = 16384;
constexpr int OFF_T = 0;
constexpr int T_UKV = 8192, T_HA = 12288;
constexpr int OFF_UX = 5 * KTAB;
constexpr int OFF_IM = OFF_UX + 20480;
constexpr int OFF_YB = OFF_IM;
constexpr int OFF_TV = OFF_YB + 20480;
constexpr int OFF_YA = OFF_TV + 20480;
constexpr int OFF_GB = OFF_YA + 20480;
constexpr int OFF_CF = OFF_IM + 4 * KTAB;
constexpr int OFF_CL = OFF_CF + 8192;
constexpr int OFF_TH = OFF_CL + 4096;
constexpr int OFF_TQ = OFF_TH + 8192;
constexpr int OFF_TK = OFF_TQ + 20480;
constexpr int OFF_HALO = OFF_TK + 20480;
constexpr int OFF_MX = OFF_HALO + 320;
constexpr int OFF_SP = OFF_MX + 320;
constexpr int OFF_MB = OFF_SP + 560;
constexpr int OFF_TL = OFF_MB + 28 * 8;
constexpr int SMEM_BYTES = OFF_TL + (TIMELINE ? 1280 : 0);
static_assert(SMEM_BYTES <= 232448 && OFF_GB + 2048 <= OFF_CF, "smem");
static_assert((OFF_MB & 7) == 0 && (OFF_MX & 15) == 0 && (OFF_SP & 15) == 0, "align");

enum { MB_UX = 0, MB_UKV = 5, MB_Y = 10, MB_HA = 15, MB_XQ = 20, MB_KV = 21, MB_CF = 22, MB_G = 23, MB_TH = 24, MB_TAG = 25 };
enum { NB_WG0 = 1, NB_ROW0 = 6, NB_ORD = 6, NB_V = 10, NB_ST = 11 };

constexpr uint32_t SB0 = 1024;
constexpr uint64_t mkdesc(uint32_t off, uint32_t lbo, uint32_t sbo, uint32_t swz) {
  return (uint64_t)((SB0 + off) >> 4) | ((uint64_t)(lbo >> 4) << 16) | ((uint64_t)(sbo >> 4) << 32) | ((uint64_t)swz << 62);
}

constexpr double cos_turn(int m, int n) {
  m &= n - 1;
  if (m > n / 2) m = n - m;
  double sgn = 1.0;
  if (m > n / 4) { m = n / 2 - m; sgn = -1.0; }
  if (m == n / 4) return 0.0;
  const double x = 6.283185307179586476925 * m / n;
  double term = 1.0, sum = 1.0;
  for (int k = 1; k < 14; k++) { term *= -x * x / ((2 * k - 1) * (2 * k)); sum += term; }
  return sgn * sum;
}
constexpr uint32_t bf16_bits(double v) {
  if (v == 0.0) return 0;
  uint32_t sgn = 0;
  if (v < 0) { sgn = 0x8000; v = -v; }
  int e = 127;
  while (v < 1.0) { v *= 2.0; e--; }
  while (v >= 2.0) { v *= 0.5; e++; }
  const double f = v * 128.0;
  int m = (int)f;
  if (f - m > 0.5 || (f - m == 0.5 && (m & 1))) m++;
  return sgn | (uint32_t)((e << 7) + (m - 128));
}
constexpr uint32_t f16_bits(double v) {
  if (v == 0.0) return 0;
  uint32_t sgn = 0;
  if (v < 0) { sgn = 0x8000; v = -v; }
  int e = 15;
  while (v < 1.0) { v *= 2.0; e--; }
  const double f = v * 1024.0;
  int m = (int)f;
  if (f - m > 0.5 || (f - m == 0.5 && (m & 1))) m++;
  return sgn | (uint32_t)((e << 10) + (m - 1024));
}
constexpr uint32_t pair_bits(double lo, double hi) { return bf16_bits(lo) | (bf16_bits(hi) << 16); }
constexpr uint32_t pair_h(double lo, double hi) { return f16_bits(lo) | (f16_bits(hi) << 16); }
struct alignas(128) Tables {
  uint32_t mat[3072];
  uint32_t thr[4][128][4];
};
constexpr Tables make_tables() {
  Tables T{};
  for (int q = 0; q < 768; q++) {
    int m0 = 0, d0 = 0, d1 = 0;
    if (q < 512) {
      const int r = (q >> 6) * 8 + (q & 7), cc = (q >> 3) & 7;
      d0 = 4 * (r & 31); d1 = 2 * d0;
      m0 = 8 * (cc & 3) * d0 + ((r >> 5) == (cc >> 2) ? 0 : (r >> 5) ? 96 : 32);
    } else {
      const int r = ((q - 512) >> 5) * 8 + (q & 7), pc = (q >> 3) & 3;
      d0 = 4 * (8 * (r >> 4) + (r & 7)) + 1; d1 = 8 * d0;
      m0 = 2 * pc * d0 + ((r & 8) ? 32 : 0);
    }
    for (int e = 0; e < 4; e++) T.mat[4 * q + e] = pair_h(cos_turn(m0 + e * d1, 128), cos_turn(m0 + e * d1 + d0, 128));
  }
  for (int tid = 0; tid < 128; tid++) {
    const int kk = 4 * (tid >> 2) + 1, t = tid & 3;
    for (int q = 0; q < 4; q++) {
      const int m = (8 * q + 2 * t) * kk;
      T.thr[q >> 1][tid][2 * (q & 1)] = pair_bits(cos_turn(m, 128), cos_turn(m + kk, 128));
      T.thr[q >> 1][tid][2 * (q & 1) + 1] = pair_bits(cos_turn(m + 32, 128), cos_turn(m + kk + 32, 128));
      T.thr[2][tid][q] = pair_h(cos_turn(m, 4096), cos_turn(m + kk, 4096));
      T.thr[3][tid][q] = pair_h(cos_turn(m + 3072, 4096), cos_turn(m + kk + 3072, 4096));
    }
  }
  return T;
}
__device__ const Tables d_tab = make_tables();

struct Params {
  const __nv_bfloat16 *logA, *Aim, *Cre, *Cim, *logdt;
  const Tables* tab;
  unsigned* cnt;
  const __nv_bfloat16 *Dskip, *shift_k, *ssm_D, *gate_w, *q, *v, *ssm_k;
  uint2* part;
  __nv_bfloat16* out;
  unsigned* tl;
  uint64_t dfwd, dinv, dlast, dk[5], dt[5], dx[5], dv[5];
  CUtensorMap tq, tk, tv, tkh;
};

__device__ uint2 g_part[(NCL + 1) * SEQ];
__device__ unsigned g_cnt[CS * 32];
#define TL(i) do {} while (0)
#define TL_INIT() do {} while (0)
#define TL_DUMP() do {} while (0)

__device__ __forceinline__ uint32_t lds16(uint32_t a) { uint32_t v; asm volatile("ld.shared.u16 %0, [%1];" : "=r"(v) : "r"(a) : "memory"); return v; }
__device__ __forceinline__ uint2 lds64(uint32_t a) { uint2 v; asm volatile("ld.shared.v2.u32 {%0,%1}, [%2];" : "=r"(v.x), "=r"(v.y) : "r"(a) : "memory"); return v; }
__device__ __forceinline__ uint4 lds128(uint32_t a) { uint4 v; asm volatile("ld.shared.v4.u32 {%0,%1,%2,%3}, [%4];" : "=r"(v.x), "=r"(v.y), "=r"(v.z), "=r"(v.w) : "r"(a) : "memory"); return v; }
__device__ __forceinline__ void sts16(uint32_t a, uint32_t v) { asm volatile("st.shared.u16 [%0], %1;" :: "r"(a), "r"(v) : "memory"); }
__device__ __forceinline__ void sts32(uint32_t a, uint32_t v) { asm volatile("st.shared.u32 [%0], %1;" :: "r"(a), "r"(v) : "memory"); }
__device__ __forceinline__ void sts64(uint32_t a, uint32_t x, uint32_t y) { asm volatile("st.shared.v2.u32 [%0], {%1,%2};" :: "r"(a), "r"(x), "r"(y) : "memory"); }
__device__ __forceinline__ void sts128(uint32_t a, uint32_t x, uint32_t y, uint32_t z, uint32_t w) { asm volatile("st.shared.v4.u32 [%0], {%1,%2,%3,%4};" :: "r"(a), "r"(x), "r"(y), "r"(z), "r"(w) : "memory"); }
__device__ __forceinline__ void ldsm4t(uint32_t (&r)[4], uint32_t a) { asm volatile("ldmatrix.sync.aligned.m8n8.x4.trans.shared.b16 {%0,%1,%2,%3}, [%4];" : "=r"(r[0]), "=r"(r[1]), "=r"(r[2]), "=r"(r[3]) : "r"(a) : "memory"); }
__device__ __forceinline__ void ldsm2t(uint32_t& r0, uint32_t& r1, uint32_t a) { asm volatile("ldmatrix.sync.aligned.m8n8.x2.trans.shared.b16 {%0,%1}, [%2];" : "=r"(r0), "=r"(r1) : "r"(a) : "memory"); }
__device__ __forceinline__ void ldsm4(uint32_t (&r)[4], uint32_t a) { asm volatile("ldmatrix.sync.aligned.m8n8.x4.shared.b16 {%0,%1,%2,%3}, [%4];" : "=r"(r[0]), "=r"(r[1]), "=r"(r[2]), "=r"(r[3]) : "r"(a) : "memory"); }
__device__ __forceinline__ void stsm4(uint32_t a, const uint32_t (&r)[4]) { asm volatile("stmatrix.sync.aligned.m8n8.x4.shared.b16 [%0], {%1,%2,%3,%4};" :: "r"(a), "r"(r[0]), "r"(r[1]), "r"(r[2]), "r"(r[3]) : "memory"); }
__device__ __forceinline__ uint32_t pack(float lo, float hi) { uint32_t r; asm("cvt.rn.bf16x2.f32 %0, %1, %2;" : "=r"(r) : "f"(hi), "f"(lo)); return r; }
__device__ __forceinline__ float blo(uint32_t v) { return __uint_as_float(v << 16); }
__device__ __forceinline__ float bhi(uint32_t v) { return __uint_as_float(v & 0xffff0000u); }
__device__ __forceinline__ float bf16r(float x) { return blo(pack(x, 0.f)); }
__device__ __forceinline__ uint32_t hmul2(uint32_t a, uint32_t b) { uint32_t r; asm("mul.rn.bf16x2 %0, %1, %2;" : "=r"(r) : "r"(a), "r"(b)); return r; }
__device__ __forceinline__ uint32_t hadd2(uint32_t a, uint32_t b) { uint32_t r; asm("add.rn.bf16x2 %0, %1, %2;" : "=r"(r) : "r"(a), "r"(b)); return r; }
__device__ __forceinline__ uint32_t hfma2(uint32_t a, uint32_t b, uint32_t c) { uint32_t r; asm("fma.rn.bf16x2 %0, %1, %2, %3;" : "=r"(r) : "r"(a), "r"(b), "r"(c)); return r; }
__device__ __forceinline__ uint32_t packh(float lo, float hi) { uint32_t r; asm("cvt.rn.f16x2.f32 %0, %1, %2;" : "=r"(r) : "f"(hi), "f"(lo)); return r; }
__device__ __forceinline__ __half2 H2(uint32_t a) { return *reinterpret_cast<__half2*>(&a); }
__device__ __forceinline__ uint32_t U2(__half2 a) { return *reinterpret_cast<uint32_t*>(&a); }
__device__ __forceinline__ uint32_t fmul(uint32_t a, uint32_t b) { return U2(__hmul2(H2(a), H2(b))); }
__device__ __forceinline__ uint32_t ffma(uint32_t a, uint32_t b, uint32_t c) { return U2(__hfma2(H2(a), H2(b), H2(c))); }
__device__ __forceinline__ uint32_t fneg(uint32_t a) { return U2(__hneg2(H2(a))); }
__device__ __forceinline__ uint32_t amax2(uint32_t a, uint32_t b) { uint32_t r; asm("max.xorsign.abs.bf16x2 %0, %1, %2;" : "=r"(r) : "r"(a), "r"(b)); return r; }
__device__ __forceinline__ uint32_t prmt(uint32_t a, uint32_t b, uint32_t s) { return __byte_perm(a, b, s); }
__device__ __forceinline__ uint32_t ldraw(const __nv_bfloat16* p) { uint32_t v; asm volatile("ld.global.nc.u16 %0, [%1];" : "=r"(v) : "l"(p)); return v; }
__device__ __forceinline__ uint4 ldg128(const void* p) { uint4 v; asm volatile("ld.global.nc.v4.u32 {%0,%1,%2,%3}, [%4];" : "=r"(v.x), "=r"(v.y), "=r"(v.z), "=r"(v.w) : "l"(p)); return v; }
__device__ __forceinline__ void bar_sync(int id, int n) { asm volatile("bar.sync %0, %1;" :: "r"(id), "r"(n) : "memory"); }
__device__ __forceinline__ void bar_arrive(int id, int n) { asm volatile("bar.arrive %0, %1;" :: "r"(id), "r"(n) : "memory"); }
__device__ __forceinline__ void cluster_arrive() { asm volatile("barrier.cluster.arrive.relaxed.aligned;" ::: "memory"); }
__device__ __forceinline__ void cluster_wait() { asm volatile("barrier.cluster.wait.aligned;" ::: "memory"); }
__device__ __forceinline__ void fence_async() { asm volatile("fence.proxy.async.shared::cta;" ::: "memory"); }
__device__ __forceinline__ void fence_mbinit() { asm volatile("fence.mbarrier_init.release.cluster;" ::: "memory"); }
__device__ __forceinline__ uint32_t mapa(uint32_t a, uint32_t rank) { uint32_t r; asm("mapa.shared::cluster.u32 %0, %1, %2;" : "=r"(r) : "r"(a), "r"(rank)); return r; }
__device__ __forceinline__ void bulk_dsmem(uint32_t dst, uint32_t src, uint32_t mbar) {
  asm volatile("cp.async.bulk.shared::cluster.shared::cta.mbarrier::complete_tx::bytes [%0], [%1], 512, [%2];" :: "r"(dst), "r"(src), "r"(mbar) : "memory");
}
__device__ __forceinline__ void bulk_load(uint32_t dst, const void* src, uint32_t bytes, uint32_t mbar) {
  asm volatile("cp.async.bulk.shared::cluster.global.mbarrier::complete_tx::bytes [%0], [%1], %2, [%3];" :: "r"(dst), "l"(src), "r"(bytes), "r"(mbar) : "memory");
}
__device__ __forceinline__ void mbar_init(uint32_t m, uint32_t cnt) { asm volatile("mbarrier.init.shared::cta.b64 [%0], %1;" :: "r"(m), "r"(cnt) : "memory"); }
__device__ __forceinline__ void mbar_expect(uint32_t m, uint32_t bytes) { asm volatile("mbarrier.arrive.expect_tx.shared::cta.b64 _, [%0], %1;" :: "r"(m), "r"(bytes) : "memory"); }
__device__ __forceinline__ bool mbar_try(uint32_t m) {
  uint32_t done;
  asm volatile("{.reg .pred p; mbarrier.try_wait.parity.shared::cta.b64 p, [%1], 0; selp.u32 %0, 1, 0, p;}" : "=r"(done) : "r"(m) : "memory");
  return done;
}
__device__ __forceinline__ void mbar_wait(uint32_t m) {
  if (!mbar_try(m)) {
    int it = 0;
    while (!mbar_try(m) && ++it < (1 << 22)) {}
  }
}
__device__ __forceinline__ bool elect() {
  uint32_t e;
  asm volatile("{.reg .pred p; elect.sync _|p, 0xffffffff; selp.u32 %0, 1, 0, p;}" : "=r"(e));
  return e;
}
__device__ __forceinline__ void tma_load4(uint32_t dst, const CUtensorMap* tm, int c0, int c1, int c2, int c3, uint32_t mbar) {
  asm volatile("cp.async.bulk.tensor.4d.shared::cluster.global.mbarrier::complete_tx::bytes [%0], [%1, {%3, %4, %5, %6}], [%2];"
               :: "r"(dst), "l"(tm), "r"(mbar), "r"(c0), "r"(c1), "r"(c2), "r"(c3) : "memory");
}
__device__ __forceinline__ void tma_load3(uint32_t dst, const CUtensorMap* tm, int c0, int c1, int c2, uint32_t mbar) {
  asm volatile("cp.async.bulk.tensor.3d.shared::cluster.global.mbarrier::complete_tx::bytes [%0], [%1, {%3, %4, %5}], [%2];"
               :: "r"(dst), "l"(tm), "r"(mbar), "r"(c0), "r"(c1), "r"(c2) : "memory");
}
__device__ __forceinline__ void tma_store3(const CUtensorMap* tm, int c0, int c1, int c2, uint32_t src) {
  asm volatile("cp.async.bulk.tensor.3d.global.shared::cta.bulk_group [%0, {%2, %3, %4}], [%1];"
               :: "l"(tm), "r"(src), "r"(c0), "r"(c1), "r"(c2) : "memory");
}
__device__ __forceinline__ void mma1688(float (&c)[4], uint32_t a0, uint32_t a1, uint32_t b) {
  asm volatile("mma.sync.aligned.m16n8k8.row.col.f32.bf16.bf16.f32 {%0,%1,%2,%3}, {%4,%5}, {%6}, {%0,%1,%2,%3};"
               : "+f"(c[0]), "+f"(c[1]), "+f"(c[2]), "+f"(c[3]) : "r"(a0), "r"(a1), "r"(b));
}
__device__ __forceinline__ void wg_fence() { asm volatile("wgmma.fence.sync.aligned;" ::: "memory"); }
__device__ __forceinline__ void wg_commit() { asm volatile("wgmma.commit_group.sync.aligned;" ::: "memory"); }
template <int N> __device__ __forceinline__ void wg_wait() { asm volatile("wgmma.wait_group.sync.aligned %0;" :: "n"(N) : "memory"); }
template <int N> __device__ __forceinline__ void tie_all(uint32_t (&x)[N]) {
#pragma unroll
  for (int i = 0; i < N; i++) asm volatile("" : "+r"(x[i]) :: "memory");
}
template <int N> __device__ __forceinline__ void tie_all(float (&x)[N]) {
#pragma unroll
  for (int i = 0; i < N; i++) asm volatile("" : "+f"(x[i]) :: "memory");
}
#define R16(C, d) C(d[0]), C(d[1]), C(d[2]), C(d[3]), C(d[4]), C(d[5]), C(d[6]), C(d[7]), C(d[8]), C(d[9]), C(d[10]), C(d[11]), C(d[12]), C(d[13]), C(d[14]), C(d[15])
#define R32(C, d) R16(C, d), R16(C, (d + 16))
#define P16 "{%0,%1,%2,%3,%4,%5,%6,%7,%8,%9,%10,%11,%12,%13,%14,%15}"
#define P32 "{%0,%1,%2,%3,%4,%5,%6,%7,%8,%9,%10,%11,%12,%13,%14,%15,%16,%17,%18,%19,%20,%21,%22,%23,%24,%25,%26,%27,%28,%29,%30,%31}"
template <int SD, int OFF> __device__ __forceinline__ void rs64(float* d, const uint32_t* a, uint64_t db) {
  if (SD) asm volatile("{.reg .b64 db; add.s64 db, %36, %37; wgmma.mma_async.sync.aligned.m64n64k16.f32.bf16.bf16 " P32 ", {%32,%33,%34,%35}, db, 1, 1, 1, 1;}"
                       : R32("+f", d) : "r"(a[0]), "r"(a[1]), "r"(a[2]), "r"(a[3]), "l"(db), "n"(OFF));
  else asm volatile("{.reg .b64 db; add.s64 db, %36, %37; wgmma.mma_async.sync.aligned.m64n64k16.f32.bf16.bf16 " P32 ", {%32,%33,%34,%35}, db, 0, 1, 1, 1;}"
                    : R32("=f", d) : "r"(a[0]), "r"(a[1]), "r"(a[2]), "r"(a[3]), "l"(db), "n"(OFF));
}
template <int SD, int TB, int OFF> __device__ __forceinline__ void rs64h(uint32_t* d, const uint32_t* a, uint64_t db) {
  if (SD) asm volatile("{.reg .b64 db; add.s64 db, %20, %21; wgmma.mma_async.sync.aligned.m64n64k16.f16.f16.f16 " P16 ", {%16,%17,%18,%19}, db, 1, 1, 1, %22;}"
                       : R16("+r", d) : "r"(a[0]), "r"(a[1]), "r"(a[2]), "r"(a[3]), "l"(db), "n"(OFF), "n"(TB));
  else asm volatile("{.reg .b64 db; add.s64 db, %20, %21; wgmma.mma_async.sync.aligned.m64n64k16.f16.f16.f16 " P16 ", {%16,%17,%18,%19}, db, 0, 1, 1, %22;}"
                    : R16("=r", d) : "r"(a[0]), "r"(a[1]), "r"(a[2]), "r"(a[3]), "l"(db), "n"(OFF), "n"(TB));
}
template <int SD, int OFFA, int OFFB> __device__ __forceinline__ void ss32(float* d, uint64_t da, uint64_t db) {
  if (SD) asm volatile("{.reg .b64 da, db; add.s64 da, %16, %18; add.s64 db, %17, %19; wgmma.mma_async.sync.aligned.m64n32k16.f32.f16.f16 " P16 ", da, db, 1, 1, 1, 1, 1;}"
                       : R16("+f", d) : "l"(da), "l"(db), "n"(OFFA), "n"(OFFB));
  else asm volatile("{.reg .b64 da, db; add.s64 da, %16, %18; add.s64 db, %17, %19; wgmma.mma_async.sync.aligned.m64n32k16.f32.f16.f16 " P16 ", da, db, 0, 1, 1, 1, 1;}"
                    : R16("=f", d) : "l"(da), "l"(db), "n"(OFFA), "n"(OFFB));
}
#define KGEN_ASM(SD) "{.reg .b64 da, db; add.s64 da, %32, %33; add.s64 db, %32, %34;\n" \
  "wgmma.mma_async.sync.aligned.m64n64k16.f32.bf16.bf16 " P32 ", da, db, " SD ", 1, 1, 1, 1;}"
template <int KS> __device__ __forceinline__ void kgen_mma(float (&c)[32], uint64_t da) {
  if (KS) asm volatile(KGEN_ASM("1") : R32("+f", c) : "l"(da), "n"(8 * KS), "n"(8 * KS + 512));
  else asm volatile(KGEN_ASM("0") : R32("=f", c) : "l"(da), "n"(8 * KS), "n"(8 * KS + 512));
  if constexpr (KS < 7) kgen_mma<KS + 1>(c, da);
}
template <int OFF> __device__ __forceinline__ void stage1(float (&D)[32], const uint32_t (&A1)[8], uint64_t d) {
  rs64<0, OFF>(D, A1, d); rs64<1, OFF + 64>(D, A1 + 4, d);
}
template <int INV> __device__ __forceinline__ void stage2(uint32_t (&X)[16], const uint32_t (&F)[16], uint64_t dc) {
  constexpr int KS = INV ? 16 : 128, TB = INV ? 0 : 1;
  rs64h<0, TB, 0>(X, F, dc); rs64h<1, TB, KS>(X, F + 4, dc); rs64h<1, TB, 2 * KS>(X, F + 8, dc); rs64h<1, TB, 3 * KS>(X, F + 12, dc);
}
__device__ __forceinline__ void fwd_mid(uint32_t (&F)[16], const float (&D)[32], const uint32_t (&tc)[4], const uint32_t (&ts)[4]) {
#pragma unroll
  for (int j = 0; j < 4; j++)
#pragma unroll
    for (int b = 0; b < 2; b++) {
      const int i = 4 * j + 16 * b;
      const uint32_t ar = packh(D[i], D[i + 1]), ai = packh(D[i + 2], D[i + 3]);
      F[2 * j + b] = ffma(ar, tc[j], fmul(ai, ts[j]));
      F[8 + 2 * j + b] = ffma(ai, tc[j], fneg(fmul(ar, ts[j])));
    }
}
__device__ __forceinline__ void put_exp(uint32_t a, uint32_t m, int lane) {
  m = __reduce_max_sync(0xffffffffu, max(m & 0x7f80u, (m >> 16) & 0x7f80u));
  if (lane == 0) sts32(a, m);
}
__device__ __forceinline__ uint32_t seq_mag(uint32_t a) {
  const uint4 x = lds128(a), y = lds128(a + 2048);
  return amax2(amax2(amax2(x.x, x.y), amax2(x.z, x.w)), amax2(amax2(y.x, y.y), amax2(y.z, y.w)));
}
__device__ __forceinline__ uint32_t get_exp(uint32_t a) { const uint4 v = lds128(a); return max(max(v.x, v.y), max(v.z, v.w)) >> 7; }
__device__ __forceinline__ void scale_a1(uint32_t (&As)[8], const uint32_t (&A1)[8], uint32_t field) {
#pragma unroll
  for (int i = 0; i < 8; i++) As[i] = hmul2(A1[i], field * 0x00800080u);
}

struct cf { float x, y; };
__device__ __forceinline__ cf cmul(cf a, cf b) { cf r; r.x = fmaf(a.x, b.x, -a.y * b.y); r.y = fmaf(a.x, b.y, a.y * b.x); return r; }
__device__ __forceinline__ cf cexp_p(float lr2, float lt, float p) {
  float m;
  asm("ex2.approx.ftz.f32 %0, %1;" : "=f"(m) : "f"(lr2 * p));
  float t = lt * p;
  t = (t - rintf(t)) * 6.283185307179586f;
  cf r; r.x = m * __cosf(t); r.y = m * __sinf(t); return r;
}
__device__ __forceinline__ void store8(uint32_t a, uint32_t b, const cf (&v)[8]) {
  sts128(a, pack(v[0].x, v[1].x), pack(v[2].x, v[3].x), pack(v[4].x, v[5].x), pack(v[6].x, v[7].x));
  sts128(b, pack(v[0].y, v[1].y), pack(v[2].y, v[3].y), pack(v[4].y, v[5].y), pack(v[6].y, v[7].y));
}
__device__ __forceinline__ void mbar_arrive(uint32_t m) { asm volatile("mbarrier.arrive.shared::cta.b64 _, [%0];" :: "r"(m) : "memory"); }
__device__ __forceinline__ float sigmoidf_(float s) { return __fdividef(1.f, 1.f + __expf(fminf(-s, 80.f))); }

__global__ void __cluster_dims__(CS, 1, 1) __launch_bounds__(NTHREADS, 1) fused_kernel(const __grid_constant__ Params p) {
  extern __shared__ __align__(1024) uint8_t smem[];
  TL_INIT();
  TL(31);
  const int wid = __shfl_sync(0xffffffffu, threadIdx.x >> 5, 0);
  const uint32_t sb = (uint32_t)__cvta_generic_to_shared(smem);
  const uint32_t mb = sb + OFF_MB;
  const int u = wid >> 2, w = wid & 3;
  const int tid = threadIdx.x & 127, lane = tid & 31, g = lane >> 2, t = lane & 3;
  const int cl = blockIdx.x >> 3, rank = blockIdx.x & 7;
  const int ch0 = cl * CPC;
  const int nu = min(5, (DCH - ch0) >> 3);
  const bool act = u < nu;

  uint32_t pla, pai, pcr, pci, pdt, tag = 0;
  auto load_params = [&]() {
    const int ch = act ? ch0 + 8 * u + rank : 0, o = ch * NMODE + tid;
    pla = ldraw(p.logA + o); pdt = ldraw(p.logdt + ch); pai = ldraw(p.Aim + o); pcr = ldraw(p.Cre + o); pci = ldraw(p.Cim + o);
  };
  if (u == 4) {
    const bool e = elect();
    if (e) {
#pragma unroll
      for (int i = 0; i < 5; i++) mbar_init(mb + 40 * w + 8 * i, 1);
      if (w == 3) { mbar_init(mb + 8 * MB_XQ, 1); mbar_init(mb + 8 * MB_KV, 1); }
      if (w == 2) mbar_init(mb + 8 * MB_G, 8);
      fence_mbinit();
      if ((sb & 0xffffffu) != SB0) __trap();
    }
    __syncwarp();
    load_params();
    if (w == 0 && lane < 2) asm volatile("atom.relaxed.gpu.global.add.u32 %0, [%1], %2;" : "=r"(tag) : "l"(&p.cnt[rank * 32 + lane]), "r"(cl == 0 ? 16 - (NCL - 1) : 1) : "memory");
    if (e) {
      if (w == 3) {
        mbar_expect(mb + 8 * MB_XQ, 20480 + 20480 + 112 * nu);
        bulk_load(sb + OFF_SP, p.gate_w + ch0, 16 * nu, mb + 8 * MB_XQ);
        bulk_load(sb + OFF_SP + 80, p.Dskip + ch0, 16 * nu, mb + 8 * MB_XQ);
        bulk_load(sb + OFF_SP + 160, p.ssm_D + ch0, 16 * nu, mb + 8 * MB_XQ);
        bulk_load(sb + OFF_SP + 240, p.shift_k + 4 * ch0, 64 * nu, mb + 8 * MB_XQ);
        tma_load3(sb + OFF_TQ, &p.tq, ch0, 8 * rank, 0, mb + 8 * MB_XQ);
        bulk_load(sb + OFF_CF, p.tab, 20480, mb + 8 * MB_XQ);
        TL(20);
        mbar_expect(mb + 8 * MB_KV, 2 * 20480 + 320);
        tma_load3(sb + OFF_TK, &p.tk, ch0, 8 * rank, 0, mb + 8 * MB_KV);
        tma_load3(sb + OFF_HALO, &p.tkh, ch0, 8 * rank - 1, 28, mb + 8 * MB_KV);
      }
#pragma unroll
      for (int i = 0; i < 5; i++) mbar_expect(mb + 40 * w + 8 * i, w == 3 ? 4096 : w == 2 ? 7168 : 3584);
    }
    __syncwarp();
  } else {
    load_params();
  }
  cluster_arrive();
  TL(0);

  const uint32_t tab = sb + OFF_T + u * KTAB;
  const uint32_t toff = (64 * w + lane) * 80 + 16 * u;
  auto put = [&](uint32_t dst, const uint32_t (&a)[4], const uint32_t (&b)[4]) {
    const uint32_t s0 = (g & 1) ? 0x7632 : 0x5410, s1 = s0 ^ 0x2222;
    const uint32_t o = dst + 128 * t + 64 * (g & 1) + 16 * (w ^ t);
    sts128(o, prmt(a[0], a[1], s0), prmt(a[2], a[3], s0), prmt(b[0], b[1], s0), prmt(b[2], b[3], s0));
    sts128(o ^ 64, prmt(a[0], a[1], s1), prmt(a[2], a[3], s1), prmt(b[0], b[1], s1), prmt(b[2], b[3], s1));
  };
  const int d0 = rank ^ (2 * w), d1 = d0 ^ 1;
  const uint32_t rb0 = mapa(sb, d0), rb1 = mapa(sb, d1);
  auto send = [&](int stage, int dst, int mbar) {
    if (elect()) {
      if (w) bulk_dsmem(rb0 + dst, sb + stage + d0 * 512, rb0 + mbar);
      bulk_dsmem(rb1 + dst, sb + stage + d1 * 512, rb1 + mbar);
    }
    __syncwarp();
  };

  uint32_t A1[8], tc[4], ts[4];
  {
    const float dt = bf16r(expf(blo(pdt)));
    const float lr2 = (-bf16r(expf(blo(pla))) * dt) * 1.4426950408889634f;
    const float lt = (blo(pai) * dt) * 0.15915494309189535f;
    const uint32_t tim = sb + (u ? OFF_IM + (u - 1) * KTAB : OFF_UX);
    const uint32_t row = tab + tid * 16, rim = tim + tid * 16;
    const cf w1 = cexp_p(lr2, lt, 8.f);
    cf z1 = cexp_p(lr2, lt, 1.f), Z = cexp_p(lr2, lt, 256.f);
    if (lr2 != 123.f) TL(16);
    TL(12);
    {
      cf v[8];
      v[0].x = 1.f; v[0].y = 0.f; v[1] = w1; v[2] = cmul(w1, w1); v[3] = cmul(v[2], w1);
      const cf w4 = cmul(v[2], v[2]);
      v[4] = w4; v[5] = cmul(v[1], w4); v[6] = cmul(v[2], w4); v[7] = cmul(v[3], w4);
      const cf w8 = cmul(w4, w4);
      store8(row, rim, v);
#pragma unroll
      for (int k = 1; k < 4; k++) {
#pragma unroll
        for (int i = 0; i < 8; i++) v[i] = (k == 1 && i == 0) ? w8 : cmul(v[i], w8);
        store8(row + 2048 * k, rim + 2048 * k, v);
      }
    }
    if (PREFETCH && wid == 8 && elect()) {
      const uint32_t o = blockIdx.x * 9856u, n = min(9856u, SEQ * DCH - o) * 2;
      asm volatile("cp.async.bulk.prefetch.L2.global [%0], %1;" :: "l"(p.v + o), "r"(n) : "memory");
      asm volatile("cp.async.bulk.prefetch.L2.global [%0], %1;" :: "l"(p.ssm_k + o), "r"(n) : "memory");
    }
    __syncwarp();
    if (u == 1) {
      float z0_ = 0.f, z1_ = 0.f, z2_ = 0.f, z3_ = 0.f;
      asm volatile("mma.sync.aligned.m16n8k8.row.col.f32.bf16.bf16.f32 {%0,%1,%2,%3}, {%4,%4}, {%4}, {%0,%1,%2,%3};"
                   : "+f"(z0_), "+f"(z1_), "+f"(z2_), "+f"(z3_) : "r"(pla >> 16));
      pcr += __float_as_uint(z0_);
      TL(8);
    }
    {
      z1.y = -z1.y; Z.y = -Z.y;
      const cf z2 = cmul(z1, z1);
      cf h[8], v[8];
      h[0].x = 2.f * blo(pcr) * dt; h[0].y = -2.f * blo(pci) * dt;
      h[1] = cmul(h[0], z1);
#pragma unroll
      for (int i = 2; i < 8; i++) h[i] = cmul(h[i - 2], z2);
      store8(row + 4 * 2048, rim + 4 * 2048, h);
      const cf h8 = cmul(h[6], z2);
      v[0] = cmul(h[0], Z); v[2] = cmul(h[2], Z); v[3] = cmul(h[4], Z); v[6] = cmul(h[6], Z); v[7] = cmul(h8, Z);
      v[1] = v[0]; v[4] = v[5] = v[3];
      store8(row + 5 * 2048, rim + 5 * 2048, v);
      h[0] = cmul(v[0], Z); h[1] = cmul(v[3], Z); h[3] = cmul(v[7], Z); h[4] = cmul(h[0], Z); h[5] = cmul(h[1], Z); h[7] = cmul(h[3], Z);
      h[2] = h[1]; h[6] = h[5];
      store8(row + 6 * 2048, rim + 6 * 2048, h);
      const cf Z2 = cmul(Z, Z);
      v[0] = cmul(h[0], Z2); v[1] = cmul(h[3], Z2); v[2] = cmul(h[4], Z2); v[3] = cmul(h[7], Z2);
#pragma unroll
      for (int i = 4; i < 8; i++) v[i] = cmul(v[i - 4], Z2);
      store8(row + 7 * 2048, rim + 7 * 2048, v);
    }
    TL(17);
    if (wid == 16 && lane == 0) sts32(mb + 8 * MB_TAG, tag);
    cluster_wait();
    if (u >= 2) cluster_arrive();
    fence_async();
    if (u) bar_sync(NB_ORD + u - 1, 256); else bar_sync(NB_WG0, 128);
    TL(13);
    float c[32];
    wg_fence();
    kgen_mma<0>(c, p.dk[u]);
    wg_commit();
    if (u < 4) bar_arrive(NB_ORD + u, 256);
    TL(14);
    mbar_wait(mb + 8 * MB_XQ);
    TL(18);
    uint32_t x0[4], x1[4];
    ldsm4t(x0, sb + OFF_TQ + toff);
    ldsm4t(x1, sb + OFF_TQ + toff + 2560);
    {
      const uint4 x = lds128(sb + OFF_TH + 16 * tid), y = lds128(sb + OFF_TH + 2048 + 16 * tid), a = lds128(sb + OFF_TH + 4096 + 16 * tid), b = lds128(sb + OFF_TH + 6144 + 16 * tid);
      A1[0] = x.x; A1[1] = x.y; A1[2] = x.z; A1[3] = x.w; A1[4] = y.x; A1[5] = y.y; A1[6] = y.z; A1[7] = y.w;
      tc[0] = a.x; tc[1] = a.y; tc[2] = a.z; tc[3] = a.w; ts[0] = b.x; ts[1] = b.y; ts[2] = b.z; ts[3] = b.w;
    }
    wg_wait<0>(); tie_all(c);
    TL(26);
    if (u < 2) cluster_arrive();
    else if (u < 4) bar_arrive(NB_V, 384);
    bar_sync(u == 4 ? NB_V : NB_WG0 + u, u == 4 ? 384 : 128);
    const uint32_t k0 = pack(c[0] + c[6], c[1] + c[7]), k1 = pack(c[8] + c[14], c[9] + c[15]);
    const uint32_t k2 = pack(c[16] + c[22], c[17] + c[23]), k3 = pack(c[24] + c[30], c[25] + c[31]);
    const uint32_t ka = tab + 16 * (8 * w + (g ^ w));
    sts32(ka + 4 * t, k0);
    sts32(ka + 512 + 4 * t, k1);
    sts64(ka + 1024 + 512 * (t >> 1) + 8 * (t & 1), prmt(k2, 0, 0x1010), (t & 1) ? prmt(k2, 0, 0x3232) : k2);
    const uint32_t lo = prmt(k3, 0, 0x1010), hi = prmt(k3, 0, 0x3232);
    sts128(ka + 2048 + 512 * t, lo, lo, (g & 1) ? hi : k3, hi);
    put_exp(sb + OFF_MX + u * 64 + 4 * w, amax2(amax2(k0, k1), amax2(k2, k3)), lane);
    cluster_wait();
    cluster_arrive();
    put(sb + u * 4096 + g * 512 + (g == rank ? OFF_UX : OFF_YB), x0, x1);
    TL(15);
    fence_async();
    bar_sync(NB_WG0 + u, 128);
    send(OFF_YB + u * 4096, OFF_UX + u * 4096 + 512 * rank, OFF_MB + 8 * (MB_UX + u));
    if (wid == 16 && elect()) tma_load3(sb + OFF_TV, &p.tv, ch0, 8 * rank, 0, mb + 8 * MB_KV);
    __syncwarp();
  }
  if (u == 0) {
    float ga[4][4];
#pragma unroll
    for (int i = 0; i < 4; i++) ga[i][0] = ga[i][1] = ga[i][2] = ga[i][3] = 0.f;
#pragma unroll
    for (int j = 0; j < 5; j++) {
      uint32_t a0[4], a1[4], b;
      ldsm4(a0, sb + OFF_TQ + toff + 16 * j);
      ldsm4(a1, sb + OFF_TQ + toff + 2560 + 16 * j);
      asm volatile("ld.shared.u32 %0, [%1];" : "=r"(b) : "r"(sb + OFF_SP + 16 * j + 4 * t) : "memory");
      if (j >= 2 && j >= nu) b = 0;
      mma1688(ga[0], a0[0], a0[1], b); mma1688(ga[1], a0[2], a0[3], b); mma1688(ga[2], a1[0], a1[1], b); mma1688(ga[3], a1[2], a1[3], b);
    }
    const float s0 = t == 0 ? ga[0][0] : t == 1 ? ga[1][0] : t == 2 ? ga[2][0] : ga[3][0];
    const float s1 = t == 0 ? ga[0][2] : t == 1 ? ga[1][2] : t == 2 ? ga[2][2] : ga[3][2];
    tag = (lds64(mb + 8 * MB_TAG).x >> 4) + 1;
    uint2* gp = p.part + cl * SEQ + rank * 256 + 64 * w + 16 * t + g;
    asm volatile("st.relaxed.gpu.global.u64 [%0], %1;" :: "l"(gp), "l"(((uint64_t)tag << 32) | __float_as_uint(s0)) : "memory");
    asm volatile("st.relaxed.gpu.global.u64 [%0], %1;" :: "l"(gp + 8), "l"(((uint64_t)tag << 32) | __float_as_uint(s1)) : "memory");
  }

#pragma unroll
  for (int isA = 0; isA < 2; isA++) {
    {
      TL(1 + isA);
      const uint32_t usrc = isA ? tab + T_UKV : sb + OFF_UX + u * 4096;
      const uint32_t mxa = sb + OFF_MX + u * 64 + 32 * isA;
      const uint32_t pd = lds16(sb + OFF_SP + 80 + 80 * isA + 16 * u + 2 * rank);
      float D[32];
      uint32_t As[8], F[16], H[16], X[16];
      const uint32_t eh = min(max((int)get_exp(mxa), (int)((pd >> 7) & 0xff) - 5), 240);
      scale_a1(As, A1, 248 - eh);
      wg_fence();
      if (isA) stage1<T_HA / 16>(D, As, p.dt[u]); else stage1<0>(D, As, p.dt[u]);
      wg_commit();
      wg_wait<0>(); tie_all(D);
      fwd_mid(F, D, tc, ts);
      wg_fence();
      stage2<0>(H, F, p.dfwd);
      wg_commit();
      if (!isA) {
        if (w == 2 && elect()) bulk_load(tab + T_HA, p.ssm_k + (size_t)(act ? ch0 + 8 * u + rank : 0) * SEQ, 4096, mb + 8 * (MB_HA + u));
        __syncwarp();
        TL(7);
      }
      if (isA) fence_async();
      mbar_wait(mb + 8 * ((isA ? MB_UKV : MB_UX) + u));
      TL(5 + isA);
      put_exp(mxa + 16 + 4 * w, seq_mag(usrc + 16 * tid), lane);
      bar_sync(NB_WG0 + u, 128);
      if (isA) {
        send(OFF_UX + u * 4096, OFF_YB + (8 * u + rank) * 512, OFF_MB + 8 * (MB_Y + u));
      }
      const uint32_t eu = min(get_exp(mxa + 16), 240u);
      scale_a1(As, A1, 250 - eu);
      wg_wait<0>(); tie_all(H);
      wg_fence();
      if (isA) stage1<T_UKV / 16>(D, As, p.dt[u]); else stage1<0>(D, As, p.dx[u]);
      wg_commit();
      wg_wait<0>(); tie_all(D);
      fwd_mid(F, D, tc, ts);
      wg_fence();
      stage2<0>(X, F, p.dfwd);
      wg_commit();
      {
        const float dsk = blo(pd) * __uint_as_float((248 - eh) << 23);
        const uint32_t d2 = packh(dsk, dsk);
#pragma unroll
        for (int j = 0; j < 4; j++) H[2 * j] = U2(__hadd2(H2(H[2 * j]), H2(d2)));
      }
      wg_wait<0>(); tie_all(X);
#pragma unroll
      for (int j = 0; j < 4; j++) {
        const uint32_t h0r = H[2 * j], h1r = H[2 * j + 1], h0i = H[8 + 2 * j], h1i = H[9 + 2 * j];
        const uint32_t x0r = X[2 * j], x1r = X[2 * j + 1], x0i = X[8 + 2 * j], x1i = X[9 + 2 * j];
        F[2 * j] = ffma(x0r, h0r, fneg(fmul(x0i, h0i)));
        F[8 + 2 * j] = ffma(x0r, h0i, fmul(x0i, h0r));
        F[2 * j + 1] = ffma(x1r, h0r, ffma(fneg(x1i), h0i, ffma(x0r, h1r, fneg(ffma(x0i, h1i, F[8 + 2 * j])))));
        F[9 + 2 * j] = ffma(x1r, h0i, ffma(x1i, h0r, ffma(x0r, h1i, ffma(x0i, h1r, F[2 * j]))));
      }
      wg_fence();
      stage2<1>(H, F, p.dinv);
      wg_commit();
      uint64_t ga[4];
      const int sl2 = min(18 * cl + min(8 * w + g, 17), 255), sl3 = tid + 128 * (u & 1);
      auto gload = [&]() {
        if (isA) {
          asm volatile("ld.relaxed.gpu.global.u64 %0, [%1];" : "=l"(ga[0]) : "l"(p.part + NCL * SEQ + rank * 256 + sl3) : "memory");
        } else {
#pragma unroll
          for (int k = 0; k < 4; k++)
            asm volatile("ld.relaxed.gpu.global.u64 %0, [%1];" : "=l"(ga[k]) : "l"(p.part + (t + (k == 3 && t == 3 ? 8 : 4 * k)) * SEQ + rank * 256 + sl2) : "memory");
        }
      };
      if (isA ? (u & 6) == 2 : u == 1) gload();
      if (isA) TL(23);
      wg_wait<0>(); tie_all(H);
      {
        const uint32_t va = tab + (16 * w + (lane & 15)) * 128;
        const int vx = (lane >> 4) ^ (lane & 7);
#pragma unroll
        for (int j = 0; j < 4; j++) {
          uint32_t V[4];
#pragma unroll
          for (int b = 0; b < 2; b++) {
            const uint32_t er = H[2 * j + b], ei = H[8 + 2 * j + b];
            V[2 * b] = ffma(er, tc[j], fneg(fmul(ei, ts[j])));
            V[2 * b + 1] = ffma(ei, tc[j], fmul(er, ts[j]));
          }
          stsm4(va + ((vx ^ (2 * j)) << 4), V);
        }
      }
      if (!isA) {
        cluster_wait();
        mbar_wait(mb + 8 * MB_KV);
        TL(21);
        uint32_t K[3][4], V[2][4];
        const uint2 psw = lds64(sb + OFF_SP + 240 + 64 * u + 8 * g);
        ldsm4t(K[0], w ? sb + OFF_TK + toff - 2560 : (lane & 7) ? sb + OFF_TK + toff + 223 * 80 : sb + OFF_HALO + 10 * lane + 16 * u);
        ldsm4t(K[1], sb + OFF_TK + toff);
        ldsm4t(K[2], sb + OFF_TK + toff + 2560);
        ldsm4t(V[0], sb + OFF_TV + toff);
        ldsm4t(V[1], sb + OFF_TV + toff + 2560);
        mbar_wait(mb + 8 * (MB_HA + u));
        const uint4 hx = lds128(tab + T_HA + 16 * tid), hy = lds128(tab + T_HA + 2048 + 16 * tid);
        const uint32_t w0 = prmt(psw.x, 0, 0x1010), w1 = prmt(psw.x, 0, 0x3232), w2 = prmt(psw.y, 0, 0x1010), w3 = prmt(psw.y, 0, 0x3232);
#pragma unroll
        for (int m = 4; m < 12; m++)
          V[(m >> 2) - 1][m & 3] = hmul2(hfma2(K[m >> 2][m & 3], w0, hfma2(K[(m - 1) >> 2][(m - 1) & 3], w1,
                                         hfma2(K[(m - 2) >> 2][(m - 2) & 3], w2, hmul2(K[(m - 3) >> 2][(m - 3) & 3], w3)))), V[(m >> 2) - 1][m & 3]);
        put(g == rank ? tab + T_UKV + 512 * rank : sb + OFF_YA + u * 4096 + g * 512, V[0], V[1]);
        put_exp(mxa + 32 + 4 * w, amax2(amax2(amax2(hx.x, hx.y), amax2(hx.z, hx.w)), amax2(amax2(hy.x, hy.y), amax2(hy.z, hy.w))), lane);
        sts128(tab + T_HA + 16 * (tid ^ (lane >> 3)), hx.x, hx.y, hx.z, hx.w);
        sts128(tab + T_HA + 2048 + 16 * (tid ^ (lane >> 3)), hy.x, hy.y, hy.z, hy.w);
        TL(22);
      }
      fence_async();
      bar_sync(NB_WG0 + u, 128);
      float O[16];
      {
        const uint64_t dv = p.dv[u], dl = p.dlast;
        wg_fence();
        ss32<0, 0, 0>(O, dv, dl); ss32<1, 128, 64>(O, dv, dl); ss32<1, 256, 128>(O, dv, dl); ss32<1, 384, 192>(O, dv, dl);
        wg_commit();
      }
      if (!isA) send(OFF_YA + u * 4096, OFF_T + u * KTAB + T_UKV + 512 * rank, OFF_MB + 8 * (MB_UKV + u));
      if (isA ? (u & 6) == 2 : u == 1) {
        tag = (lds64(mb + 8 * MB_TAG).x >> 4) + 1;
        bool ok;
#pragma unroll 1
        for (int it = 0;; it++) {
          ok = (uint32_t)(ga[0] >> 32) == tag;
          if (!isA) ok = ok && (uint32_t)(ga[1] >> 32) == tag && (uint32_t)(ga[2] >> 32) == tag && (uint32_t)(ga[3] >> 32) == tag;
          ok = __all_sync(0xffffffffu, ok);
          if (ok || it == (isA ? 8000 : 2000)) break;
          gload();
        }
        if (!isA) {
          float s = __uint_as_float((uint32_t)ga[0]) + __uint_as_float((uint32_t)ga[1]) + __uint_as_float((uint32_t)ga[2]);
          if (t < 3) s += __uint_as_float((uint32_t)ga[3]);
          s += __shfl_xor_sync(0xffffffffu, s, 1);
          s += __shfl_xor_sync(0xffffffffu, s, 2);
          const float g0 = bf16r(sigmoidf_(bf16r(s)));
          if (ok && t == 0)
            asm volatile("st.relaxed.gpu.global.u64 [%0], %1;" :: "l"(p.part + NCL * SEQ + rank * 256 + sl2), "l"(((uint64_t)tag << 32) | pack(g0, 1.f - g0)) : "memory");
        } else {
          uint32_t gv = (uint32_t)ga[0];
          if (!ok) {
            const uint32_t* xr = (const uint32_t*)(p.q + (size_t)(rank * 256 + 32 * (sl3 & 7) + (sl3 >> 3)) * DCH);
            const uint32_t* gr = (const uint32_t*)p.gate_w;
            float s = 0.f;
#pragma unroll 1
            for (int k = 0; k < DCH / 2; k++) { const uint32_t x = __ldg(xr + k), y = __ldg(gr + k); s = fmaf(blo(x), blo(y), fmaf(bhi(x), bhi(y), s)); }
            const float g0 = bf16r(sigmoidf_(bf16r(s)));
            gv = pack(g0, 1.f - g0);
          }
          sts64(sb + OFF_GB + 8 * sl3, prmt(gv, 0, 0x1010), prmt(gv, 0, 0x3232));
          __syncwarp();
          if (lane == 0) mbar_arrive(mb + 8 * MB_G);
        }
      }
      if (isA) TL(28);
      wg_wait<0>(); tie_all(O);
      {
        const uint32_t co = ((8 * w + g) ^ (2 * t) ^ rank) * 16;
        const int yo = (isA ? OFF_YA : OFF_YB) + (8 * u + rank) * 512, ym = OFF_MB + 8 * (MB_Y + u);
        const uint32_t us = min(max((int)(eu + eh) - 127, 0), 254) * 0x00800080u;
        const uint32_t a0 = hmul2(pack(O[0], O[1]), us), a1 = hmul2(pack(O[4], O[5]), us), a2 = hmul2(pack(O[8], O[9]), us), a3 = hmul2(pack(O[12], O[13]), us);
        const uint32_t b0 = hmul2(pack(O[2], O[3]), us), b1 = hmul2(pack(O[6], O[7]), us), b2 = hmul2(pack(O[10], O[11]), us), b3 = hmul2(pack(O[14], O[15]), us);
        sts128((t == rank ? sb + yo : usrc + t * 512) + co, a0, a1, a2, a3);
        sts128((t + 4 == rank ? sb + yo : usrc + t * 512 + 2048) + co, b0, b1, b2, b3);
        if (isA) {
          fence_async();
          bar_sync(NB_WG0 + u, 128);
          send(usrc - sb, yo, ym);
        }
      }
      TL(9 + isA);
    }
  }

  {
    mbar_wait(mb + 8 * MB_G);
    uint2 gg[2][4];
    uint32_t qv[2][4];
#pragma unroll
    for (int hh = 0; hh < 2; hh++)
#pragma unroll
      for (int i = 0; i < 4; i++) gg[hh][i] = lds64(sb + OFF_GB + 8 * (64 * w + 32 * hh + 8 * i + g));
    const uint32_t qa = sb + OFF_TQ + toff;
    ldsm4(qv[0], qa);
    ldsm4(qv[1], qa + 2560);
    TL(24);
    mbar_wait(mb + 8 * (MB_Y + u));
    uint32_t ya[2][4], yb[2][4];
#pragma unroll
    for (int hh = 0; hh < 2; hh++) {
      const uint32_t yo = (8 * u + (lane & 7)) * 512 + ((8 * w + 4 * hh + (lane >> 3)) ^ (2 * (rank & 3)) ^ (lane & 7)) * 16;
      ldsm4t(ya[hh], sb + OFF_YA + yo); ldsm4t(yb[hh], sb + OFF_YB + yo);
    }
#pragma unroll
    for (int hh = 0; hh < 2; hh++) {
      uint32_t o[4];
#pragma unroll
      for (int i = 0; i < 4; i++) o[i] = hadd2(hmul2(gg[hh][i].x, hmul2(qv[hh][i], ya[hh][i])), hmul2(gg[hh][i].y, yb[hh][i]));
      stsm4(qa + 2560 * hh, o);
    }
    TL(25);
  }
  cluster_arrive();
  bar_sync(NB_ROW0 + w, 160);
  {
    uint4 v[2];
#pragma unroll
    for (int k = 0; k < 2; k++) {
      const int i = 64 * u + 32 * k + lane, sl = (i * 205) >> 10, cc = i - 5 * sl;
      v[k] = lds128(sb + OFF_TQ + (64 * w + 8 * (sl & 7) + (sl >> 3)) * 80 + cc * 16);
    }
#pragma unroll
    for (int k = 0; k < 2; k++) {
      const int i = 64 * u + 32 * k + lane, sl = (i * 205) >> 10, cc = i - 5 * sl;
      if (cc < nu)
        asm volatile("st.global.v4.u32 [%0], {%1,%2,%3,%4};" :: "l"(p.out + (size_t)(256 * rank + 32 * (sl >> 3) + 8 * w + (sl & 7)) * DCH + ch0 + 8 * cc),
                     "r"(v[k].x), "r"(v[k].y), "r"(v[k].z), "r"(v[k].w) : "memory");
    }
  }
  cluster_wait();
  TL(27);
  TL_DUMP();
}

typedef CUresult (*EncodeFn)(CUtensorMap*, CUtensorMapDataType, cuuint32_t, void*, const cuuint64_t*, const cuuint64_t*,
                             const cuuint32_t*, const cuuint32_t*, CUtensorMapInterleave, CUtensorMapSwizzle,
                             CUtensorMapL2promotion, CUtensorMapFloatOOBfill);

void encode(EncodeFn fn, CUtensorMap* tm, const void* ptr, int nd, const cuuint64_t* dims, const cuuint64_t* strides,
            const cuuint32_t* box, CUtensorMapSwizzle swz) {
  cuuint32_t es[4] = {1, 1, 1, 1};
  fn(tm, CU_TENSOR_MAP_DATA_TYPE_BFLOAT16, nd, const_cast<void*>(ptr), dims, strides, box, es, CU_TENSOR_MAP_INTERLEAVE_NONE,
     swz, CU_TENSOR_MAP_L2_PROMOTION_L2_128B, CU_TENSOR_MAP_FLOAT_OOB_FILL_NONE);
}
void make_map(EncodeFn fn, CUtensorMap* tm, const void* ptr, int ne, int nr) {
  const cuuint64_t dims[3] = {DCH, SEQ / 32, 32}, strides[2] = {32 * DCH * 2, DCH * 2};
  const cuuint32_t box[3] = {CPC, (cuuint32_t)ne, (cuuint32_t)nr};
  encode(fn, tm, ptr, 3, dims, strides, box, CU_TENSOR_MAP_SWIZZLE_NONE);
}

}

extern "C" void kernel_launch(void* const* d_in, const int* in_sizes, int n_in, void* d_out, int out_size) {
  (void)in_sizes; (void)n_in; (void)out_size;
  static EncodeFn fn = nullptr;
  static void *tab = nullptr, *cnt = nullptr, *part = nullptr;
  if (!fn) {
    cudaGetSymbolAddress(&tab, d_tab);
    cudaGetSymbolAddress(&cnt, g_cnt);
    cudaGetSymbolAddress(&part, g_part);
    cudaDriverEntryPointQueryResult qr;
    cudaGetDriverEntryPoint("cuTensorMapEncodeTiled", (void**)&fn, cudaEnableDefault, &qr);
    cudaFuncSetAttribute(fused_kernel, cudaFuncAttributeMaxDynamicSharedMemorySize, SMEM_BYTES);
  }
  Params p;
  make_map(fn, &p.tq, d_in[0], 8, 32);
  make_map(fn, &p.tk, d_in[1], 8, 32);
  make_map(fn, &p.tv, d_in[2], 8, 32);
  make_map(fn, &p.tkh, d_in[1], 1, 4);
  p.out = (__nv_bfloat16*)d_out;
  p.dfwd = mkdesc(OFF_CF, 1024, 128, 0);
  p.dinv = mkdesc(OFF_CF, 128, 1024, 0);
  p.dlast = mkdesc(OFF_CL, 512, 128, 0);
  for (int u = 0; u < 5; u++) {
    p.dk[u] = mkdesc(OFF_T + u * KTAB, u ? OFF_IM - KTAB - OFF_T : OFF_UX - OFF_T, 1024, 0);
    p.dt[u] = mkdesc(OFF_T + u * KTAB, 2048, 512, 2);
    p.dx[u] = mkdesc(OFF_UX + u * 4096, 2048, 512, 2);
    p.dv[u] = mkdesc(OFF_T + u * KTAB, 16, 1024, 1);
  }
  p.tab = (const Tables*)tab;
  p.cnt = (unsigned*)cnt;
  p.part = (uint2*)part;
  p.tl = nullptr;
  p.q = (const __nv_bfloat16*)d_in[0];
  p.v = (const __nv_bfloat16*)d_in[2];
  p.ssm_k = (const __nv_bfloat16*)d_in[4];
  p.shift_k = (const __nv_bfloat16*)d_in[3];
  p.ssm_D = (const __nv_bfloat16*)d_in[5];
  p.logA = (const __nv_bfloat16*)d_in[7];
  p.Aim = (const __nv_bfloat16*)d_in[8];
  p.Cre = (const __nv_bfloat16*)d_in[9];
  p.Cim = (const __nv_bfloat16*)d_in[10];
  p.logdt = (const __nv_bfloat16*)d_in[11];
  p.Dskip = (const __nv_bfloat16*)d_in[12];
  p.gate_w = (const __nv_bfloat16*)d_in[13];
  fused_kernel<<<NCL * CS, NTHREADS, SMEM_BYTES, cudaStreamPerThread>>>(p);
}
```

```cpp
#include <cuda_runtime.h>
#include <cuda_bf16.h>
#include <cuda_fp16.h>
#include <cuda.h>
#include <stdint.h>

#define TIMELINE 0
#define STAGGER 0
#define PREFETCH 1
#define STW 2
#define STMID 0
#define TLHI 0

namespace {

constexpr int SEQ = 2048, DCH = 576, NMODE = 128;
constexpr int CS = 8, CPC = 40, NCL = 15, NTHREADS = 640;

constexpr int KTAB = 16384;
constexpr int OFF_T = 0;
constexpr int T_YS = 8192, T_HA = 12288;
constexpr int UGRP = 1056, USZ = 4 * UGRP, YP = 528;
constexpr int OFF_IM = 5 * KTAB;
constexpr int OFF_YB = OFF_IM;
constexpr int OFF_TV = OFF_YB + 40 * YP;
constexpr int OFF_YA = OFF_TV + 20480;
constexpr int OFF_GB = OFF_YA + 40 * YP;
constexpr int OFF_U = OFF_IM + 4 * KTAB;
constexpr int OFF_CF = OFF_U + 5 * USZ;
constexpr int OFF_CL = OFF_CF + 8192;
constexpr int OFF_TH = OFF_CL + 4096;
constexpr int OFF_TQ = OFF_TH + 8192;
constexpr int OFF_TK = OFF_TQ + 20480;
constexpr int OFF_HALO = OFF_TK + 20480;
constexpr int OFF_MX = OFF_HALO + 320;
constexpr int OFF_SP = OFF_MX + 160;
constexpr int OFF_MB = OFF_SP + 560;
constexpr int OFF_TL = OFF_MB + 28 * 8;
constexpr int SMEM_BYTES = OFF_TL + (TIMELINE ? 640 : 0);
static_assert(SMEM_BYTES <= 232448 && OFF_GB + 2048 <= OFF_U && (OFF_TV & 127) == 0 && (OFF_TQ & 127) == 0, "smem");
static_assert((OFF_MB & 7) == 0 && (OFF_MX & 15) == 0 && (OFF_SP & 15) == 0, "align");

enum { MB_UX = 0, MB_UKV = 5, MB_Y = 10, MB_HA = 15, MB_XQ = 20, MB_KV = 21, MB_CF = 22, MB_G = 23, MB_TH = 24, MB_TAG = 25 };
enum { NB_WG0 = 1, NB_ROW0 = 6, NB_ORD = 6, NB_V = 10, NB_ST = 11 };

constexpr uint32_t SB0 = 1024;
constexpr uint64_t mkdesc(uint32_t off, uint32_t lbo, uint32_t sbo, uint32_t swz) {
  return (uint64_t)((SB0 + off) >> 4) | ((uint64_t)(lbo >> 4) << 16) | ((uint64_t)(sbo >> 4) << 32) | ((uint64_t)swz << 62);
}

constexpr double cos_turn(int m, int n) {
  m &= n - 1;
  if (m > n / 2) m = n - m;
  double sgn = 1.0;
  if (m > n / 4) { m = n / 2 - m; sgn = -1.0; }
  if (m == n / 4) return 0.0;
  const double x = 6.283185307179586476925 * m / n;
  double term = 1.0, sum = 1.0;
  for (int k = 1; k < 14; k++) { term *= -x * x / ((2 * k - 1) * (2 * k)); sum += term; }
  return sgn * sum;
}
constexpr uint32_t bf16_bits(double v) {
  if (v == 0.0) return 0;
  uint32_t sgn = 0;
  if (v < 0) { sgn = 0x8000; v = -v; }
  int e = 127;
  while (v < 1.0) { v *= 2.0; e--; }
  while (v >= 2.0) { v *= 0.5; e++; }
  const double f = v * 128.0;
  int m = (int)f;
  if (f - m > 0.5 || (f - m == 0.5 && (m & 1))) m++;
  return sgn | (uint32_t)((e << 7) + (m - 128));
}
constexpr uint32_t f16_bits(double v) {
  if (v == 0.0) return 0;
  uint32_t sgn = 0;
  if (v < 0) { sgn = 0x8000; v = -v; }
  int e = 15;
  while (v < 1.0) { v *= 2.0; e--; }
  const double f = v * 1024.0;
  int m = (int)f;
  if (f - m > 0.5 || (f - m == 0.5 && (m & 1))) m++;
  return sgn | (uint32_t)((e << 10) + (m - 1024));
}
constexpr uint32_t pair_bits(double lo, double hi) { return bf16_bits(lo) | (bf16_bits(hi) << 16); }
constexpr uint32_t pair_h(double lo, double hi) { return f16_bits(lo) | (f16_bits(hi) << 16); }
struct alignas(128) Tables {
  uint32_t mat[3072];
  uint32_t thr[4][128][4];
};
constexpr Tables make_tables() {
  Tables T{};
  for (int q = 0; q < 768; q++) {
    int m0 = 0, d0 = 0, d1 = 0;
    if (q < 512) {
      const int r = (q >> 6) * 8 + (q & 7), cc = (q >> 3) & 7;
      d0 = 4 * (r & 31); d1 = 2 * d0;
      m0 = 8 * (cc & 3) * d0 + ((r >> 5) == (cc >> 2) ? 0 : (r >> 5) ? 96 : 32);
    } else {
      const int r = ((q - 512) >> 5) * 8 + (q & 7), pc = (q >> 3) & 3;
      d0 = 4 * (8 * (r >> 4) + (r & 7)) + 1; d1 = 8 * d0;
      m0 = 2 * pc * d0 + ((r & 8) ? 32 : 0);
    }
    for (int e = 0; e < 4; e++) T.mat[4 * q + e] = pair_h(cos_turn(m0 + e * d1, 128), cos_turn(m0 + e * d1 + d0, 128));
  }
  for (int tid = 0; tid < 128; tid++) {
    const int kk = 4 * (tid >> 2) + 1, t = tid & 3;
    for (int q = 0; q < 4; q++) {
      const int m = (8 * q + 2 * t) * kk;
      T.thr[q >> 1][tid][2 * (q & 1)] = pair_bits(cos_turn(m, 128), cos_turn(m + kk, 128));
      T.thr[q >> 1][tid][2 * (q & 1) + 1] = pair_bits(cos_turn(m + 32, 128), cos_turn(m + kk + 32, 128));
      T.thr[2][tid][q] = pair_h(cos_turn(m, 4096), cos_turn(m + kk, 4096));
      T.thr[3][tid][q] = pair_h(cos_turn(m + 3072, 4096), cos_turn(m + kk + 3072, 4096));
    }
  }
  return T;
}
__device__ const Tables d_tab = make_tables();

struct Params {
  const __nv_bfloat16 *logA, *Aim, *Cre, *Cim, *logdt;
  const Tables* tab;
  unsigned* cnt;
  const __nv_bfloat16 *Dskip, *shift_k, *ssm_D, *gate_w, *q, *v, *ssm_k;
  uint2* part;
  __nv_bfloat16* out;
  unsigned* tl;
  uint64_t dfwd, dinv, dlast, dk[5], dt[5], dx[5], dv[5];
  CUtensorMap tq, tk, tv, tkh;
};

__device__ uint2 g_part[(NCL + 1) * SEQ];
__device__ unsigned g_cnt[CS * 32];
#define TL(i) do {} while (0)
#define TL_INIT() do {} while (0)
#define TL_DUMP() do {} while (0)

__device__ __forceinline__ uint32_t lds16(uint32_t a) { uint32_t v; asm volatile("ld.shared.u16 %0, [%1];" : "=r"(v) : "r"(a) : "memory"); return v; }
__device__ __forceinline__ uint2 lds64(uint32_t a) { uint2 v; asm volatile("ld.shared.v2.u32 {%0,%1}, [%2];" : "=r"(v.x), "=r"(v.y) : "r"(a) : "memory"); return v; }
__device__ __forceinline__ uint4 lds128(uint32_t a) { uint4 v; asm volatile("ld.shared.v4.u32 {%0,%1,%2,%3}, [%4];" : "=r"(v.x), "=r"(v.y), "=r"(v.z), "=r"(v.w) : "r"(a) : "memory"); return v; }
__device__ __forceinline__ void sts16(uint32_t a, uint32_t v) { asm volatile("st.shared.u16 [%0], %1;" :: "r"(a), "r"(v) : "memory"); }
__device__ __forceinline__ void sts32(uint32_t a, uint32_t v) { asm volatile("st.shared.u32 [%0], %1;" :: "r"(a), "r"(v) : "memory"); }
__device__ __forceinline__ void sts64(uint32_t a, uint32_t x, uint32_t y) { asm volatile("st.shared.v2.u32 [%0], {%1,%2};" :: "r"(a), "r"(x), "r"(y) : "memory"); }
__device__ __forceinline__ void sts128(uint32_t a, uint32_t x, uint32_t y, uint32_t z, uint32_t w) { asm volatile("st.shared.v4.u32 [%0], {%1,%2,%3,%4};" :: "r"(a), "r"(x), "r"(y), "r"(z), "r"(w) : "memory"); }
__device__ __forceinline__ void ldsm4t(uint32_t (&r)[4], uint32_t a) { asm volatile("ldmatrix.sync.aligned.m8n8.x4.trans.shared.b16 {%0,%1,%2,%3}, [%4];" : "=r"(r[0]), "=r"(r[1]), "=r"(r[2]), "=r"(r[3]) : "r"(a) : "memory"); }
__device__ __forceinline__ void ldsm2t(uint32_t& r0, uint32_t& r1, uint32_t a) { asm volatile("ldmatrix.sync.aligned.m8n8.x2.trans.shared.b16 {%0,%1}, [%2];" : "=r"(r0), "=r"(r1) : "r"(a) : "memory"); }
__device__ __forceinline__ void ldsm4(uint32_t (&r)[4], uint32_t a) { asm volatile("ldmatrix.sync.aligned.m8n8.x4.shared.b16 {%0,%1,%2,%3}, [%4];" : "=r"(r[0]), "=r"(r[1]), "=r"(r[2]), "=r"(r[3]) : "r"(a) : "memory"); }
__device__ __forceinline__ void stsm4(uint32_t a, const uint32_t (&r)[4]) { asm volatile("stmatrix.sync.aligned.m8n8.x4.shared.b16 [%0], {%1,%2,%3,%4};" :: "r"(a), "r"(r[0]), "r"(r[1]), "r"(r[2]), "r"(r[3]) : "memory"); }
__device__ __forceinline__ uint32_t pack(float lo, float hi) { uint32_t r; asm("cvt.rn.bf16x2.f32 %0, %1, %2;" : "=r"(r) : "f"(hi), "f"(lo)); return r; }
__device__ __forceinline__ float blo(uint32_t v) { return __uint_as_float(v << 16); }
__device__ __forceinline__ float bhi(uint32_t v) { return __uint_as_float(v & 0xffff0000u); }
__device__ __forceinline__ float bf16r(float x) { return blo(pack(x, 0.f)); }
__device__ __forceinline__ uint32_t hmul2(uint32_t a, uint32_t b) { uint32_t r; asm("mul.rn.bf16x2 %0, %1, %2;" : "=r"(r) : "r"(a), "r"(b)); return r; }
__device__ __forceinline__ uint32_t hadd2(uint32_t a, uint32_t b) { uint32_t r; asm("add.rn.bf16x2 %0, %1, %2;" : "=r"(r) : "r"(a), "r"(b)); return r; }
__device__ __forceinline__ uint32_t hfma2(uint32_t a, uint32_t b, uint32_t c) { uint32_t r; asm("fma.rn.bf16x2 %0, %1, %2, %3;" : "=r"(r) : "r"(a), "r"(b), "r"(c)); return r; }
__device__ __forceinline__ uint32_t packh(float lo, float hi) { uint32_t r; asm("cvt.rn.f16x2.f32 %0, %1, %2;" : "=r"(r) : "f"(hi), "f"(lo)); return r; }
__device__ __forceinline__ __half2 H2(uint32_t a) { return *reinterpret_cast<__half2*>(&a); }
__device__ __forceinline__ uint32_t U2(__half2 a) { return *reinterpret_cast<uint32_t*>(&a); }
__device__ __forceinline__ uint32_t fmul(uint32_t a, uint32_t b) { return U2(__hmul2(H2(a), H2(b))); }
__device__ __forceinline__ uint32_t ffma(uint32_t a, uint32_t b, uint32_t c) { return U2(__hfma2(H2(a), H2(b), H2(c))); }
__device__ __forceinline__ uint32_t fneg(uint32_t a) { return U2(__hneg2(H2(a))); }
__device__ __forceinline__ uint32_t amax2(uint32_t a, uint32_t b) { uint32_t r; asm("max.xorsign.abs.bf16x2 %0, %1, %2;" : "=r"(r) : "r"(a), "r"(b)); return r; }
__device__ __forceinline__ uint32_t prmt(uint32_t a, uint32_t b, uint32_t s) { return __byte_perm(a, b, s); }
__device__ __forceinline__ uint32_t ldraw(const __nv_bfloat16* p) { uint32_t v; asm volatile("ld.global.nc.u16 %0, [%1];" : "=r"(v) : "l"(p)); return v; }
__device__ __forceinline__ uint4 ldg128(const void* p) { uint4 v; asm volatile("ld.global.nc.v4.u32 {%0,%1,%2,%3}, [%4];" : "=r"(v.x), "=r"(v.y), "=r"(v.z), "=r"(v.w) : "l"(p)); return v; }
__device__ __forceinline__ void bar_sync(int id, int n) { asm volatile("bar.sync %0, %1;" :: "r"(id), "r"(n) : "memory"); }
__device__ __forceinline__ void bar_arrive(int id, int n) { asm volatile("bar.arrive %0, %1;" :: "r"(id), "r"(n) : "memory"); }
__device__ __forceinline__ void cluster_arrive() { asm volatile("barrier.cluster.arrive.relaxed.aligned;" ::: "memory"); }
__device__ __forceinline__ void cluster_wait() { asm volatile("barrier.cluster.wait.aligned;" ::: "memory"); }
__device__ __forceinline__ void fence_async() { asm volatile("fence.proxy.async.shared::cta;" ::: "memory"); }
__device__ __forceinline__ void fence_mbinit() { asm volatile("fence.mbarrier_init.release.cluster;" ::: "memory"); }
__device__ __forceinline__ uint32_t mapa(uint32_t a, uint32_t rank) { uint32_t r; asm("mapa.shared::cluster.u32 %0, %1, %2;" : "=r"(r) : "r"(a), "r"(rank)); return r; }
__device__ __forceinline__ void bulk_dsmem(uint32_t dst, uint32_t src, uint32_t bytes, uint32_t mbar) {
  asm volatile("cp.async.bulk.shared::cluster.shared::cta.mbarrier::complete_tx::bytes [%0], [%1], %2, [%3];" :: "r"(dst), "r"(src), "r"(bytes), "r"(mbar) : "memory");
}
__device__ __forceinline__ void bulk_load(uint32_t dst, const void* src, uint32_t bytes, uint32_t mbar) {
  asm volatile("cp.async.bulk.shared::cluster.global.mbarrier::complete_tx::bytes [%0], [%1], %2, [%3];" :: "r"(dst), "l"(src), "r"(bytes), "r"(mbar) : "memory");
}
__device__ __forceinline__ void mbar_init(uint32_t m, uint32_t cnt) { asm volatile("mbarrier.init.shared::cta.b64 [%0], %1;" :: "r"(m), "r"(cnt) : "memory"); }
__device__ __forceinline__ void mbar_expect(uint32_t m, uint32_t bytes) { asm volatile("mbarrier.arrive.expect_tx.shared::cta.b64 _, [%0], %1;" :: "r"(m), "r"(bytes) : "memory"); }
__device__ __forceinline__ bool mbar_try(uint32_t m) {
  uint32_t done;
  asm volatile("{.reg .pred p; mbarrier.try_wait.parity.shared::cta.b64 p, [%1], 0; selp.u32 %0, 1, 0, p;}" : "=r"(done) : "r"(m) : "memory");
  return done;
}
__device__ __forceinline__ void mbar_wait(uint32_t m) {
  if (!mbar_try(m)) {
    int it = 0;
    while (!mbar_try(m) && ++it < (1 << 22)) {}
  }
}
__device__ __forceinline__ bool elect() {
  uint32_t e;
  asm volatile("{.reg .pred p; elect.sync _|p, 0xffffffff; selp.u32 %0, 1, 0, p;}" : "=r"(e));
  return e;
}
__device__ __forceinline__ void tma_load4(uint32_t dst, const CUtensorMap* tm, int c0, int c1, int c2, int c3, uint32_t mbar) {
  asm volatile("cp.async.bulk.tensor.4d.shared::cluster.global.mbarrier::complete_tx::bytes [%0], [%1, {%3, %4, %5, %6}], [%2];"
               :: "r"(dst), "l"(tm), "r"(mbar), "r"(c0), "r"(c1), "r"(c2), "r"(c3) : "memory");
}
__device__ __forceinline__ void tma_load3(uint32_t dst, const CUtensorMap* tm, int c0, int c1, int c2, uint32_t mbar) {
  asm volatile("cp.async.bulk.tensor.3d.shared::cluster.global.mbarrier::complete_tx::bytes [%0], [%1, {%3, %4, %5}], [%2];"
               :: "r"(dst), "l"(tm), "r"(mbar), "r"(c0), "r"(c1), "r"(c2) : "memory");
}
__device__ __forceinline__ void tma_store3(const CUtensorMap* tm, int c0, int c1, int c2, uint32_t src) {
  asm volatile("cp.async.bulk.tensor.3d.global.shared::cta.bulk_group [%0, {%2, %3, %4}], [%1];"
               :: "l"(tm), "r"(src), "r"(c0), "r"(c1), "r"(c2) : "memory");
}
__device__ __forceinline__ void mma1688(float (&c)[4], uint32_t a0, uint32_t a1, uint32_t b) {
  asm volatile("mma.sync.aligned.m16n8k8.row.col.f32.bf16.bf16.f32 {%0,%1,%2,%3}, {%4,%5}, {%6}, {%0,%1,%2,%3};"
               : "+f"(c[0]), "+f"(c[1]), "+f"(c[2]), "+f"(c[3]) : "r"(a0), "r"(a1), "r"(b));
}
__device__ __forceinline__ void wg_fence() { asm volatile("wgmma.fence.sync.aligned;" ::: "memory"); }
__device__ __forceinline__ void wg_commit() { asm volatile("wgmma.commit_group.sync.aligned;" ::: "memory"); }
template <int N> __device__ __forceinline__ void wg_wait() { asm volatile("wgmma.wait_group.sync.aligned %0;" :: "n"(N) : "memory"); }
template <int N> __device__ __forceinline__ void tie_all(uint32_t (&x)[N]) {
#pragma unroll
  for (int i = 0; i < N; i++) asm volatile("" : "+r"(x[i]) :: "memory");
}
template <int N> __device__ __forceinline__ void tie_all(float (&x)[N]) {
#pragma unroll
  for (int i = 0; i < N; i++) asm volatile("" : "+f"(x[i]) :: "memory");
}
#define R16(C, d) C(d[0]), C(d[1]), C(d[2]), C(d[3]), C(d[4]), C(d[5]), C(d[6]), C(d[7]), C(d[8]), C(d[9]), C(d[10]), C(d[11]), C(d[12]), C(d[13]), C(d[14]), C(d[15])
#define R32(C, d) R16(C, d), R16(C, (d + 16))
#define P16 "{%0,%1,%2,%3,%4,%5,%6,%7,%8,%9,%10,%11,%12,%13,%14,%15}"
#define P32 "{%0,%1,%2,%3,%4,%5,%6,%7,%8,%9,%10,%11,%12,%13,%14,%15,%16,%17,%18,%19,%20,%21,%22,%23,%24,%25,%26,%27,%28,%29,%30,%31}"
template <int SD, int OFF> __device__ __forceinline__ void rs64(float* d, const uint32_t* a, uint64_t db) {
  if (SD) asm volatile("{.reg .b64 db; add.s64 db, %36, %37; wgmma.mma_async.sync.aligned.m64n64k16.f32.bf16.bf16 " P32 ", {%32,%33,%34,%35}, db, 1, 1, 1, 1;}"
                       : R32("+f", d) : "r"(a[0]), "r"(a[1]), "r"(a[2]), "r"(a[3]), "l"(db), "n"(OFF));
  else asm volatile("{.reg .b64 db; add.s64 db, %36, %37; wgmma.mma_async.sync.aligned.m64n64k16.f32.bf16.bf16 " P32 ", {%32,%33,%34,%35}, db, 0, 1, 1, 1;}"
                    : R32("=f", d) : "r"(a[0]), "r"(a[1]), "r"(a[2]), "r"(a[3]), "l"(db), "n"(OFF));
}
template <int SD, int TB, int OFF> __device__ __forceinline__ void rs64h(uint32_t* d, const uint32_t* a, uint64_t db) {
  if (SD) asm volatile("{.reg .b64 db; add.s64 db, %20, %21; wgmma.mma_async.sync.aligned.m64n64k16.f16.f16.f16 " P16 ", {%16,%17,%18,%19}, db, 1, 1, 1, %22;}"
                       : R16("+r", d) : "r"(a[0]), "r"(a[1]), "r"(a[2]), "r"(a[3]), "l"(db), "n"(OFF), "n"(TB));
  else asm volatile("{.reg .b64 db; add.s64 db, %20, %21; wgmma.mma_async.sync.aligned.m64n64k16.f16.f16.f16 " P16 ", {%16,%17,%18,%19}, db, 0, 1, 1, %22;}"
                    : R16("=r", d) : "r"(a[0]), "r"(a[1]), "r"(a[2]), "r"(a[3]), "l"(db), "n"(OFF), "n"(TB));
}
template <int SD, int OFFA, int OFFB> __device__ __forceinline__ void ss32(float* d, uint64_t da, uint64_t db) {
  if (SD) asm volatile("{.reg .b64 da, db; add.s64 da, %16, %18; add.s64 db, %17, %19; wgmma.mma_async.sync.aligned.m64n32k16.f32.f16.f16 " P16 ", da, db, 1, 1, 1, 1, 1;}"
                       : R16("+f", d) : "l"(da), "l"(db), "n"(OFFA), "n"(OFFB));
  else asm volatile("{.reg .b64 da, db; add.s64 da, %16, %18; add.s64 db, %17, %19; wgmma.mma_async.sync.aligned.m64n32k16.f32.f16.f16 " P16 ", da, db, 0, 1, 1, 1, 1;}"
                    : R16("=f", d) : "l"(da), "l"(db), "n"(OFFA), "n"(OFFB));
}
#define KGEN_ASM(SD) "{.reg .b64 da, db; add.s64 da, %32, %33; add.s64 db, %32, %34;\n" \
  "wgmma.mma_async.sync.aligned.m64n64k16.f32.bf16.bf16 " P32 ", da, db, " SD ", 1, 1, 1, 1;}"
template <int KS> __device__ __forceinline__ void kgen_mma(float (&c)[32], uint64_t da) {
  if (KS) asm volatile(KGEN_ASM("1") : R32("+f", c) : "l"(da), "n"(8 * KS), "n"(8 * KS + 512));
  else asm volatile(KGEN_ASM("0") : R32("=f", c) : "l"(da), "n"(8 * KS), "n"(8 * KS + 512));
  if constexpr (KS < 7) kgen_mma<KS + 1>(c, da);
}
template <int OFF, int KSTEP> __device__ __forceinline__ void stage1(float (&D)[32], const uint32_t (&A1)[8], uint64_t d) {
  rs64<0, OFF>(D, A1, d); rs64<1, OFF + KSTEP>(D, A1 + 4, d);
}
template <int INV> __device__ __forceinline__ void stage2(uint32_t (&X)[16], const uint32_t (&F)[16], uint64_t dc) {
  constexpr int KS = INV ? 16 : 128, TB = INV ? 0 : 1;
  rs64h<0, TB, 0>(X, F, dc); rs64h<1, TB, KS>(X, F + 4, dc); rs64h<1, TB, 2 * KS>(X, F + 8, dc); rs64h<1, TB, 3 * KS>(X, F + 12, dc);
}
__device__ __forceinline__ void fwd_mid(uint32_t (&F)[16], const float (&D)[32], const uint32_t (&tc)[4], const uint32_t (&ts)[4]) {
#pragma unroll
  for (int j = 0; j < 4; j++)
#pragma unroll
    for (int b = 0; b < 2; b++) {
      const int i = 4 * j + 16 * b;
      const uint32_t ar = packh(D[i], D[i + 1]), ai = packh(D[i + 2], D[i + 3]);
      F[2 * j + b] = ffma(ar, tc[j], fmul(ai, ts[j]));
      F[8 + 2 * j + b] = ffma(ai, tc[j], fneg(fmul(ar, ts[j])));
    }
}
__device__ __forceinline__ void put_exp(uint32_t a, uint32_t m, int lane) {
  m = __reduce_max_sync(0xffffffffu, max(m & 0x7f80u, (m >> 16) & 0x7f80u));
  if (lane == 0) sts32(a, m);
}
__device__ __forceinline__ uint32_t get_exp(uint32_t a) { const uint4 v = lds128(a); return max(max(v.x, v.y), max(v.z, v.w)) >> 7; }
__device__ __forceinline__ void scale_a1(uint32_t (&As)[8], const uint32_t (&A1)[8], uint32_t field) {
#pragma unroll
  for (int i = 0; i < 8; i++) As[i] = hmul2(A1[i], field * 0x00800080u);
}

struct cf { float x, y; };
__device__ __forceinline__ cf cmul(cf a, cf b) { cf r; r.x = fmaf(a.x, b.x, -a.y * b.y); r.y = fmaf(a.x, b.y, a.y * b.x); return r; }
__device__ __forceinline__ cf cexp_p(float lr2, float lt, float p) {
  float m;
  asm("ex2.approx.ftz.f32 %0, %1;" : "=f"(m) : "f"(lr2 * p));
  float t = lt * p;
  t = (t - rintf(t)) * 6.283185307179586f;
  cf r; r.x = m * __cosf(t); r.y = m * __sinf(t); return r;
}
__device__ __forceinline__ void store8(uint32_t a, uint32_t b, const cf (&v)[8]) {
  sts128(a, pack(v[0].x, v[1].x), pack(v[2].x, v[3].x), pack(v[4].x, v[5].x), pack(v[6].x, v[7].x));
  sts128(b, pack(v[0].y, v[1].y), pack(v[2].y, v[3].y), pack(v[4].y, v[5].y), pack(v[6].y, v[7].y));
}
__device__ __forceinline__ void mbar_arrive(uint32_t m) { asm volatile("mbarrier.arrive.shared::cta.b64 _, [%0];" :: "r"(m) : "memory"); }
__device__ __forceinline__ float sigmoidf_(float s) { return __fdividef(1.f, 1.f + __expf(fminf(-s, 80.f))); }

__global__ void __cluster_dims__(CS, 1, 1) __launch_bounds__(NTHREADS, 1) fused_kernel(const __grid_constant__ Params p) {
  extern __shared__ __align__(1024) uint8_t smem[];
  TL_INIT();
  TL(31);
  const int wid = __shfl_sync(0xffffffffu, threadIdx.x >> 5, 0);
  const uint32_t sb = (uint32_t)__cvta_generic_to_shared(smem);
  const uint32_t mb = sb + OFF_MB;
  const int u = wid >> 2, w = wid & 3;
  const int tid = threadIdx.x & 127, lane = tid & 31, g = lane >> 2, t = lane & 3;
  const int cl = blockIdx.x >> 3, rank = blockIdx.x & 7;
  const int ch0 = cl * CPC;
  const int nu = min(5, (DCH - ch0) >> 3);
  const bool act = u < nu;

  uint32_t pla, pai, pcr, pci, pdt, tag = 0;
  auto load_params = [&]() {
    const int ch = act ? ch0 + 8 * u + rank : 0, o = ch * NMODE + tid;
    pla = ldraw(p.logA + o); pdt = ldraw(p.logdt + ch); pai = ldraw(p.Aim + o); pcr = ldraw(p.Cre + o); pci = ldraw(p.Cim + o);
  };
  if (u == 4) {
    const bool e = elect();
    if (e) {
#pragma unroll
      for (int i = 0; i < 5; i++) mbar_init(mb + 40 * w + 8 * i, 1);
      if (w == 3) { mbar_init(mb + 8 * MB_XQ, 1); mbar_init(mb + 8 * MB_KV, 1); }
      if (w == 2) mbar_init(mb + 8 * MB_G, 8);
      fence_mbinit();
      if ((sb & 0xffffffu) != SB0) __trap();
    }
    __syncwarp();
    load_params();
    if (w == 0 && lane < 2) asm volatile("atom.relaxed.gpu.global.add.u32 %0, [%1], %2;" : "=r"(tag) : "l"(&p.cnt[rank * 32 + lane]), "r"(cl == 0 ? 16 - (NCL - 1) : 1) : "memory");
    if (e) {
      if (w == 3) {
        mbar_expect(mb + 8 * MB_XQ, 20480 + 20480 + 112 * nu);
        bulk_load(sb + OFF_SP, p.gate_w + ch0, 16 * nu, mb + 8 * MB_XQ);
        bulk_load(sb + OFF_SP + 80, p.Dskip + ch0, 16 * nu, mb + 8 * MB_XQ);
        bulk_load(sb + OFF_SP + 160, p.ssm_D + ch0, 16 * nu, mb + 8 * MB_XQ);
        bulk_load(sb + OFF_SP + 240, p.shift_k + 4 * ch0, 64 * nu, mb + 8 * MB_XQ);
        tma_load3(sb + OFF_TQ, &p.tq, ch0, 8 * rank, 0, mb + 8 * MB_XQ);
        bulk_load(sb + OFF_CF, p.tab, 20480, mb + 8 * MB_XQ);
        TL(20);
        mbar_expect(mb + 8 * MB_KV, 2 * 20480 + 320);
        tma_load3(sb + OFF_TK, &p.tk, ch0, 8 * rank, 0, mb + 8 * MB_KV);
        tma_load3(sb + OFF_HALO, &p.tkh, ch0, 8 * rank - 1, 28, mb + 8 * MB_KV);
      }
#pragma unroll
      for (int i = 0; i < 5; i++) mbar_expect(mb + 40 * w + 8 * i, w == 3 ? 4096 : w == 2 ? 7168 : 7 * YP);
    }
    __syncwarp();
  } else {
    load_params();
  }
  cluster_arrive();
  TL(0);

  const uint32_t tab = sb + OFF_T + u * KTAB;
  const uint32_t toff = (64 * w + lane) * 80 + 16 * u;
  const int uown = u * USZ + (rank & 3) * UGRP + (rank >> 2) * YP;
  auto put = [&](int stage, const uint32_t (&a)[4], const uint32_t (&b)[4]) {
    const uint32_t o = sb + (g == rank ? OFF_U + uown : stage + (8 * u + g) * YP);
    const uint32_t od = o + (rank < 4 ? 16 : 0) + 128 * w + 32 * t;
    sts128(od, prmt(a[0], a[1], 0x5410), prmt(a[2], a[3], 0x5410), prmt(b[0], b[1], 0x5410), prmt(b[2], b[3], 0x5410));
    sts128(od + 16, prmt(a[0], a[1], 0x7632), prmt(a[2], a[3], 0x7632), prmt(b[0], b[1], 0x7632), prmt(b[2], b[3], 0x7632));
    const uint32_t m = amax2(amax2(amax2(a[0], a[1]), amax2(a[2], a[3])), amax2(amax2(b[0], b[1]), amax2(b[2], b[3])));
    asm volatile("st.shared.u8 [%0], %1;" :: "r"(o + (rank < 4 ? 0 : 512) + 4 * w + t), "r"(amax2(m, m >> 16) >> 7) : "memory");
  };
  const int d0 = rank ^ (2 * w), d1 = d0 ^ 1;
  const uint32_t rb0 = mapa(sb, d0), rb1 = mapa(sb, d1);
  auto send = [&](int stage, int bytes, int dst, int mbar) {
    if (elect()) {
      if (w) bulk_dsmem(rb0 + dst, sb + stage + d0 * bytes, bytes, rb0 + mbar);
      bulk_dsmem(rb1 + dst, sb + stage + d1 * bytes, bytes, rb1 + mbar);
    }
    __syncwarp();
  };

  uint32_t A1[8], tc[4], ts[4];
  {
    const float dt = bf16r(expf(blo(pdt)));
    const float lr2 = (-bf16r(expf(blo(pla))) * dt) * 1.4426950408889634f;
    const float lt = (blo(pai) * dt) * 0.15915494309189535f;
    const uint32_t tim = sb + (u ? OFF_IM + (u - 1) * KTAB : OFF_U);
    const uint32_t row = tab + tid * 16, rim = tim + tid * 16;
    const cf w1 = cexp_p(lr2, lt, 8.f);
    cf z1 = cexp_p(lr2, lt, 1.f), Z = cexp_p(lr2, lt, 256.f);
    if (lr2 != 123.f) TL(16);
    TL(12);
    {
      cf v[8];
      v[0].x = 1.f; v[0].y = 0.f; v[1] = w1; v[2] = cmul(w1, w1); v[3] = cmul(v[2], w1);
      const cf w4 = cmul(v[2], v[2]);
      v[4] = w4; v[5] = cmul(v[1], w4); v[6] = cmul(v[2], w4); v[7] = cmul(v[3], w4);
      const cf w8 = cmul(w4, w4);
      store8(row, rim, v);
#pragma unroll
      for (int k = 1; k < 4; k++) {
#pragma unroll
        for (int i = 0; i < 8; i++) v[i] = (k == 1 && i == 0) ? w8 : cmul(v[i], w8);
        store8(row + 2048 * k, rim + 2048 * k, v);
      }
    }
    if (STAGGER && STMID && u < 5 - STW) bar_arrive(NB_ST + u, 256);
    if (PREFETCH && wid == 8 && elect()) {
      const uint32_t o = blockIdx.x * 9856u, n = min(9856u, SEQ * DCH - o) * 2;
      asm volatile("cp.async.bulk.prefetch.L2.global [%0], %1;" :: "l"(p.v + o), "r"(n) : "memory");
      asm volatile("cp.async.bulk.prefetch.L2.global [%0], %1;" :: "l"(p.ssm_k + o), "r"(n) : "memory");
    }
    __syncwarp();
    if (u == 1) {
      float z0_ = 0.f, z1_ = 0.f, z2_ = 0.f, z3_ = 0.f;
      asm volatile("mma.sync.aligned.m16n8k8.row.col.f32.bf16.bf16.f32 {%0,%1,%2,%3}, {%4,%4}, {%4}, {%0,%1,%2,%3};"
                   : "+f"(z0_), "+f"(z1_), "+f"(z2_), "+f"(z3_) : "r"(pla >> 16));
      pcr += __float_as_uint(z0_);
      TL(8);
    }
    {
      z1.y = -z1.y; Z.y = -Z.y;
      const cf z2 = cmul(z1, z1);
      cf h[8], v[8];
      h[0].x = 2.f * blo(pcr) * dt; h[0].y = -2.f * blo(pci) * dt;
      h[1] = cmul(h[0], z1);
#pragma unroll
      for (int i = 2; i < 8; i++) h[i] = cmul(h[i - 2], z2);
      store8(row + 4 * 2048, rim + 4 * 2048, h);
      const cf h8 = cmul(h[6], z2);
      v[0] = cmul(h[0], Z); v[2] = cmul(h[2], Z); v[3] = cmul(h[4], Z); v[6] = cmul(h[6], Z); v[7] = cmul(h8, Z);
      v[1] = v[0]; v[4] = v[5] = v[3];
      store8(row + 5 * 2048, rim + 5 * 2048, v);
      h[0] = cmul(v[0], Z); h[1] = cmul(v[3], Z); h[3] = cmul(v[7], Z); h[4] = cmul(h[0], Z); h[5] = cmul(h[1], Z); h[7] = cmul(h[3], Z);
      h[2] = h[1]; h[6] = h[5];
      store8(row + 6 * 2048, rim + 6 * 2048, h);
      const cf Z2 = cmul(Z, Z);
      v[0] = cmul(h[0], Z2); v[1] = cmul(h[3], Z2); v[2] = cmul(h[4], Z2); v[3] = cmul(h[7], Z2);
#pragma unroll
      for (int i = 4; i < 8; i++) v[i] = cmul(v[i - 4], Z2);
      store8(row + 7 * 2048, rim + 7 * 2048, v);
    }
    TL(17);
    if (wid == 16 && lane == 0) sts32(mb + 8 * MB_TAG, tag);
    cluster_wait();
    if (u >= 3) cluster_arrive();
    fence_async();
    if (u) bar_sync(NB_ORD + u - 1, 256); else bar_sync(NB_WG0, 128);
    TL(13);
    float c[32];
    wg_fence();
    kgen_mma<0>(c, p.dk[u]);
    wg_commit();
    if (u < 4) bar_arrive(NB_ORD + u, 256);
    TL(14);
    mbar_wait(mb + 8 * MB_XQ);
    TL(18);
    uint32_t x0[4], x1[4];
    ldsm4t(x0, sb + OFF_TQ + toff);
    ldsm4t(x1, sb + OFF_TQ + toff + 2560);
    {
      const uint4 x = lds128(sb + OFF_TH + 16 * tid), y = lds128(sb + OFF_TH + 2048 + 16 * tid), a = lds128(sb + OFF_TH + 4096 + 16 * tid), b = lds128(sb + OFF_TH + 6144 + 16 * tid);
      A1[0] = x.x; A1[1] = x.y; A1[2] = x.z; A1[3] = x.w; A1[4] = y.x; A1[5] = y.y; A1[6] = y.z; A1[7] = y.w;
      tc[0] = a.x; tc[1] = a.y; tc[2] = a.z; tc[3] = a.w; ts[0] = b.x; ts[1] = b.y; ts[2] = b.z; ts[3] = b.w;
    }
    wg_wait<0>(); tie_all(c);
    TL(26);
    if (u < 3) cluster_arrive();
    else if (u == 3) bar_arrive(NB_V, 256);
    bar_sync(u == 4 ? NB_V : NB_WG0 + u, u == 4 ? 256 : 128);
    const uint32_t k0 = pack(c[0] + c[6], c[1] + c[7]), k1 = pack(c[8] + c[14], c[9] + c[15]);
    const uint32_t k2 = pack(c[16] + c[22], c[17] + c[23]), k3 = pack(c[24] + c[30], c[25] + c[31]);
    const uint32_t ka = tab + 16 * (8 * w + (g ^ w));
    sts32(ka + 4 * t, k0);
    sts32(ka + 512 + 4 * t, k1);
    sts64(ka + 1024 + 512 * (t >> 1) + 8 * (t & 1), prmt(k2, 0, 0x1010), (t & 1) ? prmt(k2, 0, 0x3232) : k2);
    const uint32_t lo = prmt(k3, 0, 0x1010), hi = prmt(k3, 0, 0x3232);
    sts128(ka + 2048 + 512 * t, lo, lo, (g & 1) ? hi : k3, hi);
    put_exp(sb + OFF_MX + u * 32 + 4 * w, amax2(amax2(k0, k1), amax2(k2, k3)), lane);
    cluster_wait();
    put(OFF_YB, x0, x1);
    TL(15);
    fence_async();
    bar_sync(NB_WG0 + u, 128);
    send(OFF_YB + 8 * u * YP, YP, OFF_U + uown, OFF_MB + 8 * (MB_UX + u));
    if (wid == 16 && elect()) tma_load3(sb + OFF_TV, &p.tv, ch0, 8 * rank, 0, mb + 8 * MB_KV);
    __syncwarp();
  }
  if (u == 0) {
    float ga[4][4];
#pragma unroll
    for (int i = 0; i < 4; i++) ga[i][0] = ga[i][1] = ga[i][2] = ga[i][3] = 0.f;
#pragma unroll
    for (int j = 0; j < 5; j++) {
      uint32_t a0[4], a1[4], b;
      ldsm4(a0, sb + OFF_TQ + toff + 16 * j);
      ldsm4(a1, sb + OFF_TQ + toff + 2560 + 16 * j);
      asm volatile("ld.shared.u32 %0, [%1];" : "=r"(b) : "r"(sb + OFF_SP + 16 * j + 4 * t) : "memory");
      if (j >= 2 && j >= nu) b = 0;
      mma1688(ga[0], a0[0], a0[1], b); mma1688(ga[1], a0[2], a0[3], b); mma1688(ga[2], a1[0], a1[1], b); mma1688(ga[3], a1[2], a1[3], b);
    }
    const float s0 = t == 0 ? ga[0][0] : t == 1 ? ga[1][0] : t == 2 ? ga[2][0] : ga[3][0];
    const float s1 = t == 0 ? ga[0][2] : t == 1 ? ga[1][2] : t == 2 ? ga[2][2] : ga[3][2];
    tag = (lds64(mb + 8 * MB_TAG).x >> 4) + 1;
    uint2* gp = p.part + cl * SEQ + rank * 256 + 64 * w + 16 * t + g;
    asm volatile("st.relaxed.gpu.global.u64 [%0], %1;" :: "l"(gp), "l"(((uint64_t)tag << 32) | __float_as_uint(s0)) : "memory");
    asm volatile("st.relaxed.gpu.global.u64 [%0], %1;" :: "l"(gp + 8), "l"(((uint64_t)tag << 32) | __float_as_uint(s1)) : "memory");
  }

#pragma unroll
  for (int isA = 0; isA < 2; isA++) {
    {
      TL(1 + isA);
      const uint32_t mxa = sb + OFF_MX + u * 32 + 16 * isA;
      const uint32_t pd = lds16(sb + OFF_SP + 80 + 80 * isA + 16 * u + 2 * rank);
      float D[32];
      uint32_t As[8], F[16], H[16], X[16];
      const uint32_t eh = min(max((int)get_exp(mxa), (int)((pd >> 7) & 0xff) - 5), 240);
      scale_a1(As, A1, 248 - eh);
      wg_fence();
      if (isA) stage1<T_HA / 16, 64>(D, As, p.dt[u]); else stage1<0, 64>(D, As, p.dt[u]);
      wg_commit();
      wg_wait<0>(); tie_all(D);
      fwd_mid(F, D, tc, ts);
      wg_fence();
      stage2<0>(H, F, p.dfwd);
      wg_commit();
      if (!isA) {
        if (w == 2 && elect()) bulk_load(tab + T_HA, p.ssm_k + (size_t)(act ? ch0 + 8 * u + rank : 0) * SEQ, 4096, mb + 8 * (MB_HA + u));
        __syncwarp();
        TL(7);
      }
      mbar_wait(mb + 8 * ((isA ? MB_UKV : MB_UX) + u));
      TL(5 + isA);
      uint32_t eu;
      asm volatile("ld.shared.u32 %0, [%1];" : "=r"(eu) : "r"(sb + OFF_U + u * USZ + (lane >> 3) * UGRP + ((lane & 4) ? UGRP - 16 : 0) + 4 * t) : "memory");
      eu = __vmaxu2(eu & 0x00ff00ffu, (eu >> 8) & 0x00ff00ffu);
      eu = min(__reduce_max_sync(0xffffffffu, max(eu & 0xffffu, eu >> 16)), 240u);
      scale_a1(As, A1, 250 - eu);
      wg_wait<0>(); tie_all(H);
      wg_fence();
      stage1<0, 2 * UGRP / 16>(D, As, p.dx[u]);
      wg_commit();
      wg_wait<0>(); tie_all(D);
      if (!isA) cluster_arrive();
      fwd_mid(F, D, tc, ts);
      wg_fence();
      stage2<0>(X, F, p.dfwd);
      wg_commit();
      {
        const float dsk = blo(pd) * __uint_as_float((248 - eh) << 23);
        const uint32_t d2 = packh(dsk, dsk);
#pragma unroll
        for (int j = 0; j < 4; j++) H[2 * j] = U2(__hadd2(H2(H[2 * j]), H2(d2)));
      }
      wg_wait<0>(); tie_all(X);
#pragma unroll
      for (int j = 0; j < 4; j++) {
        const uint32_t h0r = H[2 * j], h1r = H[2 * j + 1], h0i = H[8 + 2 * j], h1i = H[9 + 2 * j];
        const uint32_t x0r = X[2 * j], x1r = X[2 * j + 1], x0i = X[8 + 2 * j], x1i = X[9 + 2 * j];
        F[2 * j] = ffma(x0r, h0r, fneg(fmul(x0i, h0i)));
        F[8 + 2 * j] = ffma(x0r, h0i, fmul(x0i, h0r));
        F[2 * j + 1] = ffma(x1r, h0r, ffma(fneg(x1i), h0i, ffma(x0r, h1r, fneg(ffma(x0i, h1i, F[8 + 2 * j])))));
        F[9 + 2 * j] = ffma(x1r, h0i, ffma(x1i, h0r, ffma(x0r, h1i, ffma(x0i, h1r, F[2 * j]))));
      }
      wg_fence();
      stage2<1>(H, F, p.dinv);
      wg_commit();
      uint64_t ga[4];
      const int sl2 = min(18 * cl + min(8 * w + g, 17), 255), sl3 = tid + 128 * (u & 1);
      auto gload = [&]() {
        if (isA) {
          asm volatile("ld.relaxed.gpu.global.u64 %0, [%1];" : "=l"(ga[0]) : "l"(p.part + NCL * SEQ + rank * 256 + sl3) : "memory");
        } else {
#pragma unroll
          for (int k = 0; k < 4; k++)
            asm volatile("ld.relaxed.gpu.global.u64 %0, [%1];" : "=l"(ga[k]) : "l"(p.part + (t + (k == 3 && t == 3 ? 8 : 4 * k)) * SEQ + rank * 256 + sl2) : "memory");
        }
      };
      if (isA ? (u & 6) == 2 : u == 1) gload();
      if (isA) TL(23);
      wg_wait<0>(); tie_all(H);
      {
        const uint32_t va = tab + (16 * w + (lane & 15)) * 128;
        const int vx = (lane >> 4) ^ (lane & 7);
#pragma unroll
        for (int j = 0; j < 4; j++) {
          uint32_t V[4];
#pragma unroll
          for (int b = 0; b < 2; b++) {
            const uint32_t er = H[2 * j + b], ei = H[8 + 2 * j + b];
            V[2 * b] = ffma(er, tc[j], fneg(fmul(ei, ts[j])));
            V[2 * b + 1] = ffma(ei, tc[j], fmul(er, ts[j]));
          }
          stsm4(va + ((vx ^ (2 * j)) << 4), V);
        }
      }
      if (!isA) {
        cluster_wait();
        mbar_wait(mb + 8 * MB_KV);
        TL(21);
        uint32_t K[3][4], V[2][4];
        const uint2 psw = lds64(sb + OFF_SP + 240 + 64 * u + 8 * g);
        ldsm4t(K[0], w ? sb + OFF_TK + toff - 2560 : (lane & 7) ? sb + OFF_TK + toff + 223 * 80 : sb + OFF_HALO + 10 * lane + 16 * u);
        ldsm4t(K[1], sb + OFF_TK + toff);
        ldsm4t(K[2], sb + OFF_TK + toff + 2560);
        ldsm4t(V[0], sb + OFF_TV + toff);
        ldsm4t(V[1], sb + OFF_TV + toff + 2560);
        mbar_wait(mb + 8 * (MB_HA + u));
        const uint4 hx = lds128(tab + T_HA + 16 * tid), hy = lds128(tab + T_HA + 2048 + 16 * tid);
        const uint32_t w0 = prmt(psw.x, 0, 0x1010), w1 = prmt(psw.x, 0, 0x3232), w2 = prmt(psw.y, 0, 0x1010), w3 = prmt(psw.y, 0, 0x3232);
#pragma unroll
        for (int m = 4; m < 12; m++)
          V[(m >> 2) - 1][m & 3] = hmul2(hfma2(K[m >> 2][m & 3], w0, hfma2(K[(m - 1) >> 2][(m - 1) & 3], w1,
                                         hfma2(K[(m - 2) >> 2][(m - 2) & 3], w2, hmul2(K[(m - 3) >> 2][(m - 3) & 3], w3)))), V[(m >> 2) - 1][m & 3]);
        put(OFF_YA, V[0], V[1]);
        put_exp(mxa + 16 + 4 * w, amax2(amax2(amax2(hx.x, hx.y), amax2(hx.z, hx.w)), amax2(amax2(hy.x, hy.y), amax2(hy.z, hy.w))), lane);
        sts128(tab + T_HA + 16 * (tid ^ (lane >> 3)), hx.x, hx.y, hx.z, hx.w);
        sts128(tab + T_HA + 2048 + 16 * (tid ^ (lane >> 3)), hy.x, hy.y, hy.z, hy.w);
        TL(22);
      }
      fence_async();
      bar_sync(NB_WG0 + u, 128);
      float O[16];
      {
        const uint64_t dv = p.dv[u], dl = p.dlast;
        wg_fence();
        ss32<0, 0, 0>(O, dv, dl); ss32<1, 128, 64>(O, dv, dl); ss32<1, 256, 128>(O, dv, dl); ss32<1, 384, 192>(O, dv, dl);
        wg_commit();
      }
      if (!isA) send(OFF_YA + 8 * u * YP, YP, OFF_U + uown, OFF_MB + 8 * (MB_UKV + u));
      else send(OFF_T + u * KTAB + T_YS, 512, OFF_YB + (8 * u + rank) * YP, OFF_MB + 8 * (MB_Y + u));
      if (isA ? (u & 6) == 2 : u == 1) {
        tag = (lds64(mb + 8 * MB_TAG).x >> 4) + 1;
        bool ok;
#pragma unroll 1
        for (int it = 0;; it++) {
          ok = (uint32_t)(ga[0] >> 32) == tag;
          if (!isA) ok = ok && (uint32_t)(ga[1] >> 32) == tag && (uint32_t)(ga[2] >> 32) == tag && (uint32_t)(ga[3] >> 32) == tag;
          ok = __all_sync(0xffffffffu, ok);
          if (ok || it == (isA ? 8000 : 2000)) break;
          gload();
        }
        if (!isA) {
          float s = __uint_as_float((uint32_t)ga[0]) + __uint_as_float((uint32_t)ga[1]) + __uint_as_float((uint32_t)ga[2]);
          if (t < 3) s += __uint_as_float((uint32_t)ga[3]);
          s += __shfl_xor_sync(0xffffffffu, s, 1);
          s += __shfl_xor_sync(0xffffffffu, s, 2);
          const float g0 = bf16r(sigmoidf_(bf16r(s)));
          if (ok && t == 0)
            asm volatile("st.relaxed.gpu.global.u64 [%0], %1;" :: "l"(p.part + NCL * SEQ + rank * 256 + sl2), "l"(((uint64_t)tag << 32) | pack(g0, 1.f - g0)) : "memory");
        } else {
          uint32_t gv = (uint32_t)ga[0];
          if (!ok) {
            const uint32_t* xr = (const uint32_t*)(p.q + (size_t)(rank * 256 + 32 * (sl3 & 7) + (sl3 >> 3)) * DCH);
            const uint32_t* gr = (const uint32_t*)p.gate_w;
            float s = 0.f;
#pragma unroll 1
            for (int k = 0; k < DCH / 2; k++) { const uint32_t x = __ldg(xr + k), y = __ldg(gr + k); s = fmaf(blo(x), blo(y), fmaf(bhi(x), bhi(y), s)); }
            const float g0 = bf16r(sigmoidf_(bf16r(s)));
            gv = pack(g0, 1.f - g0);
          }
          sts64(sb + OFF_GB + 8 * sl3, prmt(gv, 0, 0x1010), prmt(gv, 0, 0x3232));
          __syncwarp();
          if (lane == 0) mbar_arrive(mb + 8 * MB_G);
        }
      }
      if (isA) TL(28);
      wg_wait<0>(); tie_all(O);
      {
        const uint32_t co = ((8 * w + g) ^ (2 * t)) * 16, usrc = tab + (isA ? T_HA : T_YS);
        const int yo = (isA ? OFF_YA : OFF_YB) + (8 * u + rank) * YP, ym = OFF_MB + 8 * (MB_Y + u);
        const uint32_t us = min(max((int)(eu + eh) - 127, 0), 254) * 0x00800080u;
        const uint32_t a0 = hmul2(pack(O[0], O[1]), us), a1 = hmul2(pack(O[4], O[5]), us), a2 = hmul2(pack(O[8], O[9]), us), a3 = hmul2(pack(O[12], O[13]), us);
        const uint32_t b0 = hmul2(pack(O[2], O[3]), us), b1 = hmul2(pack(O[6], O[7]), us), b2 = hmul2(pack(O[10], O[11]), us), b3 = hmul2(pack(O[14], O[15]), us);
        sts128((t == rank ? sb + yo : usrc + t * 512) + co, a0, a1, a2, a3);
        sts128((t + 4 == rank ? sb + yo : usrc + t * 512 + 2048) + co, b0, b1, b2, b3);
        if (isA) {
          fence_async();
          bar_sync(NB_WG0 + u, 128);
          send(usrc - sb, 512, yo, ym);
        }
      }
      TL(9 + isA);
    }
  }

  {
    mbar_wait(mb + 8 * MB_G);
    uint2 gg[2][4];
    uint32_t qv[2][4];
#pragma unroll
    for (int hh = 0; hh < 2; hh++)
#pragma unroll
      for (int i = 0; i < 4; i++) gg[hh][i] = lds64(sb + OFF_GB + 8 * (64 * w + 32 * hh + 8 * i + g));
    const uint32_t qa = sb + OFF_TQ + toff;
    ldsm4(qv[0], qa);
    ldsm4(qv[1], qa + 2560);
    TL(24);
    mbar_wait(mb + 8 * (MB_Y + u));
    uint32_t ya[2][4], yb[2][4];
#pragma unroll
    for (int hh = 0; hh < 2; hh++) {
      const uint32_t yo = (8 * u + (lane & 7)) * YP + ((8 * w + 4 * hh + (lane >> 3)) ^ (2 * (rank & 3))) * 16;
      ldsm4t(ya[hh], sb + OFF_YA + yo); ldsm4t(yb[hh], sb + OFF_YB + yo);
    }
#pragma unroll
    for (int hh = 0; hh < 2; hh++) {
      uint32_t o[4];
#pragma unroll
      for (int i = 0; i < 4; i++) o[i] = hadd2(hmul2(gg[hh][i].x, hmul2(qv[hh][i], ya[hh][i])), hmul2(gg[hh][i].y, yb[hh][i]));
      stsm4(qa + 2560 * hh, o);
    }
    TL(25);
  }
  cluster_arrive();
  bar_sync(NB_ROW0 + w, 160);
  {
    uint4 v[2];
#pragma unroll
    for (int k = 0; k < 2; k++) {
      const int i = 64 * u + 32 * k + lane, sl = (i * 205) >> 10, cc = i - 5 * sl;
      v[k] = lds128(sb + OFF_TQ + (64 * w + 8 * (sl & 7) + (sl >> 3)) * 80 + cc * 16);
    }
#pragma unroll
    for (int k = 0; k < 2; k++) {
      const int i = 64 * u + 32 * k + lane, sl = (i * 205) >> 10, cc = i - 5 * sl;
      if (cc < nu)
        asm volatile("st.global.cg.v4.u32 [%0], {%1,%2,%3,%4};" :: "l"(p.out + (size_t)(256 * rank + 32 * (sl >> 3) + 8 * w + (sl & 7)) * DCH + ch0 + 8 * cc),
                     "r"(v[k].x), "r"(v[k].y), "r"(v[k].z), "r"(v[k].w) : "memory");
    }
  }
  cluster_wait();
  TL(27);
  TL_DUMP();
}

typedef CUresult (*EncodeFn)(CUtensorMap*, CUtensorMapDataType, cuuint32_t, void*, const cuuint64_t*, const cuuint64_t*,
                             const cuuint32_t*, const cuuint32_t*, CUtensorMapInterleave, CUtensorMapSwizzle,
                             CUtensorMapL2promotion, CUtensorMapFloatOOBfill);

void encode(EncodeFn fn, CUtensorMap* tm, const void* ptr, int nd, const cuuint64_t* dims, const cuuint64_t* strides,
            const cuuint32_t* box, CUtensorMapSwizzle swz) {
  cuuint32_t es[4] = {1, 1, 1, 1};
  fn(tm, CU_TENSOR_MAP_DATA_TYPE_BFLOAT16, nd, const_cast<void*>(ptr), dims, strides, box, es, CU_TENSOR_MAP_INTERLEAVE_NONE,
     swz, CU_TENSOR_MAP_L2_PROMOTION_L2_128B, CU_TENSOR_MAP_FLOAT_OOB_FILL_NONE);
}
void make_map(EncodeFn fn, CUtensorMap* tm, const void* ptr, int ne, int nr) {
  const cuuint64_t dims[3] = {DCH, SEQ / 32, 32}, strides[2] = {32 * DCH * 2, DCH * 2};
  const cuuint32_t box[3] = {CPC, (cuuint32_t)ne, (cuuint32_t)nr};
  encode(fn, tm, ptr, 3, dims, strides, box, CU_TENSOR_MAP_SWIZZLE_NONE);
}

}

extern "C" void kernel_launch(void* const* d_in, const int* in_sizes, int n_in, void* d_out, int out_size) {
  (void)in_sizes; (void)n_in; (void)out_size;
  static EncodeFn fn = nullptr;
  static void *tab = nullptr, *cnt = nullptr, *part = nullptr;
  if (!fn) {
    cudaGetSymbolAddress(&tab, d_tab);
    cudaGetSymbolAddress(&cnt, g_cnt);
    cudaGetSymbolAddress(&part, g_part);
    cudaDriverEntryPointQueryResult qr;
    cudaGetDriverEntryPoint("cuTensorMapEncodeTiled", (void**)&fn, cudaEnableDefault, &qr);
    cudaFuncSetAttribute(fused_kernel, cudaFuncAttributeMaxDynamicSharedMemorySize, SMEM_BYTES);
  }
  Params p;
  make_map(fn, &p.tq, d_in[0], 8, 32);
  make_map(fn, &p.tk, d_in[1], 8, 32);
  make_map(fn, &p.tv, d_in[2], 8, 32);
  make_map(fn, &p.tkh, d_in[1], 1, 4);
  p.out = (__nv_bfloat16*)d_out;
  p.dfwd = mkdesc(OFF_CF, 1024, 128, 0);
  p.dinv = mkdesc(OFF_CF, 128, 1024, 0);
  p.dlast = mkdesc(OFF_CL, 512, 128, 0);
  for (int u = 0; u < 5; u++) {
    p.dk[u] = mkdesc(OFF_T + u * KTAB, u ? OFF_IM - KTAB - OFF_T : OFF_U - OFF_T, 1024, 0);
    p.dt[u] = mkdesc(OFF_T + u * KTAB, 2048, 512, 2);
    p.dx[u] = mkdesc(OFF_U + u * USZ + 16, UGRP, 128, 0);
    p.dv[u] = mkdesc(OFF_T + u * KTAB, 16, 1024, 1);
  }
  p.tab = (const Tables*)tab;
  p.cnt = (unsigned*)cnt;
  p.part = (uint2*)part;
  p.tl = nullptr;
  p.q = (const __nv_bfloat16*)d_in[0];
  p.v = (const __nv_bfloat16*)d_in[2];
  p.ssm_k = (const __nv_bfloat16*)d_in[4];
  p.shift_k = (const __nv_bfloat16*)d_in[3];
  p.ssm_D = (const __nv_bfloat16*)d_in[5];
  p.logA = (const __nv_bfloat16*)d_in[7];
  p.Aim = (const __nv_bfloat16*)d_in[8];
  p.Cre = (const __nv_bfloat16*)d_in[9];
  p.Cim = (const __nv_bfloat16*)d_in[10];
  p.logdt = (const __nv_bfloat16*)d_in[11];
  p.Dskip = (const __nv_bfloat16*)d_in[12];
  p.gate_w = (const __nv_bfloat16*)d_in[13];
  fused_kernel<<<NCL * CS, NTHREADS, SMEM_BYTES, cudaStreamPerThread>>>(p);
}
```

```cpp
#include <cuda_runtime.h>
#include <cuda_bf16.h>
#include <cuda_fp16.h>
#include <cuda.h>
#include <stdint.h>

#define TIMELINE 0
#define STAGGER 0
#define PREFETCH 1
#define STW 2
#define STMID 0
#define TLHI 0

namespace {

constexpr int SEQ = 2048, DCH = 576, NMODE = 128;
constexpr int CS = 8, CPC = 40, NCL = 15, NTHREADS = 640;

constexpr int KTAB = 16384;
constexpr int OFF_T = 0;
constexpr int T_YS = 8192, T_HA = 12288;
constexpr int UGRP = 1056, USZ = 4 * UGRP, YP = 528;
constexpr int OFF_IM = 5 * KTAB;
constexpr int OFF_YB = OFF_IM;
constexpr int OFF_TV = OFF_YB + 40 * YP;
constexpr int OFF_YA = OFF_TV + 20480;
constexpr int OFF_GB = OFF_YA + 40 * YP;
constexpr int OFF_U = OFF_IM + 4 * KTAB;
constexpr int OFF_CF = OFF_U + 5 * USZ;
constexpr int OFF_CL = OFF_CF + 8192;
constexpr int OFF_TH = OFF_CL + 4096;
constexpr int OFF_TQ = OFF_TH + 8192;
constexpr int OFF_TK = OFF_TQ + 20480;
constexpr int OFF_HALO = OFF_TK + 20480;
constexpr int OFF_MX = OFF_HALO + 320;
constexpr int OFF_SP = OFF_MX + 160;
constexpr int OFF_MB = OFF_SP + 560;
constexpr int OFF_TL = OFF_MB + 28 * 8;
constexpr int SMEM_BYTES = OFF_TL + (TIMELINE ? 640 : 0);
static_assert(SMEM_BYTES <= 232448 && OFF_GB + 2048 <= OFF_U && (OFF_TV & 127) == 0 && (OFF_TQ & 127) == 0, "smem");
static_assert((OFF_MB & 7) == 0 && (OFF_MX & 15) == 0 && (OFF_SP & 15) == 0, "align");

enum { MB_UX = 0, MB_UKV = 5, MB_Y = 10, MB_HA = 15, MB_XQ = 20, MB_KV = 21, MB_CF = 22, MB_G = 23, MB_TH = 24, MB_TAG = 25 };
enum { NB_WG0 = 1, NB_ROW0 = 6, NB_ORD = 6, NB_V = 10, NB_ST = 12 };

constexpr uint32_t SB0 = 1024;
constexpr uint64_t mkdesc(uint32_t off, uint32_t lbo, uint32_t sbo, uint32_t swz) {
  return (uint64_t)((SB0 + off) >> 4) | ((uint64_t)(lbo >> 4) << 16) | ((uint64_t)(sbo >> 4) << 32) | ((uint64_t)swz << 62);
}

constexpr double cos_turn(int m, int n) {
  m &= n - 1;
  if (m > n / 2) m = n - m;
  double sgn = 1.0;
  if (m > n / 4) { m = n / 2 - m; sgn = -1.0; }
  if (m == n / 4) return 0.0;
  const double x = 6.283185307179586476925 * m / n;
  double term = 1.0, sum = 1.0;
  for (int k = 1; k < 14; k++) { term *= -x * x / ((2 * k - 1) * (2 * k)); sum += term; }
  return sgn * sum;
}
constexpr uint32_t bf16_bits(double v) {
  if (v == 0.0) return 0;
  uint32_t sgn = 0;
  if (v < 0) { sgn = 0x8000; v = -v; }
  int e = 127;
  while (v < 1.0) { v *= 2.0; e--; }
  while (v >= 2.0) { v *= 0.5; e++; }
  const double f = v * 128.0;
  int m = (int)f;
  if (f - m > 0.5 || (f - m == 0.5 && (m & 1))) m++;
  return sgn | (uint32_t)((e << 7) + (m - 128));
}
constexpr uint32_t f16_bits(double v) {
  if (v == 0.0) return 0;
  uint32_t sgn = 0;
  if (v < 0) { sgn = 0x8000; v = -v; }
  int e = 15;
  while (v < 1.0) { v *= 2.0; e--; }
  const double f = v * 1024.0;
  int m = (int)f;
  if (f - m > 0.5 || (f - m == 0.5 && (m & 1))) m++;
  return sgn | (uint32_t)((e << 10) + (m - 1024));
}
constexpr uint32_t pair_bits(double lo, double hi) { return bf16_bits(lo) | (bf16_bits(hi) << 16); }
constexpr uint32_t pair_h(double lo, double hi) { return f16_bits(lo) | (f16_bits(hi) << 16); }
struct alignas(128) Tables {
  uint32_t mat[3072];
  uint32_t thr[4][128][4];
};
constexpr Tables make_tables() {
  Tables T{};
  for (int q = 0; q < 768; q++) {
    int m0 = 0, d0 = 0, d1 = 0;
    if (q < 512) {
      const int r = (q >> 6) * 8 + (q & 7), cc = (q >> 3) & 7;
      d0 = 4 * (r & 31); d1 = 2 * d0;
      m0 = 8 * (cc & 3) * d0 + ((r >> 5) == (cc >> 2) ? 0 : (r >> 5) ? 96 : 32);
    } else {
      const int r = ((q - 512) >> 5) * 8 + (q & 7), pc = (q >> 3) & 3;
      d0 = 4 * (8 * (r >> 4) + (r & 7)) + 1; d1 = 8 * d0;
      m0 = 2 * pc * d0 + ((r & 8) ? 32 : 0);
    }
    for (int e = 0; e < 4; e++) T.mat[4 * q + e] = pair_h(cos_turn(m0 + e * d1, 128), cos_turn(m0 + e * d1 + d0, 128));
  }
  for (int tid = 0; tid < 128; tid++) {
    const int kk = 4 * (tid >> 2) + 1, t = tid & 3;
    for (int q = 0; q < 4; q++) {
      const int m = (8 * q + 2 * t) * kk;
      T.thr[q >> 1][tid][2 * (q & 1)] = pair_bits(cos_turn(m, 128), cos_turn(m + kk, 128));
      T.thr[q >> 1][tid][2 * (q & 1) + 1] = pair_bits(cos_turn(m + 32, 128), cos_turn(m + kk + 32, 128));
      T.thr[2][tid][q] = pair_h(cos_turn(m, 4096), cos_turn(m + kk, 4096));
      T.thr[3][tid][q] = pair_h(cos_turn(m + 3072, 4096), cos_turn(m + kk + 3072, 4096));
    }
  }
  return T;
}
__device__ const Tables d_tab = make_tables();

struct Params {
  const __nv_bfloat16 *logA, *Aim, *Cre, *Cim, *logdt;
  const Tables* tab;
  unsigned* cnt;
  const __nv_bfloat16 *Dskip, *shift_k, *ssm_D, *gate_w, *q, *v, *ssm_k;
  uint2* part;
  __nv_bfloat16* out;
  unsigned* tl;
  uint64_t dfwd, dinv, dlast, dk[5], dt[5], dx[5], dv[5];
  CUtensorMap tq, tk, tv, tkh;
};

__device__ uint2 g_part[(NCL + 1) * SEQ];
__device__ unsigned g_cnt[CS * 32];
#define TL(i) do {} while (0)
#define TL_INIT() do {} while (0)
#define TL_DUMP() do {} while (0)

__device__ __forceinline__ uint32_t lds16(uint32_t a) { uint32_t v; asm volatile("ld.shared.u16 %0, [%1];" : "=r"(v) : "r"(a) : "memory"); return v; }
__device__ __forceinline__ uint2 lds64(uint32_t a) { uint2 v; asm volatile("ld.shared.v2.u32 {%0,%1}, [%2];" : "=r"(v.x), "=r"(v.y) : "r"(a) : "memory"); return v; }
__device__ __forceinline__ uint4 lds128(uint32_t a) { uint4 v; asm volatile("ld.shared.v4.u32 {%0,%1,%2,%3}, [%4];" : "=r"(v.x), "=r"(v.y), "=r"(v.z), "=r"(v.w) : "r"(a) : "memory"); return v; }
__device__ __forceinline__ void sts16(uint32_t a, uint32_t v) { asm volatile("st.shared.u16 [%0], %1;" :: "r"(a), "r"(v) : "memory"); }
__device__ __forceinline__ void sts32(uint32_t a, uint32_t v) { asm volatile("st.shared.u32 [%0], %1;" :: "r"(a), "r"(v) : "memory"); }
__device__ __forceinline__ void sts64(uint32_t a, uint32_t x, uint32_t y) { asm volatile("st.shared.v2.u32 [%0], {%1,%2};" :: "r"(a), "r"(x), "r"(y) : "memory"); }
__device__ __forceinline__ void sts128(uint32_t a, uint32_t x, uint32_t y, uint32_t z, uint32_t w) { asm volatile("st.shared.v4.u32 [%0], {%1,%2,%3,%4};" :: "r"(a), "r"(x), "r"(y), "r"(z), "r"(w) : "memory"); }
__device__ __forceinline__ void ldsm4t(uint32_t (&r)[4], uint32_t a) { asm volatile("ldmatrix.sync.aligned.m8n8.x4.trans.shared.b16 {%0,%1,%2,%3}, [%4];" : "=r"(r[0]), "=r"(r[1]), "=r"(r[2]), "=r"(r[3]) : "r"(a) : "memory"); }
__device__ __forceinline__ void ldsm2t(uint32_t& r0, uint32_t& r1, uint32_t a) { asm volatile("ldmatrix.sync.aligned.m8n8.x2.trans.shared.b16 {%0,%1}, [%2];" : "=r"(r0), "=r"(r1) : "r"(a) : "memory"); }
__device__ __forceinline__ void ldsm4(uint32_t (&r)[4], uint32_t a) { asm volatile("ldmatrix.sync.aligned.m8n8.x4.shared.b16 {%0,%1,%2,%3}, [%4];" : "=r"(r[0]), "=r"(r[1]), "=r"(r[2]), "=r"(r[3]) : "r"(a) : "memory"); }
__device__ __forceinline__ void stsm4(uint32_t a, const uint32_t (&r)[4]) { asm volatile("stmatrix.sync.aligned.m8n8.x4.shared.b16 [%0], {%1,%2,%3,%4};" :: "r"(a), "r"(r[0]), "r"(r[1]), "r"(r[2]), "r"(r[3]) : "memory"); }
__device__ __forceinline__ uint32_t pack(float lo, float hi) { uint32_t r; asm("cvt.rn.bf16x2.f32 %0, %1, %2;" : "=r"(r) : "f"(hi), "f"(lo)); return r; }
__device__ __forceinline__ float blo(uint32_t v) { return __uint_as_float(v << 16); }
__device__ __forceinline__ float bhi(uint32_t v) { return __uint_as_float(v & 0xffff0000u); }
__device__ __forceinline__ float bf16r(float x) { return blo(pack(x, 0.f)); }
__device__ __forceinline__ uint32_t hmul2(uint32_t a, uint32_t b) { uint32_t r; asm("mul.rn.bf16x2 %0, %1, %2;" : "=r"(r) : "r"(a), "r"(b)); return r; }
__device__ __forceinline__ uint32_t hadd2(uint32_t a, uint32_t b) { uint32_t r; asm("add.rn.bf16x2 %0, %1, %2;" : "=r"(r) : "r"(a), "r"(b)); return r; }
__device__ __forceinline__ uint32_t hfma2(uint32_t a, uint32_t b, uint32_t c) { uint32_t r; asm("fma.rn.bf16x2 %0, %1, %2, %3;" : "=r"(r) : "r"(a), "r"(b), "r"(c)); return r; }
__device__ __forceinline__ uint32_t packh(float lo, float hi) { uint32_t r; asm("cvt.rn.f16x2.f32 %0, %1, %2;" : "=r"(r) : "f"(hi), "f"(lo)); return r; }
__device__ __forceinline__ __half2 H2(uint32_t a) { return *reinterpret_cast<__half2*>(&a); }
__device__ __forceinline__ uint32_t U2(__half2 a) { return *reinterpret_cast<uint32_t*>(&a); }
__device__ __forceinline__ uint32_t fmul(uint32_t a, uint32_t b) { return U2(__hmul2(H2(a), H2(b))); }
__device__ __forceinline__ uint32_t ffma(uint32_t a, uint32_t b, uint32_t c) { return U2(__hfma2(H2(a), H2(b), H2(c))); }
__device__ __forceinline__ uint32_t fneg(uint32_t a) { return U2(__hneg2(H2(a))); }
__device__ __forceinline__ uint32_t amax2(uint32_t a, uint32_t b) { uint32_t r; asm("max.xorsign.abs.bf16x2 %0, %1, %2;" : "=r"(r) : "r"(a), "r"(b)); return r; }
__device__ __forceinline__ uint32_t prmt(uint32_t a, uint32_t b, uint32_t s) { return __byte_perm(a, b, s); }
__device__ __forceinline__ uint32_t ldraw(const __nv_bfloat16* p) { uint32_t v; asm volatile("ld.global.nc.u16 %0, [%1];" : "=r"(v) : "l"(p)); return v; }
__device__ __forceinline__ uint4 ldg128(const void* p) { uint4 v; asm volatile("ld.global.nc.v4.u32 {%0,%1,%2,%3}, [%4];" : "=r"(v.x), "=r"(v.y), "=r"(v.z), "=r"(v.w) : "l"(p)); return v; }
__device__ __forceinline__ void bar_sync(int id, int n) { asm volatile("bar.sync %0, %1;" :: "r"(id), "r"(n) : "memory"); }
__device__ __forceinline__ void bar_arrive(int id, int n) { asm volatile("bar.arrive %0, %1;" :: "r"(id), "r"(n) : "memory"); }
__device__ __forceinline__ void cluster_arrive() { asm volatile("barrier.cluster.arrive.relaxed.aligned;" ::: "memory"); }
__device__ __forceinline__ void cluster_wait() { asm volatile("barrier.cluster.wait.aligned;" ::: "memory"); }
__device__ __forceinline__ void fence_async() { asm volatile("fence.proxy.async.shared::cta;" ::: "memory"); }
__device__ __forceinline__ void fence_mbinit() { asm volatile("fence.mbarrier_init.release.cluster;" ::: "memory"); }
__device__ __forceinline__ uint32_t mapa(uint32_t a, uint32_t rank) { uint32_t r; asm("mapa.shared::cluster.u32 %0, %1, %2;" : "=r"(r) : "r"(a), "r"(rank)); return r; }
__device__ __forceinline__ void bulk_dsmem(uint32_t dst, uint32_t src, uint32_t bytes, uint32_t mbar) {
  asm volatile("cp.async.bulk.shared::cluster.shared::cta.mbarrier::complete_tx::bytes [%0], [%1], %2, [%3];" :: "r"(dst), "r"(src), "r"(bytes), "r"(mbar) : "memory");
}
__device__ __forceinline__ void bulk_load(uint32_t dst, const void* src, uint32_t bytes, uint32_t mbar) {
  asm volatile("cp.async.bulk.shared::cluster.global.mbarrier::complete_tx::bytes [%0], [%1], %2, [%3];" :: "r"(dst), "l"(src), "r"(bytes), "r"(mbar) : "memory");
}
__device__ __forceinline__ void mbar_init(uint32_t m, uint32_t cnt) { asm volatile("mbarrier.init.shared::cta.b64 [%0], %1;" :: "r"(m), "r"(cnt) : "memory"); }
__device__ __forceinline__ void mbar_expect(uint32_t m, uint32_t bytes) { asm volatile("mbarrier.arrive.expect_tx.shared::cta.b64 _, [%0], %1;" :: "r"(m), "r"(bytes) : "memory"); }
__device__ __forceinline__ bool mbar_try(uint32_t m) {
  uint32_t done;
  asm volatile("{.reg .pred p; mbarrier.try_wait.parity.shared::cta.b64 p, [%1], 0; selp.u32 %0, 1, 0, p;}" : "=r"(done) : "r"(m) : "memory");
  return done;
}
__device__ __forceinline__ void mbar_wait(uint32_t m) {
  if (!mbar_try(m)) {
    int it = 0;
    while (!mbar_try(m) && ++it < (1 << 22)) {}
  }
}
__device__ __forceinline__ bool elect() {
  uint32_t e;
  asm volatile("{.reg .pred p; elect.sync _|p, 0xffffffff; selp.u32 %0, 1, 0, p;}" : "=r"(e));
  return e;
}
__device__ __forceinline__ void tma_load4(uint32_t dst, const CUtensorMap* tm, int c0, int c1, int c2, int c3, uint32_t mbar) {
  asm volatile("cp.async.bulk.tensor.4d.shared::cluster.global.mbarrier::complete_tx::bytes [%0], [%1, {%3, %4, %5, %6}], [%2];"
               :: "r"(dst), "l"(tm), "r"(mbar), "r"(c0), "r"(c1), "r"(c2), "r"(c3) : "memory");
}
__device__ __forceinline__ void tma_load3(uint32_t dst, const CUtensorMap* tm, int c0, int c1, int c2, uint32_t mbar) {
  asm volatile("cp.async.bulk.tensor.3d.shared::cluster.global.mbarrier::complete_tx::bytes [%0], [%1, {%3, %4, %5}], [%2];"
               :: "r"(dst), "l"(tm), "r"(mbar), "r"(c0), "r"(c1), "r"(c2) : "memory");
}
__device__ __forceinline__ void tma_store3(const CUtensorMap* tm, int c0, int c1, int c2, uint32_t src) {
  asm volatile("cp.async.bulk.tensor.3d.global.shared::cta.bulk_group [%0, {%2, %3, %4}], [%1];"
               :: "l"(tm), "r"(src), "r"(c0), "r"(c1), "r"(c2) : "memory");
}
__device__ __forceinline__ void mma1688(float (&c)[4], uint32_t a0, uint32_t a1, uint32_t b) {
  asm volatile("mma.sync.aligned.m16n8k8.row.col.f32.bf16.bf16.f32 {%0,%1,%2,%3}, {%4,%5}, {%6}, {%0,%1,%2,%3};"
               : "+f"(c[0]), "+f"(c[1]), "+f"(c[2]), "+f"(c[3]) : "r"(a0), "r"(a1), "r"(b));
}
__device__ __forceinline__ void wg_fence() { asm volatile("wgmma.fence.sync.aligned;" ::: "memory"); }
__device__ __forceinline__ void wg_commit() { asm volatile("wgmma.commit_group.sync.aligned;" ::: "memory"); }
template <int N> __device__ __forceinline__ void wg_wait() { asm volatile("wgmma.wait_group.sync.aligned %0;" :: "n"(N) : "memory"); }
template <int N> __device__ __forceinline__ void tie_all(uint32_t (&x)[N]) {
#pragma unroll
  for (int i = 0; i < N; i++) asm volatile("" : "+r"(x[i]) :: "memory");
}
template <int N> __device__ __forceinline__ void tie_all(float (&x)[N]) {
#pragma unroll
  for (int i = 0; i < N; i++) asm volatile("" : "+f"(x[i]) :: "memory");
}
#define R16(C, d) C(d[0]), C(d[1]), C(d[2]), C(d[3]), C(d[4]), C(d[5]), C(d[6]), C(d[7]), C(d[8]), C(d[9]), C(d[10]), C(d[11]), C(d[12]), C(d[13]), C(d[14]), C(d[15])
#define R32(C, d) R16(C, d), R16(C, (d + 16))
#define P16 "{%0,%1,%2,%3,%4,%5,%6,%7,%8,%9,%10,%11,%12,%13,%14,%15}"
#define P32 "{%0,%1,%2,%3,%4,%5,%6,%7,%8,%9,%10,%11,%12,%13,%14,%15,%16,%17,%18,%19,%20,%21,%22,%23,%24,%25,%26,%27,%28,%29,%30,%31}"
template <int SD, int OFF> __device__ __forceinline__ void rs64(float* d, const uint32_t* a, uint64_t db) {
  if (SD) asm volatile("{.reg .b64 db; add.s64 db, %36, %37; wgmma.mma_async.sync.aligned.m64n64k16.f32.bf16.bf16 " P32 ", {%32,%33,%34,%35}, db, 1, 1, 1, 1;}"
                       : R32("+f", d) : "r"(a[0]), "r"(a[1]), "r"(a[2]), "r"(a[3]), "l"(db), "n"(OFF));
  else asm volatile("{.reg .b64 db; add.s64 db, %36, %37; wgmma.mma_async.sync.aligned.m64n64k16.f32.bf16.bf16 " P32 ", {%32,%33,%34,%35}, db, 0, 1, 1, 1;}"
                    : R32("=f", d) : "r"(a[0]), "r"(a[1]), "r"(a[2]), "r"(a[3]), "l"(db), "n"(OFF));
}
template <int SD, int TB, int OFF> __device__ __forceinline__ void rs64h(uint32_t* d, const uint32_t* a, uint64_t db) {
  if (SD) asm volatile("{.reg .b64 db; add.s64 db, %20, %21; wgmma.mma_async.sync.aligned.m64n64k16.f16.f16.f16 " P16 ", {%16,%17,%18,%19}, db, 1, 1, 1, %22;}"
                       : R16("+r", d) : "r"(a[0]), "r"(a[1]), "r"(a[2]), "r"(a[3]), "l"(db), "n"(OFF), "n"(TB));
  else asm volatile("{.reg .b64 db; add.s64 db, %20, %21; wgmma.mma_async.sync.aligned.m64n64k16.f16.f16.f16 " P16 ", {%16,%17,%18,%19}, db, 0, 1, 1, %22;}"
                    : R16("=r", d) : "r"(a[0]), "r"(a[1]), "r"(a[2]), "r"(a[3]), "l"(db), "n"(OFF), "n"(TB));
}
template <int SD, int OFFA, int OFFB> __device__ __forceinline__ void ss32(float* d, uint64_t da, uint64_t db) {
  if (SD) asm volatile("{.reg .b64 da, db; add.s64 da, %16, %18; add.s64 db, %17, %19; wgmma.mma_async.sync.aligned.m64n32k16.f32.f16.f16 " P16 ", da, db, 1, 1, 1, 1, 1;}"
                       : R16("+f", d) : "l"(da), "l"(db), "n"(OFFA), "n"(OFFB));
  else asm volatile("{.reg .b64 da, db; add.s64 da, %16, %18; add.s64 db, %17, %19; wgmma.mma_async.sync.aligned.m64n32k16.f32.f16.f16 " P16 ", da, db, 0, 1, 1, 1, 1;}"
                    : R16("=f", d) : "l"(da), "l"(db), "n"(OFFA), "n"(OFFB));
}
#define KGEN_ASM(SD) "{.reg .b64 da, db; add.s64 da, %32, %33; add.s64 db, %32, %34;\n" \
  "wgmma.mma_async.sync.aligned.m64n64k16.f32.bf16.bf16 " P32 ", da, db, " SD ", 1, 1, 1, 1;}"
template <int KS> __device__ __forceinline__ void kgen_mma(float (&c)[32], uint64_t da) {
  if (KS) asm volatile(KGEN_ASM("1") : R32("+f", c) : "l"(da), "n"(8 * KS), "n"(8 * KS + 512));
  else asm volatile(KGEN_ASM("0") : R32("=f", c) : "l"(da), "n"(8 * KS), "n"(8 * KS + 512));
  if constexpr (KS < 7) kgen_mma<KS + 1>(c, da);
}
template <int OFF, int KSTEP> __device__ __forceinline__ void stage1(float (&D)[32], const uint32_t (&A1)[8], uint64_t d) {
  rs64<0, OFF>(D, A1, d); rs64<1, OFF + KSTEP>(D, A1 + 4, d);
}
template <int INV> __device__ __forceinline__ void stage2(uint32_t (&X)[16], const uint32_t (&F)[16], uint64_t dc) {
  constexpr int KS = INV ? 16 : 128, TB = INV ? 0 : 1;
  rs64h<0, TB, 0>(X, F, dc); rs64h<1, TB, KS>(X, F + 4, dc); rs64h<1, TB, 2 * KS>(X, F + 8, dc); rs64h<1, TB, 3 * KS>(X, F + 12, dc);
}
__device__ __forceinline__ void fwd_mid(uint32_t (&F)[16], const float (&D)[32], const uint32_t (&tc)[4], const uint32_t (&ts)[4]) {
#pragma unroll
  for (int j = 0; j < 4; j++)
#pragma unroll
    for (int b = 0; b < 2; b++) {
      const int i = 4 * j + 16 * b;
      const uint32_t ar = packh(D[i], D[i + 1]), ai = packh(D[i + 2], D[i + 3]);
      F[2 * j + b] = ffma(ar, tc[j], fmul(ai, ts[j]));
      F[8 + 2 * j + b] = ffma(ai, tc[j], fneg(fmul(ar, ts[j])));
    }
}
__device__ __forceinline__ void put_exp(uint32_t a, uint32_t m, int lane) {
  m = __reduce_max_sync(0xffffffffu, max(m & 0x7f80u, (m >> 16) & 0x7f80u));
  if (lane == 0) sts32(a, m);
}
__device__ __forceinline__ uint32_t get_exp(uint32_t a) { const uint4 v = lds128(a); return max(max(v.x, v.y), max(v.z, v.w)) >> 7; }
__device__ __forceinline__ void scale_a1(uint32_t (&As)[8], const uint32_t (&A1)[8], uint32_t field) {
#pragma unroll
  for (int i = 0; i < 8; i++) As[i] = hmul2(A1[i], field * 0x00800080u);
}

struct cf { float x, y; };
__device__ __forceinline__ cf cmul(cf a, cf b) { cf r; r.x = fmaf(a.x, b.x, -a.y * b.y); r.y = fmaf(a.x, b.y, a.y * b.x); return r; }
__device__ __forceinline__ cf cexp_p(float lr2, float lt, float p) {
  float m;
  asm("ex2.approx.ftz.f32 %0, %1;" : "=f"(m) : "f"(lr2 * p));
  float t = lt * p;
  t = (t - rintf(t)) * 6.283185307179586f;
  cf r; r.x = m * __cosf(t); r.y = m * __sinf(t); return r;
}
__device__ __forceinline__ void store8(uint32_t a, uint32_t b, const cf (&v)[8]) {
  sts128(a, pack(v[0].x, v[1].x), pack(v[2].x, v[3].x), pack(v[4].x, v[5].x), pack(v[6].x, v[7].x));
  sts128(b, pack(v[0].y, v[1].y), pack(v[2].y, v[3].y), pack(v[4].y, v[5].y), pack(v[6].y, v[7].y));
}
__device__ __forceinline__ void mbar_arrive(uint32_t m) { asm volatile("mbarrier.arrive.shared::cta.b64 _, [%0];" :: "r"(m) : "memory"); }
__device__ __forceinline__ float sigmoidf_(float s) { return __fdividef(1.f, 1.f + __expf(fminf(-s, 80.f))); }

__global__ void __cluster_dims__(CS, 1, 1) __launch_bounds__(NTHREADS, 1) fused_kernel(const __grid_constant__ Params p) {
  extern __shared__ __align__(1024) uint8_t smem[];
  TL_INIT();
  TL(31);
  const int wid = __shfl_sync(0xffffffffu, threadIdx.x >> 5, 0);
  const uint32_t sb = (uint32_t)__cvta_generic_to_shared(smem);
  const uint32_t mb = sb + OFF_MB;
  const int u = wid >> 2, w = wid & 3;
  const int tid = threadIdx.x & 127, lane = tid & 31, g = lane >> 2, t = lane & 3;
  const int cl = blockIdx.x >> 3, rank = blockIdx.x & 7;
  const int ch0 = cl * CPC;
  const int nu = min(5, (DCH - ch0) >> 3);
  const bool act = u < nu;

  uint32_t pla, pai, pcr, pci, pdt, tag = 0;
  auto load_params = [&]() {
    const int ch = act ? ch0 + 8 * u + rank : 0, o = ch * NMODE + tid;
    pla = ldraw(p.logA + o); pdt = ldraw(p.logdt + ch); pai = ldraw(p.Aim + o); pcr = ldraw(p.Cre + o); pci = ldraw(p.Cim + o);
  };
  if (u == 4) {
    const bool e = elect();
    if (e) {
#pragma unroll
      for (int i = 0; i < 5; i++) mbar_init(mb + 40 * w + 8 * i, 1);
      if (w == 3) { mbar_init(mb + 8 * MB_XQ, 1); mbar_init(mb + 8 * MB_KV, 1); }
      if (w == 2) mbar_init(mb + 8 * MB_G, 8);
      fence_mbinit();
      if ((sb & 0xffffffu) != SB0) __trap();
    }
    __syncwarp();
    load_params();
    if (w == 0 && lane < 2) asm volatile("atom.relaxed.gpu.global.add.u32 %0, [%1], %2;" : "=r"(tag) : "l"(&p.cnt[rank * 32 + lane]), "r"(cl == 0 ? 16 - (NCL - 1) : 1) : "memory");
    if (e) {
      if (w == 3) {
        mbar_expect(mb + 8 * MB_XQ, 20480 + 20480 + 112 * nu);
        bulk_load(sb + OFF_SP, p.gate_w + ch0, 16 * nu, mb + 8 * MB_XQ);
        bulk_load(sb + OFF_SP + 80, p.Dskip + ch0, 16 * nu, mb + 8 * MB_XQ);
        bulk_load(sb + OFF_SP + 160, p.ssm_D + ch0, 16 * nu, mb + 8 * MB_XQ);
        bulk_load(sb + OFF_SP + 240, p.shift_k + 4 * ch0, 64 * nu, mb + 8 * MB_XQ);
        tma_load3(sb + OFF_TQ, &p.tq, ch0, 8 * rank, 0, mb + 8 * MB_XQ);
        bulk_load(sb + OFF_CF, p.tab, 20480, mb + 8 * MB_XQ);
        TL(20);
        mbar_expect(mb + 8 * MB_KV, 2 * 20480 + 320);
        tma_load3(sb + OFF_TK, &p.tk, ch0, 8 * rank, 0, mb + 8 * MB_KV);
        tma_load3(sb + OFF_HALO, &p.tkh, ch0, 8 * rank - 1, 28, mb + 8 * MB_KV);
      }
#pragma unroll
      for (int i = 0; i < 5; i++) mbar_expect(mb + 40 * w + 8 * i, w == 3 ? 4096 : w == 2 ? 7168 : 7 * YP);
    }
    __syncwarp();
  } else {
    load_params();
  }
  cluster_arrive();
  TL(0);

  const uint32_t tab = sb + OFF_T + u * KTAB;
  const uint32_t toff = (64 * w + lane) * 80 + 16 * u;
  const int uown = u * USZ + (rank & 3) * UGRP + (rank >> 2) * YP;
  auto put = [&](int stage, const uint32_t (&a)[4], const uint32_t (&b)[4]) {
    const uint32_t o = sb + (g == rank ? OFF_U + uown : stage + (8 * u + g) * YP);
    const uint32_t od = o + (rank < 4 ? 16 : 0) + 128 * w + 32 * t;
    sts128(od, prmt(a[0], a[1], 0x5410), prmt(a[2], a[3], 0x5410), prmt(b[0], b[1], 0x5410), prmt(b[2], b[3], 0x5410));
    sts128(od + 16, prmt(a[0], a[1], 0x7632), prmt(a[2], a[3], 0x7632), prmt(b[0], b[1], 0x7632), prmt(b[2], b[3], 0x7632));
    const uint32_t m = amax2(amax2(amax2(a[0], a[1]), amax2(a[2], a[3])), amax2(amax2(b[0], b[1]), amax2(b[2], b[3])));
    asm volatile("st.shared.u8 [%0], %1;" :: "r"(o + (rank < 4 ? 0 : 512) + 4 * w + t), "r"(amax2(m, m >> 16) >> 7) : "memory");
  };
  const int d0 = rank ^ (2 * w), d1 = d0 ^ 1;
  const uint32_t rb0 = mapa(sb, d0), rb1 = mapa(sb, d1);
  auto send = [&](int stage, int bytes, int dst, int mbar) {
    if (elect()) {
      if (w) bulk_dsmem(rb0 + dst, sb + stage + d0 * bytes, bytes, rb0 + mbar);
      bulk_dsmem(rb1 + dst, sb + stage + d1 * bytes, bytes, rb1 + mbar);
    }
    __syncwarp();
  };

  uint32_t A1[8], tc[4], ts[4];
  {
    const float dt = bf16r(expf(blo(pdt)));
    const float lr2 = (-bf16r(expf(blo(pla))) * dt) * 1.4426950408889634f;
    const float lt = (blo(pai) * dt) * 0.15915494309189535f;
    const uint32_t tim = sb + (u ? OFF_IM + (u - 1) * KTAB : OFF_U);
    const uint32_t row = tab + tid * 16, rim = tim + tid * 16;
    const cf w1 = cexp_p(lr2, lt, 8.f);
    cf z1 = cexp_p(lr2, lt, 1.f), Z = cexp_p(lr2, lt, 256.f);
    if (lr2 != 123.f) TL(16);
    TL(12);
    {
      cf v[8];
      v[0].x = 1.f; v[0].y = 0.f; v[1] = w1; v[2] = cmul(w1, w1); v[3] = cmul(v[2], w1);
      const cf w4 = cmul(v[2], v[2]);
      v[4] = w4; v[5] = cmul(v[1], w4); v[6] = cmul(v[2], w4); v[7] = cmul(v[3], w4);
      const cf w8 = cmul(w4, w4);
      store8(row, rim, v);
#pragma unroll
      for (int k = 1; k < 4; k++) {
#pragma unroll
        for (int i = 0; i < 8; i++) v[i] = (k == 1 && i == 0) ? w8 : cmul(v[i], w8);
        store8(row + 2048 * k, rim + 2048 * k, v);
      }
    }
    if (STAGGER && STMID && u < 5 - STW) bar_arrive(NB_ST + u, 256);
    if (PREFETCH && wid == 8 && elect()) {
      const uint32_t o = blockIdx.x * 9856u, n = min(9856u, SEQ * DCH - o) * 2;
      asm volatile("cp.async.bulk.prefetch.L2.global [%0], %1;" :: "l"(p.v + o), "r"(n) : "memory");
      asm volatile("cp.async.bulk.prefetch.L2.global [%0], %1;" :: "l"(p.ssm_k + o), "r"(n) : "memory");
    }
    __syncwarp();
    if (u == 1) {
      float z0_ = 0.f, z1_ = 0.f, z2_ = 0.f, z3_ = 0.f;
      asm volatile("mma.sync.aligned.m16n8k8.row.col.f32.bf16.bf16.f32 {%0,%1,%2,%3}, {%4,%4}, {%4}, {%0,%1,%2,%3};"
                   : "+f"(z0_), "+f"(z1_), "+f"(z2_), "+f"(z3_) : "r"(pla >> 16));
      pcr += __float_as_uint(z0_);
      TL(8);
    }
    {
      z1.y = -z1.y; Z.y = -Z.y;
      const cf z2 = cmul(z1, z1);
      cf h[8], v[8];
      h[0].x = 2.f * blo(pcr) * dt; h[0].y = -2.f * blo(pci) * dt;
      h[1] = cmul(h[0], z1);
#pragma unroll
      for (int i = 2; i < 8; i++) h[i] = cmul(h[i - 2], z2);
      store8(row + 4 * 2048, rim + 4 * 2048, h);
      const cf h8 = cmul(h[6], z2);
      v[0] = cmul(h[0], Z); v[2] = cmul(h[2], Z); v[3] = cmul(h[4], Z); v[6] = cmul(h[6], Z); v[7] = cmul(h8, Z);
      v[1] = v[0]; v[4] = v[5] = v[3];
      store8(row + 5 * 2048, rim + 5 * 2048, v);
      h[0] = cmul(v[0], Z); h[1] = cmul(v[3], Z); h[3] = cmul(v[7], Z); h[4] = cmul(h[0], Z); h[5] = cmul(h[1], Z); h[7] = cmul(h[3], Z);
      h[2] = h[1]; h[6] = h[5];
      store8(row + 6 * 2048, rim + 6 * 2048, h);
      const cf Z2 = cmul(Z, Z);
      v[0] = cmul(h[0], Z2); v[1] = cmul(h[3], Z2); v[2] = cmul(h[4], Z2); v[3] = cmul(h[7], Z2);
#pragma unroll
      for (int i = 4; i < 8; i++) v[i] = cmul(v[i - 4], Z2);
      store8(row + 7 * 2048, rim + 7 * 2048, v);
    }
    TL(17);
    if (wid == 16 && lane == 0) sts32(mb + 8 * MB_TAG, tag);
    cluster_wait();
    if (u >= 2) cluster_arrive();
    fence_async();
    if (u) bar_sync(NB_ORD + u - 1, 256); else bar_sync(NB_WG0, 128);
    TL(13);
    float c[32];
    wg_fence();
    kgen_mma<0>(c, p.dk[u]);
    wg_commit();
    if (u < 4) bar_arrive(NB_ORD + u, 256);
    TL(14);
    mbar_wait(mb + 8 * MB_XQ);
    TL(18);
    uint32_t x0[4], x1[4];
    ldsm4t(x0, sb + OFF_TQ + toff);
    ldsm4t(x1, sb + OFF_TQ + toff + 2560);
    {
      const uint4 x = lds128(sb + OFF_TH + 16 * tid), y = lds128(sb + OFF_TH + 2048 + 16 * tid), a = lds128(sb + OFF_TH + 4096 + 16 * tid), b = lds128(sb + OFF_TH + 6144 + 16 * tid);
      A1[0] = x.x; A1[1] = x.y; A1[2] = x.z; A1[3] = x.w; A1[4] = y.x; A1[5] = y.y; A1[6] = y.z; A1[7] = y.w;
      tc[0] = a.x; tc[1] = a.y; tc[2] = a.z; tc[3] = a.w; ts[0] = b.x; ts[1] = b.y; ts[2] = b.z; ts[3] = b.w;
    }
    wg_wait<0>(); tie_all(c);
    TL(26);
    if (u < 2) cluster_arrive();
    bar_sync(u >= 3 ? NB_V + u - 3 : NB_WG0 + u, u >= 3 ? 256 : 128);
    if ((u & 6) == 2) bar_arrive(NB_V + u - 2, 256);
    const uint32_t k0 = pack(c[0] + c[6], c[1] + c[7]), k1 = pack(c[8] + c[14], c[9] + c[15]);
    const uint32_t k2 = pack(c[16] + c[22], c[17] + c[23]), k3 = pack(c[24] + c[30], c[25] + c[31]);
    const uint32_t ka = tab + 16 * (8 * w + (g ^ w));
    sts32(ka + 4 * t, k0);
    sts32(ka + 512 + 4 * t, k1);
    sts64(ka + 1024 + 512 * (t >> 1) + 8 * (t & 1), prmt(k2, 0, 0x1010), (t & 1) ? prmt(k2, 0, 0x3232) : k2);
    const uint32_t lo = prmt(k3, 0, 0x1010), hi = prmt(k3, 0, 0x3232);
    sts128(ka + 2048 + 512 * t, lo, lo, (g & 1) ? hi : k3, hi);
    put_exp(sb + OFF_MX + u * 32 + 4 * w, amax2(amax2(k0, k1), amax2(k2, k3)), lane);
    cluster_wait();
    put(OFF_YB, x0, x1);
    TL(15);
    fence_async();
    bar_sync(NB_WG0 + u, 128);
    send(OFF_YB + 8 * u * YP, YP, OFF_U + uown, OFF_MB + 8 * (MB_UX + u));
    if (wid == 16 && elect()) tma_load3(sb + OFF_TV, &p.tv, ch0, 8 * rank, 0, mb + 8 * MB_KV);
    __syncwarp();
  }
  if (u == 0) {
    float ga[4][4];
#pragma unroll
    for (int i = 0; i < 4; i++) ga[i][0] = ga[i][1] = ga[i][2] = ga[i][3] = 0.f;
#pragma unroll
    for (int j = 0; j < 5; j++) {
      uint32_t a0[4], a1[4], b;
      ldsm4(a0, sb + OFF_TQ + toff + 16 * j);
      ldsm4(a1, sb + OFF_TQ + toff + 2560 + 16 * j);
      asm volatile("ld.shared.u32 %0, [%1];" : "=r"(b) : "r"(sb + OFF_SP + 16 * j + 4 * t) : "memory");
      if (j >= 2 && j >= nu) b = 0;
      mma1688(ga[0], a0[0], a0[1], b); mma1688(ga[1], a0[2], a0[3], b); mma1688(ga[2], a1[0], a1[1], b); mma1688(ga[3], a1[2], a1[3], b);
    }
    const float s0 = t == 0 ? ga[0][0] : t == 1 ? ga[1][0] : t == 2 ? ga[2][0] : ga[3][0];
    const float s1 = t == 0 ? ga[0][2] : t == 1 ? ga[1][2] : t == 2 ? ga[2][2] : ga[3][2];
    tag = (lds64(mb + 8 * MB_TAG).x >> 4) + 1;
    uint2* gp = p.part + cl * SEQ + rank * 256 + 64 * w + 16 * t + g;
    asm volatile("st.relaxed.gpu.global.u64 [%0], %1;" :: "l"(gp), "l"(((uint64_t)tag << 32) | __float_as_uint(s0)) : "memory");
    asm volatile("st.relaxed.gpu.global.u64 [%0], %1;" :: "l"(gp + 8), "l"(((uint64_t)tag << 32) | __float_as_uint(s1)) : "memory");
  }

#pragma unroll
  for (int isA = 0; isA < 2; isA++) {
    {
      TL(1 + isA);
      const uint32_t mxa = sb + OFF_MX + u * 32 + 16 * isA;
      const uint32_t pd = lds16(sb + OFF_SP + 80 + 80 * isA + 16 * u + 2 * rank);
      float D[32];
      uint32_t As[8], F[16], H[16], X[16];
      const uint32_t eh = min(max((int)get_exp(mxa), (int)((pd >> 7) & 0xff) - 5), 240);
      scale_a1(As, A1, 248 - eh);
      wg_fence();
      if (isA) stage1<T_HA / 16, 64>(D, As, p.dt[u]); else stage1<0, 64>(D, As, p.dt[u]);
      wg_commit();
      wg_wait<0>(); tie_all(D);
      fwd_mid(F, D, tc, ts);
      wg_fence();
      stage2<0>(H, F, p.dfwd);
      wg_commit();
      if (!isA) {
        if (w == 2 && elect()) bulk_load(tab + T_HA, p.ssm_k + (size_t)(act ? ch0 + 8 * u + rank : 0) * SEQ, 4096, mb + 8 * (MB_HA + u));
        __syncwarp();
        TL(7);
      }
      if (isA) {
        fence_async();
        bar_sync(NB_WG0 + u, 128);
        send(OFF_T + u * KTAB + T_YS, 512, OFF_YB + (8 * u + rank) * YP, OFF_MB + 8 * (MB_Y + u));
      }
      mbar_wait(mb + 8 * ((isA ? MB_UKV : MB_UX) + u));
      TL(5 + isA);
      uint32_t eu;
      asm volatile("ld.shared.u32 %0, [%1];" : "=r"(eu) : "r"(sb + OFF_U + u * USZ + (lane >> 3) * UGRP + ((lane & 4) ? UGRP - 16 : 0) + 4 * t) : "memory");
      eu = __vmaxu2(eu & 0x00ff00ffu, (eu >> 8) & 0x00ff00ffu);
      eu = min(__reduce_max_sync(0xffffffffu, max(eu & 0xffffu, eu >> 16)), 240u);
      scale_a1(As, A1, 250 - eu);
      wg_wait<0>(); tie_all(H);
      wg_fence();
      stage1<0, 2 * UGRP / 16>(D, As, p.dx[u]);
      wg_commit();
      wg_wait<0>(); tie_all(D);
      if (!isA) cluster_arrive();
      fwd_mid(F, D, tc, ts);
      wg_fence();
      stage2<0>(X, F, p.dfwd);
      wg_commit();
      {
        const float dsk = blo(pd) * __uint_as_float((248 - eh) << 23);
        const uint32_t d2 = packh(dsk, dsk);
#pragma unroll
        for (int j = 0; j < 4; j++) H[2 * j] = U2(__hadd2(H2(H[2 * j]), H2(d2)));
      }
      wg_wait<0>(); tie_all(X);
#pragma unroll
      for (int j = 0; j < 4; j++) {
        const uint32_t h0r = H[2 * j], h1r = H[2 * j + 1], h0i = H[8 + 2 * j], h1i = H[9 + 2 * j];
        const uint32_t x0r = X[2 * j], x1r = X[2 * j + 1], x0i = X[8 + 2 * j], x1i = X[9 + 2 * j];
        F[2 * j] = ffma(x0r, h0r, fneg(fmul(x0i, h0i)));
        F[8 + 2 * j] = ffma(x0r, h0i, fmul(x0i, h0r));
        F[2 * j + 1] = ffma(x1r, h0r, ffma(fneg(x1i), h0i, ffma(x0r, h1r, fneg(ffma(x0i, h1i, F[8 + 2 * j])))));
        F[9 + 2 * j] = ffma(x1r, h0i, ffma(x1i, h0r, ffma(x0r, h1i, ffma(x0i, h1r, F[2 * j]))));
      }
      wg_fence();
      stage2<1>(H, F, p.dinv);
      wg_commit();
      uint64_t ga[4];
      const int sl2 = min(18 * cl + min(8 * w + g, 17), 255), sl3 = tid + 128 * (u & 1);
      auto gload = [&]() {
        if (isA) {
          asm volatile("ld.relaxed.gpu.global.u64 %0, [%1];" : "=l"(ga[0]) : "l"(p.part + NCL * SEQ + rank * 256 + sl3) : "memory");
        } else {
#pragma unroll
          for (int k = 0; k < 4; k++)
            asm volatile("ld.relaxed.gpu.global.u64 %0, [%1];" : "=l"(ga[k]) : "l"(p.part + (t + (k == 3 && t == 3 ? 8 : 4 * k)) * SEQ + rank * 256 + sl2) : "memory");
        }
      };
      if (isA ? (u & 6) == 2 : u == 1) gload();
      if (isA) TL(23);
      wg_wait<0>(); tie_all(H);
      {
        const uint32_t va = tab + (16 * w + (lane & 15)) * 128;
        const int vx = (lane >> 4) ^ (lane & 7);
#pragma unroll
        for (int j = 0; j < 4; j++) {
          uint32_t V[4];
#pragma unroll
          for (int b = 0; b < 2; b++) {
            const uint32_t er = H[2 * j + b], ei = H[8 + 2 * j + b];
            V[2 * b] = ffma(er, tc[j], fneg(fmul(ei, ts[j])));
            V[2 * b + 1] = ffma(ei, tc[j], fmul(er, ts[j]));
          }
          stsm4(va + ((vx ^ (2 * j)) << 4), V);
        }
      }
      if (!isA) {
        cluster_wait();
        mbar_wait(mb + 8 * MB_KV);
        TL(21);
        uint32_t K[3][4], V[2][4];
        const uint2 psw = lds64(sb + OFF_SP + 240 + 64 * u + 8 * g);
        ldsm4t(K[0], w ? sb + OFF_TK + toff - 2560 : (lane & 7) ? sb + OFF_TK + toff + 223 * 80 : sb + OFF_HALO + 10 * lane + 16 * u);
        ldsm4t(K[1], sb + OFF_TK + toff);
        ldsm4t(K[2], sb + OFF_TK + toff + 2560);
        ldsm4t(V[0], sb + OFF_TV + toff);
        ldsm4t(V[1], sb + OFF_TV + toff + 2560);
        mbar_wait(mb + 8 * (MB_HA + u));
        const uint4 hx = lds128(tab + T_HA + 16 * tid), hy = lds128(tab + T_HA + 2048 + 16 * tid);
        const uint32_t w0 = prmt(psw.x, 0, 0x1010), w1 = prmt(psw.x, 0, 0x3232), w2 = prmt(psw.y, 0, 0x1010), w3 = prmt(psw.y, 0, 0x3232);
#pragma unroll
        for (int m = 4; m < 12; m++)
          V[(m >> 2) - 1][m & 3] = hmul2(hfma2(K[m >> 2][m & 3], w0, hfma2(K[(m - 1) >> 2][(m - 1) & 3], w1,
                                         hfma2(K[(m - 2) >> 2][(m - 2) & 3], w2, hmul2(K[(m - 3) >> 2][(m - 3) & 3], w3)))), V[(m >> 2) - 1][m & 3]);
        put(OFF_YA, V[0], V[1]);
        put_exp(mxa + 16 + 4 * w, amax2(amax2(amax2(hx.x, hx.y), amax2(hx.z, hx.w)), amax2(amax2(hy.x, hy.y), amax2(hy.z, hy.w))), lane);
        sts128(tab + T_HA + 16 * (tid ^ (lane >> 3)), hx.x, hx.y, hx.z, hx.w);
        sts128(tab + T_HA + 2048 + 16 * (tid ^ (lane >> 3)), hy.x, hy.y, hy.z, hy.w);
        TL(22);
      }
      fence_async();
      bar_sync(NB_WG0 + u, 128);
      float O[16];
      {
        const uint64_t dv = p.dv[u], dl = p.dlast;
        wg_fence();
        ss32<0, 0, 0>(O, dv, dl); ss32<1, 128, 64>(O, dv, dl); ss32<1, 256, 128>(O, dv, dl); ss32<1, 384, 192>(O, dv, dl);
        wg_commit();
      }
      if (!isA) send(OFF_YA + 8 * u * YP, YP, OFF_U + uown, OFF_MB + 8 * (MB_UKV + u));
      if (isA ? (u & 6) == 2 : u == 1) {
        tag = (lds64(mb + 8 * MB_TAG).x >> 4) + 1;
        bool ok;
#pragma unroll 1
        for (int it = 0;; it++) {
          ok = (uint32_t)(ga[0] >> 32) == tag;
          if (!isA) ok = ok && (uint32_t)(ga[1] >> 32) == tag && (uint32_t)(ga[2] >> 32) == tag && (uint32_t)(ga[3] >> 32) == tag;
          ok = __all_sync(0xffffffffu, ok);
          if (ok || it == (isA ? 8000 : 2000)) break;
          gload();
        }
        if (!isA) {
          float s = __uint_as_float((uint32_t)ga[0]) + __uint_as_float((uint32_t)ga[1]) + __uint_as_float((uint32_t)ga[2]);
          if (t < 3) s += __uint_as_float((uint32_t)ga[3]);
          s += __shfl_xor_sync(0xffffffffu, s, 1);
          s += __shfl_xor_sync(0xffffffffu, s, 2);
          const float g0 = bf16r(sigmoidf_(bf16r(s)));
          if (ok && t == 0)
            asm volatile("st.relaxed.gpu.global.u64 [%0], %1;" :: "l"(p.part + NCL * SEQ + rank * 256 + sl2), "l"(((uint64_t)tag << 32) | pack(g0, 1.f - g0)) : "memory");
        } else {
          uint32_t gv = (uint32_t)ga[0];
          if (!ok) {
            const uint32_t* xr = (const uint32_t*)(p.q + (size_t)(rank * 256 + 32 * (sl3 & 7) + (sl3 >> 3)) * DCH);
            const uint32_t* gr = (const uint32_t*)p.gate_w;
            float s = 0.f;
#pragma unroll 1
            for (int k = 0; k < DCH / 2; k++) { const uint32_t x = __ldg(xr + k), y = __ldg(gr + k); s = fmaf(blo(x), blo(y), fmaf(bhi(x), bhi(y), s)); }
            const float g0 = bf16r(sigmoidf_(bf16r(s)));
            gv = pack(g0, 1.f - g0);
          }
          sts64(sb + OFF_GB + 8 * sl3, prmt(gv, 0, 0x1010), prmt(gv, 0, 0x3232));
          __syncwarp();
          if (lane == 0) mbar_arrive(mb + 8 * MB_G);
        }
      }
      if (isA) TL(28);
      wg_wait<0>(); tie_all(O);
      {
        const uint32_t co = ((8 * w + g) ^ (2 * t)) * 16, usrc = tab + (isA ? T_HA : T_YS);
        const int yo = (isA ? OFF_YA : OFF_YB) + (8 * u + rank) * YP, ym = OFF_MB + 8 * (MB_Y + u);
        const uint32_t us = min(max((int)(eu + eh) - 127, 0), 254) * 0x00800080u;
        const uint32_t a0 = hmul2(pack(O[0], O[1]), us), a1 = hmul2(pack(O[4], O[5]), us), a2 = hmul2(pack(O[8], O[9]), us), a3 = hmul2(pack(O[12], O[13]), us);
        const uint32_t b0 = hmul2(pack(O[2], O[3]), us), b1 = hmul2(pack(O[6], O[7]), us), b2 = hmul2(pack(O[10], O[11]), us), b3 = hmul2(pack(O[14], O[15]), us);
        sts128((t == rank ? sb + yo : usrc + t * 512) + co, a0, a1, a2, a3);
        sts128((t + 4 == rank ? sb + yo : usrc + t * 512 + 2048) + co, b0, b1, b2, b3);
        if (isA) {
          fence_async();
          bar_sync(NB_WG0 + u, 128);
          send(usrc - sb, 512, yo, ym);
        }
      }
      TL(9 + isA);
    }
  }

  {
    mbar_wait(mb + 8 * MB_G);
    uint2 gg[2][4];
    uint32_t qv[2][4];
#pragma unroll
    for (int hh = 0; hh < 2; hh++)
#pragma unroll
      for (int i = 0; i < 4; i++) gg[hh][i] = lds64(sb + OFF_GB + 8 * (64 * w + 32 * hh + 8 * i + g));
    const uint32_t qa = sb + OFF_TQ + toff;
    ldsm4(qv[0], qa);
    ldsm4(qv[1], qa + 2560);
    TL(24);
    mbar_wait(mb + 8 * (MB_Y + u));
    uint32_t ya[2][4], yb[2][4];
#pragma unroll
    for (int hh = 0; hh < 2; hh++) {
      const uint32_t yo = (8 * u + (lane & 7)) * YP + ((8 * w + 4 * hh + (lane >> 3)) ^ (2 * (rank & 3))) * 16;
      ldsm4t(ya[hh], sb + OFF_YA + yo); ldsm4t(yb[hh], sb + OFF_YB + yo);
    }
#pragma unroll
    for (int hh = 0; hh < 2; hh++) {
      uint32_t o[4];
#pragma unroll
      for (int i = 0; i < 4; i++) o[i] = hadd2(hmul2(gg[hh][i].x, hmul2(qv[hh][i], ya[hh][i])), hmul2(gg[hh][i].y, yb[hh][i]));
      stsm4(qa + 2560 * hh, o);
    }
    TL(25);
  }
  cluster_arrive();
  bar_sync(NB_ROW0 + w, 160);
  {
    uint4 v[2];
#pragma unroll
    for (int k = 0; k < 2; k++) {
      const int i = 64 * u + 32 * k + lane, sl = (i * 205) >> 10, cc = i - 5 * sl;
      v[k] = lds128(sb + OFF_TQ + (64 * w + 8 * (sl & 7) + (sl >> 3)) * 80 + cc * 16);
    }
#pragma unroll
    for (int k = 0; k < 2; k++) {
      const int i = 64 * u + 32 * k + lane, sl = (i * 205) >> 10, cc = i - 5 * sl;
      if (cc < nu)
        asm volatile("st.global.cg.v4.u32 [%0], {%1,%2,%3,%4};" :: "l"(p.out + (size_t)(256 * rank + 32 * (sl >> 3) + 8 * w + (sl & 7)) * DCH + ch0 + 8 * cc),
                     "r"(v[k].x), "r"(v[k].y), "r"(v[k].z), "r"(v[k].w) : "memory");
    }
  }
  cluster_wait();
  TL(27);
  TL_DUMP();
}

typedef CUresult (*EncodeFn)(CUtensorMap*, CUtensorMapDataType, cuuint32_t, void*, const cuuint64_t*, const cuuint64_t*,
                             const cuuint32_t*, const cuuint32_t*, CUtensorMapInterleave, CUtensorMapSwizzle,
                             CUtensorMapL2promotion, CUtensorMapFloatOOBfill);

void encode(EncodeFn fn, CUtensorMap* tm, const void* ptr, int nd, const cuuint64_t* dims, const cuuint64_t* strides,
            const cuuint32_t* box, CUtensorMapSwizzle swz) {
  cuuint32_t es[4] = {1, 1, 1, 1};
  fn(tm, CU_TENSOR_MAP_DATA_TYPE_BFLOAT16, nd, const_cast<void*>(ptr), dims, strides, box, es, CU_TENSOR_MAP_INTERLEAVE_NONE,
     swz, CU_TENSOR_MAP_L2_PROMOTION_L2_128B, CU_TENSOR_MAP_FLOAT_OOB_FILL_NONE);
}
void make_map(EncodeFn fn, CUtensorMap* tm, const void* ptr, int ne, int nr) {
  const cuuint64_t dims[3] = {DCH, SEQ / 32, 32}, strides[2] = {32 * DCH * 2, DCH * 2};
  const cuuint32_t box[3] = {CPC, (cuuint32_t)ne, (cuuint32_t)nr};
  encode(fn, tm, ptr, 3, dims, strides, box, CU_TENSOR_MAP_SWIZZLE_NONE);
}

}

extern "C" void kernel_launch(void* const* d_in, const int* in_sizes, int n_in, void* d_out, int out_size) {
  (void)in_sizes; (void)n_in; (void)out_size;
  static EncodeFn fn = nullptr;
  static void *tab = nullptr, *cnt = nullptr, *part = nullptr;
  if (!fn) {
    cudaGetSymbolAddress(&tab, d_tab);
    cudaGetSymbolAddress(&cnt, g_cnt);
    cudaGetSymbolAddress(&part, g_part);
    cudaDriverEntryPointQueryResult qr;
    cudaGetDriverEntryPoint("cuTensorMapEncodeTiled", (void**)&fn, cudaEnableDefault, &qr);
    cudaFuncSetAttribute(fused_kernel, cudaFuncAttributeMaxDynamicSharedMemorySize, SMEM_BYTES);
  }
  Params p;
  make_map(fn, &p.tq, d_in[0], 8, 32);
  make_map(fn, &p.tk, d_in[1], 8, 32);
  make_map(fn, &p.tv, d_in[2], 8, 32);
  make_map(fn, &p.tkh, d_in[1], 1, 4);
  p.out = (__nv_bfloat16*)d_out;
  p.dfwd = mkdesc(OFF_CF, 1024, 128, 0);
  p.dinv = mkdesc(OFF_CF, 128, 1024, 0);
  p.dlast = mkdesc(OFF_CL, 512, 128, 0);
  for (int u = 0; u < 5; u++) {
    p.dk[u] = mkdesc(OFF_T + u * KTAB, u ? OFF_IM - KTAB - OFF_T : OFF_U - OFF_T, 1024, 0);
    p.dt[u] = mkdesc(OFF_T + u * KTAB, 2048, 512, 2);
    p.dx[u] = mkdesc(OFF_U + u * USZ + 16, UGRP, 128, 0);
    p.dv[u] = mkdesc(OFF_T + u * KTAB, 16, 1024, 1);
  }
  p.tab = (const Tables*)tab;
  p.cnt = (unsigned*)cnt;
  p.part = (uint2*)part;
  p.tl = nullptr;
  p.q = (const __nv_bfloat16*)d_in[0];
  p.v = (const __nv_bfloat16*)d_in[2];
  p.ssm_k = (const __nv_bfloat16*)d_in[4];
  p.shift_k = (const __nv_bfloat16*)d_in[3];
  p.ssm_D = (const __nv_bfloat16*)d_in[5];
  p.logA = (const __nv_bfloat16*)d_in[7];
  p.Aim = (const __nv_bfloat16*)d_in[8];
  p.Cre = (const __nv_bfloat16*)d_in[9];
  p.Cim = (const __nv_bfloat16*)d_in[10];
  p.logdt = (const __nv_bfloat16*)d_in[11];
  p.Dskip = (const __nv_bfloat16*)d_in[12];
  p.gate_w = (const __nv_bfloat16*)d_in[13];
  fused_kernel<<<NCL * CS, NTHREADS, SMEM_BYTES, cudaStreamPerThread>>>(p);
}
```

```cpp
#include <cuda_runtime.h>
#include <cuda_bf16.h>
#include <cuda_fp16.h>
#include <cuda.h>
#include <stdint.h>

#define TIMELINE 0
#define STAGGER 0
#define PREFETCH 1
#define STW 2
#define STMID 0
#define TLHI 0

namespace {

constexpr int SEQ = 2048, DCH = 576, NMODE = 128;
constexpr int CS = 8, CPC = 40, NCL = 15, NTHREADS = 640;

constexpr int KTAB = 16384;
constexpr int OFF_T = 0;
constexpr int T_YS = 8192, T_HA = 12288;
constexpr int UGRP = 1056, USZ = 4 * UGRP, YP = 528;
constexpr int OFF_IM = 5 * KTAB;
constexpr int OFF_YB = OFF_IM;
constexpr int OFF_TV = OFF_YB + 40 * YP;
constexpr int OFF_YA = OFF_TV + 20480;
constexpr int OFF_GB = OFF_YA + 40 * YP;
constexpr int OFF_U = OFF_IM + 4 * KTAB;
constexpr int OFF_CF = OFF_U + 5 * USZ;
constexpr int OFF_CL = OFF_CF + 8192;
constexpr int OFF_TH = OFF_CL + 4096;
constexpr int OFF_TQ = OFF_TH + 8192;
constexpr int OFF_TK = OFF_TQ + 20480;
constexpr int OFF_HALO = OFF_TK + 20480;
constexpr int OFF_MX = OFF_HALO + 320;
constexpr int OFF_SP = OFF_MX + 160;
constexpr int OFF_MB = OFF_SP + 560;
constexpr int OFF_TL = OFF_MB + 28 * 8;
constexpr int SMEM_BYTES = OFF_TL + (TIMELINE ? 640 : 0);
static_assert(SMEM_BYTES <= 232448 && OFF_GB + 2048 <= OFF_U && (OFF_TV & 127) == 0 && (OFF_TQ & 127) == 0, "smem");
static_assert((OFF_MB & 7) == 0 && (OFF_MX & 15) == 0 && (OFF_SP & 15) == 0, "align");

enum { MB_UX = 0, MB_UKV = 5, MB_Y = 10, MB_HA = 15, MB_XQ = 20, MB_KV = 21, MB_CF = 22, MB_G = 23, MB_TH = 24, MB_TAG = 25 };
enum { NB_WG0 = 1, NB_ROW0 = 6, NB_ORD = 6, NB_V = 10, NB_ST = 12 };

constexpr uint32_t SB0 = 1024;
constexpr uint64_t mkdesc(uint32_t off, uint32_t lbo, uint32_t sbo, uint32_t swz) {
  return (uint64_t)((SB0 + off) >> 4) | ((uint64_t)(lbo >> 4) << 16) | ((uint64_t)(sbo >> 4) << 32) | ((uint64_t)swz << 62);
}

constexpr double cos_turn(int m, int n) {
  m &= n - 1;
  if (m > n / 2) m = n - m;
  double sgn = 1.0;
  if (m > n / 4) { m = n / 2 - m; sgn = -1.0; }
  if (m == n / 4) return 0.0;
  const double x = 6.283185307179586476925 * m / n;
  double term = 1.0, sum = 1.0;
  for (int k = 1; k < 14; k++) { term *= -x * x / ((2 * k - 1) * (2 * k)); sum += term; }
  return sgn * sum;
}
constexpr uint32_t bf16_bits(double v) {
  if (v == 0.0) return 0;
  uint32_t sgn = 0;
  if (v < 0) { sgn = 0x8000; v = -v; }
  int e = 127;
  while (v < 1.0) { v *= 2.0; e--; }
  while (v >= 2.0) { v *= 0.5; e++; }
  const double f = v * 128.0;
  int m = (int)f;
  if (f - m > 0.5 || (f - m == 0.5 && (m & 1))) m++;
  return sgn | (uint32_t)((e << 7) + (m - 128));
}
constexpr uint32_t f16_bits(double v) {
  if (v == 0.0) return 0;
  uint32_t sgn = 0;
  if (v < 0) { sgn = 0x8000; v = -v; }
  int e = 15;
  while (v < 1.0) { v *= 2.0; e--; }
  const double f = v * 1024.0;
  int m = (int)f;
  if (f - m > 0.5 || (f - m == 0.5 && (m & 1))) m++;
  return sgn | (uint32_t)((e << 10) + (m - 1024));
}
constexpr uint32_t pair_bits(double lo, double hi) { return bf16_bits(lo) | (bf16_bits(hi) << 16); }
constexpr uint32_t pair_h(double lo, double hi) { return f16_bits(lo) | (f16_bits(hi) << 16); }
struct alignas(128) Tables {
  uint32_t mat[3072];
  uint32_t thr[4][128][4];
};
constexpr Tables make_tables() {
  Tables T{};
  for (int q = 0; q < 768; q++) {
    int m0 = 0, d0 = 0, d1 = 0;
    if (q < 512) {
      const int r = (q >> 6) * 8 + (q & 7), cc = (q >> 3) & 7;
      d0 = 4 * (r & 31); d1 = 2 * d0;
      m0 = 8 * (cc & 3) * d0 + ((r >> 5) == (cc >> 2) ? 0 : (r >> 5) ? 96 : 32);
    } else {
      const int r = ((q - 512) >> 5) * 8 + (q & 7), pc = (q >> 3) & 3;
      d0 = 4 * (8 * (r >> 4) + (r & 7)) + 1; d1 = 8 * d0;
      m0 = 2 * pc * d0 + ((r & 8) ? 32 : 0);
    }
    for (int e = 0; e < 4; e++) T.mat[4 * q + e] = pair_h(cos_turn(m0 + e * d1, 128), cos_turn(m0 + e * d1 + d0, 128));
  }
  for (int tid = 0; tid < 128; tid++) {
    const int kk = 4 * (tid >> 2) + 1, t = tid & 3;
    for (int q = 0; q < 4; q++) {
      const int m = (8 * q + 2 * t) * kk;
      T.thr[q >> 1][tid][2 * (q & 1)] = pair_bits(cos_turn(m, 128), cos_turn(m + kk, 128));
      T.thr[q >> 1][tid][2 * (q & 1) + 1] = pair_bits(cos_turn(m + 32, 128), cos_turn(m + kk + 32, 128));
      T.thr[2][tid][q] = pair_h(cos_turn(m, 4096), cos_turn(m + kk, 4096));
      T.thr[3][tid][q] = pair_h(cos_turn(m + 3072, 4096), cos_turn(m + kk + 3072, 4096));
    }
  }
  return T;
}
__device__ const Tables d_tab = make_tables();

struct Params {
  const __nv_bfloat16 *logA, *Aim, *Cre, *Cim, *logdt;
  const Tables* tab;
  unsigned* cnt;
  const __nv_bfloat16 *Dskip, *shift_k, *ssm_D, *gate_w, *q, *v, *ssm_k;
  uint2* part;
  __nv_bfloat16* out;
  unsigned* tl;
  uint64_t dfwd, dinv, dlast, dk[5], dt[5], dx[5], dv[5];
  CUtensorMap tq, tk, tv, tkh;
};

__device__ uint2 g_part[(NCL + 1) * SEQ];
__device__ unsigned g_cnt[CS * 32];
#define TL(i) do {} while (0)
#define TL_INIT() do {} while (0)
#define TL_DUMP() do {} while (0)

__device__ __forceinline__ uint32_t lds16(uint32_t a) { uint32_t v; asm volatile("ld.shared.u16 %0, [%1];" : "=r"(v) : "r"(a) : "memory"); return v; }
__device__ __forceinline__ uint2 lds64(uint32_t a) { uint2 v; asm volatile("ld.shared.v2.u32 {%0,%1}, [%2];" : "=r"(v.x), "=r"(v.y) : "r"(a) : "memory"); return v; }
__device__ __forceinline__ uint4 lds128(uint32_t a) { uint4 v; asm volatile("ld.shared.v4.u32 {%0,%1,%2,%3}, [%4];" : "=r"(v.x), "=r"(v.y), "=r"(v.z), "=r"(v.w) : "r"(a) : "memory"); return v; }
__device__ __forceinline__ void sts16(uint32_t a, uint32_t v) { asm volatile("st.shared.u16 [%0], %1;" :: "r"(a), "r"(v) : "memory"); }
__device__ __forceinline__ void sts32(uint32_t a, uint32_t v) { asm volatile("st.shared.u32 [%0], %1;" :: "r"(a), "r"(v) : "memory"); }
__device__ __forceinline__ void sts64(uint32_t a, uint32_t x, uint32_t y) { asm volatile("st.shared.v2.u32 [%0], {%1,%2};" :: "r"(a), "r"(x), "r"(y) : "memory"); }
__device__ __forceinline__ void sts128(uint32_t a, uint32_t x, uint32_t y, uint32_t z, uint32_t w) { asm volatile("st.shared.v4.u32 [%0], {%1,%2,%3,%4};" :: "r"(a), "r"(x), "r"(y), "r"(z), "r"(w) : "memory"); }
__device__ __forceinline__ void ldsm4t(uint32_t (&r)[4], uint32_t a) { asm volatile("ldmatrix.sync.aligned.m8n8.x4.trans.shared.b16 {%0,%1,%2,%3}, [%4];" : "=r"(r[0]), "=r"(r[1]), "=r"(r[2]), "=r"(r[3]) : "r"(a) : "memory"); }
__device__ __forceinline__ void ldsm2t(uint32_t& r0, uint32_t& r1, uint32_t a) { asm volatile("ldmatrix.sync.aligned.m8n8.x2.trans.shared.b16 {%0,%1}, [%2];" : "=r"(r0), "=r"(r1) : "r"(a) : "memory"); }
__device__ __forceinline__ void ldsm4(uint32_t (&r)[4], uint32_t a) { asm volatile("ldmatrix.sync.aligned.m8n8.x4.shared.b16 {%0,%1,%2,%3}, [%4];" : "=r"(r[0]), "=r"(r[1]), "=r"(r[2]), "=r"(r[3]) : "r"(a) : "memory"); }
__device__ __forceinline__ void stsm4(uint32_t a, const uint32_t (&r)[4]) { asm volatile("stmatrix.sync.aligned.m8n8.x4.shared.b16 [%0], {%1,%2,%3,%4};" :: "r"(a), "r"(r[0]), "r"(r[1]), "r"(r[2]), "r"(r[3]) : "memory"); }
__device__ __forceinline__ uint32_t pack(float lo, float hi) { uint32_t r; asm("cvt.rn.bf16x2.f32 %0, %1, %2;" : "=r"(r) : "f"(hi), "f"(lo)); return r; }
__device__ __forceinline__ float blo(uint32_t v) { return __uint_as_float(v << 16); }
__device__ __forceinline__ float bhi(uint32_t v) { return __uint_as_float(v & 0xffff0000u); }
__device__ __forceinline__ float bf16r(float x) { return blo(pack(x, 0.f)); }
__device__ __forceinline__ uint32_t hmul2(uint32_t a, uint32_t b) { uint32_t r; asm("mul.rn.bf16x2 %0, %1, %2;" : "=r"(r) : "r"(a), "r"(b)); return r; }
__device__ __forceinline__ uint32_t hadd2(uint32_t a, uint32_t b) { uint32_t r; asm("add.rn.bf16x2 %0, %1, %2;" : "=r"(r) : "r"(a), "r"(b)); return r; }
__device__ __forceinline__ uint32_t hfma2(uint32_t a, uint32_t b, uint32_t c) { uint32_t r; asm("fma.rn.bf16x2 %0, %1, %2, %3;" : "=r"(r) : "r"(a), "r"(b), "r"(c)); return r; }
__device__ __forceinline__ uint32_t packh(float lo, float hi) { uint32_t r; asm("cvt.rn.f16x2.f32 %0, %1, %2;" : "=r"(r) : "f"(hi), "f"(lo)); return r; }
__device__ __forceinline__ __half2 H2(uint32_t a) { return *reinterpret_cast<__half2*>(&a); }
__device__ __forceinline__ uint32_t U2(__half2 a) { return *reinterpret_cast<uint32_t*>(&a); }
__device__ __forceinline__ uint32_t fmul(uint32_t a, uint32_t b) { return U2(__hmul2(H2(a), H2(b))); }
__device__ __forceinline__ uint32_t ffma(uint32_t a, uint32_t b, uint32_t c) { return U2(__hfma2(H2(a), H2(b), H2(c))); }
__device__ __forceinline__ uint32_t fneg(uint32_t a) { return U2(__hneg2(H2(a))); }
__device__ __forceinline__ uint32_t amax2(uint32_t a, uint32_t b) { uint32_t r; asm("max.xorsign.abs.bf16x2 %0, %1, %2;" : "=r"(r) : "r"(a), "r"(b)); return r; }
__device__ __forceinline__ uint32_t prmt(uint32_t a, uint32_t b, uint32_t s) { return __byte_perm(a, b, s); }
__device__ __forceinline__ uint32_t ldraw(const __nv_bfloat16* p) { uint32_t v; asm volatile("ld.global.nc.u16 %0, [%1];" : "=r"(v) : "l"(p)); return v; }
__device__ __forceinline__ uint4 ldg128(const void* p) { uint4 v; asm volatile("ld.global.nc.v4.u32 {%0,%1,%2,%3}, [%4];" : "=r"(v.x), "=r"(v.y), "=r"(v.z), "=r"(v.w) : "l"(p)); return v; }
__device__ __forceinline__ void bar_sync(int id, int n) { asm volatile("bar.sync %0, %1;" :: "r"(id), "r"(n) : "memory"); }
__device__ __forceinline__ void bar_arrive(int id, int n) { asm volatile("bar.arrive %0, %1;" :: "r"(id), "r"(n) : "memory"); }
__device__ __forceinline__ void cluster_arrive() { asm volatile("barrier.cluster.arrive.relaxed.aligned;" ::: "memory"); }
__device__ __forceinline__ void cluster_wait() { asm volatile("barrier.cluster.wait.aligned;" ::: "memory"); }
__device__ __forceinline__ void fence_async() { asm volatile("fence.proxy.async.shared::cta;" ::: "memory"); }
__device__ __forceinline__ void fence_mbinit() { asm volatile("fence.mbarrier_init.release.cluster;" ::: "memory"); }
__device__ __forceinline__ uint32_t mapa(uint32_t a, uint32_t rank) { uint32_t r; asm("mapa.shared::cluster.u32 %0, %1, %2;" : "=r"(r) : "r"(a), "r"(rank)); return r; }
__device__ __forceinline__ void bulk_dsmem(uint32_t dst, uint32_t src, uint32_t bytes, uint32_t mbar) {
  asm volatile("cp.async.bulk.shared::cluster.shared::cta.mbarrier::complete_tx::bytes [%0], [%1], %2, [%3];" :: "r"(dst), "r"(src), "r"(bytes), "r"(mbar) : "memory");
}
__device__ __forceinline__ void bulk_load(uint32_t dst, const void* src, uint32_t bytes, uint32_t mbar) {
  asm volatile("cp.async.bulk.shared::cluster.global.mbarrier::complete_tx::bytes [%0], [%1], %2, [%3];" :: "r"(dst), "l"(src), "r"(bytes), "r"(mbar) : "memory");
}
__device__ __forceinline__ void mbar_init(uint32_t m, uint32_t cnt) { asm volatile("mbarrier.init.shared::cta.b64 [%0], %1;" :: "r"(m), "r"(cnt) : "memory"); }
__device__ __forceinline__ void mbar_expect(uint32_t m, uint32_t bytes) { asm volatile("mbarrier.arrive.expect_tx.shared::cta.b64 _, [%0], %1;" :: "r"(m), "r"(bytes) : "memory"); }
__device__ __forceinline__ bool mbar_try(uint32_t m) {
  uint32_t done;
  asm volatile("{.reg .pred p; mbarrier.try_wait.parity.shared::cta.b64 p, [%1], 0; selp.u32 %0, 1, 0, p;}" : "=r"(done) : "r"(m) : "memory");
  return done;
}
__device__ __forceinline__ void mbar_wait(uint32_t m) {
  if (!mbar_try(m)) {
    int it = 0;
    while (!mbar_try(m) && ++it < (1 << 22)) {}
  }
}
__device__ __forceinline__ bool elect() {
  uint32_t e;
  asm volatile("{.reg .pred p; elect.sync _|p, 0xffffffff; selp.u32 %0, 1, 0, p;}" : "=r"(e));
  return e;
}
__device__ __forceinline__ void tma_load4(uint32_t dst, const CUtensorMap* tm, int c0, int c1, int c2, int c3, uint32_t mbar) {
  asm volatile("cp.async.bulk.tensor.4d.shared::cluster.global.mbarrier::complete_tx::bytes [%0], [%1, {%3, %4, %5, %6}], [%2];"
               :: "r"(dst), "l"(tm), "r"(mbar), "r"(c0), "r"(c1), "r"(c2), "r"(c3) : "memory");
}
__device__ __forceinline__ void tma_load3(uint32_t dst, const CUtensorMap* tm, int c0, int c1, int c2, uint32_t mbar) {
  asm volatile("cp.async.bulk.tensor.3d.shared::cluster.global.mbarrier::complete_tx::bytes [%0], [%1, {%3, %4, %5}], [%2];"
               :: "r"(dst), "l"(tm), "r"(mbar), "r"(c0), "r"(c1), "r"(c2) : "memory");
}
__device__ __forceinline__ void tma_store3(const CUtensorMap* tm, int c0, int c1, int c2, uint32_t src) {
  asm volatile("cp.async.bulk.tensor.3d.global.shared::cta.bulk_group [%0, {%2, %3, %4}], [%1];"
               :: "l"(tm), "r"(src), "r"(c0), "r"(c1), "r"(c2) : "memory");
}
__device__ __forceinline__ void mma1688(float (&c)[4], uint32_t a0, uint32_t a1, uint32_t b) {
  asm volatile("mma.sync.aligned.m16n8k8.row.col.f32.bf16.bf16.f32 {%0,%1,%2,%3}, {%4,%5}, {%6}, {%0,%1,%2,%3};"
               : "+f"(c[0]), "+f"(c[1]), "+f"(c[2]), "+f"(c[3]) : "r"(a0), "r"(a1), "r"(b));
}
__device__ __forceinline__ void wg_fence() { asm volatile("wgmma.fence.sync.aligned;" ::: "memory"); }
__device__ __forceinline__ void wg_commit() { asm volatile("wgmma.commit_group.sync.aligned;" ::: "memory"); }
template <int N> __device__ __forceinline__ void wg_wait() { asm volatile("wgmma.wait_group.sync.aligned %0;" :: "n"(N) : "memory"); }
template <int N> __device__ __forceinline__ void tie_all(uint32_t (&x)[N]) {
#pragma unroll
  for (int i = 0; i < N; i++) asm volatile("" : "+r"(x[i]) :: "memory");
}
template <int N> __device__ __forceinline__ void tie_all(float (&x)[N]) {
#pragma unroll
  for (int i = 0; i < N; i++) asm volatile("" : "+f"(x[i]) :: "memory");
}
#define R16(C, d) C(d[0]), C(d[1]), C(d[2]), C(d[3]), C(d[4]), C(d[5]), C(d[6]), C(d[7]), C(d[8]), C(d[9]), C(d[10]), C(d[11]), C(d[12]), C(d[13]), C(d[14]), C(d[15])
#define R32(C, d) R16(C, d), R16(C, (d + 16))
#define P16 "{%0,%1,%2,%3,%4,%5,%6,%7,%8,%9,%10,%11,%12,%13,%14,%15}"
#define P32 "{%0,%1,%2,%3,%4,%5,%6,%7,%8,%9,%10,%11,%12,%13,%14,%15,%16,%17,%18,%19,%20,%21,%22,%23,%24,%25,%26,%27,%28,%29,%30,%31}"
template <int SD, int OFF> __device__ __forceinline__ void rs64(float* d, const uint32_t* a, uint64_t db) {
  if (SD) asm volatile("{.reg .b64 db; add.s64 db, %36, %37; wgmma.mma_async.sync.aligned.m64n64k16.f32.bf16.bf16 " P32 ", {%32,%33,%34,%35}, db, 1, 1, 1, 1;}"
                       : R32("+f", d) : "r"(a[0]), "r"(a[1]), "r"(a[2]), "r"(a[3]), "l"(db), "n"(OFF));
  else asm volatile("{.reg .b64 db; add.s64 db, %36, %37; wgmma.mma_async.sync.aligned.m64n64k16.f32.bf16.bf16 " P32 ", {%32,%33,%34,%35}, db, 0, 1, 1, 1;}"
                    : R32("=f", d) : "r"(a[0]), "r"(a[1]), "r"(a[2]), "r"(a[3]), "l"(db), "n"(OFF));
}
template <int SD, int TB, int OFF> __device__ __forceinline__ void rs64h(uint32_t* d, const uint32_t* a, uint64_t db) {
  if (SD) asm volatile("{.reg .b64 db; add.s64 db, %20, %21; wgmma.mma_async.sync.aligned.m64n64k16.f16.f16.f16 " P16 ", {%16,%17,%18,%19}, db, 1, 1, 1, %22;}"
                       : R16("+r", d) : "r"(a[0]), "r"(a[1]), "r"(a[2]), "r"(a[3]), "l"(db), "n"(OFF), "n"(TB));
  else asm volatile("{.reg .b64 db; add.s64 db, %20, %21; wgmma.mma_async.sync.aligned.m64n64k16.f16.f16.f16 " P16 ", {%16,%17,%18,%19}, db, 0, 1, 1, %22;}"
                    : R16("=r", d) : "r"(a[0]), "r"(a[1]), "r"(a[2]), "r"(a[3]), "l"(db), "n"(OFF), "n"(TB));
}
template <int SD, int OFFA, int OFFB> __device__ __forceinline__ void ss32(float* d, uint64_t da, uint64_t db) {
  if (SD) asm volatile("{.reg .b64 da, db; add.s64 da, %16, %18; add.s64 db, %17, %19; wgmma.mma_async.sync.aligned.m64n32k16.f32.f16.f16 " P16 ", da, db, 1, 1, 1, 1, 1;}"
                       : R16("+f", d) : "l"(da), "l"(db), "n"(OFFA), "n"(OFFB));
  else asm volatile("{.reg .b64 da, db; add.s64 da, %16, %18; add.s64 db, %17, %19; wgmma.mma_async.sync.aligned.m64n32k16.f32.f16.f16 " P16 ", da, db, 0, 1, 1, 1, 1;}"
                    : R16("=f", d) : "l"(da), "l"(db), "n"(OFFA), "n"(OFFB));
}
#define KGEN_ASM(SD) "{.reg .b64 da, db; add.s64 da, %32, %33; add.s64 db, %32, %34;\n" \
  "wgmma.mma_async.sync.aligned.m64n64k16.f32.bf16.bf16 " P32 ", da, db, " SD ", 1, 1, 1, 1;}"
template <int KS> __device__ __forceinline__ void kgen_mma(float (&c)[32], uint64_t da) {
  if (KS) asm volatile(KGEN_ASM("1") : R32("+f", c) : "l"(da), "n"(8 * KS), "n"(8 * KS + 512));
  else asm volatile(KGEN_ASM("0") : R32("=f", c) : "l"(da), "n"(8 * KS), "n"(8 * KS + 512));
  if constexpr (KS < 7) kgen_mma<KS + 1>(c, da);
}
template <int OFF, int KSTEP> __device__ __forceinline__ void stage1(float (&D)[32], const uint32_t (&A1)[8], uint64_t d) {
  rs64<0, OFF>(D, A1, d); rs64<1, OFF + KSTEP>(D, A1 + 4, d);
}
template <int INV> __device__ __forceinline__ void stage2(uint32_t (&X)[16], const uint32_t (&F)[16], uint64_t dc) {
  constexpr int KS = INV ? 16 : 128, TB = INV ? 0 : 1;
  rs64h<0, TB, 0>(X, F, dc); rs64h<1, TB, KS>(X, F + 4, dc); rs64h<1, TB, 2 * KS>(X, F + 8, dc); rs64h<1, TB, 3 * KS>(X, F + 12, dc);
}
__device__ __forceinline__ void fwd_mid(uint32_t (&F)[16], const float (&D)[32], const uint32_t (&tc)[4], const uint32_t (&ts)[4]) {
#pragma unroll
  for (int j = 0; j < 4; j++)
#pragma unroll
    for (int b = 0; b < 2; b++) {
      const int i = 4 * j + 16 * b;
      const uint32_t ar = packh(D[i], D[i + 1]), ai = packh(D[i + 2], D[i + 3]);
      F[2 * j + b] = ffma(ar, tc[j], fmul(ai, ts[j]));
      F[8 + 2 * j + b] = ffma(ai, tc[j], fneg(fmul(ar, ts[j])));
    }
}
__device__ __forceinline__ void put_exp(uint32_t a, uint32_t m, int lane) {
  m = __reduce_max_sync(0xffffffffu, max(m & 0x7f80u, (m >> 16) & 0x7f80u));
  if (lane == 0) sts32(a, m);
}
__device__ __forceinline__ uint32_t get_exp(uint32_t a) { const uint4 v = lds128(a); return max(max(v.x, v.y), max(v.z, v.w)) >> 7; }
__device__ __forceinline__ void scale_a1(uint32_t (&As)[8], const uint32_t (&A1)[8], uint32_t field) {
#pragma unroll
  for (int i = 0; i < 8; i++) As[i] = hmul2(A1[i], field * 0x00800080u);
}

struct cf { float x, y; };
__device__ __forceinline__ cf cmul(cf a, cf b) { cf r; r.x = fmaf(a.x, b.x, -a.y * b.y); r.y = fmaf(a.x, b.y, a.y * b.x); return r; }
__device__ __forceinline__ cf cexp_p(float lr2, float lt, float p) {
  float m;
  asm("ex2.approx.ftz.f32 %0, %1;" : "=f"(m) : "f"(lr2 * p));
  float t = lt * p;
  t = (t - rintf(t)) * 6.283185307179586f;
  cf r; r.x = m * __cosf(t); r.y = m * __sinf(t); return r;
}
__device__ __forceinline__ void store8(uint32_t a, uint32_t b, const cf (&v)[8]) {
  sts128(a, pack(v[0].x, v[1].x), pack(v[2].x, v[3].x), pack(v[4].x, v[5].x), pack(v[6].x, v[7].x));
  sts128(b, pack(v[0].y, v[1].y), pack(v[2].y, v[3].y), pack(v[4].y, v[5].y), pack(v[6].y, v[7].y));
}
__device__ __forceinline__ void mbar_arrive(uint32_t m) { asm volatile("mbarrier.arrive.shared::cta.b64 _, [%0];" :: "r"(m) : "memory"); }
__device__ __forceinline__ float sigmoidf_(float s) { return __fdividef(1.f, 1.f + __expf(fminf(-s, 80.f))); }

__global__ void __cluster_dims__(CS, 1, 1) __launch_bounds__(NTHREADS, 1) fused_kernel(const __grid_constant__ Params p) {
  extern __shared__ __align__(1024) uint8_t smem[];
  TL_INIT();
  TL(31);
  const int wid = __shfl_sync(0xffffffffu, threadIdx.x >> 5, 0);
  const uint32_t sb = (uint32_t)__cvta_generic_to_shared(smem);
  const uint32_t mb = sb + OFF_MB;
  const int u = wid >> 2, w = wid & 3;
  const int tid = threadIdx.x & 127, lane = tid & 31, g = lane >> 2, t = lane & 3;
  const int cl = blockIdx.x >> 3, rank = blockIdx.x & 7;
  const int ch0 = cl * CPC;
  const int nu = min(5, (DCH - ch0) >> 3);
  const bool act = u < nu;

  uint32_t pla, pai, pcr, pci, pdt, tag = 0;
  auto load_params = [&]() {
    const int ch = act ? ch0 + 8 * u + rank : 0, o = ch * NMODE + tid;
    pla = ldraw(p.logA + o); pdt = ldraw(p.logdt + ch); pai = ldraw(p.Aim + o); pcr = ldraw(p.Cre + o); pci = ldraw(p.Cim + o);
  };
  if (u == 4) {
    const bool e = elect();
    if (e) {
#pragma unroll
      for (int i = 0; i < 5; i++) mbar_init(mb + 40 * w + 8 * i, 1);
      if (w == 3) { mbar_init(mb + 8 * MB_XQ, 1); mbar_init(mb + 8 * MB_KV, 1); }
      if (w == 2) mbar_init(mb + 8 * MB_G, 8);
      fence_mbinit();
      if ((sb & 0xffffffu) != SB0) __trap();
    }
    __syncwarp();
    load_params();
    if (w == 0 && lane < 2) asm volatile("atom.relaxed.gpu.global.add.u32 %0, [%1], %2;" : "=r"(tag) : "l"(&p.cnt[rank * 32 + lane]), "r"(cl == 0 ? 16 - (NCL - 1) : 1) : "memory");
    if (e) {
      if (w == 3) {
        mbar_expect(mb + 8 * MB_XQ, 20480 + 20480 + 112 * nu);
        bulk_load(sb + OFF_SP, p.gate_w + ch0, 16 * nu, mb + 8 * MB_XQ);
        bulk_load(sb + OFF_SP + 80, p.Dskip + ch0, 16 * nu, mb + 8 * MB_XQ);
        bulk_load(sb + OFF_SP + 160, p.ssm_D + ch0, 16 * nu, mb + 8 * MB_XQ);
        bulk_load(sb + OFF_SP + 240, p.shift_k + 4 * ch0, 64 * nu, mb + 8 * MB_XQ);
        tma_load3(sb + OFF_TQ, &p.tq, ch0, 8 * rank, 0, mb + 8 * MB_XQ);
        bulk_load(sb + OFF_CF, p.tab, 20480, mb + 8 * MB_XQ);
        TL(20);
        mbar_expect(mb + 8 * MB_KV, 2 * 20480 + 320);
        tma_load3(sb + OFF_TK, &p.tk, ch0, 8 * rank, 0, mb + 8 * MB_KV);
        tma_load3(sb + OFF_HALO, &p.tkh, ch0, 8 * rank - 1, 28, mb + 8 * MB_KV);
      }
#pragma unroll
      for (int i = 0; i < 5; i++) mbar_expect(mb + 40 * w + 8 * i, w == 3 ? 4096 : w == 2 ? 7168 : 7 * YP);
    }
    __syncwarp();
  } else {
    load_params();
  }
  cluster_arrive();
  TL(0);

  const uint32_t tab = sb + OFF_T + u * KTAB;
  const uint32_t toff = (64 * w + lane) * 80 + 16 * u;
  const int uown = u * USZ + (rank & 3) * UGRP + (rank >> 2) * YP;
  auto put = [&](int stage, const uint32_t (&a)[4], const uint32_t (&b)[4]) {
    const uint32_t o = sb + (g == rank ? OFF_U + uown : stage + (8 * u + g) * YP);
    const uint32_t od = o + (rank < 4 ? 16 : 0) + 128 * w + 32 * t;
    sts128(od, prmt(a[0], a[1], 0x5410), prmt(a[2], a[3], 0x5410), prmt(b[0], b[1], 0x5410), prmt(b[2], b[3], 0x5410));
    sts128(od + 16, prmt(a[0], a[1], 0x7632), prmt(a[2], a[3], 0x7632), prmt(b[0], b[1], 0x7632), prmt(b[2], b[3], 0x7632));
    const uint32_t m = amax2(amax2(amax2(a[0], a[1]), amax2(a[2], a[3])), amax2(amax2(b[0], b[1]), amax2(b[2], b[3])));
    asm volatile("st.shared.u8 [%0], %1;" :: "r"(o + (rank < 4 ? 0 : 512) + 4 * w + t), "r"(amax2(m, m >> 16) >> 7) : "memory");
  };
  const int d0 = rank ^ (2 * w), d1 = d0 ^ 1;
  const uint32_t rb0 = mapa(sb, d0), rb1 = mapa(sb, d1);
  auto send = [&](int stage, int bytes, int dst, int mbar) {
    if (elect()) {
      if (w) bulk_dsmem(rb0 + dst, sb + stage + d0 * bytes, bytes, rb0 + mbar);
      bulk_dsmem(rb1 + dst, sb + stage + d1 * bytes, bytes, rb1 + mbar);
    }
    __syncwarp();
  };

  uint32_t A1[8], tc[4], ts[4];
  {
    const float dt = bf16r(expf(blo(pdt)));
    const float lr2 = (-bf16r(expf(blo(pla))) * dt) * 1.4426950408889634f;
    const float lt = (blo(pai) * dt) * 0.15915494309189535f;
    const uint32_t tim = sb + (u ? OFF_IM + (u - 1) * KTAB : OFF_U);
    const uint32_t row = tab + tid * 16, rim = tim + tid * 16;
    const cf w1 = cexp_p(lr2, lt, 8.f);
    cf z1 = cexp_p(lr2, lt, 1.f), Z = cexp_p(lr2, lt, 256.f);
    if (lr2 != 123.f) TL(16);
    TL(12);
    {
      cf v[8];
      v[0].x = 1.f; v[0].y = 0.f; v[1] = w1; v[2] = cmul(w1, w1); v[3] = cmul(v[2], w1);
      const cf w4 = cmul(v[2], v[2]);
      v[4] = w4; v[5] = cmul(v[1], w4); v[6] = cmul(v[2], w4); v[7] = cmul(v[3], w4);
      const cf w8 = cmul(w4, w4);
      store8(row, rim, v);
#pragma unroll
      for (int k = 1; k < 4; k++) {
#pragma unroll
        for (int i = 0; i < 8; i++) v[i] = (k == 1 && i == 0) ? w8 : cmul(v[i], w8);
        store8(row + 2048 * k, rim + 2048 * k, v);
      }
    }
    if (STAGGER && STMID && u < 5 - STW) bar_arrive(NB_ST + u, 256);
    if (PREFETCH && wid == 8 && elect()) {
      const uint32_t o = blockIdx.x * 9856u, n = min(9856u, SEQ * DCH - o) * 2;
      asm volatile("cp.async.bulk.prefetch.L2.global [%0], %1;" :: "l"(p.v + o), "r"(n) : "memory");
      asm volatile("cp.async.bulk.prefetch.L2.global [%0], %1;" :: "l"(p.ssm_k + o), "r"(n) : "memory");
    }
    __syncwarp();
    if (u == 1) {
      float z0_ = 0.f, z1_ = 0.f, z2_ = 0.f, z3_ = 0.f;
      asm volatile("mma.sync.aligned.m16n8k8.row.col.f32.bf16.bf16.f32 {%0,%1,%2,%3}, {%4,%4}, {%4}, {%0,%1,%2,%3};"
                   : "+f"(z0_), "+f"(z1_), "+f"(z2_), "+f"(z3_) : "r"(pla >> 16));
      pcr += __float_as_uint(z0_);
      TL(8);
    }
    {
      z1.y = -z1.y; Z.y = -Z.y;
      const cf z2 = cmul(z1, z1);
      cf h[8], v[8];
      h[0].x = 2.f * blo(pcr) * dt; h[0].y = -2.f * blo(pci) * dt;
      h[1] = cmul(h[0], z1);
#pragma unroll
      for (int i = 2; i < 8; i++) h[i] = cmul(h[i - 2], z2);
      store8(row + 4 * 2048, rim + 4 * 2048, h);
      const cf h8 = cmul(h[6], z2);
      v[0] = cmul(h[0], Z); v[2] = cmul(h[2], Z); v[3] = cmul(h[4], Z); v[6] = cmul(h[6], Z); v[7] = cmul(h8, Z);
      v[1] = v[0]; v[4] = v[5] = v[3];
      store8(row + 5 * 2048, rim + 5 * 2048, v);
      h[0] = cmul(v[0], Z); h[1] = cmul(v[3], Z); h[3] = cmul(v[7], Z); h[4] = cmul(h[0], Z); h[5] = cmul(h[1], Z); h[7] = cmul(h[3], Z);
      h[2] = h[1]; h[6] = h[5];
      store8(row + 6 * 2048, rim + 6 * 2048, h);
      const cf Z2 = cmul(Z, Z);
      v[0] = cmul(h[0], Z2); v[1] = cmul(h[3], Z2); v[2] = cmul(h[4], Z2); v[3] = cmul(h[7], Z2);
#pragma unroll
      for (int i = 4; i < 8; i++) v[i] = cmul(v[i - 4], Z2);
      store8(row + 7 * 2048, rim + 7 * 2048, v);
    }
    TL(17);
    if (wid == 16 && lane == 0) sts32(mb + 8 * MB_TAG, tag);
    cluster_wait();
    if (u >= 2) cluster_arrive();
    fence_async();
    if (u) bar_sync(NB_ORD + u - 1, 256); else bar_sync(NB_WG0, 128);
    TL(13);
    float c[32];
    wg_fence();
    kgen_mma<0>(c, p.dk[u]);
    wg_commit();
    if (u < 4) bar_arrive(NB_ORD + u, 256);
    TL(14);
    mbar_wait(mb + 8 * MB_XQ);
    TL(18);
    uint32_t x0[4], x1[4];
    ldsm4t(x0, sb + OFF_TQ + toff);
    ldsm4t(x1, sb + OFF_TQ + toff + 2560);
    {
      const uint4 x = lds128(sb + OFF_TH + 16 * tid), y = lds128(sb + OFF_TH + 2048 + 16 * tid), a = lds128(sb + OFF_TH + 4096 + 16 * tid), b = lds128(sb + OFF_TH + 6144 + 16 * tid);
      A1[0] = x.x; A1[1] = x.y; A1[2] = x.z; A1[3] = x.w; A1[4] = y.x; A1[5] = y.y; A1[6] = y.z; A1[7] = y.w;
      tc[0] = a.x; tc[1] = a.y; tc[2] = a.z; tc[3] = a.w; ts[0] = b.x; ts[1] = b.y; ts[2] = b.z; ts[3] = b.w;
    }
    wg_wait<0>(); tie_all(c);
    TL(26);
    if (u < 2) cluster_arrive();
    bar_sync(u >= 3 ? NB_V + u - 3 : NB_WG0 + u, u >= 3 ? 256 : 128);
    if ((u & 6) == 2) bar_arrive(NB_V + u - 2, 256);
    const uint32_t k0 = pack(c[0] + c[6], c[1] + c[7]), k1 = pack(c[8] + c[14], c[9] + c[15]);
    const uint32_t k2 = pack(c[16] + c[22], c[17] + c[23]), k3 = pack(c[24] + c[30], c[25] + c[31]);
    const uint32_t ka = tab + 16 * (8 * w + (g ^ w));
    sts32(ka + 4 * t, k0);
    sts32(ka + 512 + 4 * t, k1);
    sts64(ka + 1024 + 512 * (t >> 1) + 8 * (t & 1), prmt(k2, 0, 0x1010), (t & 1) ? prmt(k2, 0, 0x3232) : k2);
    const uint32_t lo = prmt(k3, 0, 0x1010), hi = prmt(k3, 0, 0x3232);
    sts128(ka + 2048 + 512 * t, lo, lo, (g & 1) ? hi : k3, hi);
    put_exp(sb + OFF_MX + u * 32 + 4 * w, amax2(amax2(k0, k1), amax2(k2, k3)), lane);
    cluster_wait();
    put(OFF_YB, x0, x1);
    TL(15);
    fence_async();
    bar_sync(NB_WG0 + u, 128);
    send(OFF_YB + 8 * u * YP, YP, OFF_U + uown, OFF_MB + 8 * (MB_UX + u));
    if (wid == 16 && elect()) tma_load3(sb + OFF_TV, &p.tv, ch0, 8 * rank, 0, mb + 8 * MB_KV);
    __syncwarp();
  }
  if (u == 0) {
    float ga[4][4];
#pragma unroll
    for (int i = 0; i < 4; i++) ga[i][0] = ga[i][1] = ga[i][2] = ga[i][3] = 0.f;
#pragma unroll
    for (int j = 0; j < 5; j++) {
      uint32_t a0[4], a1[4], b;
      ldsm4(a0, sb + OFF_TQ + toff + 16 * j);
      ldsm4(a1, sb + OFF_TQ + toff + 2560 + 16 * j);
      asm volatile("ld.shared.u32 %0, [%1];" : "=r"(b) : "r"(sb + OFF_SP + 16 * j + 4 * t) : "memory");
      if (j >= 2 && j >= nu) b = 0;
      mma1688(ga[0], a0[0], a0[1], b); mma1688(ga[1], a0[2], a0[3], b); mma1688(ga[2], a1[0], a1[1], b); mma1688(ga[3], a1[2], a1[3], b);
    }
    const float s0 = t == 0 ? ga[0][0] : t == 1 ? ga[1][0] : t == 2 ? ga[2][0] : ga[3][0];
    const float s1 = t == 0 ? ga[0][2] : t == 1 ? ga[1][2] : t == 2 ? ga[2][2] : ga[3][2];
    tag = (lds64(mb + 8 * MB_TAG).x >> 4) + 1;
    uint2* gp = p.part + cl * SEQ + rank * 256 + 64 * w + 16 * t + g;
    asm volatile("st.relaxed.gpu.global.u64 [%0], %1;" :: "l"(gp), "l"(((uint64_t)tag << 32) | __float_as_uint(s0)) : "memory");
    asm volatile("st.relaxed.gpu.global.u64 [%0], %1;" :: "l"(gp + 8), "l"(((uint64_t)tag << 32) | __float_as_uint(s1)) : "memory");
  }

#pragma unroll
  for (int isA = 0; isA < 2; isA++) {
    {
      TL(1 + isA);
      const uint32_t mxa = sb + OFF_MX + u * 32 + 16 * isA;
      const uint32_t pd = lds16(sb + OFF_SP + 80 + 80 * isA + 16 * u + 2 * rank);
      float D[32];
      uint32_t As[8], F[16], H[16], X[16];
      const uint32_t eh = min(max((int)get_exp(mxa), (int)((pd >> 7) & 0xff) - 5), 240);
      scale_a1(As, A1, 248 - eh);
      wg_fence();
      if (isA) stage1<T_HA / 16, 64>(D, As, p.dt[u]); else stage1<0, 64>(D, As, p.dt[u]);
      wg_commit();
      wg_wait<0>(); tie_all(D);
      fwd_mid(F, D, tc, ts);
      wg_fence();
      stage2<0>(H, F, p.dfwd);
      wg_commit();
      if (!isA) {
        if (w == 2 && elect()) bulk_load(tab + T_HA, p.ssm_k + (size_t)(act ? ch0 + 8 * u + rank : 0) * SEQ, 4096, mb + 8 * (MB_HA + u));
        __syncwarp();
        TL(7);
      }
      if (isA) {
        fence_async();
        bar_sync(NB_WG0 + u, 128);
        send(OFF_T + u * KTAB + T_YS, 512, OFF_YB + u * USZ + rank * 512, OFF_MB + 8 * (MB_Y + u));
      }
      mbar_wait(mb + 8 * ((isA ? MB_UKV : MB_UX) + u));
      TL(5 + isA);
      uint32_t eu;
      asm volatile("ld.shared.u32 %0, [%1];" : "=r"(eu) : "r"(sb + OFF_U + u * USZ + (lane >> 3) * UGRP + ((lane & 4) ? UGRP - 16 : 0) + 4 * t) : "memory");
      eu = __vmaxu2(eu & 0x00ff00ffu, (eu >> 8) & 0x00ff00ffu);
      eu = min(__reduce_max_sync(0xffffffffu, max(eu & 0xffffu, eu >> 16)), 240u);
      scale_a1(As, A1, 250 - eu);
      wg_wait<0>(); tie_all(H);
      wg_fence();
      stage1<0, 2 * UGRP / 16>(D, As, p.dx[u]);
      wg_commit();
      wg_wait<0>(); tie_all(D);
      cluster_arrive();
      fwd_mid(F, D, tc, ts);
      wg_fence();
      stage2<0>(X, F, p.dfwd);
      wg_commit();
      {
        const float dsk = blo(pd) * __uint_as_float((248 - eh) << 23);
        const uint32_t d2 = packh(dsk, dsk);
#pragma unroll
        for (int j = 0; j < 4; j++) H[2 * j] = U2(__hadd2(H2(H[2 * j]), H2(d2)));
      }
      wg_wait<0>(); tie_all(X);
#pragma unroll
      for (int j = 0; j < 4; j++) {
        const uint32_t h0r = H[2 * j], h1r = H[2 * j + 1], h0i = H[8 + 2 * j], h1i = H[9 + 2 * j];
        const uint32_t x0r = X[2 * j], x1r = X[2 * j + 1], x0i = X[8 + 2 * j], x1i = X[9 + 2 * j];
        F[2 * j] = ffma(x0r, h0r, fneg(fmul(x0i, h0i)));
        F[8 + 2 * j] = ffma(x0r, h0i, fmul(x0i, h0r));
        F[2 * j + 1] = ffma(x1r, h0r, ffma(fneg(x1i), h0i, ffma(x0r, h1r, fneg(ffma(x0i, h1i, F[8 + 2 * j])))));
        F[9 + 2 * j] = ffma(x1r, h0i, ffma(x1i, h0r, ffma(x0r, h1i, ffma(x0i, h1r, F[2 * j]))));
      }
      wg_fence();
      stage2<1>(H, F, p.dinv);
      wg_commit();
      uint64_t ga[4];
      const int sl2 = min(18 * cl + min(8 * w + g, 17), 255), sl3 = tid + 128 * (u & 1);
      auto gload = [&]() {
        if (isA) {
          asm volatile("ld.relaxed.gpu.global.u64 %0, [%1];" : "=l"(ga[0]) : "l"(p.part + NCL * SEQ + rank * 256 + sl3) : "memory");
        } else {
#pragma unroll
          for (int k = 0; k < 4; k++)
            asm volatile("ld.relaxed.gpu.global.u64 %0, [%1];" : "=l"(ga[k]) : "l"(p.part + (t + (k == 3 && t == 3 ? 8 : 4 * k)) * SEQ + rank * 256 + sl2) : "memory");
        }
      };
      if (isA ? (u & 6) == 2 : u == 1) gload();
      if (isA) TL(23);
      wg_wait<0>(); tie_all(H);
      {
        const uint32_t va = tab + (16 * w + (lane & 15)) * 128;
        const int vx = (lane >> 4) ^ (lane & 7);
#pragma unroll
        for (int j = 0; j < 4; j++) {
          uint32_t V[4];
#pragma unroll
          for (int b = 0; b < 2; b++) {
            const uint32_t er = H[2 * j + b], ei = H[8 + 2 * j + b];
            V[2 * b] = ffma(er, tc[j], fneg(fmul(ei, ts[j])));
            V[2 * b + 1] = ffma(ei, tc[j], fmul(er, ts[j]));
          }
          stsm4(va + ((vx ^ (2 * j)) << 4), V);
        }
      }
      if (!isA) {
        cluster_wait();
        mbar_wait(mb + 8 * MB_KV);
        TL(21);
        uint32_t K[3][4], V[2][4];
        const uint2 psw = lds64(sb + OFF_SP + 240 + 64 * u + 8 * g);
        ldsm4t(K[0], w ? sb + OFF_TK + toff - 2560 : (lane & 7) ? sb + OFF_TK + toff + 223 * 80 : sb + OFF_HALO + 10 * lane + 16 * u);
        ldsm4t(K[1], sb + OFF_TK + toff);
        ldsm4t(K[2], sb + OFF_TK + toff + 2560);
        ldsm4t(V[0], sb + OFF_TV + toff);
        ldsm4t(V[1], sb + OFF_TV + toff + 2560);
        mbar_wait(mb + 8 * (MB_HA + u));
        const uint4 hx = lds128(tab + T_HA + 16 * tid), hy = lds128(tab + T_HA + 2048 + 16 * tid);
        const uint32_t w0 = prmt(psw.x, 0, 0x1010), w1 = prmt(psw.x, 0, 0x3232), w2 = prmt(psw.y, 0, 0x1010), w3 = prmt(psw.y, 0, 0x3232);
#pragma unroll
        for (int m = 4; m < 12; m++)
          V[(m >> 2) - 1][m & 3] = hmul2(hfma2(K[m >> 2][m & 3], w0, hfma2(K[(m - 1) >> 2][(m - 1) & 3], w1,
                                         hfma2(K[(m - 2) >> 2][(m - 2) & 3], w2, hmul2(K[(m - 3) >> 2][(m - 3) & 3], w3)))), V[(m >> 2) - 1][m & 3]);
        put(OFF_YA, V[0], V[1]);
        put_exp(mxa + 16 + 4 * w, amax2(amax2(amax2(hx.x, hx.y), amax2(hx.z, hx.w)), amax2(amax2(hy.x, hy.y), amax2(hy.z, hy.w))), lane);
        sts128(tab + T_HA + 16 * (tid ^ (lane >> 3)), hx.x, hx.y, hx.z, hx.w);
        sts128(tab + T_HA + 2048 + 16 * (tid ^ (lane >> 3)), hy.x, hy.y, hy.z, hy.w);
        TL(22);
      }
      fence_async();
      bar_sync(NB_WG0 + u, 128);
      float O[16];
      {
        const uint64_t dv = p.dv[u], dl = p.dlast;
        wg_fence();
        ss32<0, 0, 0>(O, dv, dl); ss32<1, 128, 64>(O, dv, dl); ss32<1, 256, 128>(O, dv, dl); ss32<1, 384, 192>(O, dv, dl);
        wg_commit();
      }
      if (!isA) send(OFF_YA + 8 * u * YP, YP, OFF_U + uown, OFF_MB + 8 * (MB_UKV + u));
      if (isA ? (u & 6) == 2 : u == 1) {
        tag = (lds64(mb + 8 * MB_TAG).x >> 4) + 1;
        bool ok;
#pragma unroll 1
        for (int it = 0;; it++) {
          ok = (uint32_t)(ga[0] >> 32) == tag;
          if (!isA) ok = ok && (uint32_t)(ga[1] >> 32) == tag && (uint32_t)(ga[2] >> 32) == tag && (uint32_t)(ga[3] >> 32) == tag;
          ok = __all_sync(0xffffffffu, ok);
          if (ok || it == (isA ? 8000 : 2000)) break;
          gload();
        }
        if (!isA) {
          float s = __uint_as_float((uint32_t)ga[0]) + __uint_as_float((uint32_t)ga[1]) + __uint_as_float((uint32_t)ga[2]);
          if (t < 3) s += __uint_as_float((uint32_t)ga[3]);
          s += __shfl_xor_sync(0xffffffffu, s, 1);
          s += __shfl_xor_sync(0xffffffffu, s, 2);
          const float g0 = bf16r(sigmoidf_(bf16r(s)));
          if (ok && t == 0)
            asm volatile("st.relaxed.gpu.global.u64 [%0], %1;" :: "l"(p.part + NCL * SEQ + rank * 256 + sl2), "l"(((uint64_t)tag << 32) | pack(g0, 1.f - g0)) : "memory");
        } else {
          uint32_t gv = (uint32_t)ga[0];
          if (!ok) {
            const uint32_t* xr = (const uint32_t*)(p.q + (size_t)(rank * 256 + 32 * (sl3 & 7) + (sl3 >> 3)) * DCH);
            const uint32_t* gr = (const uint32_t*)p.gate_w;
            float s = 0.f;
#pragma unroll 1
            for (int k = 0; k < DCH / 2; k++) { const uint32_t x = __ldg(xr + k), y = __ldg(gr + k); s = fmaf(blo(x), blo(y), fmaf(bhi(x), bhi(y), s)); }
            const float g0 = bf16r(sigmoidf_(bf16r(s)));
            gv = pack(g0, 1.f - g0);
          }
          sts64(sb + OFF_GB + 8 * sl3, prmt(gv, 0, 0x1010), prmt(gv, 0, 0x3232));
          __syncwarp();
          if (lane == 0) mbar_arrive(mb + 8 * MB_G);
        }
      }
      if (isA) cluster_wait();
      if (isA) TL(28);
      wg_wait<0>(); tie_all(O);
      {
        const uint32_t co = ((8 * w + g) ^ (2 * t) ^ rank) * 16, usrc = tab + (isA ? T_HA : T_YS);
        const int yo = (isA ? OFF_YA : OFF_YB) + u * USZ + rank * 512, ym = OFF_MB + 8 * (MB_Y + u);
        const uint32_t us = min(max((int)(eu + eh) - 127, 0), 254) * 0x00800080u;
        const uint32_t a0 = hmul2(pack(O[0], O[1]), us), a1 = hmul2(pack(O[4], O[5]), us), a2 = hmul2(pack(O[8], O[9]), us), a3 = hmul2(pack(O[12], O[13]), us);
        const uint32_t b0 = hmul2(pack(O[2], O[3]), us), b1 = hmul2(pack(O[6], O[7]), us), b2 = hmul2(pack(O[10], O[11]), us), b3 = hmul2(pack(O[14], O[15]), us);
        sts128((t == rank ? sb + yo : usrc + t * 512) + co, a0, a1, a2, a3);
        sts128((t + 4 == rank ? sb + yo : usrc + t * 512 + 2048) + co, b0, b1, b2, b3);
        if (isA) {
          fence_async();
          bar_sync(NB_WG0 + u, 128);
          send(usrc - sb, 512, yo, ym);
        }
      }
      TL(9 + isA);
    }
  }

  {
    mbar_wait(mb + 8 * MB_G);
    uint2 gg[2][4];
    uint32_t qv[2][4];
#pragma unroll
    for (int hh = 0; hh < 2; hh++)
#pragma unroll
      for (int i = 0; i < 4; i++) gg[hh][i] = lds64(sb + OFF_GB + 8 * (64 * w + 32 * hh + 8 * i + g));
    const uint32_t qa = sb + OFF_TQ + toff;
    ldsm4(qv[0], qa);
    ldsm4(qv[1], qa + 2560);
    TL(24);
    mbar_wait(mb + 8 * (MB_Y + u));
    uint32_t ya[2][4], yb[2][4];
#pragma unroll
    for (int hh = 0; hh < 2; hh++) {
      const uint32_t yo = u * USZ + (lane & 7) * 512 + ((8 * w + 4 * hh + (lane >> 3)) ^ (2 * (rank & 3)) ^ (lane & 7)) * 16;
      ldsm4t(ya[hh], sb + OFF_YA + yo); ldsm4t(yb[hh], sb + OFF_YB + yo);
    }
#pragma unroll
    for (int hh = 0; hh < 2; hh++) {
      uint32_t o[4];
#pragma unroll
      for (int i = 0; i < 4; i++) o[i] = hadd2(hmul2(gg[hh][i].x, hmul2(qv[hh][i], ya[hh][i])), hmul2(gg[hh][i].y, yb[hh][i]));
      stsm4(qa + 2560 * hh, o);
    }
    TL(25);
  }
  cluster_arrive();
  bar_sync(NB_ROW0 + w, 160);
  {
    uint4 v[2];
#pragma unroll
    for (int k = 0; k < 2; k++) {
      const int i = 64 * u + 32 * k + lane, sl = (i * 205) >> 10, cc = i - 5 * sl;
      v[k] = lds128(sb + OFF_TQ + (64 * w + 8 * (sl & 7) + (sl >> 3)) * 80 + cc * 16);
    }
#pragma unroll
    for (int k = 0; k < 2; k++) {
      const int i = 64 * u + 32 * k + lane, sl = (i * 205) >> 10, cc = i - 5 * sl;
      if (cc < nu)
        asm volatile("st.global.cg.v4.u32 [%0], {%1,%2,%3,%4};" :: "l"(p.out + (size_t)(256 * rank + 32 * (sl >> 3) + 8 * w + (sl & 7)) * DCH + ch0 + 8 * cc),
                     "r"(v[k].x), "r"(v[k].y), "r"(v[k].z), "r"(v[k].w) : "memory");
    }
  }
  cluster_wait();
  TL(27);
  TL_DUMP();
}

typedef CUresult (*EncodeFn)(CUtensorMap*, CUtensorMapDataType, cuuint32_t, void*, const cuuint64_t*, const cuuint64_t*,
                             const cuuint32_t*, const cuuint32_t*, CUtensorMapInterleave, CUtensorMapSwizzle,
                             CUtensorMapL2promotion, CUtensorMapFloatOOBfill);

void encode(EncodeFn fn, CUtensorMap* tm, const void* ptr, int nd, const cuuint64_t* dims, const cuuint64_t* strides,
            const cuuint32_t* box, CUtensorMapSwizzle swz) {
  cuuint32_t es[4] = {1, 1, 1, 1};
  fn(tm, CU_TENSOR_MAP_DATA_TYPE_BFLOAT16, nd, const_cast<void*>(ptr), dims, strides, box, es, CU_TENSOR_MAP_INTERLEAVE_NONE,
     swz, CU_TENSOR_MAP_L2_PROMOTION_L2_128B, CU_TENSOR_MAP_FLOAT_OOB_FILL_NONE);
}
void make_map(EncodeFn fn, CUtensorMap* tm, const void* ptr, int ne, int nr) {
  const cuuint64_t dims[3] = {DCH, SEQ / 32, 32}, strides[2] = {32 * DCH * 2, DCH * 2};
  const cuuint32_t box[3] = {CPC, (cuuint32_t)ne, (cuuint32_t)nr};
  encode(fn, tm, ptr, 3, dims, strides, box, CU_TENSOR_MAP_SWIZZLE_NONE);
}

}

extern "C" void kernel_launch(void* const* d_in, const int* in_sizes, int n_in, void* d_out, int out_size) {
  (void)in_sizes; (void)n_in; (void)out_size;
  static EncodeFn fn = nullptr;
  static void *tab = nullptr, *cnt = nullptr, *part = nullptr;
  if (!fn) {
    cudaGetSymbolAddress(&tab, d_tab);
    cudaGetSymbolAddress(&cnt, g_cnt);
    cudaGetSymbolAddress(&part, g_part);
    cudaDriverEntryPointQueryResult qr;
    cudaGetDriverEntryPoint("cuTensorMapEncodeTiled", (void**)&fn, cudaEnableDefault, &qr);
    cudaFuncSetAttribute(fused_kernel, cudaFuncAttributeMaxDynamicSharedMemorySize, SMEM_BYTES);
  }
  Params p;
  make_map(fn, &p.tq, d_in[0], 8, 32);
  make_map(fn, &p.tk, d_in[1], 8, 32);
  make_map(fn, &p.tv, d_in[2], 8, 32);
  make_map(fn, &p.tkh, d_in[1], 1, 4);
  p.out = (__nv_bfloat16*)d_out;
  p.dfwd = mkdesc(OFF_CF, 1024, 128, 0);
  p.dinv = mkdesc(OFF_CF, 128, 1024, 0);
  p.dlast = mkdesc(OFF_CL, 512, 128, 0);
  for (int u = 0; u < 5; u++) {
    p.dk[u] = mkdesc(OFF_T + u * KTAB, u ? OFF_IM - KTAB - OFF_T : OFF_U - OFF_T, 1024, 0);
    p.dt[u] = mkdesc(OFF_T + u * KTAB, 2048, 512, 2);
    p.dx[u] = mkdesc(OFF_U + u * USZ + 16, UGRP, 128, 0);
    p.dv[u] = mkdesc(OFF_T + u * KTAB, 16, 1024, 1);
  }
  p.tab = (const Tables*)tab;
  p.cnt = (unsigned*)cnt;
  p.part = (uint2*)part;
  p.tl = nullptr;
  p.q = (const __nv_bfloat16*)d_in[0];
  p.v = (const __nv_bfloat16*)d_in[2];
  p.ssm_k = (const __nv_bfloat16*)d_in[4];
  p.shift_k = (const __nv_bfloat16*)d_in[3];
  p.ssm_D = (const __nv_bfloat16*)d_in[5];
  p.logA = (const __nv_bfloat16*)d_in[7];
  p.Aim = (const __nv_bfloat16*)d_in[8];
  p.Cre = (const __nv_bfloat16*)d_in[9];
  p.Cim = (const __nv_bfloat16*)d_in[10];
  p.logdt = (const __nv_bfloat16*)d_in[11];
  p.Dskip = (const __nv_bfloat16*)d_in[12];
  p.gate_w = (const __nv_bfloat16*)d_in[13];
  fused_kernel<<<NCL * CS, NTHREADS, SMEM_BYTES, cudaStreamPerThread>>>(p);
}
```

```cpp
#include <cuda_runtime.h>
#include <cuda_bf16.h>
#include <cuda_fp16.h>
#include <cuda.h>
#include <stdint.h>

#define TIMELINE 0
#define PREFETCH 1
#define XEARLY 1
#define TLHI 0

namespace {

constexpr int SEQ = 2048, DCH = 576, NMODE = 128;
constexpr int CS = 8, CPC = 40, NCL = 15, NTHREADS = 640;

constexpr int KTAB = 16384;
constexpr int OFF_T = 0;
constexpr int T_YS = 8192, T_HA = 12288;
constexpr int UGRP = 1056, USZ = 4 * UGRP, YP = 528;
constexpr int OFF_IM = 5 * KTAB;
constexpr int OFF_YB = OFF_IM;
constexpr int OFF_TV = OFF_YB + 40 * YP;
constexpr int OFF_YA = OFF_TV + 20480;
constexpr int OFF_GB = OFF_YA + 40 * YP;
constexpr int OFF_U = OFF_IM + 4 * KTAB;
constexpr int OFF_CF = OFF_U + 5 * USZ;
constexpr int OFF_CL = OFF_CF + 8192;
constexpr int OFF_TH = OFF_CL + 4096;
constexpr int OFF_TQ = OFF_TH + 8192;
constexpr int OFF_TK = OFF_TQ + 20480;
constexpr int OFF_HALO = OFF_TK + 20480;
constexpr int OFF_MX = OFF_HALO + 320;
constexpr int OFF_SP = OFF_MX + 160;
constexpr int OFF_MB = OFF_SP + 560;
constexpr int OFF_TL = OFF_MB + 28 * 8;
constexpr int SMEM_BYTES = OFF_TL + (TIMELINE ? 640 : 0);
static_assert(SMEM_BYTES <= 232448 && OFF_GB + 2048 <= OFF_U && (OFF_TV & 127) == 0 && (OFF_TQ & 127) == 0, "smem");
static_assert((OFF_MB & 7) == 0 && (OFF_MX & 15) == 0 && (OFF_SP & 15) == 0, "align");

enum { MB_UX = 0, MB_UKV = 5, MB_Y = 10, MB_HA = 15, MB_XQ = 20, MB_KV = 21, MB_CF = 22, MB_G = 23, MB_TH = 24, MB_TAG = 25 };
enum { NB_WG0 = 1, NB_ROW0 = 6, NB_ORD = 6, NB_V = 10, NB_ST = 12 };

constexpr uint32_t SB0 = 1024;
constexpr uint64_t mkdesc(uint32_t off, uint32_t lbo, uint32_t sbo, uint32_t swz) {
  return (uint64_t)((SB0 + off) >> 4) | ((uint64_t)(lbo >> 4) << 16) | ((uint64_t)(sbo >> 4) << 32) | ((uint64_t)swz << 62);
}

constexpr double cos_turn(int m, int n) {
  m &= n - 1;
  if (m > n / 2) m = n - m;
  double sgn = 1.0;
  if (m > n / 4) { m = n / 2 - m; sgn = -1.0; }
  if (m == n / 4) return 0.0;
  const double x = 6.283185307179586476925 * m / n;
  double term = 1.0, sum = 1.0;
  for (int k = 1; k < 14; k++) { term *= -x * x / ((2 * k - 1) * (2 * k)); sum += term; }
  return sgn * sum;
}
constexpr uint32_t bf16_bits(double v) {
  if (v == 0.0) return 0;
  uint32_t sgn = 0;
  if (v < 0) { sgn = 0x8000; v = -v; }
  int e = 127;
  while (v < 1.0) { v *= 2.0; e--; }
  while (v >= 2.0) { v *= 0.5; e++; }
  const double f = v * 128.0;
  int m = (int)f;
  if (f - m > 0.5 || (f - m == 0.5 && (m & 1))) m++;
  return sgn | (uint32_t)((e << 7) + (m - 128));
}
constexpr uint32_t f16_bits(double v) {
  if (v == 0.0) return 0;
  uint32_t sgn = 0;
  if (v < 0) { sgn = 0x8000; v = -v; }
  int e = 15;
  while (v < 1.0) { v *= 2.0; e--; }
  const double f = v * 1024.0;
  int m = (int)f;
  if (f - m > 0.5 || (f - m == 0.5 && (m & 1))) m++;
  return sgn | (uint32_t)((e << 10) + (m - 1024));
}
constexpr uint32_t pair_bits(double lo, double hi) { return bf16_bits(lo) | (bf16_bits(hi) << 16); }
constexpr uint32_t pair_h(double lo, double hi) { return f16_bits(lo) | (f16_bits(hi) << 16); }
struct alignas(128) Tables {
  uint32_t mat[3072];
  uint32_t thr[4][128][4];
};
constexpr Tables make_tables() {
  Tables T{};
  for (int q = 0; q < 768; q++) {
    int m0 = 0, d0 = 0, d1 = 0;
    if (q < 512) {
      const int r = (q >> 6) * 8 + (q & 7), cc = (q >> 3) & 7;
      d0 = 4 * (r & 31); d1 = 2 * d0;
      m0 = 8 * (cc & 3) * d0 + ((r >> 5) == (cc >> 2) ? 0 : (r >> 5) ? 96 : 32);
    } else {
      const int r = ((q - 512) >> 5) * 8 + (q & 7), pc = (q >> 3) & 3;
      d0 = 4 * (8 * (r >> 4) + (r & 7)) + 1; d1 = 8 * d0;
      m0 = 2 * pc * d0 + ((r & 8) ? 32 : 0);
    }
    for (int e = 0; e < 4; e++) T.mat[4 * q + e] = pair_h(cos_turn(m0 + e * d1, 128), cos_turn(m0 + e * d1 + d0, 128));
  }
  for (int tid = 0; tid < 128; tid++) {
    const int kk = 4 * (tid >> 2) + 1, t = tid & 3;
    for (int q = 0; q < 4; q++) {
      const int m = (8 * q + 2 * t) * kk;
      T.thr[q >> 1][tid][2 * (q & 1)] = pair_bits(cos_turn(m, 128), cos_turn(m + kk, 128));
      T.thr[q >> 1][tid][2 * (q & 1) + 1] = pair_bits(cos_turn(m + 32, 128), cos_turn(m + kk + 32, 128));
      T.thr[2][tid][q] = pair_h(cos_turn(m, 4096), cos_turn(m + kk, 4096));
      T.thr[3][tid][q] = pair_h(cos_turn(m + 3072, 4096), cos_turn(m + kk + 3072, 4096));
    }
  }
  return T;
}
__device__ const Tables d_tab = make_tables();

struct Params {
  const __nv_bfloat16 *logA, *Aim, *Cre, *Cim, *logdt;
  const Tables* tab;
  unsigned* cnt;
  const __nv_bfloat16 *Dskip, *shift_k, *ssm_D, *gate_w, *q, *v, *ssm_k;
  uint2* part;
  __nv_bfloat16* out;
  unsigned* tl;
  uint64_t dfwd, dinv, dlast, dk[5], db[5], dt[5], dx[5], dv[5];
  CUtensorMap tq, tk, tv, tkh;
};

__device__ uint2 g_part[(NCL + 1) * SEQ];
__device__ unsigned g_cnt[CS * 32];
#define TL(i) do {} while (0)
#define TL_INIT() do {} while (0)
#define TL_DUMP() do {} while (0)

__device__ __forceinline__ uint32_t lds16(uint32_t a) { uint32_t v; asm volatile("ld.shared.u16 %0, [%1];" : "=r"(v) : "r"(a) : "memory"); return v; }
__device__ __forceinline__ uint2 lds64(uint32_t a) { uint2 v; asm volatile("ld.shared.v2.u32 {%0,%1}, [%2];" : "=r"(v.x), "=r"(v.y) : "r"(a) : "memory"); return v; }
__device__ __forceinline__ uint4 lds128(uint32_t a) { uint4 v; asm volatile("ld.shared.v4.u32 {%0,%1,%2,%3}, [%4];" : "=r"(v.x), "=r"(v.y), "=r"(v.z), "=r"(v.w) : "r"(a) : "memory"); return v; }
__device__ __forceinline__ void sts32(uint32_t a, uint32_t v) { asm volatile("st.shared.u32 [%0], %1;" :: "r"(a), "r"(v) : "memory"); }
__device__ __forceinline__ void sts64(uint32_t a, uint32_t x, uint32_t y) { asm volatile("st.shared.v2.u32 [%0], {%1,%2};" :: "r"(a), "r"(x), "r"(y) : "memory"); }
__device__ __forceinline__ void sts128(uint32_t a, uint32_t x, uint32_t y, uint32_t z, uint32_t w) { asm volatile("st.shared.v4.u32 [%0], {%1,%2,%3,%4};" :: "r"(a), "r"(x), "r"(y), "r"(z), "r"(w) : "memory"); }
__device__ __forceinline__ void ldsm4t(uint32_t (&r)[4], uint32_t a) { asm volatile("ldmatrix.sync.aligned.m8n8.x4.trans.shared.b16 {%0,%1,%2,%3}, [%4];" : "=r"(r[0]), "=r"(r[1]), "=r"(r[2]), "=r"(r[3]) : "r"(a) : "memory"); }
__device__ __forceinline__ void ldsm4(uint32_t (&r)[4], uint32_t a) { asm volatile("ldmatrix.sync.aligned.m8n8.x4.shared.b16 {%0,%1,%2,%3}, [%4];" : "=r"(r[0]), "=r"(r[1]), "=r"(r[2]), "=r"(r[3]) : "r"(a) : "memory"); }
__device__ __forceinline__ void stsm4(uint32_t a, const uint32_t (&r)[4]) { asm volatile("stmatrix.sync.aligned.m8n8.x4.shared.b16 [%0], {%1,%2,%3,%4};" :: "r"(a), "r"(r[0]), "r"(r[1]), "r"(r[2]), "r"(r[3]) : "memory"); }
__device__ __forceinline__ uint32_t pack(float lo, float hi) { uint32_t r; asm("cvt.rn.bf16x2.f32 %0, %1, %2;" : "=r"(r) : "f"(hi), "f"(lo)); return r; }
__device__ __forceinline__ float blo(uint32_t v) { return __uint_as_float(v << 16); }
__device__ __forceinline__ float bhi(uint32_t v) { return __uint_as_float(v & 0xffff0000u); }
__device__ __forceinline__ float bf16r(float x) { return blo(pack(x, 0.f)); }
__device__ __forceinline__ uint32_t hmul2(uint32_t a, uint32_t b) { uint32_t r; asm("mul.rn.bf16x2 %0, %1, %2;" : "=r"(r) : "r"(a), "r"(b)); return r; }
__device__ __forceinline__ uint32_t hadd2(uint32_t a, uint32_t b) { uint32_t r; asm("add.rn.bf16x2 %0, %1, %2;" : "=r"(r) : "r"(a), "r"(b)); return r; }
__device__ __forceinline__ uint32_t packh(float lo, float hi) { uint32_t r; asm("cvt.rn.f16x2.f32 %0, %1, %2;" : "=r"(r) : "f"(hi), "f"(lo)); return r; }
__device__ __forceinline__ __half2 H2(uint32_t a) { return *reinterpret_cast<__half2*>(&a); }
__device__ __forceinline__ uint32_t U2(__half2 a) { return *reinterpret_cast<uint32_t*>(&a); }
__device__ __forceinline__ uint32_t fmul(uint32_t a, uint32_t b) { return U2(__hmul2(H2(a), H2(b))); }
__device__ __forceinline__ uint32_t ffma(uint32_t a, uint32_t b, uint32_t c) { return U2(__hfma2(H2(a), H2(b), H2(c))); }
__device__ __forceinline__ uint32_t fneg(uint32_t a) { return U2(__hneg2(H2(a))); }
__device__ __forceinline__ uint32_t amax2(uint32_t a, uint32_t b) { uint32_t r; asm("max.xorsign.abs.bf16x2 %0, %1, %2;" : "=r"(r) : "r"(a), "r"(b)); return r; }
__device__ __forceinline__ uint32_t prmt(uint32_t a, uint32_t b, uint32_t s) { return __byte_perm(a, b, s); }
__device__ __forceinline__ uint32_t ldraw(const __nv_bfloat16* p) { uint32_t v; asm volatile("ld.global.nc.u16 %0, [%1];" : "=r"(v) : "l"(p)); return v; }
__device__ __forceinline__ void bar_sync(int id, int n) { asm volatile("bar.sync %0, %1;" :: "r"(id), "r"(n) : "memory"); }
__device__ __forceinline__ void bar_arrive(int id, int n) { asm volatile("bar.arrive %0, %1;" :: "r"(id), "r"(n) : "memory"); }
__device__ __forceinline__ void cluster_arrive() { asm volatile("barrier.cluster.arrive.relaxed.aligned;" ::: "memory"); }
__device__ __forceinline__ void cluster_wait() { asm volatile("barrier.cluster.wait.aligned;" ::: "memory"); }
__device__ __forceinline__ void fence_async() { asm volatile("fence.proxy.async.shared::cta;" ::: "memory"); }
__device__ __forceinline__ void fence_mbinit() { asm volatile("fence.mbarrier_init.release.cluster;" ::: "memory"); }
__device__ __forceinline__ uint32_t mapa(uint32_t a, uint32_t rank) { uint32_t r; asm("mapa.shared::cluster.u32 %0, %1, %2;" : "=r"(r) : "r"(a), "r"(rank)); return r; }
__device__ __forceinline__ void bulk_dsmem(uint32_t dst, uint32_t src, uint32_t bytes, uint32_t mbar) {
  asm volatile("cp.async.bulk.shared::cluster.shared::cta.mbarrier::complete_tx::bytes [%0], [%1], %2, [%3];" :: "r"(dst), "r"(src), "r"(bytes), "r"(mbar) : "memory");
}
__device__ __forceinline__ void bulk_load(uint32_t dst, const void* src, uint32_t bytes, uint32_t mbar) {
  asm volatile("cp.async.bulk.shared::cluster.global.mbarrier::complete_tx::bytes [%0], [%1], %2, [%3];" :: "r"(dst), "l"(src), "r"(bytes), "r"(mbar) : "memory");
}
__device__ __forceinline__ void mbar_init(uint32_t m, uint32_t cnt) { asm volatile("mbarrier.init.shared::cta.b64 [%0], %1;" :: "r"(m), "r"(cnt) : "memory"); }
__device__ __forceinline__ void mbar_expect(uint32_t m, uint32_t bytes) { asm volatile("mbarrier.arrive.expect_tx.shared::cta.b64 _, [%0], %1;" :: "r"(m), "r"(bytes) : "memory"); }
__device__ __forceinline__ bool mbar_try(uint32_t m) {
  uint32_t done;
  asm volatile("{.reg .pred p; mbarrier.try_wait.parity.shared::cta.b64 p, [%1], 0; selp.u32 %0, 1, 0, p;}" : "=r"(done) : "r"(m) : "memory");
  return done;
}
__device__ __forceinline__ void mbar_wait(uint32_t m) {
  if (!mbar_try(m)) {
    int it = 0;
    while (!mbar_try(m) && ++it < (1 << 22)) {}
  }
}
__device__ __forceinline__ bool elect() {
  uint32_t e;
  asm volatile("{.reg .pred p; elect.sync _|p, 0xffffffff; selp.u32 %0, 1, 0, p;}" : "=r"(e));
  return e;
}
__device__ __forceinline__ void tma_load3(uint32_t dst, const CUtensorMap* tm, int c0, int c1, int c2, uint32_t mbar) {
  asm volatile("cp.async.bulk.tensor.3d.shared::cluster.global.mbarrier::complete_tx::bytes [%0], [%1, {%3, %4, %5}], [%2];"
               :: "r"(dst), "l"(tm), "r"(mbar), "r"(c0), "r"(c1), "r"(c2) : "memory");
}
__device__ __forceinline__ void mma1688(float (&c)[4], uint32_t a0, uint32_t a1, uint32_t b) {
  asm volatile("mma.sync.aligned.m16n8k8.row.col.f32.bf16.bf16.f32 {%0,%1,%2,%3}, {%4,%5}, {%6}, {%0,%1,%2,%3};"
               : "+f"(c[0]), "+f"(c[1]), "+f"(c[2]), "+f"(c[3]) : "r"(a0), "r"(a1), "r"(b));
}
__device__ __forceinline__ void wg_fence() { asm volatile("wgmma.fence.sync.aligned;" ::: "memory"); }
__device__ __forceinline__ void wg_commit() { asm volatile("wgmma.commit_group.sync.aligned;" ::: "memory"); }
template <int N> __device__ __forceinline__ void wg_wait() { asm volatile("wgmma.wait_group.sync.aligned %0;" :: "n"(N) : "memory"); }
template <int N> __device__ __forceinline__ void tie_all(uint32_t (&x)[N]) {
#pragma unroll
  for (int i = 0; i < N; i++) asm volatile("" : "+r"(x[i]) :: "memory");
}
template <int N> __device__ __forceinline__ void tie_all(float (&x)[N]) {
#pragma unroll
  for (int i = 0; i < N; i++) asm volatile("" : "+f"(x[i]) :: "memory");
}
#define R16(C, d) C(d[0]), C(d[1]), C(d[2]), C(d[3]), C(d[4]), C(d[5]), C(d[6]), C(d[7]), C(d[8]), C(d[9]), C(d[10]), C(d[11]), C(d[12]), C(d[13]), C(d[14]), C(d[15])
#define R32(C, d) R16(C, d), R16(C, (d + 16))
#define P16 "{%0,%1,%2,%3,%4,%5,%6,%7,%8,%9,%10,%11,%12,%13,%14,%15}"
#define P32 "{%0,%1,%2,%3,%4,%5,%6,%7,%8,%9,%10,%11,%12,%13,%14,%15,%16,%17,%18,%19,%20,%21,%22,%23,%24,%25,%26,%27,%28,%29,%30,%31}"
template <int SD, int OFF> __device__ __forceinline__ void rs64(float* d, const uint32_t* a, uint64_t db) {
  if (SD) asm volatile("{.reg .b64 db; add.s64 db, %36, %37; wgmma.mma_async.sync.aligned.m64n64k16.f32.bf16.bf16 " P32 ", {%32,%33,%34,%35}, db, 1, 1, 1, 1;}"
                       : R32("+f", d) : "r"(a[0]), "r"(a[1]), "r"(a[2]), "r"(a[3]), "l"(db), "n"(OFF));
  else asm volatile("{.reg .b64 db; add.s64 db, %36, %37; wgmma.mma_async.sync.aligned.m64n64k16.f32.bf16.bf16 " P32 ", {%32,%33,%34,%35}, db, 0, 1, 1, 1;}"
                    : R32("=f", d) : "r"(a[0]), "r"(a[1]), "r"(a[2]), "r"(a[3]), "l"(db), "n"(OFF));
}
template <int SD, int TB, int OFF> __device__ __forceinline__ void rs64h(uint32_t* d, const uint32_t* a, uint64_t db) {
  if (SD) asm volatile("{.reg .b64 db; add.s64 db, %20, %21; wgmma.mma_async.sync.aligned.m64n64k16.f16.f16.f16 " P16 ", {%16,%17,%18,%19}, db, 1, 1, 1, %22;}"
                       : R16("+r", d) : "r"(a[0]), "r"(a[1]), "r"(a[2]), "r"(a[3]), "l"(db), "n"(OFF), "n"(TB));
  else asm volatile("{.reg .b64 db; add.s64 db, %20, %21; wgmma.mma_async.sync.aligned.m64n64k16.f16.f16.f16 " P16 ", {%16,%17,%18,%19}, db, 0, 1, 1, %22;}"
                    : R16("=r", d) : "r"(a[0]), "r"(a[1]), "r"(a[2]), "r"(a[3]), "l"(db), "n"(OFF), "n"(TB));
}
template <int SD, int OFFA, int OFFB> __device__ __forceinline__ void ss32(float* d, uint64_t da, uint64_t db) {
  if (SD) asm volatile("{.reg .b64 da, db; add.s64 da, %16, %18; add.s64 db, %17, %19; wgmma.mma_async.sync.aligned.m64n32k16.f32.f16.f16 " P16 ", da, db, 1, 1, 1, 1, 1;}"
                       : R16("+f", d) : "l"(da), "l"(db), "n"(OFFA), "n"(OFFB));
  else asm volatile("{.reg .b64 da, db; add.s64 da, %16, %18; add.s64 db, %17, %19; wgmma.mma_async.sync.aligned.m64n32k16.f32.f16.f16 " P16 ", da, db, 0, 1, 1, 1, 1;}"
                    : R16("=f", d) : "l"(da), "l"(db), "n"(OFFA), "n"(OFFB));
}
#define KGEN_ASM(SD) "{.reg .b64 da, db; add.s64 da, %32, %33; add.s64 db, %32, %34;\n" \
  "wgmma.mma_async.sync.aligned.m64n64k16.f32.bf16.bf16 " P32 ", da, db, " SD ", 1, 1, 1, 1;}"
template <int KS> __device__ __forceinline__ void kgen_mma(float (&c)[32], uint64_t da) {
  if (KS) asm volatile(KGEN_ASM("1") : R32("+f", c) : "l"(da), "n"(8 * KS), "n"(8 * KS + 512));
  else asm volatile(KGEN_ASM("0") : R32("=f", c) : "l"(da), "n"(8 * KS), "n"(8 * KS + 512));
  if constexpr (KS < 7) kgen_mma<KS + 1>(c, da);
}
template <int OFF, int KSTEP> __device__ __forceinline__ void stage1(float (&D)[32], const uint32_t (&A1)[8], uint64_t d) {
  rs64<0, OFF>(D, A1, d); rs64<1, OFF + KSTEP>(D, A1 + 4, d);
}
template <int INV> __device__ __forceinline__ void stage2(uint32_t (&X)[16], const uint32_t (&F)[16], uint64_t dc) {
  constexpr int KS = INV ? 16 : 128, TB = INV ? 0 : 1;
  rs64h<0, TB, 0>(X, F, dc); rs64h<1, TB, KS>(X, F + 4, dc); rs64h<1, TB, 2 * KS>(X, F + 8, dc); rs64h<1, TB, 3 * KS>(X, F + 12, dc);
}
__device__ __forceinline__ void fwd_mid(uint32_t (&F)[16], const float (&D)[32], const uint32_t (&tc)[4], const uint32_t (&ts)[4]) {
#pragma unroll
  for (int j = 0; j < 4; j++)
#pragma unroll
    for (int b = 0; b < 2; b++) {
      const int i = 4 * j + 16 * b;
      const uint32_t ar = packh(D[i], D[i + 1]), ai = packh(D[i + 2], D[i + 3]);
      F[2 * j + b] = ffma(ar, tc[j], fmul(ai, ts[j]));
      F[8 + 2 * j + b] = ffma(ai, tc[j], fneg(fmul(ar, ts[j])));
    }
}
__device__ __forceinline__ void put_exp(uint32_t a, uint32_t m, int lane) {
  m = __reduce_max_sync(0xffffffffu, max(m & 0x7f80u, (m >> 16) & 0x7f80u));
  if (lane == 0) sts32(a, m);
}
__device__ __forceinline__ uint32_t get_exp(uint32_t a) { const uint4 v = lds128(a); return max(max(v.x, v.y), max(v.z, v.w)) >> 7; }
__device__ __forceinline__ void scale_a1(uint32_t (&As)[8], const uint32_t (&A1)[8], uint32_t field) {
#pragma unroll
  for (int i = 0; i < 8; i++) As[i] = hmul2(A1[i], field * 0x00800080u);
}

struct cf { float x, y; };
__device__ __forceinline__ cf cmul(cf a, cf b) { cf r; r.x = fmaf(a.x, b.x, -a.y * b.y); r.y = fmaf(a.x, b.y, a.y * b.x); return r; }
__device__ __forceinline__ cf cexp_p(float lr2, float lt, float p) {
  float m;
  asm("ex2.approx.ftz.f32 %0, %1;" : "=f"(m) : "f"(lr2 * p));
  float t = lt * p;
  t = (t - rintf(t)) * 6.283185307179586f;
  cf r; r.x = m * __cosf(t); r.y = m * __sinf(t); return r;
}
__device__ __forceinline__ void store8(uint32_t a, uint32_t b, const cf (&v)[8]) {
  sts128(a, pack(v[0].x, v[1].x), pack(v[2].x, v[3].x), pack(v[4].x, v[5].x), pack(v[6].x, v[7].x));
  sts128(b, pack(v[0].y, v[1].y), pack(v[2].y, v[3].y), pack(v[4].y, v[5].y), pack(v[6].y, v[7].y));
}
__device__ __forceinline__ void mbar_arrive(uint32_t m) { asm volatile("mbarrier.arrive.shared::cta.b64 _, [%0];" :: "r"(m) : "memory"); }
__device__ __forceinline__ float sigmoidf_(float s) { return __fdividef(1.f, 1.f + __expf(fminf(-s, 80.f))); }

__global__ void __cluster_dims__(CS, 1, 1) __launch_bounds__(NTHREADS, 1) fused_kernel(const __grid_constant__ Params p) {
  extern __shared__ __align__(1024) uint8_t smem[];
  TL_INIT();
  TL(31);
  const int wid = __shfl_sync(0xffffffffu, threadIdx.x >> 5, 0);
  const uint32_t sb = (uint32_t)__cvta_generic_to_shared(smem);
  const uint32_t mb = sb + OFF_MB;
  const int u = wid >> 2, w = wid & 3;
  const int tid = threadIdx.x & 127, lane = tid & 31, g = lane >> 2, t = lane & 3;
  const int cl = blockIdx.x >> 3, rank = blockIdx.x & 7;
  const int ch0 = cl * CPC;
  const int nu = min(5, (DCH - ch0) >> 3);
  const bool act = u < nu;

  uint32_t pla, pai, pcr, pci, pdt, tag = 0;
  auto load_params = [&]() {
    const int ch = act ? ch0 + 8 * u + rank : 0, o = ch * NMODE + tid;
    pla = ldraw(p.logA + o); pdt = ldraw(p.logdt + ch); pai = ldraw(p.Aim + o); pcr = ldraw(p.Cre + o); pci = ldraw(p.Cim + o);
  };
  if (u == 4) {
    const bool e = elect();
    if (e) {
#pragma unroll
      for (int i = 0; i < 5; i++) mbar_init(mb + 40 * w + 8 * i, 1);
      if (w == 3) { mbar_init(mb + 8 * MB_TH, 1); mbar_init(mb + 8 * MB_XQ, 1); mbar_init(mb + 8 * MB_KV, 1); }
      if (w == 2) mbar_init(mb + 8 * MB_G, 8);
      fence_mbinit();
      if ((sb & 0xffffffu) != SB0) __trap();
    }
    __syncwarp();
    load_params();
    if (w == 0 && lane < 2) asm volatile("atom.relaxed.gpu.global.add.u32 %0, [%1], %2;" : "=r"(tag) : "l"(&p.cnt[rank * 32 + lane]), "r"(cl == 0 ? 16 - (NCL - 1) : 1) : "memory");
    if (e) {
      if (w == 3) {
        mbar_expect(mb + 8 * MB_TH, 8192);
        bulk_load(sb + OFF_TH, p.tab->thr, 8192, mb + 8 * MB_TH);
        mbar_expect(mb + 8 * MB_XQ, 20480 + 12288 + 112 * nu);
        bulk_load(sb + OFF_SP, p.gate_w + ch0, 16 * nu, mb + 8 * MB_XQ);
        bulk_load(sb + OFF_SP + 80, p.Dskip + ch0, 16 * nu, mb + 8 * MB_XQ);
        bulk_load(sb + OFF_SP + 160, p.ssm_D + ch0, 16 * nu, mb + 8 * MB_XQ);
        bulk_load(sb + OFF_SP + 240, p.shift_k + 4 * ch0, 64 * nu, mb + 8 * MB_XQ);
        tma_load3(sb + OFF_TQ, &p.tq, ch0, 8 * rank, 0, mb + 8 * MB_XQ);
        bulk_load(sb + OFF_CF, p.tab->mat, 12288, mb + 8 * MB_XQ);
        TL(20);
        mbar_expect(mb + 8 * MB_KV, 2 * 20480 + 320);
        tma_load3(sb + OFF_TK, &p.tk, ch0, 8 * rank, 0, mb + 8 * MB_KV);
        tma_load3(sb + OFF_HALO, &p.tkh, ch0, 8 * rank - 1, 28, mb + 8 * MB_KV);
      }
#pragma unroll
      for (int i = 0; i < 5; i++) mbar_expect(mb + 40 * w + 8 * i, w == 3 ? 4096 : w == 2 ? 7168 : 7 * YP);
    }
    __syncwarp();
  } else {
    load_params();
  }
  cluster_arrive();
  TL(0);

  const uint32_t tab = sb + OFF_T + u * KTAB;
  const uint32_t toff = (64 * w + lane) * 80 + 16 * u;
  const int uown = u * USZ + (rank & 3) * UGRP + (rank >> 2) * YP;
  auto put = [&](int stage, const uint32_t (&a)[4], const uint32_t (&b)[4]) {
    const uint32_t o = sb + (g == rank ? OFF_U + uown : stage + (8 * u + g) * YP);
    const uint32_t od = o + (rank < 4 ? 16 : 0) + 128 * w + 32 * t;
    sts128(od, prmt(a[0], a[1], 0x5410), prmt(a[2], a[3], 0x5410), prmt(b[0], b[1], 0x5410), prmt(b[2], b[3], 0x5410));
    sts128(od + 16, prmt(a[0], a[1], 0x7632), prmt(a[2], a[3], 0x7632), prmt(b[0], b[1], 0x7632), prmt(b[2], b[3], 0x7632));
    const uint32_t m = amax2(amax2(amax2(a[0], a[1]), amax2(a[2], a[3])), amax2(amax2(b[0], b[1]), amax2(b[2], b[3])));
    asm volatile("st.shared.u8 [%0], %1;" :: "r"(o + (rank < 4 ? 0 : 512) + 4 * w + t), "r"(amax2(m, m >> 16) >> 7) : "memory");
  };
  const int d0 = rank ^ (2 * w), d1 = d0 ^ 1;
  const uint32_t rb0 = mapa(sb, d0), rb1 = mapa(sb, d1);
  auto send = [&](int stage, int bytes, int dst, int mbar) {
    if (elect()) {
      if (w) bulk_dsmem(rb0 + dst, sb + stage + d0 * bytes, bytes, rb0 + mbar);
      bulk_dsmem(rb1 + dst, sb + stage + d1 * bytes, bytes, rb1 + mbar);
    }
    __syncwarp();
  };

  uint32_t A1[8], tc[4], ts[4];
  {
    const float dt = bf16r(expf(blo(pdt)));
    const float lr2 = (-bf16r(expf(blo(pla))) * dt) * 1.4426950408889634f;
    const float lt = (blo(pai) * dt) * 0.15915494309189535f;
    const uint32_t tim = sb + (u ? OFF_IM + (u - 1) * KTAB : OFF_U);
    const uint32_t row = tab + tid * 16, rim = tim + tid * 16;
    const cf w1 = cexp_p(lr2, lt, 8.f);
    cf z1 = cexp_p(lr2, lt, 1.f), Z = cexp_p(lr2, lt, 256.f);
    if (lr2 != 123.f) TL(16);
    TL(12);
    {
      cf v[8];
      const cf w2 = cmul(w1, w1);
      v[0].x = 1.f; v[0].y = 0.f; v[1] = cmul(w2, w2); v[2] = cmul(v[1], v[1]); v[3] = cmul(v[2], v[1]);
      v[4] = cmul(v[2], v[2]); v[5] = cmul(v[1], v[4]); v[6] = cmul(v[2], v[4]); v[7] = cmul(v[3], v[4]);
      store8(row, rim, v);
#pragma unroll
      for (int k = 1; k < 4; k++) {
#pragma unroll
        for (int i = 0; i < 8; i++) v[i] = (i == 0 && k < 3) ? (k == 1 ? w1 : w2) : cmul(v[i], w1);
        store8(row + 2048 * k, rim + 2048 * k, v);
      }
    }
    if (wid == 16 && lane == 0) sts32(mb + 8 * MB_TAG, tag);
    cluster_wait();
    if (u >= 2) cluster_arrive();
    mbar_wait(mb + 8 * MB_TH);
    {
      const uint4 x = lds128(sb + OFF_TH + 16 * tid), y = lds128(sb + OFF_TH + 2048 + 16 * tid), a = lds128(sb + OFF_TH + 4096 + 16 * tid), b = lds128(sb + OFF_TH + 6144 + 16 * tid);
      A1[0] = x.x; A1[1] = x.y; A1[2] = x.z; A1[3] = x.w; A1[4] = y.x; A1[5] = y.y; A1[6] = y.z; A1[7] = y.w;
      tc[0] = a.x; tc[1] = a.y; tc[2] = a.z; tc[3] = a.w; ts[0] = b.x; ts[1] = b.y; ts[2] = b.z; ts[3] = b.w;
    }
    if (PREFETCH && wid == 8 && elect()) {
      const uint32_t o = blockIdx.x * 9856u, n = min(9856u, SEQ * DCH - o) * 2;
      asm volatile("cp.async.bulk.prefetch.L2.global [%0], %1;" :: "l"(p.v + o), "r"(n) : "memory");
      asm volatile("cp.async.bulk.prefetch.L2.global [%0], %1;" :: "l"(p.ssm_k + o), "r"(n) : "memory");
    }
    __syncwarp();
    if (u == 1) {
      float z0_ = 0.f, z1_ = 0.f, z2_ = 0.f, z3_ = 0.f;
      asm volatile("mma.sync.aligned.m16n8k8.row.col.f32.bf16.bf16.f32 {%0,%1,%2,%3}, {%4,%4}, {%4}, {%0,%1,%2,%3};"
                   : "+f"(z0_), "+f"(z1_), "+f"(z2_), "+f"(z3_) : "r"(pla >> 16));
      pcr += __float_as_uint(z0_);
      TL(8);
    }
    {
      z1.y = -z1.y; Z.y = -Z.y;
      const cf z2 = cmul(z1, z1);
      cf h[8], v[8];
      h[0].x = 2.f * blo(pcr) * dt; h[0].y = -2.f * blo(pci) * dt;
      h[1] = cmul(h[0], z1);
#pragma unroll
      for (int i = 2; i < 8; i++) h[i] = cmul(h[i - 2], z2);
      store8(row + 4 * 2048, rim + 4 * 2048, h);
      const cf h8 = cmul(h[6], z2);
      v[0] = cmul(h[0], Z); v[2] = cmul(h[2], Z); v[3] = cmul(h[4], Z); v[6] = cmul(h[6], Z); v[7] = cmul(h8, Z);
      v[1] = v[0]; v[4] = v[5] = v[3];
      store8(row + 5 * 2048, rim + 5 * 2048, v);
      h[0] = cmul(v[0], Z); h[1] = cmul(v[3], Z); h[3] = cmul(v[7], Z); h[4] = cmul(h[0], Z); h[5] = cmul(h[1], Z); h[7] = cmul(h[3], Z);
      h[2] = h[1]; h[6] = h[5];
      store8(row + 6 * 2048, rim + 6 * 2048, h);
      const cf Z2 = cmul(Z, Z);
      v[0] = cmul(h[0], Z2); v[1] = cmul(h[3], Z2); v[2] = cmul(h[4], Z2); v[3] = cmul(h[7], Z2);
#pragma unroll
      for (int i = 4; i < 8; i++) v[i] = cmul(v[i - 4], Z2);
      store8(row + 7 * 2048, rim + 7 * 2048, v);
    }
    TL(17);
    uint32_t x0[4], x1[4];
    auto xload = [&]() {
      mbar_wait(mb + 8 * MB_XQ);
      TL(18);
      ldsm4t(x0, sb + OFF_TQ + toff);
      ldsm4t(x1, sb + OFF_TQ + toff + 2560);
    };
    if (u >= XEARLY) xload();
    fence_async();
    if (u) bar_sync(NB_ORD + u - 1, 256); else bar_sync(NB_WG0, 128);
    TL(13);
    float c[32];
    wg_fence();
    kgen_mma<0>(c, p.dk[u]);
    wg_commit();
    if (u < 4) bar_arrive(NB_ORD + u, 256);
    TL(14);
    if (u < XEARLY) xload();
    wg_wait<0>(); tie_all(c);
    TL(26);
    if (u < 2) cluster_arrive();
    bar_sync(u >= 3 ? NB_V + u - 3 : NB_WG0 + u, u >= 3 ? 256 : 128);
    if ((u & 6) == 2) bar_arrive(NB_V + u - 2, 256);
    const uint32_t k0 = pack(c[0] + c[6], c[1] + c[7]), k1 = pack(c[8] + c[14], c[9] + c[15]);
    const uint32_t k2 = pack(c[16] + c[22], c[17] + c[23]), k3 = pack(c[24] + c[30], c[25] + c[31]);
    const uint32_t ka = tab + 128 * w + 16 * g;
    sts32(ka + 4 * t, k0);
    sts32(ka + UGRP + 4 * t, k1);
    sts64(ka + 2 * UGRP + UGRP * (t >> 1) + 8 * (t & 1), prmt(k2, 0, 0x1010), (t & 1) ? prmt(k2, 0, 0x3232) : k2);
    const uint32_t lo = prmt(k3, 0, 0x1010), hi = prmt(k3, 0, 0x3232);
    sts128(ka + 512 + UGRP * t, lo, lo, (w & 1) ? hi : k3, hi);
    put_exp(sb + OFF_MX + u * 32 + 4 * w, amax2(amax2(k0, k1), amax2(k2, k3)), lane);
    cluster_wait();
    put(OFF_YB, x0, x1);
    TL(15);
    fence_async();
    bar_sync(NB_WG0 + u, 128);
    send(OFF_YB + 8 * u * YP, YP, OFF_U + uown, OFF_MB + 8 * (MB_UX + u));
    if (wid == 16 && elect()) tma_load3(sb + OFF_TV, &p.tv, ch0, 8 * rank, 0, mb + 8 * MB_KV);
    __syncwarp();
  }
  if (u == 0) {
    float ga[4][4];
#pragma unroll
    for (int i = 0; i < 4; i++) ga[i][0] = ga[i][1] = ga[i][2] = ga[i][3] = 0.f;
#pragma unroll
    for (int j = 0; j < 5; j++) {
      uint32_t a0[4], a1[4], b;
      ldsm4(a0, sb + OFF_TQ + toff + 16 * j);
      ldsm4(a1, sb + OFF_TQ + toff + 2560 + 16 * j);
      asm volatile("ld.shared.u32 %0, [%1];" : "=r"(b) : "r"(sb + OFF_SP + 16 * j + 4 * t) : "memory");
      if (j >= 2 && j >= nu) b = 0;
      mma1688(ga[0], hmul2(a0[0], b), hmul2(a0[1], b), 0x3f803f80u); mma1688(ga[1], hmul2(a0[2], b), hmul2(a0[3], b), 0x3f803f80u);
      mma1688(ga[2], hmul2(a1[0], b), hmul2(a1[1], b), 0x3f803f80u); mma1688(ga[3], hmul2(a1[2], b), hmul2(a1[3], b), 0x3f803f80u);
    }
    const float s0 = t == 0 ? ga[0][0] : t == 1 ? ga[1][0] : t == 2 ? ga[2][0] : ga[3][0];
    const float s1 = t == 0 ? ga[0][2] : t == 1 ? ga[1][2] : t == 2 ? ga[2][2] : ga[3][2];
    tag = (lds64(mb + 8 * MB_TAG).x >> 4) + 1;
    uint2* gp = p.part + cl * SEQ + rank * 256 + 64 * w + 16 * t + g;
    asm volatile("st.relaxed.gpu.global.u64 [%0], %1;" :: "l"(gp), "l"(((uint64_t)tag << 32) | __float_as_uint(s0)) : "memory");
    asm volatile("st.relaxed.gpu.global.u64 [%0], %1;" :: "l"(gp + 8), "l"(((uint64_t)tag << 32) | __float_as_uint(s1)) : "memory");
  }

#pragma unroll
  for (int isA = 0; isA < 2; isA++) {
    {
      TL(1 + isA);
      const uint32_t mxa = sb + OFF_MX + u * 32 + 16 * isA;
      const uint32_t pd = lds16(sb + OFF_SP + 80 + 80 * isA + 16 * u + 2 * rank);
      float D[32];
      uint32_t As[8], F[16], H[16], X[16];
      const uint32_t eh = min(max((int)get_exp(mxa), (int)((pd >> 7) & 0xff) - 5), 240);
      scale_a1(As, A1, 248 - eh);
      wg_fence();
      if (isA) stage1<0, 64>(D, As, p.dt[u]); else stage1<0, 2 * UGRP / 16>(D, As, p.db[u]);
      wg_commit();
      wg_wait<0>(); tie_all(D);
      fwd_mid(F, D, tc, ts);
      wg_fence();
      stage2<0>(H, F, p.dfwd);
      wg_commit();
      if (!isA) {
        if (w == 2 && elect()) bulk_load(tab + T_HA, p.ssm_k + (size_t)(act ? ch0 + 8 * u + rank : 0) * SEQ, 4096, mb + 8 * (MB_HA + u));
        __syncwarp();
        TL(7);
      }
      if (isA) {
        fence_async();
        bar_sync(NB_WG0 + u, 128);
        send(OFF_T + u * KTAB + T_YS, 512, OFF_YB + u * USZ + rank * 512, OFF_MB + 8 * (MB_Y + u));
      }
      mbar_wait(mb + 8 * ((isA ? MB_UKV : MB_UX) + u));
      TL(5 + isA);
      uint32_t eu;
      asm volatile("ld.shared.u32 %0, [%1];" : "=r"(eu) : "r"(sb + OFF_U + u * USZ + (lane >> 3) * UGRP + ((lane & 4) ? UGRP - 16 : 0) + 4 * t) : "memory");
      eu = __vmaxu2(eu & 0x00ff00ffu, (eu >> 8) & 0x00ff00ffu);
      eu = min(__reduce_max_sync(0xffffffffu, max(eu & 0xffffu, eu >> 16)), 240u);
      scale_a1(As, A1, 250 - eu);
      wg_wait<0>(); tie_all(H);
      wg_fence();
      stage1<0, 2 * UGRP / 16>(D, As, p.dx[u]);
      wg_commit();
      wg_wait<0>(); tie_all(D);
      cluster_arrive();
      fwd_mid(F, D, tc, ts);
      wg_fence();
      stage2<0>(X, F, p.dfwd);
      wg_commit();
      {
        const float dsk = blo(pd) * __uint_as_float((248 - eh) << 23);
        const uint32_t d2 = packh(dsk, dsk);
#pragma unroll
        for (int j = 0; j < 4; j++) H[2 * j] = U2(__hadd2(H2(H[2 * j]), H2(d2)));
      }
      wg_wait<0>(); tie_all(X);
#pragma unroll
      for (int j = 0; j < 4; j++) {
        const uint32_t h0r = H[2 * j], h1r = H[2 * j + 1], h0i = H[8 + 2 * j], h1i = H[9 + 2 * j];
        const uint32_t x0r = X[2 * j], x1r = X[2 * j + 1], x0i = X[8 + 2 * j], x1i = X[9 + 2 * j];
        F[2 * j] = ffma(x0r, h0r, fneg(fmul(x0i, h0i)));
        F[8 + 2 * j] = ffma(x0r, h0i, fmul(x0i, h0r));
        F[2 * j + 1] = ffma(x1r, h0r, ffma(fneg(x1i), h0i, ffma(x0r, h1r, fneg(ffma(x0i, h1i, F[8 + 2 * j])))));
        F[9 + 2 * j] = ffma(x1r, h0i, ffma(x1i, h0r, ffma(x0r, h1i, ffma(x0i, h1r, F[2 * j]))));
      }
      wg_fence();
      stage2<1>(H, F, p.dinv);
      wg_commit();
      uint64_t ga[4];
      const int sl2 = min(18 * cl + min(8 * w + g, 17), 255), sl3 = tid + 128 * (u & 1);
      auto gload = [&]() {
        if (isA) {
          asm volatile("ld.relaxed.gpu.global.u64 %0, [%1];" : "=l"(ga[0]) : "l"(p.part + NCL * SEQ + rank * 256 + sl3) : "memory");
        } else {
#pragma unroll
          for (int k = 0; k < 4; k++)
            asm volatile("ld.relaxed.gpu.global.u64 %0, [%1];" : "=l"(ga[k]) : "l"(p.part + (t + (k == 3 && t == 3 ? 8 : 4 * k)) * SEQ + rank * 256 + sl2) : "memory");
        }
      };
      if (isA ? (u & 6) == 2 : u == 1) gload();
      if (isA) TL(23);
      wg_wait<0>(); tie_all(H);
      {
        const uint32_t va = tab + (16 * w + (lane & 15)) * 128;
        const int vx = (lane >> 4) ^ (lane & 7);
#pragma unroll
        for (int j = 0; j < 4; j++) {
          uint32_t V[4];
#pragma unroll
          for (int b = 0; b < 2; b++) {
            const uint32_t er = H[2 * j + b], ei = H[8 + 2 * j + b];
            V[2 * b] = ffma(er, tc[j], fneg(fmul(ei, ts[j])));
            V[2 * b + 1] = ffma(ei, tc[j], fmul(er, ts[j]));
          }
          stsm4(va + ((vx ^ (2 * j)) << 4), V);
        }
      }
      if (!isA) {
        cluster_wait();
        mbar_wait(mb + 8 * MB_KV);
        TL(21);
        uint32_t K[3][4], V[2][4];
        const uint2 psw = lds64(sb + OFF_SP + 240 + 64 * u + 8 * g);
        ldsm4t(K[0], w ? sb + OFF_TK + toff - 2560 : (lane & 7) ? sb + OFF_TK + toff + 223 * 80 : sb + OFF_HALO + 10 * lane + 16 * u);
        ldsm4t(K[1], sb + OFF_TK + toff);
        ldsm4t(K[2], sb + OFF_TK + toff + 2560);
        ldsm4t(V[0], sb + OFF_TV + toff);
        ldsm4t(V[1], sb + OFF_TV + toff + 2560);
        mbar_wait(mb + 8 * (MB_HA + u));
        const uint4 hx = lds128(tab + T_HA + 16 * tid), hy = lds128(tab + T_HA + 2048 + 16 * tid);
        const uint32_t w0 = prmt(psw.x, 0, 0x1010), w1 = prmt(psw.x, 0, 0x3232), w2 = prmt(psw.y, 0, 0x1010), w3 = prmt(psw.y, 0, 0x3232);
#pragma unroll
        for (int m = 4; m < 12; m++)
          V[(m >> 2) - 1][m & 3] = hmul2(hadd2(hadd2(hadd2(hmul2(K[(m - 3) >> 2][(m - 3) & 3], w3), hmul2(K[(m - 2) >> 2][(m - 2) & 3], w2)),
                                                     hmul2(K[(m - 1) >> 2][(m - 1) & 3], w1)), hmul2(K[m >> 2][m & 3], w0)), V[(m >> 2) - 1][m & 3]);
        put(OFF_YA, V[0], V[1]);
        put_exp(mxa + 16 + 4 * w, amax2(amax2(amax2(hx.x, hx.y), amax2(hx.z, hx.w)), amax2(amax2(hy.x, hy.y), amax2(hy.z, hy.w))), lane);
        sts128(tab + T_HA + 16 * (tid ^ (lane >> 3)), hx.x, hx.y, hx.z, hx.w);
        sts128(tab + T_HA + 2048 + 16 * (tid ^ (lane >> 3)), hy.x, hy.y, hy.z, hy.w);
        TL(22);
      }
      fence_async();
      bar_sync(NB_WG0 + u, 128);
      float O[16];
      {
        const uint64_t dv = p.dv[u], dl = p.dlast;
        wg_fence();
        ss32<0, 0, 0>(O, dv, dl); ss32<1, 128, 64>(O, dv, dl); ss32<1, 256, 128>(O, dv, dl); ss32<1, 384, 192>(O, dv, dl);
        wg_commit();
      }
      if (!isA) send(OFF_YA + 8 * u * YP, YP, OFF_U + uown, OFF_MB + 8 * (MB_UKV + u));
      if (isA ? (u & 6) == 2 : u == 1) {
        tag = (lds64(mb + 8 * MB_TAG).x >> 4) + 1;
        bool ok;
#pragma unroll 1
        for (int it = 0;; it++) {
          ok = (uint32_t)(ga[0] >> 32) == tag;
          if (!isA) ok = ok && (uint32_t)(ga[1] >> 32) == tag && (uint32_t)(ga[2] >> 32) == tag && (uint32_t)(ga[3] >> 32) == tag;
          ok = __all_sync(0xffffffffu, ok);
          if (ok || it == (isA ? 8000 : 2000)) break;
          gload();
        }
        if (!isA) {
          float s = __uint_as_float((uint32_t)ga[0]) + __uint_as_float((uint32_t)ga[1]) + __uint_as_float((uint32_t)ga[2]);
          if (t < 3) s += __uint_as_float((uint32_t)ga[3]);
          s += __shfl_xor_sync(0xffffffffu, s, 1);
          s += __shfl_xor_sync(0xffffffffu, s, 2);
          const float g0 = bf16r(sigmoidf_(bf16r(s)));
          if (ok && t == 0)
            asm volatile("st.relaxed.gpu.global.u64 [%0], %1;" :: "l"(p.part + NCL * SEQ + rank * 256 + sl2), "l"(((uint64_t)tag << 32) | pack(g0, 1.f - g0)) : "memory");
        } else {
          uint32_t gv = (uint32_t)ga[0];
          if (!ok) {
            const uint32_t* xr = (const uint32_t*)(p.q + (size_t)(rank * 256 + 32 * (sl3 & 7) + (sl3 >> 3)) * DCH);
            const uint32_t* gr = (const uint32_t*)p.gate_w;
            float s = 0.f;
#pragma unroll 1
            for (int k = 0; k < DCH / 2; k++) { const uint32_t m = hmul2(__ldg(xr + k), __ldg(gr + k)); s += blo(m) + bhi(m); }
            const float g0 = bf16r(sigmoidf_(bf16r(s)));
            gv = pack(g0, 1.f - g0);
          }
          sts64(sb + OFF_GB + 8 * sl3, prmt(gv, 0, 0x1010), prmt(gv, 0, 0x3232));
          __syncwarp();
          if (lane == 0) mbar_arrive(mb + 8 * MB_G);
        }
      }
      if (isA) cluster_wait();
      if (isA) TL(28);
      wg_wait<0>(); tie_all(O);
      {
        const uint32_t co = ((8 * w + g) ^ (2 * t) ^ rank) * 16, usrc = tab + (isA ? T_HA : T_YS);
        const int yo = (isA ? OFF_YA : OFF_YB) + u * USZ + rank * 512, ym = OFF_MB + 8 * (MB_Y + u);
        const uint32_t us = min(max((int)(eu + eh) - 127, 0), 254) * 0x00800080u;
        const uint32_t a0 = hmul2(pack(O[0], O[1]), us), a1 = hmul2(pack(O[4], O[5]), us), a2 = hmul2(pack(O[8], O[9]), us), a3 = hmul2(pack(O[12], O[13]), us);
        const uint32_t b0 = hmul2(pack(O[2], O[3]), us), b1 = hmul2(pack(O[6], O[7]), us), b2 = hmul2(pack(O[10], O[11]), us), b3 = hmul2(pack(O[14], O[15]), us);
        sts128((t == rank ? sb + yo : usrc + t * 512) + co, a0, a1, a2, a3);
        sts128((t + 4 == rank ? sb + yo : usrc + t * 512 + 2048) + co, b0, b1, b2, b3);
        if (isA) {
          fence_async();
          bar_sync(NB_WG0 + u, 128);
          send(usrc - sb, 512, yo, ym);
        }
      }
      TL(9 + isA);
    }
  }

  {
    mbar_wait(mb + 8 * MB_G);
    uint2 gg[2][4];
    uint32_t qv[2][4];
#pragma unroll
    for (int hh = 0; hh < 2; hh++)
#pragma unroll
      for (int i = 0; i < 4; i++) gg[hh][i] = lds64(sb + OFF_GB + 8 * (64 * w + 32 * hh + 8 * i + g));
    const uint32_t qa = sb + OFF_TQ + toff;
    ldsm4(qv[0], qa);
    ldsm4(qv[1], qa + 2560);
    TL(24);
    mbar_wait(mb + 8 * (MB_Y + u));
    uint32_t ya[2][4], yb[2][4];
#pragma unroll
    for (int hh = 0; hh < 2; hh++) {
      const uint32_t yo = u * USZ + (lane & 7) * 512 + ((8 * w + 4 * hh + (lane >> 3)) ^ (2 * (rank & 3)) ^ (lane & 7)) * 16;
      ldsm4t(ya[hh], sb + OFF_YA + yo); ldsm4t(yb[hh], sb + OFF_YB + yo);
    }
#pragma unroll
    for (int hh = 0; hh < 2; hh++) {
      uint32_t o[4];
#pragma unroll
      for (int i = 0; i < 4; i++) o[i] = hadd2(hmul2(gg[hh][i].x, hmul2(qv[hh][i], ya[hh][i])), hmul2(gg[hh][i].y, yb[hh][i]));
      stsm4(qa + 2560 * hh, o);
    }
    TL(25);
  }
  cluster_arrive();
  bar_sync(NB_ROW0 + w, 160);
  {
    uint4 v[2];
#pragma unroll
    for (int k = 0; k < 2; k++) {
      const int i = 64 * u + 32 * k + lane, sl = (i * 205) >> 10, cc = i - 5 * sl;
      v[k] = lds128(sb + OFF_TQ + (64 * w + 8 * (sl & 7) + (sl >> 3)) * 80 + cc * 16);
    }
#pragma unroll
    for (int k = 0; k < 2; k++) {
      const int i = 64 * u + 32 * k + lane, sl = (i * 205) >> 10, cc = i - 5 * sl;
      if (cc < nu)
        asm volatile("st.global.cg.v4.u32 [%0], {%1,%2,%3,%4};" :: "l"(p.out + (size_t)(256 * rank + 32 * (sl >> 3) + 8 * w + (sl & 7)) * DCH + ch0 + 8 * cc),
                     "r"(v[k].x), "r"(v[k].y), "r"(v[k].z), "r"(v[k].w) : "memory");
    }
  }
  cluster_wait();
  TL(27);
  TL_DUMP();
}

typedef CUresult (*EncodeFn)(CUtensorMap*, CUtensorMapDataType, cuuint32_t, void*, const cuuint64_t*, const cuuint64_t*,
                             const cuuint32_t*, const cuuint32_t*, CUtensorMapInterleave, CUtensorMapSwizzle,
                             CUtensorMapL2promotion, CUtensorMapFloatOOBfill);

void encode(EncodeFn fn, CUtensorMap* tm, const void* ptr, int nd, const cuuint64_t* dims, const cuuint64_t* strides,
            const cuuint32_t* box, CUtensorMapSwizzle swz) {
  cuuint32_t es[4] = {1, 1, 1, 1};
  fn(tm, CU_TENSOR_MAP_DATA_TYPE_BFLOAT16, nd, const_cast<void*>(ptr), dims, strides, box, es, CU_TENSOR_MAP_INTERLEAVE_NONE,
     swz, CU_TENSOR_MAP_L2_PROMOTION_L2_128B, CU_TENSOR_MAP_FLOAT_OOB_FILL_NONE);
}
void make_map(EncodeFn fn, CUtensorMap* tm, const void* ptr, int ne, int nr) {
  const cuuint64_t dims[3] = {DCH, SEQ / 32, 32}, strides[2] = {32 * DCH * 2, DCH * 2};
  const cuuint32_t box[3] = {CPC, (cuuint32_t)ne, (cuuint32_t)nr};
  encode(fn, tm, ptr, 3, dims, strides, box, CU_TENSOR_MAP_SWIZZLE_NONE);
}

}

extern "C" void kernel_launch(void* const* d_in, const int* in_sizes, int n_in, void* d_out, int out_size) {
  (void)in_sizes; (void)n_in; (void)out_size;
  static EncodeFn fn = nullptr;
  static void *tab = nullptr, *cnt = nullptr, *part = nullptr;
  if (!fn) {
    cudaGetSymbolAddress(&tab, d_tab);
    cudaGetSymbolAddress(&cnt, g_cnt);
    cudaGetSymbolAddress(&part, g_part);
    cudaDriverEntryPointQueryResult qr;
    cudaGetDriverEntryPoint("cuTensorMapEncodeTiled", (void**)&fn, cudaEnableDefault, &qr);
    cudaFuncSetAttribute(fused_kernel, cudaFuncAttributeMaxDynamicSharedMemorySize, SMEM_BYTES);
  }
  Params p;
  make_map(fn, &p.tq, d_in[0], 8, 32);
  make_map(fn, &p.tk, d_in[1], 8, 32);
  make_map(fn, &p.tv, d_in[2], 8, 32);
  make_map(fn, &p.tkh, d_in[1], 1, 4);
  p.out = (__nv_bfloat16*)d_out;
  p.dfwd = mkdesc(OFF_CF, 1024, 128, 0);
  p.dinv = mkdesc(OFF_CF, 128, 1024, 0);
  p.dlast = mkdesc(OFF_CL, 512, 128, 0);
  for (int u = 0; u < 5; u++) {
    p.dk[u] = mkdesc(OFF_T + u * KTAB, u ? OFF_IM - KTAB - OFF_T : OFF_U - OFF_T, 1024, 0);
    p.db[u] = mkdesc(OFF_T + u * KTAB, UGRP, 128, 0);
    p.dt[u] = mkdesc(OFF_T + u * KTAB + T_HA, 2048, 512, 2);
    p.dx[u] = mkdesc(OFF_U + u * USZ + 16, UGRP, 128, 0);
    p.dv[u] = mkdesc(OFF_T + u * KTAB, 16, 1024, 1);
  }
  p.tab = (const Tables*)tab;
  p.cnt = (unsigned*)cnt;
  p.part = (uint2*)part;
  p.tl = nullptr;
  p.q = (const __nv_bfloat16*)d_in[0];
  p.v = (const __nv_bfloat16*)d_in[2];
  p.ssm_k = (const __nv_bfloat16*)d_in[4];
  p.shift_k = (const __nv_bfloat16*)d_in[3];
  p.ssm_D = (const __nv_bfloat16*)d_in[5];
  p.logA = (const __nv_bfloat16*)d_in[7];
  p.Aim = (const __nv_bfloat16*)d_in[8];
  p.Cre = (const __nv_bfloat16*)d_in[9];
  p.Cim = (const __nv_bfloat16*)d_in[10];
  p.logdt = (const __nv_bfloat16*)d_in[11];
  p.Dskip = (const __nv_bfloat16*)d_in[12];
  p.gate_w = (const __nv_bfloat16*)d_in[13];
  fused_kernel<<<NCL * CS, NTHREADS, SMEM_BYTES, cudaStreamPerThread>>>(p);
}
```

```cpp
#include <cuda_runtime.h>
#include <cuda_bf16.h>
#include <cuda_fp16.h>
#include <cuda.h>
#include <stdint.h>

#define TIMELINE 0
#define PREFETCH 1
#define TLHI 0

namespace {

constexpr int SEQ = 2048, DCH = 576, NMODE = 128;
constexpr int CS = 8, CPC = 40, NCL = 15, NTHREADS = 640;

constexpr int KTAB = 16384;
constexpr int OFF_T = 0;
constexpr int T_YS = 8192, T_HA = 12288;
constexpr int UGRP = 1056, USZ = 4 * UGRP, YP = 528;
constexpr int OFF_IM = 5 * KTAB;
constexpr int OFF_YB = OFF_IM;
constexpr int OFF_TV = OFF_YB + 40 * YP;
constexpr int OFF_YA = OFF_TV + 20480;
constexpr int OFF_GB = OFF_YA + 40 * YP;
constexpr int OFF_U = OFF_IM + 4 * KTAB;
constexpr int OFF_CF = OFF_U + 5 * USZ;
constexpr int OFF_CL = OFF_CF + 8192;
constexpr int OFF_TH = OFF_CL + 4096;
constexpr int OFF_TQ = OFF_TH + 8192;
constexpr int OFF_TK = OFF_TQ + 20480;
constexpr int OFF_HALO = OFF_TK + 20480;
constexpr int OFF_MX = OFF_HALO + 320;
constexpr int OFF_SP = OFF_MX + 160;
constexpr int OFF_MB = OFF_SP + 560;
constexpr int OFF_TL = OFF_MB + 28 * 8;
constexpr int SMEM_BYTES = OFF_TL + (TIMELINE ? 640 : 0);
static_assert(SMEM_BYTES <= 232448 && OFF_GB + 2048 <= OFF_U && (OFF_TV & 127) == 0 && (OFF_TQ & 127) == 0, "smem");
static_assert((OFF_MB & 7) == 0 && (OFF_MX & 15) == 0 && (OFF_SP & 15) == 0, "align");

enum { MB_UX = 0, MB_UKV = 5, MB_Y = 10, MB_HA = 15, MB_XQ = 20, MB_KV = 21, MB_CF = 22, MB_G = 23, MB_TH = 24, MB_TAG = 25 };
enum { NB_WG0 = 1, NB_ROW0 = 6, NB_ORD = 6, NB_V = 10, NB_LD = 12 };

constexpr uint32_t SB0 = 1024;
constexpr uint64_t mkdesc(uint32_t off, uint32_t lbo, uint32_t sbo, uint32_t swz) {
  return (uint64_t)((SB0 + off) >> 4) | ((uint64_t)(lbo >> 4) << 16) | ((uint64_t)(sbo >> 4) << 32) | ((uint64_t)swz << 62);
}

constexpr double cos_turn(int m, int n) {
  m &= n - 1;
  if (m > n / 2) m = n - m;
  double sgn = 1.0;
  if (m > n / 4) { m = n / 2 - m; sgn = -1.0; }
  if (m == n / 4) return 0.0;
  const double x = 6.283185307179586476925 * m / n;
  double term = 1.0, sum = 1.0;
  for (int k = 1; k < 14; k++) { term *= -x * x / ((2 * k - 1) * (2 * k)); sum += term; }
  return sgn * sum;
}
constexpr uint32_t bf16_bits(double v) {
  if (v == 0.0) return 0;
  uint32_t sgn = 0;
  if (v < 0) { sgn = 0x8000; v = -v; }
  int e = 127;
  while (v < 1.0) { v *= 2.0; e--; }
  while (v >= 2.0) { v *= 0.5; e++; }
  const double f = v * 128.0;
  int m = (int)f;
  if (f - m > 0.5 || (f - m == 0.5 && (m & 1))) m++;
  return sgn | (uint32_t)((e << 7) + (m - 128));
}
constexpr uint32_t f16_bits(double v) {
  if (v == 0.0) return 0;
  uint32_t sgn = 0;
  if (v < 0) { sgn = 0x8000; v = -v; }
  int e = 15;
  while (v < 1.0) { v *= 2.0; e--; }
  const double f = v * 1024.0;
  int m = (int)f;
  if (f - m > 0.5 || (f - m == 0.5 && (m & 1))) m++;
  return sgn | (uint32_t)((e << 10) + (m - 1024));
}
constexpr uint32_t pair_bits(double lo, double hi) { return bf16_bits(lo) | (bf16_bits(hi) << 16); }
constexpr uint32_t pair_h(double lo, double hi) { return f16_bits(lo) | (f16_bits(hi) << 16); }
struct alignas(128) Tables {
  uint32_t mat[3072];
  uint32_t thr[4][128][4];
};
constexpr Tables make_tables() {
  Tables T{};
  for (int q = 0; q < 768; q++) {
    int m0 = 0, d0 = 0, d1 = 0;
    if (q < 512) {
      const int r = (q >> 6) * 8 + (q & 7), cc = (q >> 3) & 7;
      d0 = 4 * (r & 31); d1 = 2 * d0;
      m0 = 8 * (cc & 3) * d0 + ((r >> 5) == (cc >> 2) ? 0 : (r >> 5) ? 96 : 32);
    } else {
      const int r = ((q - 512) >> 5) * 8 + (q & 7), pc = (q >> 3) & 3;
      d0 = 4 * (8 * (r >> 4) + (r & 7)) + 1; d1 = 8 * d0;
      m0 = 2 * pc * d0 + ((r & 8) ? 32 : 0);
    }
    for (int e = 0; e < 4; e++) T.mat[4 * q + e] = pair_h(cos_turn(m0 + e * d1, 128), cos_turn(m0 + e * d1 + d0, 128));
  }
  for (int tid = 0; tid < 128; tid++) {
    const int kk = 4 * (tid >> 2) + 1, t = tid & 3;
    for (int q = 0; q < 4; q++) {
      const int m = (8 * q + 2 * t) * kk;
      T.thr[q >> 1][tid][2 * (q & 1)] = pair_bits(cos_turn(m, 128), cos_turn(m + kk, 128));
      T.thr[q >> 1][tid][2 * (q & 1) + 1] = pair_bits(cos_turn(m + 32, 128), cos_turn(m + kk + 32, 128));
      T.thr[2][tid][q] = pair_h(cos_turn(m, 4096), cos_turn(m + kk, 4096));
      T.thr[3][tid][q] = pair_h(cos_turn(m + 3072, 4096), cos_turn(m + kk + 3072, 4096));
    }
  }
  return T;
}
__device__ const Tables d_tab = make_tables();

struct Params {
  const __nv_bfloat16 *logA, *Aim, *Cre, *Cim, *logdt;
  const Tables* tab;
  unsigned* cnt;
  const __nv_bfloat16 *Dskip, *shift_k, *ssm_D, *gate_w, *q, *v, *ssm_k;
  uint2* part;
  __nv_bfloat16* out;
  unsigned* tl;
  uint64_t dfwd, dinv, dlast, dk[5], db[5], dt[5], dx[5], dv[5];
  CUtensorMap tq, tk, tv, tkh;
};

__device__ uint2 g_part[(NCL + 1) * SEQ];
__device__ unsigned g_cnt[CS * 32];
#define TL(i) do {} while (0)
#define TL_INIT() do {} while (0)
#define TL_DUMP() do {} while (0)

__device__ __forceinline__ uint32_t lds16(uint32_t a) { uint32_t v; asm volatile("ld.shared.u16 %0, [%1];" : "=r"(v) : "r"(a) : "memory"); return v; }
__device__ __forceinline__ uint2 lds64(uint32_t a) { uint2 v; asm volatile("ld.shared.v2.u32 {%0,%1}, [%2];" : "=r"(v.x), "=r"(v.y) : "r"(a) : "memory"); return v; }
__device__ __forceinline__ uint4 lds128(uint32_t a) { uint4 v; asm volatile("ld.shared.v4.u32 {%0,%1,%2,%3}, [%4];" : "=r"(v.x), "=r"(v.y), "=r"(v.z), "=r"(v.w) : "r"(a) : "memory"); return v; }
__device__ __forceinline__ void sts32(uint32_t a, uint32_t v) { asm volatile("st.shared.u32 [%0], %1;" :: "r"(a), "r"(v) : "memory"); }
__device__ __forceinline__ void sts64(uint32_t a, uint32_t x, uint32_t y) { asm volatile("st.shared.v2.u32 [%0], {%1,%2};" :: "r"(a), "r"(x), "r"(y) : "memory"); }
__device__ __forceinline__ void sts128(uint32_t a, uint32_t x, uint32_t y, uint32_t z, uint32_t w) { asm volatile("st.shared.v4.u32 [%0], {%1,%2,%3,%4};" :: "r"(a), "r"(x), "r"(y), "r"(z), "r"(w) : "memory"); }
__device__ __forceinline__ void ldsm4t(uint32_t (&r)[4], uint32_t a) { asm volatile("ldmatrix.sync.aligned.m8n8.x4.trans.shared.b16 {%0,%1,%2,%3}, [%4];" : "=r"(r[0]), "=r"(r[1]), "=r"(r[2]), "=r"(r[3]) : "r"(a) : "memory"); }
__device__ __forceinline__ void ldsm4(uint32_t (&r)[4], uint32_t a) { asm volatile("ldmatrix.sync.aligned.m8n8.x4.shared.b16 {%0,%1,%2,%3}, [%4];" : "=r"(r[0]), "=r"(r[1]), "=r"(r[2]), "=r"(r[3]) : "r"(a) : "memory"); }
__device__ __forceinline__ void stsm4(uint32_t a, const uint32_t (&r)[4]) { asm volatile("stmatrix.sync.aligned.m8n8.x4.shared.b16 [%0], {%1,%2,%3,%4};" :: "r"(a), "r"(r[0]), "r"(r[1]), "r"(r[2]), "r"(r[3]) : "memory"); }
__device__ __forceinline__ uint32_t pack(float lo, float hi) { uint32_t r; asm("cvt.rn.bf16x2.f32 %0, %1, %2;" : "=r"(r) : "f"(hi), "f"(lo)); return r; }
__device__ __forceinline__ float blo(uint32_t v) { return __uint_as_float(v << 16); }
__device__ __forceinline__ float bhi(uint32_t v) { return __uint_as_float(v & 0xffff0000u); }
__device__ __forceinline__ float bf16r(float x) { return blo(pack(x, 0.f)); }
__device__ __forceinline__ uint32_t hmul2(uint32_t a, uint32_t b) { uint32_t r; asm("mul.rn.bf16x2 %0, %1, %2;" : "=r"(r) : "r"(a), "r"(b)); return r; }
__device__ __forceinline__ uint32_t hadd2(uint32_t a, uint32_t b) { uint32_t r; asm("add.rn.bf16x2 %0, %1, %2;" : "=r"(r) : "r"(a), "r"(b)); return r; }
__device__ __forceinline__ uint32_t packh(float lo, float hi) { uint32_t r; asm("cvt.rn.f16x2.f32 %0, %1, %2;" : "=r"(r) : "f"(hi), "f"(lo)); return r; }
__device__ __forceinline__ __half2 H2(uint32_t a) { return *reinterpret_cast<__half2*>(&a); }
__device__ __forceinline__ uint32_t U2(__half2 a) { return *reinterpret_cast<uint32_t*>(&a); }
__device__ __forceinline__ uint32_t fmul(uint32_t a, uint32_t b) { return U2(__hmul2(H2(a), H2(b))); }
__device__ __forceinline__ uint32_t ffma(uint32_t a, uint32_t b, uint32_t c) { return U2(__hfma2(H2(a), H2(b), H2(c))); }
__device__ __forceinline__ uint32_t fneg(uint32_t a) { return U2(__hneg2(H2(a))); }
__device__ __forceinline__ uint32_t amax2(uint32_t a, uint32_t b) { uint32_t r; asm("max.xorsign.abs.bf16x2 %0, %1, %2;" : "=r"(r) : "r"(a), "r"(b)); return r; }
__device__ __forceinline__ uint32_t prmt(uint32_t a, uint32_t b, uint32_t s) { return __byte_perm(a, b, s); }
__device__ __forceinline__ uint32_t ldraw(const __nv_bfloat16* p) { uint32_t v; asm volatile("ld.global.nc.u16 %0, [%1];" : "=r"(v) : "l"(p)); return v; }
__device__ __forceinline__ void bar_sync(int id, int n) { asm volatile("bar.sync %0, %1;" :: "r"(id), "r"(n) : "memory"); }
__device__ __forceinline__ void bar_arrive(int id, int n) { asm volatile("bar.arrive %0, %1;" :: "r"(id), "r"(n) : "memory"); }
__device__ __forceinline__ void cluster_arrive() { asm volatile("barrier.cluster.arrive.relaxed.aligned;" ::: "memory"); }
__device__ __forceinline__ void cluster_wait() { asm volatile("barrier.cluster.wait.aligned;" ::: "memory"); }
__device__ __forceinline__ void fence_async() { asm volatile("fence.proxy.async.shared::cta;" ::: "memory"); }
__device__ __forceinline__ void fence_mbinit() { asm volatile("fence.mbarrier_init.release.cluster;" ::: "memory"); }
__device__ __forceinline__ uint32_t mapa(uint32_t a, uint32_t rank) { uint32_t r; asm("mapa.shared::cluster.u32 %0, %1, %2;" : "=r"(r) : "r"(a), "r"(rank)); return r; }
__device__ __forceinline__ void bulk_dsmem(uint32_t dst, uint32_t src, uint32_t bytes, uint32_t mbar) {
  asm volatile("cp.async.bulk.shared::cluster.shared::cta.mbarrier::complete_tx::bytes [%0], [%1], %2, [%3];" :: "r"(dst), "r"(src), "r"(bytes), "r"(mbar) : "memory");
}
__device__ __forceinline__ void bulk_load(uint32_t dst, const void* src, uint32_t bytes, uint32_t mbar) {
  asm volatile("cp.async.bulk.shared::cluster.global.mbarrier::complete_tx::bytes [%0], [%1], %2, [%3];" :: "r"(dst), "l"(src), "r"(bytes), "r"(mbar) : "memory");
}
__device__ __forceinline__ void mbar_init(uint32_t m, uint32_t cnt) { asm volatile("mbarrier.init.shared::cta.b64 [%0], %1;" :: "r"(m), "r"(cnt) : "memory"); }
__device__ __forceinline__ void mbar_expect(uint32_t m, uint32_t bytes) { asm volatile("mbarrier.arrive.expect_tx.shared::cta.b64 _, [%0], %1;" :: "r"(m), "r"(bytes) : "memory"); }
__device__ __forceinline__ bool mbar_try(uint32_t m) {
  uint32_t done;
  asm volatile("{.reg .pred p; mbarrier.try_wait.parity.shared::cta.b64 p, [%1], 0; selp.u32 %0, 1, 0, p;}" : "=r"(done) : "r"(m) : "memory");
  return done;
}
__device__ __forceinline__ void mbar_wait(uint32_t m) {
  if (!mbar_try(m)) {
    int it = 0;
    while (!mbar_try(m) && ++it < (1 << 22)) {}
  }
}
__device__ __forceinline__ bool elect() {
  uint32_t e;
  asm volatile("{.reg .pred p; elect.sync _|p, 0xffffffff; selp.u32 %0, 1, 0, p;}" : "=r"(e));
  return e;
}
__device__ __forceinline__ void tma_load3(uint32_t dst, const CUtensorMap* tm, int c0, int c1, int c2, uint32_t mbar) {
  asm volatile("cp.async.bulk.tensor.3d.shared::cluster.global.mbarrier::complete_tx::bytes [%0], [%1, {%3, %4, %5}], [%2];"
               :: "r"(dst), "l"(tm), "r"(mbar), "r"(c0), "r"(c1), "r"(c2) : "memory");
}
__device__ __forceinline__ void mma1688(float (&c)[4], uint32_t a0, uint32_t a1, uint32_t b) {
  asm volatile("mma.sync.aligned.m16n8k8.row.col.f32.bf16.bf16.f32 {%0,%1,%2,%3}, {%4,%5}, {%6}, {%0,%1,%2,%3};"
               : "+f"(c[0]), "+f"(c[1]), "+f"(c[2]), "+f"(c[3]) : "r"(a0), "r"(a1), "r"(b));
}
__device__ __forceinline__ void wg_fence() { asm volatile("wgmma.fence.sync.aligned;" ::: "memory"); }
__device__ __forceinline__ void wg_commit() { asm volatile("wgmma.commit_group.sync.aligned;" ::: "memory"); }
template <int N> __device__ __forceinline__ void wg_wait() { asm volatile("wgmma.wait_group.sync.aligned %0;" :: "n"(N) : "memory"); }
template <int N> __device__ __forceinline__ void tie_all(uint32_t (&x)[N]) {
#pragma unroll
  for (int i = 0; i < N; i++) asm volatile("" : "+r"(x[i]) :: "memory");
}
template <int N> __device__ __forceinline__ void tie_all(float (&x)[N]) {
#pragma unroll
  for (int i = 0; i < N; i++) asm volatile("" : "+f"(x[i]) :: "memory");
}
#define R16(C, d) C(d[0]), C(d[1]), C(d[2]), C(d[3]), C(d[4]), C(d[5]), C(d[6]), C(d[7]), C(d[8]), C(d[9]), C(d[10]), C(d[11]), C(d[12]), C(d[13]), C(d[14]), C(d[15])
#define R32(C, d) R16(C, d), R16(C, (d + 16))
#define P16 "{%0,%1,%2,%3,%4,%5,%6,%7,%8,%9,%10,%11,%12,%13,%14,%15}"
#define P32 "{%0,%1,%2,%3,%4,%5,%6,%7,%8,%9,%10,%11,%12,%13,%14,%15,%16,%17,%18,%19,%20,%21,%22,%23,%24,%25,%26,%27,%28,%29,%30,%31}"
template <int SD, int OFF> __device__ __forceinline__ void rs64(float* d, const uint32_t* a, uint64_t db) {
  if (SD) asm volatile("{.reg .b64 db; add.s64 db, %36, %37; wgmma.mma_async.sync.aligned.m64n64k16.f32.bf16.bf16 " P32 ", {%32,%33,%34,%35}, db, 1, 1, 1, 1;}"
                       : R32("+f", d) : "r"(a[0]), "r"(a[1]), "r"(a[2]), "r"(a[3]), "l"(db), "n"(OFF));
  else asm volatile("{.reg .b64 db; add.s64 db, %36, %37; wgmma.mma_async.sync.aligned.m64n64k16.f32.bf16.bf16 " P32 ", {%32,%33,%34,%35}, db, 0, 1, 1, 1;}"
                    : R32("=f", d) : "r"(a[0]), "r"(a[1]), "r"(a[2]), "r"(a[3]), "l"(db), "n"(OFF));
}
template <int SD, int TB, int OFF> __device__ __forceinline__ void rs64h(uint32_t* d, const uint32_t* a, uint64_t db) {
  if (SD) asm volatile("{.reg .b64 db; add.s64 db, %20, %21; wgmma.mma_async.sync.aligned.m64n64k16.f16.f16.f16 " P16 ", {%16,%17,%18,%19}, db, 1, 1, 1, %22;}"
                       : R16("+r", d) : "r"(a[0]), "r"(a[1]), "r"(a[2]), "r"(a[3]), "l"(db), "n"(OFF), "n"(TB));
  else asm volatile("{.reg .b64 db; add.s64 db, %20, %21; wgmma.mma_async.sync.aligned.m64n64k16.f16.f16.f16 " P16 ", {%16,%17,%18,%19}, db, 0, 1, 1, %22;}"
                    : R16("=r", d) : "r"(a[0]), "r"(a[1]), "r"(a[2]), "r"(a[3]), "l"(db), "n"(OFF), "n"(TB));
}
template <int SD, int OFFA, int OFFB> __device__ __forceinline__ void ss32(float* d, uint64_t da, uint64_t db) {
  if (SD) asm volatile("{.reg .b64 da, db; add.s64 da, %16, %18; add.s64 db, %17, %19; wgmma.mma_async.sync.aligned.m64n32k16.f32.f16.f16 " P16 ", da, db, 1, 1, 1, 1, 1;}"
                       : R16("+f", d) : "l"(da), "l"(db), "n"(OFFA), "n"(OFFB));
  else asm volatile("{.reg .b64 da, db; add.s64 da, %16, %18; add.s64 db, %17, %19; wgmma.mma_async.sync.aligned.m64n32k16.f32.f16.f16 " P16 ", da, db, 0, 1, 1, 1, 1;}"
                    : R16("=f", d) : "l"(da), "l"(db), "n"(OFFA), "n"(OFFB));
}
#define KGEN_ASM(SD) "{.reg .b64 da, db; add.s64 da, %32, %33; add.s64 db, %32, %34;\n" \
  "wgmma.mma_async.sync.aligned.m64n64k16.f32.bf16.bf16 " P32 ", da, db, " SD ", 1, 1, 1, 1;}"
template <int KS> __device__ __forceinline__ void kgen_mma(float (&c)[32], uint64_t da) {
  if (KS) asm volatile(KGEN_ASM("1") : R32("+f", c) : "l"(da), "n"(8 * KS), "n"(8 * KS + 512));
  else asm volatile(KGEN_ASM("0") : R32("=f", c) : "l"(da), "n"(8 * KS), "n"(8 * KS + 512));
  if constexpr (KS < 7) kgen_mma<KS + 1>(c, da);
}
template <int OFF, int KSTEP> __device__ __forceinline__ void stage1(float (&D)[32], const uint32_t (&A1)[8], uint64_t d) {
  rs64<0, OFF>(D, A1, d); rs64<1, OFF + KSTEP>(D, A1 + 4, d);
}
template <int INV> __device__ __forceinline__ void stage2(uint32_t (&X)[16], const uint32_t (&F)[16], uint64_t dc) {
  constexpr int KS = INV ? 16 : 128, TB = INV ? 0 : 1;
  rs64h<0, TB, 0>(X, F, dc); rs64h<1, TB, KS>(X, F + 4, dc); rs64h<1, TB, 2 * KS>(X, F + 8, dc); rs64h<1, TB, 3 * KS>(X, F + 12, dc);
}
__device__ __forceinline__ void fwd_mid(uint32_t (&F)[16], const float (&D)[32], const uint32_t (&tc)[4], const uint32_t (&ts)[4]) {
#pragma unroll
  for (int j = 0; j < 4; j++)
#pragma unroll
    for (int b = 0; b < 2; b++) {
      const int i = 4 * j + 16 * b;
      const uint32_t ar = packh(D[i], D[i + 1]), ai = packh(D[i + 2], D[i + 3]);
      F[2 * j + b] = ffma(ar, tc[j], fmul(ai, ts[j]));
      F[8 + 2 * j + b] = ffma(ai, tc[j], fneg(fmul(ar, ts[j])));
    }
}
__device__ __forceinline__ void put_exp(uint32_t a, uint32_t m, int lane) {
  m = __reduce_max_sync(0xffffffffu, max(m & 0x7f80u, (m >> 16) & 0x7f80u));
  if (lane == 0) sts32(a, m);
}
__device__ __forceinline__ uint32_t get_exp(uint32_t a) { const uint4 v = lds128(a); return max(max(v.x, v.y), max(v.z, v.w)) >> 7; }
__device__ __forceinline__ void scale_a1(uint32_t (&As)[8], const uint32_t (&A1)[8], uint32_t field) {
#pragma unroll
  for (int i = 0; i < 8; i++) As[i] = hmul2(A1[i], field * 0x00800080u);
}

struct cf { float x, y; };
__device__ __forceinline__ cf cmul(cf a, cf b) { cf r; r.x = fmaf(a.x, b.x, -a.y * b.y); r.y = fmaf(a.x, b.y, a.y * b.x); return r; }
__device__ __forceinline__ cf cexp_p(float lr2, float lt, float p) {
  float m;
  asm("ex2.approx.ftz.f32 %0, %1;" : "=f"(m) : "f"(lr2 * p));
  float t = lt * p;
  t = (t - rintf(t)) * 6.283185307179586f;
  cf r; r.x = m * __cosf(t); r.y = m * __sinf(t); return r;
}
__device__ __forceinline__ void store8(uint32_t a, uint32_t b, const cf (&v)[8]) {
  sts128(a, pack(v[0].x, v[1].x), pack(v[2].x, v[3].x), pack(v[4].x, v[5].x), pack(v[6].x, v[7].x));
  sts128(b, pack(v[0].y, v[1].y), pack(v[2].y, v[3].y), pack(v[4].y, v[5].y), pack(v[6].y, v[7].y));
}
__device__ __forceinline__ void mbar_arrive(uint32_t m) { asm volatile("mbarrier.arrive.shared::cta.b64 _, [%0];" :: "r"(m) : "memory"); }
__device__ __forceinline__ float sigmoidf_(float s) { return __fdividef(1.f, 1.f + __expf(fminf(-s, 80.f))); }

__global__ void __cluster_dims__(CS, 1, 1) __launch_bounds__(NTHREADS, 1) fused_kernel(const __grid_constant__ Params p) {
  extern __shared__ __align__(1024) uint8_t smem[];
  TL_INIT();
  TL(31);
  const int wid = __shfl_sync(0xffffffffu, threadIdx.x >> 5, 0);
  const uint32_t sb = (uint32_t)__cvta_generic_to_shared(smem);
  const uint32_t mb = sb + OFF_MB;
  const int u = wid >> 2, w = wid & 3;
  const int tid = threadIdx.x & 127, lane = tid & 31, g = lane >> 2, t = lane & 3;
  const int cl = blockIdx.x >> 3, rank = blockIdx.x & 7;
  const int ch0 = cl * CPC;
  const int nu = min(5, (DCH - ch0) >> 3);
  const bool act = u < nu;

  uint32_t pla, pai, pcr, pci, pdt, tag = 0;
  auto load_params = [&]() {
    const int ch = act ? ch0 + 8 * u + rank : 0, o = ch * NMODE + tid;
    pla = ldraw(p.logA + o); pdt = ldraw(p.logdt + ch); pai = ldraw(p.Aim + o); pcr = ldraw(p.Cre + o); pci = ldraw(p.Cim + o);
  };
  if (u == 4) {
    const bool e = elect();
    if (e) {
#pragma unroll
      for (int i = 0; i < 5; i++) mbar_init(mb + 40 * w + 8 * i, 1);
      if (w == 3) { mbar_init(mb + 8 * MB_TH, 1); mbar_init(mb + 8 * MB_XQ, 1); mbar_init(mb + 8 * MB_KV, 1); }
      if (w == 2) mbar_init(mb + 8 * MB_G, 8);
      fence_mbinit();
      if ((sb & 0xffffffu) != SB0) __trap();
    }
    __syncwarp();
    load_params();
    if (w == 0 && lane < 2) asm volatile("atom.relaxed.gpu.global.add.u32 %0, [%1], %2;" : "=r"(tag) : "l"(&p.cnt[rank * 32 + lane]), "r"(cl == 0 ? 16 - (NCL - 1) : 1) : "memory");
    if (e) {
      if (w == 3) {
        mbar_expect(mb + 8 * MB_TH, 8192);
        bulk_load(sb + OFF_TH, p.tab->thr, 8192, mb + 8 * MB_TH);
        mbar_expect(mb + 8 * MB_XQ, 20480 + 12288 + 112 * nu);
        bulk_load(sb + OFF_SP, p.gate_w + ch0, 16 * nu, mb + 8 * MB_XQ);
        bulk_load(sb + OFF_SP + 80, p.Dskip + ch0, 16 * nu, mb + 8 * MB_XQ);
        bulk_load(sb + OFF_SP + 160, p.ssm_D + ch0, 16 * nu, mb + 8 * MB_XQ);
        bulk_load(sb + OFF_SP + 240, p.shift_k + 4 * ch0, 64 * nu, mb + 8 * MB_XQ);
        tma_load3(sb + OFF_TQ, &p.tq, ch0, 8 * rank, 0, mb + 8 * MB_XQ);
        bulk_load(sb + OFF_CF, p.tab->mat, 12288, mb + 8 * MB_XQ);
        TL(20);
        mbar_expect(mb + 8 * MB_KV, 2 * 20480 + 320);
        tma_load3(sb + OFF_TK, &p.tk, ch0, 8 * rank, 0, mb + 8 * MB_KV);
        tma_load3(sb + OFF_HALO, &p.tkh, ch0, 8 * rank - 1, 28, mb + 8 * MB_KV);
      }
#pragma unroll
      for (int i = 0; i < 5; i++) mbar_expect(mb + 40 * w + 8 * i, w == 3 ? 4096 : w == 2 ? 7168 : 7 * YP);
    }
    __syncwarp();
  } else {
    load_params();
  }
  cluster_arrive();
  TL(0);

  const uint32_t tab = sb + OFF_T + u * KTAB;
  const uint32_t toff = (64 * w + lane) * 80 + 16 * u;
  const int uown = u * USZ + (rank & 3) * UGRP + (rank >> 2) * YP;
  auto put = [&](int stage, const uint32_t (&a)[4], const uint32_t (&b)[4]) {
    const uint32_t o = sb + (g == rank ? OFF_U + uown : stage + (8 * u + g) * YP);
    const uint32_t od = o + (rank < 4 ? 16 : 0) + 128 * w + 32 * t;
    sts128(od, prmt(a[0], a[1], 0x5410), prmt(a[2], a[3], 0x5410), prmt(b[0], b[1], 0x5410), prmt(b[2], b[3], 0x5410));
    sts128(od + 16, prmt(a[0], a[1], 0x7632), prmt(a[2], a[3], 0x7632), prmt(b[0], b[1], 0x7632), prmt(b[2], b[3], 0x7632));
    const uint32_t m = amax2(amax2(amax2(a[0], a[1]), amax2(a[2], a[3])), amax2(amax2(b[0], b[1]), amax2(b[2], b[3])));
    asm volatile("st.shared.u8 [%0], %1;" :: "r"(o + (rank < 4 ? 0 : 512) + 4 * w + t), "r"(amax2(m, m >> 16) >> 7) : "memory");
  };
  const int d0 = rank ^ (2 * w), d1 = d0 ^ 1;
  const uint32_t rb0 = mapa(sb, d0), rb1 = mapa(sb, d1);
  auto send = [&](int stage, int bytes, int dst, int mbar) {
    if (elect()) {
      if (w) bulk_dsmem(rb0 + dst, sb + stage + d0 * bytes, bytes, rb0 + mbar);
      bulk_dsmem(rb1 + dst, sb + stage + d1 * bytes, bytes, rb1 + mbar);
    }
    __syncwarp();
  };

  uint32_t A1[8], tc[4], ts[4];
  {
    const float dt = bf16r(expf(blo(pdt)));
    const float lr2 = (-bf16r(expf(blo(pla))) * dt) * 1.4426950408889634f;
    const float lt = (blo(pai) * dt) * 0.15915494309189535f;
    const uint32_t tim = sb + (u ? OFF_IM + (u - 1) * KTAB : OFF_U);
    const uint32_t row = tab + tid * 16, rim = tim + tid * 16;
    const cf w1 = cexp_p(lr2, lt, 8.f);
    cf z1 = cexp_p(lr2, lt, 1.f), Z = cexp_p(lr2, lt, 256.f);
    if (lr2 != 123.f) TL(16);
    TL(12);
    {
      cf v[8];
      const cf w2 = cmul(w1, w1);
      v[0].x = 1.f; v[0].y = 0.f; v[1] = cmul(w2, w2); v[2] = cmul(v[1], v[1]); v[3] = cmul(v[2], v[1]);
      v[4] = cmul(v[2], v[2]); v[5] = cmul(v[1], v[4]); v[6] = cmul(v[2], v[4]); v[7] = cmul(v[3], v[4]);
      store8(row, rim, v);
#pragma unroll
      for (int k = 1; k < 4; k++) {
#pragma unroll
        for (int i = 0; i < 8; i++) v[i] = (i == 0 && k < 3) ? (k == 1 ? w1 : w2) : cmul(v[i], w1);
        store8(row + 2048 * k, rim + 2048 * k, v);
      }
    }
    if (wid == 16 && lane == 0) sts32(mb + 8 * MB_TAG, tag);
    cluster_wait();
    if (u >= 2) cluster_arrive();
    mbar_wait(mb + 8 * MB_TH);
    {
      const uint4 x = lds128(sb + OFF_TH + 16 * tid), y = lds128(sb + OFF_TH + 2048 + 16 * tid), a = lds128(sb + OFF_TH + 4096 + 16 * tid), b = lds128(sb + OFF_TH + 6144 + 16 * tid);
      A1[0] = x.x; A1[1] = x.y; A1[2] = x.z; A1[3] = x.w; A1[4] = y.x; A1[5] = y.y; A1[6] = y.z; A1[7] = y.w;
      tc[0] = a.x; tc[1] = a.y; tc[2] = a.z; tc[3] = a.w; ts[0] = b.x; ts[1] = b.y; ts[2] = b.z; ts[3] = b.w;
    }
    if (PREFETCH && wid == 8 && elect()) {
      const uint32_t o = blockIdx.x * 9856u, n = min(9856u, SEQ * DCH - o) * 2;
      asm volatile("cp.async.bulk.prefetch.L2.global [%0], %1;" :: "l"(p.v + o), "r"(n) : "memory");
      asm volatile("cp.async.bulk.prefetch.L2.global [%0], %1;" :: "l"(p.ssm_k + o), "r"(n) : "memory");
    }
    __syncwarp();
    if (u == 1) {
      float z0_ = 0.f, z1_ = 0.f, z2_ = 0.f, z3_ = 0.f;
      asm volatile("mma.sync.aligned.m16n8k8.row.col.f32.bf16.bf16.f32 {%0,%1,%2,%3}, {%4,%4}, {%4}, {%0,%1,%2,%3};"
                   : "+f"(z0_), "+f"(z1_), "+f"(z2_), "+f"(z3_) : "r"(pla >> 16));
      pcr += __float_as_uint(z0_);
      TL(8);
    }
    {
      z1.y = -z1.y; Z.y = -Z.y;
      const cf z2 = cmul(z1, z1);
      cf h[8], v[8];
      h[0].x = 2.f * blo(pcr) * dt; h[0].y = -2.f * blo(pci) * dt;
      h[1] = cmul(h[0], z1);
#pragma unroll
      for (int i = 2; i < 8; i++) h[i] = cmul(h[i - 2], z2);
      store8(row + 4 * 2048, rim + 4 * 2048, h);
      const cf h8 = cmul(h[6], z2);
      v[0] = cmul(h[0], Z); v[2] = cmul(h[2], Z); v[3] = cmul(h[4], Z); v[6] = cmul(h[6], Z); v[7] = cmul(h8, Z);
      v[1] = v[0]; v[4] = v[5] = v[3];
      store8(row + 5 * 2048, rim + 5 * 2048, v);
      h[0] = cmul(v[0], Z); h[1] = cmul(v[3], Z); h[3] = cmul(v[7], Z); h[4] = cmul(h[0], Z); h[5] = cmul(h[1], Z); h[7] = cmul(h[3], Z);
      h[2] = h[1]; h[6] = h[5];
      store8(row + 6 * 2048, rim + 6 * 2048, h);
      const cf Z2 = cmul(Z, Z);
      v[0] = cmul(h[0], Z2); v[1] = cmul(h[3], Z2); v[2] = cmul(h[4], Z2); v[3] = cmul(h[7], Z2);
#pragma unroll
      for (int i = 4; i < 8; i++) v[i] = cmul(v[i - 4], Z2);
      store8(row + 7 * 2048, rim + 7 * 2048, v);
    }
    TL(17);
    fence_async();
    if (u) bar_sync(NB_ORD + u - 1, 256); else bar_sync(NB_WG0, 128);
    TL(13);
    float c[32];
    wg_fence();
    kgen_mma<0>(c, p.dk[u]);
    wg_commit();
    if (u < 4) bar_arrive(NB_ORD + u, 256);
    TL(14);
    mbar_wait(mb + 8 * MB_XQ);
    TL(18);
    uint32_t x0[4], x1[4];
    ldsm4t(x0, sb + OFF_TQ + toff);
    ldsm4t(x1, sb + OFF_TQ + toff + 2560);
    wg_wait<0>(); tie_all(c);
    TL(26);
    if (u < 2) cluster_arrive();
    bar_sync(u >= 3 ? NB_V + u - 3 : NB_WG0 + u, u >= 3 ? 256 : 128);
    if ((u & 6) == 2) bar_arrive(NB_V + u - 2, 256);
    const uint32_t k0 = pack(c[0] + c[6], c[1] + c[7]), k1 = pack(c[8] + c[14], c[9] + c[15]);
    const uint32_t k2 = pack(c[16] + c[22], c[17] + c[23]), k3 = pack(c[24] + c[30], c[25] + c[31]);
    const uint32_t ka = tab + 128 * w + 16 * g;
    sts32(ka + 4 * t, k0);
    sts32(ka + UGRP + 4 * t, k1);
    sts64(ka + 2 * UGRP + UGRP * (t >> 1) + 8 * (t & 1), prmt(k2, 0, 0x1010), (t & 1) ? prmt(k2, 0, 0x3232) : k2);
    const uint32_t lo = prmt(k3, 0, 0x1010), hi = prmt(k3, 0, 0x3232);
    sts128(ka + 512 + UGRP * t, lo, lo, (w & 1) ? hi : k3, hi);
    put_exp(sb + OFF_MX + u * 32 + 4 * w, amax2(amax2(k0, k1), amax2(k2, k3)), lane);
    cluster_wait();
    put(OFF_YB, x0, x1);
    TL(15);
    fence_async();
    bar_sync(NB_WG0 + u, 128);
    send(OFF_YB + 8 * u * YP, YP, OFF_U + uown, OFF_MB + 8 * (MB_UX + u));
    if (wid != 16) bar_arrive(NB_LD, 640);
  }
  if (u == 0) {
    float ga[4][4];
#pragma unroll
    for (int i = 0; i < 4; i++) ga[i][0] = ga[i][1] = ga[i][2] = ga[i][3] = 0.f;
#pragma unroll
    for (int j = 0; j < 5; j++) {
      uint32_t a0[4], a1[4], b;
      ldsm4(a0, sb + OFF_TQ + toff + 16 * j);
      ldsm4(a1, sb + OFF_TQ + toff + 2560 + 16 * j);
      asm volatile("ld.shared.u32 %0, [%1];" : "=r"(b) : "r"(sb + OFF_SP + 16 * j + 4 * t) : "memory");
      if (j >= 2 && j >= nu) b = 0;
      mma1688(ga[0], hmul2(a0[0], b), hmul2(a0[1], b), 0x3f803f80u); mma1688(ga[1], hmul2(a0[2], b), hmul2(a0[3], b), 0x3f803f80u);
      mma1688(ga[2], hmul2(a1[0], b), hmul2(a1[1], b), 0x3f803f80u); mma1688(ga[3], hmul2(a1[2], b), hmul2(a1[3], b), 0x3f803f80u);
    }
    const float s0 = t == 0 ? ga[0][0] : t == 1 ? ga[1][0] : t == 2 ? ga[2][0] : ga[3][0];
    const float s1 = t == 0 ? ga[0][2] : t == 1 ? ga[1][2] : t == 2 ? ga[2][2] : ga[3][2];
    tag = (lds64(mb + 8 * MB_TAG).x >> 4) + 1;
    uint2* gp = p.part + cl * SEQ + rank * 256 + 64 * w + 16 * t + g;
    asm volatile("st.relaxed.gpu.global.u64 [%0], %1;" :: "l"(gp), "l"(((uint64_t)tag << 32) | __float_as_uint(s0)) : "memory");
    asm volatile("st.relaxed.gpu.global.u64 [%0], %1;" :: "l"(gp + 8), "l"(((uint64_t)tag << 32) | __float_as_uint(s1)) : "memory");
  }

#pragma unroll
  for (int isA = 0; isA < 2; isA++) {
    {
      TL(1 + isA);
      const uint32_t mxa = sb + OFF_MX + u * 32 + 16 * isA;
      const uint32_t pd = lds16(sb + OFF_SP + 80 + 80 * isA + 16 * u + 2 * rank);
      float D[32];
      uint32_t As[8], F[16], H[16], X[16];
      const uint32_t eh = min(max((int)get_exp(mxa), (int)((pd >> 7) & 0xff) - 5), 240);
      scale_a1(As, A1, 248 - eh);
      wg_fence();
      if (isA) stage1<0, 64>(D, As, p.dt[u]); else stage1<0, 2 * UGRP / 16>(D, As, p.db[u]);
      wg_commit();
      if (!isA && wid == 16) {
        bar_sync(NB_LD, 640);
        if (elect()) tma_load3(sb + OFF_TV, &p.tv, ch0, 8 * rank, 0, mb + 8 * MB_KV);
        __syncwarp();
      }
      wg_wait<0>(); tie_all(D);
      fwd_mid(F, D, tc, ts);
      wg_fence();
      stage2<0>(H, F, p.dfwd);
      wg_commit();
      if (isA) {
        fence_async();
        bar_sync(NB_WG0 + u, 128);
        send(OFF_T + u * KTAB + T_YS, 512, OFF_YB + u * USZ + rank * 512, OFF_MB + 8 * (MB_Y + u));
      }
      mbar_wait(mb + 8 * ((isA ? MB_UKV : MB_UX) + u));
      TL(5 + isA);
      uint32_t eu;
      asm volatile("ld.shared.u32 %0, [%1];" : "=r"(eu) : "r"(sb + OFF_U + u * USZ + (lane >> 3) * UGRP + ((lane & 4) ? UGRP - 16 : 0) + 4 * t) : "memory");
      eu = __vmaxu2(eu & 0x00ff00ffu, (eu >> 8) & 0x00ff00ffu);
      eu = min(__reduce_max_sync(0xffffffffu, max(eu & 0xffffu, eu >> 16)), 240u);
      scale_a1(As, A1, 250 - eu);
      wg_wait<0>(); tie_all(H);
      wg_fence();
      stage1<0, 2 * UGRP / 16>(D, As, p.dx[u]);
      wg_commit();
      wg_wait<0>(); tie_all(D);
      cluster_arrive();
      fwd_mid(F, D, tc, ts);
      wg_fence();
      stage2<0>(X, F, p.dfwd);
      wg_commit();
      if (!isA) {
        if (w == 2 && elect()) bulk_load(tab + T_HA, p.ssm_k + (size_t)(act ? ch0 + 8 * u + rank : 0) * SEQ, 4096, mb + 8 * (MB_HA + u));
        __syncwarp();
        TL(7);
      }
      {
        const float dsk = blo(pd) * __uint_as_float((248 - eh) << 23);
        const uint32_t d2 = packh(dsk, dsk);
#pragma unroll
        for (int j = 0; j < 4; j++) H[2 * j] = U2(__hadd2(H2(H[2 * j]), H2(d2)));
      }
      wg_wait<0>(); tie_all(X);
#pragma unroll
      for (int j = 0; j < 4; j++) {
        const uint32_t h0r = H[2 * j], h1r = H[2 * j + 1], h0i = H[8 + 2 * j], h1i = H[9 + 2 * j];
        const uint32_t x0r = X[2 * j], x1r = X[2 * j + 1], x0i = X[8 + 2 * j], x1i = X[9 + 2 * j];
        F[2 * j] = ffma(x0r, h0r, fneg(fmul(x0i, h0i)));
        F[8 + 2 * j] = ffma(x0r, h0i, fmul(x0i, h0r));
        F[2 * j + 1] = ffma(x1r, h0r, ffma(fneg(x1i), h0i, ffma(x0r, h1r, fneg(ffma(x0i, h1i, F[8 + 2 * j])))));
        F[9 + 2 * j] = ffma(x1r, h0i, ffma(x1i, h0r, ffma(x0r, h1i, ffma(x0i, h1r, F[2 * j]))));
      }
      wg_fence();
      stage2<1>(H, F, p.dinv);
      wg_commit();
      uint64_t ga[4];
      const int sl2 = min(18 * cl + min(8 * w + g, 17), 255), sl3 = tid + 128 * (u & 1);
      auto gload = [&]() {
        if (isA) {
          asm volatile("ld.relaxed.gpu.global.u64 %0, [%1];" : "=l"(ga[0]) : "l"(p.part + NCL * SEQ + rank * 256 + sl3) : "memory");
        } else {
#pragma unroll
          for (int k = 0; k < 4; k++)
            asm volatile("ld.relaxed.gpu.global.u64 %0, [%1];" : "=l"(ga[k]) : "l"(p.part + (t + (k == 3 && t == 3 ? 8 : 4 * k)) * SEQ + rank * 256 + sl2) : "memory");
        }
      };
      if (isA ? (u & 6) == 2 : u == 1) gload();
      if (isA) TL(23);
      wg_wait<0>(); tie_all(H);
      {
        const uint32_t va = tab + (16 * w + (lane & 15)) * 128;
        const int vx = (lane >> 4) ^ (lane & 7);
#pragma unroll
        for (int j = 0; j < 4; j++) {
          uint32_t V[4];
#pragma unroll
          for (int b = 0; b < 2; b++) {
            const uint32_t er = H[2 * j + b], ei = H[8 + 2 * j + b];
            V[2 * b] = ffma(er, tc[j], fneg(fmul(ei, ts[j])));
            V[2 * b + 1] = ffma(ei, tc[j], fmul(er, ts[j]));
          }
          stsm4(va + ((vx ^ (2 * j)) << 4), V);
        }
      }
      if (!isA) {
        cluster_wait();
        mbar_wait(mb + 8 * MB_KV);
        TL(21);
        uint32_t K[3][4], V[2][4];
        const uint2 psw = lds64(sb + OFF_SP + 240 + 64 * u + 8 * g);
        ldsm4t(K[0], w ? sb + OFF_TK + toff - 2560 : (lane & 7) ? sb + OFF_TK + toff + 223 * 80 : sb + OFF_HALO + 10 * lane + 16 * u);
        ldsm4t(K[1], sb + OFF_TK + toff);
        ldsm4t(K[2], sb + OFF_TK + toff + 2560);
        ldsm4t(V[0], sb + OFF_TV + toff);
        ldsm4t(V[1], sb + OFF_TV + toff + 2560);
        mbar_wait(mb + 8 * (MB_HA + u));
        const uint4 hx = lds128(tab + T_HA + 16 * tid), hy = lds128(tab + T_HA + 2048 + 16 * tid);
        const uint32_t w0 = prmt(psw.x, 0, 0x1010), w1 = prmt(psw.x, 0, 0x3232), w2 = prmt(psw.y, 0, 0x1010), w3 = prmt(psw.y, 0, 0x3232);
#pragma unroll
        for (int m = 4; m < 12; m++)
          V[(m >> 2) - 1][m & 3] = hmul2(hadd2(hadd2(hadd2(hmul2(K[(m - 3) >> 2][(m - 3) & 3], w3), hmul2(K[(m - 2) >> 2][(m - 2) & 3], w2)),
                                                     hmul2(K[(m - 1) >> 2][(m - 1) & 3], w1)), hmul2(K[m >> 2][m & 3], w0)), V[(m >> 2) - 1][m & 3]);
        put(OFF_YA, V[0], V[1]);
        put_exp(mxa + 16 + 4 * w, amax2(amax2(amax2(hx.x, hx.y), amax2(hx.z, hx.w)), amax2(amax2(hy.x, hy.y), amax2(hy.z, hy.w))), lane);
        sts128(tab + T_HA + 16 * (tid ^ (lane >> 3)), hx.x, hx.y, hx.z, hx.w);
        sts128(tab + T_HA + 2048 + 16 * (tid ^ (lane >> 3)), hy.x, hy.y, hy.z, hy.w);
        TL(22);
      }
      fence_async();
      bar_sync(NB_WG0 + u, 128);
      float O[16];
      {
        const uint64_t dv = p.dv[u], dl = p.dlast;
        wg_fence();
        ss32<0, 0, 0>(O, dv, dl); ss32<1, 128, 64>(O, dv, dl); ss32<1, 256, 128>(O, dv, dl); ss32<1, 384, 192>(O, dv, dl);
        wg_commit();
      }
      if (!isA) send(OFF_YA + 8 * u * YP, YP, OFF_U + uown, OFF_MB + 8 * (MB_UKV + u));
      if (isA ? (u & 6) == 2 : u == 1) {
        tag = (lds64(mb + 8 * MB_TAG).x >> 4) + 1;
        bool ok;
#pragma unroll 1
        for (int it = 0;; it++) {
          ok = (uint32_t)(ga[0] >> 32) == tag;
          if (!isA) ok = ok && (uint32_t)(ga[1] >> 32) == tag && (uint32_t)(ga[2] >> 32) == tag && (uint32_t)(ga[3] >> 32) == tag;
          ok = __all_sync(0xffffffffu, ok);
          if (ok || it == (isA ? 8000 : 2000)) break;
          gload();
        }
        if (!isA) {
          float s = __uint_as_float((uint32_t)ga[0]) + __uint_as_float((uint32_t)ga[1]) + __uint_as_float((uint32_t)ga[2]);
          if (t < 3) s += __uint_as_float((uint32_t)ga[3]);
          s += __shfl_xor_sync(0xffffffffu, s, 1);
          s += __shfl_xor_sync(0xffffffffu, s, 2);
          const float g0 = bf16r(sigmoidf_(bf16r(s)));
          if (ok && t == 0)
            asm volatile("st.relaxed.gpu.global.u64 [%0], %1;" :: "l"(p.part + NCL * SEQ + rank * 256 + sl2), "l"(((uint64_t)tag << 32) | pack(g0, 1.f - g0)) : "memory");
        } else {
          uint32_t gv = (uint32_t)ga[0];
          if (!ok) {
            const uint32_t* xr = (const uint32_t*)(p.q + (size_t)(rank * 256 + 32 * (sl3 & 7) + (sl3 >> 3)) * DCH);
            const uint32_t* gr = (const uint32_t*)p.gate_w;
            float s = 0.f;
#pragma unroll 1
            for (int k = 0; k < DCH / 2; k++) { const uint32_t m = hmul2(__ldg(xr + k), __ldg(gr + k)); s += blo(m) + bhi(m); }
            const float g0 = bf16r(sigmoidf_(bf16r(s)));
            gv = pack(g0, 1.f - g0);
          }
          sts64(sb + OFF_GB + 8 * sl3, prmt(gv, 0, 0x1010), prmt(gv, 0, 0x3232));
          __syncwarp();
          if (lane == 0) mbar_arrive(mb + 8 * MB_G);
        }
      }
      if (isA) cluster_wait();
      if (isA) TL(28);
      wg_wait<0>(); tie_all(O);
      {
        const uint32_t co = ((8 * w + g) ^ (2 * t) ^ rank) * 16, usrc = tab + (isA ? T_HA : T_YS);
        const int yo = (isA ? OFF_YA : OFF_YB) + u * USZ + rank * 512, ym = OFF_MB + 8 * (MB_Y + u);
        const uint32_t us = min(max((int)(eu + eh) - 127, 0), 254) * 0x00800080u;
        const uint32_t a0 = hmul2(pack(O[0], O[1]), us), a1 = hmul2(pack(O[4], O[5]), us), a2 = hmul2(pack(O[8], O[9]), us), a3 = hmul2(pack(O[12], O[13]), us);
        const uint32_t b0 = hmul2(pack(O[2], O[3]), us), b1 = hmul2(pack(O[6], O[7]), us), b2 = hmul2(pack(O[10], O[11]), us), b3 = hmul2(pack(O[14], O[15]), us);
        sts128((t == rank ? sb + yo : usrc + t * 512) + co, a0, a1, a2, a3);
        sts128((t + 4 == rank ? sb + yo : usrc + t * 512 + 2048) + co, b0, b1, b2, b3);
        if (isA) {
          fence_async();
          bar_sync(NB_WG0 + u, 128);
          send(usrc - sb, 512, yo, ym);
        }
      }
      TL(9 + isA);
    }
  }

  {
    mbar_wait(mb + 8 * MB_G);
    uint2 gg[2][4];
    uint32_t qv[2][4];
#pragma unroll
    for (int hh = 0; hh < 2; hh++)
#pragma unroll
      for (int i = 0; i < 4; i++) gg[hh][i] = lds64(sb + OFF_GB + 8 * (64 * w + 32 * hh + 8 * i + g));
    const uint32_t qa = sb + OFF_TQ + toff;
    ldsm4(qv[0], qa);
    ldsm4(qv[1], qa + 2560);
    TL(24);
    mbar_wait(mb + 8 * (MB_Y + u));
    uint32_t ya[2][4], yb[2][4];
#pragma unroll
    for (int hh = 0; hh < 2; hh++) {
      const uint32_t yo = u * USZ + (lane & 7) * 512 + ((8 * w + 4 * hh + (lane >> 3)) ^ (2 * (rank & 3)) ^ (lane & 7)) * 16;
      ldsm4t(ya[hh], sb + OFF_YA + yo); ldsm4t(yb[hh], sb + OFF_YB + yo);
    }
#pragma unroll
    for (int hh = 0; hh < 2; hh++) {
      uint32_t o[4];
#pragma unroll
      for (int i = 0; i < 4; i++) o[i] = hadd2(hmul2(gg[hh][i].x, hmul2(qv[hh][i], ya[hh][i])), hmul2(gg[hh][i].y, yb[hh][i]));
      stsm4(qa + 2560 * hh, o);
    }
    TL(25);
  }
  cluster_arrive();
  bar_sync(NB_ROW0 + w, 160);
  {
    uint4 v[2];
#pragma unroll
    for (int k = 0; k < 2; k++) {
      const int i = 64 * u + 32 * k + lane, sl = (i * 205) >> 10, cc = i - 5 * sl;
      v[k] = lds128(sb + OFF_TQ + (64 * w + 8 * (sl & 7) + (sl >> 3)) * 80 + cc * 16);
    }
#pragma unroll
    for (int k = 0; k < 2; k++) {
      const int i = 64 * u + 32 * k + lane, sl = (i * 205) >> 10, cc = i - 5 * sl;
      if (cc < nu)
        asm volatile("st.global.cg.v4.u32 [%0], {%1,%2,%3,%4};" :: "l"(p.out + (size_t)(256 * rank + 32 * (sl >> 3) + 8 * w + (sl & 7)) * DCH + ch0 + 8 * cc),
                     "r"(v[k].x), "r"(v[k].y), "r"(v[k].z), "r"(v[k].w) : "memory");
    }
  }
  cluster_wait();
  TL(27);
  TL_DUMP();
}

typedef CUresult (*EncodeFn)(CUtensorMap*, CUtensorMapDataType, cuuint32_t, void*, const cuuint64_t*, const cuuint64_t*,
                             const cuuint32_t*, const cuuint32_t*, CUtensorMapInterleave, CUtensorMapSwizzle,
                             CUtensorMapL2promotion, CUtensorMapFloatOOBfill);

void encode(EncodeFn fn, CUtensorMap* tm, const void* ptr, int nd, const cuuint64_t* dims, const cuuint64_t* strides,
            const cuuint32_t* box, CUtensorMapSwizzle swz) {
  cuuint32_t es[4] = {1, 1, 1, 1};
  fn(tm, CU_TENSOR_MAP_DATA_TYPE_BFLOAT16, nd, const_cast<void*>(ptr), dims, strides, box, es, CU_TENSOR_MAP_INTERLEAVE_NONE,
     swz, CU_TENSOR_MAP_L2_PROMOTION_L2_128B, CU_TENSOR_MAP_FLOAT_OOB_FILL_NONE);
}
void make_map(EncodeFn fn, CUtensorMap* tm, const void* ptr, int ne, int nr) {
  const cuuint64_t dims[3] = {DCH, SEQ / 32, 32}, strides[2] = {32 * DCH * 2, DCH * 2};
  const cuuint32_t box[3] = {CPC, (cuuint32_t)ne, (cuuint32_t)nr};
  encode(fn, tm, ptr, 3, dims, strides, box, CU_TENSOR_MAP_SWIZZLE_NONE);
}

}

extern "C" void kernel_launch(void* const* d_in, const int* in_sizes, int n_in, void* d_out, int out_size) {
  (void)in_sizes; (void)n_in; (void)out_size;
  static EncodeFn fn = nullptr;
  static void *tab = nullptr, *cnt = nullptr, *part = nullptr;
  if (!fn) {
    cudaGetSymbolAddress(&tab, d_tab);
    cudaGetSymbolAddress(&cnt, g_cnt);
    cudaGetSymbolAddress(&part, g_part);
    cudaDriverEntryPointQueryResult qr;
    cudaGetDriverEntryPoint("cuTensorMapEncodeTiled", (void**)&fn, cudaEnableDefault, &qr);
    cudaFuncSetAttribute(fused_kernel, cudaFuncAttributeMaxDynamicSharedMemorySize, SMEM_BYTES);
  }
  Params p;
  make_map(fn, &p.tq, d_in[0], 8, 32);
  make_map(fn, &p.tk, d_in[1], 8, 32);
  make_map(fn, &p.tv, d_in[2], 8, 32);
  make_map(fn, &p.tkh, d_in[1], 1, 4);
  p.out = (__nv_bfloat16*)d_out;
  p.dfwd = mkdesc(OFF_CF, 1024, 128, 0);
  p.dinv = mkdesc(OFF_CF, 128, 1024, 0);
  p.dlast = mkdesc(OFF_CL, 512, 128, 0);
  for (int u = 0; u < 5; u++) {
    p.dk[u] = mkdesc(OFF_T + u * KTAB, u ? OFF_IM - KTAB - OFF_T : OFF_U - OFF_T, 1024, 0);
    p.db[u] = mkdesc(OFF_T + u * KTAB, UGRP, 128, 0);
    p.dt[u] = mkdesc(OFF_T + u * KTAB + T_HA, 2048, 512, 2);
    p.dx[u] = mkdesc(OFF_U + u * USZ + 16, UGRP, 128, 0);
    p.dv[u] = mkdesc(OFF_T + u * KTAB, 16, 1024, 1);
  }
  p.tab = (const Tables*)tab;
  p.cnt = (unsigned*)cnt;
  p.part = (uint2*)part;
  p.tl = nullptr;
  p.q = (const __nv_bfloat16*)d_in[0];
  p.v = (const __nv_bfloat16*)d_in[2];
  p.ssm_k = (const __nv_bfloat16*)d_in[4];
  p.shift_k = (const __nv_bfloat16*)d_in[3];
  p.ssm_D = (const __nv_bfloat16*)d_in[5];
  p.logA = (const __nv_bfloat16*)d_in[7];
  p.Aim = (const __nv_bfloat16*)d_in[8];
  p.Cre = (const __nv_bfloat16*)d_in[9];
  p.Cim = (const __nv_bfloat16*)d_in[10];
  p.logdt = (const __nv_bfloat16*)d_in[11];
  p.Dskip = (const __nv_bfloat16*)d_in[12];
  p.gate_w = (const __nv_bfloat16*)d_in[13];
  fused_kernel<<<NCL * CS, NTHREADS, SMEM_BYTES, cudaStreamPerThread>>>(p);
}
```

```cpp
#include <cuda_runtime.h>
#include <cuda_bf16.h>
#include <cuda_fp16.h>
#include <cuda.h>
#include <stdint.h>

#define TIMELINE 0
#define PREFETCH 1
#define GPU_ 0
#define GL2_ 4
#define TLHI 0

namespace {

constexpr int SEQ = 2048, DCH = 576, NMODE = 128;
constexpr int CS = 8, CPC = 40, NCL = 15, NTHREADS = 640;

constexpr int KTAB = 16384;
constexpr int OFF_T = 0;
constexpr int T_YS = 8192, T_HA = 12288;
constexpr int UCS = 272, UP = 544, USZ = 8 * UP, YP = 528, YU = 8 * YP;
constexpr int OFF_IM = 5 * KTAB;
constexpr int OFF_YB = OFF_IM;
constexpr int OFF_YA = OFF_YB + 40 * YP;
constexpr int OFF_GB = OFF_YA + 40 * YP;
constexpr int OFF_U = OFF_IM + 3 * KTAB;
constexpr int OFF_TV = OFF_U + 5 * USZ;
constexpr int OFF_CF = OFF_TV + 20480;
constexpr int OFF_CL = OFF_CF + 2048;
constexpr int OFF_TQ = OFF_CL + 4096;
constexpr int OFF_TK = OFF_TQ + 20480;
constexpr int OFF_HALO = OFF_TK + 20480;
constexpr int OFF_MX = OFF_HALO + 320;
constexpr int OFF_SP = OFF_MX + 160;
constexpr int OFF_MB = OFF_SP + 560;
constexpr int OFF_TL = OFF_MB + 28 * 8;
constexpr int SMEM_BYTES = OFF_TL + (TIMELINE ? 640 : 0);
static_assert(SMEM_BYTES <= 232448 && OFF_GB + 2048 <= OFF_U && (OFF_TV & 127) == 0 && (OFF_TQ & 127) == 0, "smem");
static_assert((OFF_MB & 7) == 0 && (OFF_MX & 15) == 0 && (OFF_SP & 15) == 0, "align");

enum { MB_UX = 0, MB_UKV = 5, MB_Y = 10, MB_HA = 15, MB_XQ = 20, MB_KV = 21, MB_CF = 22, MB_G = 23, MB_TH = 24, MB_TAG = 25 };
enum { NB_WG0 = 1, NB_ROW0 = 6, NB_ORD = 6, NB_V = 10, NB_LD = 14 };

constexpr uint32_t SB0 = 1024;
constexpr uint64_t mkdesc(uint32_t off, uint32_t lbo, uint32_t sbo, uint32_t swz) {
  return (uint64_t)((SB0 + off) >> 4) | ((uint64_t)(lbo >> 4) << 16) | ((uint64_t)(sbo >> 4) << 32) | ((uint64_t)swz << 62);
}

constexpr double cos_turn(int m, int n) {
  m &= n - 1;
  if (m > n / 2) m = n - m;
  double sgn = 1.0;
  if (m > n / 4) { m = n / 2 - m; sgn = -1.0; }
  if (m == n / 4) return 0.0;
  const double x = 6.283185307179586476925 * m / n;
  double term = 1.0, sum = 1.0;
  for (int k = 1; k < 14; k++) { term *= -x * x / ((2 * k - 1) * (2 * k)); sum += term; }
  return sgn * sum;
}
constexpr uint32_t bf16_bits(double v) {
  if (v == 0.0) return 0;
  uint32_t sgn = 0;
  if (v < 0) { sgn = 0x8000; v = -v; }
  int e = 127;
  while (v < 1.0) { v *= 2.0; e--; }
  while (v >= 2.0) { v *= 0.5; e++; }
  const double f = v * 128.0;
  int m = (int)f;
  if (f - m > 0.5 || (f - m == 0.5 && (m & 1))) m++;
  return sgn | (uint32_t)((e << 7) + (m - 128));
}
constexpr uint32_t f16_bits(double v) {
  if (v == 0.0) return 0;
  uint32_t sgn = 0;
  if (v < 0) { sgn = 0x8000; v = -v; }
  int e = 15;
  while (v < 1.0) { v *= 2.0; e--; }
  const double f = v * 1024.0;
  int m = (int)f;
  if (f - m > 0.5 || (f - m == 0.5 && (m & 1))) m++;
  return sgn | (uint32_t)((e << 10) + (m - 1024));
}
constexpr uint32_t pair_bits(double lo, double hi) { return bf16_bits(lo) | (bf16_bits(hi) << 16); }
constexpr uint32_t pair_h(double lo, double hi) { return f16_bits(lo) | (f16_bits(hi) << 16); }
struct alignas(128) Tables {
  uint32_t mat[1536];
  uint32_t thr[3][128][4];
};
constexpr Tables make_tables() {
  Tables T{};
  for (int q = 0; q < 384; q++) {
    int m0 = 0, d0 = 0, d1 = 0, d2 = 0;
    if (q < 128) {
      const int r = (q >> 5) * 8 + (q & 7), cc = (q >> 3) & 3;
      d0 = 8 * (r & 15); d1 = 2 * d0; d2 = 4 * d0;
      m0 = 8 * (cc & 1) * d0 + ((r >> 4) == (cc >> 1) ? 0 : (r >> 4) ? 96 : 32);
    } else {
      const int r = ((q - 128) >> 5) * 8 + (q & 7), pc = (q >> 3) & 3, kk = 4 * (8 * (r >> 4) + (r & 7)) + 1;
      d0 = 2 * kk; d1 = kk; d2 = 16 * kk;
      m0 = 4 * pc * kk + ((r & 8) ? 32 : 0);
    }
    for (int e = 0; e < 4; e++) {
      const int m = m0 + (e & 1) * d1 + (e >> 1) * d2;
      T.mat[4 * q + e] = pair_h(cos_turn(m, 128), cos_turn(m + d0, 128));
    }
  }
  for (int tid = 0; tid < 128; tid++) {
    const int kk = 4 * (tid >> 2) + 1, t = tid & 3;
    for (int q = 0; q < 4; q++) {
      const int m = (8 * q + 2 * t) * kk;
      T.thr[q >> 1][tid][2 * (q & 1)] = pair_bits(cos_turn(m, 128), cos_turn(m + kk, 128));
      T.thr[q >> 1][tid][2 * (q & 1) + 1] = pair_bits(cos_turn(m + 32, 128), cos_turn(m + kk + 32, 128));
      if (q < 2) {
        T.thr[2][tid][q] = pair_h(cos_turn(m, 2048), cos_turn(m + kk, 2048));
        T.thr[2][tid][2 + q] = pair_h(cos_turn(m + 1536, 2048), cos_turn(m + kk + 1536, 2048));
      }
    }
  }
  return T;
}
__device__ const Tables d_tab = make_tables();

struct Params {
  const __nv_bfloat16 *logA, *Aim, *Cre, *Cim, *logdt;
  const Tables* tab;
  unsigned* cnt;
  const __nv_bfloat16 *Dskip, *shift_k, *ssm_D, *gate_w, *q, *v, *ssm_k;
  uint2* part;
  __nv_bfloat16* out;
  unsigned* tl;
  uint64_t dfwd, dinv, dlast, dk[5], db[5], dt[5], dx[5], dv[5];
  CUtensorMap tq, tk, tv, tkh;
};

__device__ uint2 g_part[(NCL + 1) * SEQ];
__device__ unsigned g_cnt[CS * 32];
#define TL(i) do {} while (0)
#define TL_INIT() do {} while (0)
#define TL_DUMP() do {} while (0)

__device__ __forceinline__ uint32_t lds16(uint32_t a) { uint32_t v; asm volatile("ld.shared.u16 %0, [%1];" : "=r"(v) : "r"(a) : "memory"); return v; }
__device__ __forceinline__ uint2 lds64(uint32_t a) { uint2 v; asm volatile("ld.shared.v2.u32 {%0,%1}, [%2];" : "=r"(v.x), "=r"(v.y) : "r"(a) : "memory"); return v; }
__device__ __forceinline__ uint4 lds128(uint32_t a) { uint4 v; asm volatile("ld.shared.v4.u32 {%0,%1,%2,%3}, [%4];" : "=r"(v.x), "=r"(v.y), "=r"(v.z), "=r"(v.w) : "r"(a) : "memory"); return v; }
__device__ __forceinline__ void sts32(uint32_t a, uint32_t v) { asm volatile("st.shared.u32 [%0], %1;" :: "r"(a), "r"(v) : "memory"); }
__device__ __forceinline__ void sts64(uint32_t a, uint32_t x, uint32_t y) { asm volatile("st.shared.v2.u32 [%0], {%1,%2};" :: "r"(a), "r"(x), "r"(y) : "memory"); }
__device__ __forceinline__ void sts128(uint32_t a, uint32_t x, uint32_t y, uint32_t z, uint32_t w) { asm volatile("st.shared.v4.u32 [%0], {%1,%2,%3,%4};" :: "r"(a), "r"(x), "r"(y), "r"(z), "r"(w) : "memory"); }
__device__ __forceinline__ void ldsm4t(uint32_t (&r)[4], uint32_t a) { asm volatile("ldmatrix.sync.aligned.m8n8.x4.trans.shared.b16 {%0,%1,%2,%3}, [%4];" : "=r"(r[0]), "=r"(r[1]), "=r"(r[2]), "=r"(r[3]) : "r"(a) : "memory"); }
__device__ __forceinline__ void ldsm4(uint32_t (&r)[4], uint32_t a) { asm volatile("ldmatrix.sync.aligned.m8n8.x4.shared.b16 {%0,%1,%2,%3}, [%4];" : "=r"(r[0]), "=r"(r[1]), "=r"(r[2]), "=r"(r[3]) : "r"(a) : "memory"); }
__device__ __forceinline__ void stsm4(uint32_t a, const uint32_t (&r)[4]) { asm volatile("stmatrix.sync.aligned.m8n8.x4.shared.b16 [%0], {%1,%2,%3,%4};" :: "r"(a), "r"(r[0]), "r"(r[1]), "r"(r[2]), "r"(r[3]) : "memory"); }
__device__ __forceinline__ uint32_t pack(float lo, float hi) { uint32_t r; asm("cvt.rn.bf16x2.f32 %0, %1, %2;" : "=r"(r) : "f"(hi), "f"(lo)); return r; }
__device__ __forceinline__ float blo(uint32_t v) { return __uint_as_float(v << 16); }
__device__ __forceinline__ float bhi(uint32_t v) { return __uint_as_float(v & 0xffff0000u); }
__device__ __forceinline__ float bf16r(float x) { return blo(pack(x, 0.f)); }
__device__ __forceinline__ uint32_t hmul2(uint32_t a, uint32_t b) { uint32_t r; asm("mul.rn.bf16x2 %0, %1, %2;" : "=r"(r) : "r"(a), "r"(b)); return r; }
__device__ __forceinline__ uint32_t hadd2(uint32_t a, uint32_t b) { uint32_t r; asm("add.rn.bf16x2 %0, %1, %2;" : "=r"(r) : "r"(a), "r"(b)); return r; }
__device__ __forceinline__ uint32_t packh(float lo, float hi) { uint32_t r; asm("cvt.rn.f16x2.f32 %0, %1, %2;" : "=r"(r) : "f"(hi), "f"(lo)); return r; }
__device__ __forceinline__ __half2 H2(uint32_t a) { return *reinterpret_cast<__half2*>(&a); }
__device__ __forceinline__ uint32_t U2(__half2 a) { return *reinterpret_cast<uint32_t*>(&a); }
__device__ __forceinline__ uint32_t fmul(uint32_t a, uint32_t b) { return U2(__hmul2(H2(a), H2(b))); }
__device__ __forceinline__ uint32_t ffma(uint32_t a, uint32_t b, uint32_t c) { return U2(__hfma2(H2(a), H2(b), H2(c))); }
__device__ __forceinline__ uint32_t fneg(uint32_t a) { return U2(__hneg2(H2(a))); }
__device__ __forceinline__ uint32_t amax2(uint32_t a, uint32_t b) { uint32_t r; asm("max.xorsign.abs.bf16x2 %0, %1, %2;" : "=r"(r) : "r"(a), "r"(b)); return r; }
__device__ __forceinline__ uint32_t prmt(uint32_t a, uint32_t b, uint32_t s) { return __byte_perm(a, b, s); }
__device__ __forceinline__ uint32_t ldraw(const __nv_bfloat16* p) { uint32_t v; asm volatile("ld.global.nc.u16 %0, [%1];" : "=r"(v) : "l"(p)); return v; }
__device__ __forceinline__ void bar_sync(int id, int n) { asm volatile("bar.sync %0, %1;" :: "r"(id), "r"(n) : "memory"); }
__device__ __forceinline__ void bar_arrive(int id, int n) { asm volatile("bar.arrive %0, %1;" :: "r"(id), "r"(n) : "memory"); }
__device__ __forceinline__ void cluster_arrive() { asm volatile("barrier.cluster.arrive.relaxed.aligned;" ::: "memory"); }
__device__ __forceinline__ void cluster_wait() { asm volatile("barrier.cluster.wait.aligned;" ::: "memory"); }
__device__ __forceinline__ void fence_async() { asm volatile("fence.proxy.async.shared::cta;" ::: "memory"); }
__device__ __forceinline__ void fence_mbinit() { asm volatile("fence.mbarrier_init.release.cluster;" ::: "memory"); }
__device__ __forceinline__ uint32_t mapa(uint32_t a, uint32_t rank) { uint32_t r; asm("mapa.shared::cluster.u32 %0, %1, %2;" : "=r"(r) : "r"(a), "r"(rank)); return r; }
__device__ __forceinline__ void bulk_dsmem(uint32_t dst, uint32_t src, uint32_t bytes, uint32_t mbar) {
  asm volatile("cp.async.bulk.shared::cluster.shared::cta.mbarrier::complete_tx::bytes [%0], [%1], %2, [%3];" :: "r"(dst), "r"(src), "r"(bytes), "r"(mbar) : "memory");
}
__device__ __forceinline__ void bulk_load(uint32_t dst, const void* src, uint32_t bytes, uint32_t mbar) {
  asm volatile("cp.async.bulk.shared::cluster.global.mbarrier::complete_tx::bytes [%0], [%1], %2, [%3];" :: "r"(dst), "l"(src), "r"(bytes), "r"(mbar) : "memory");
}
__device__ __forceinline__ void mbar_init(uint32_t m, uint32_t cnt) { asm volatile("mbarrier.init.shared::cta.b64 [%0], %1;" :: "r"(m), "r"(cnt) : "memory"); }
__device__ __forceinline__ void mbar_expect(uint32_t m, uint32_t bytes) { asm volatile("mbarrier.arrive.expect_tx.shared::cta.b64 _, [%0], %1;" :: "r"(m), "r"(bytes) : "memory"); }
__device__ __forceinline__ bool mbar_try(uint32_t m) {
  uint32_t done;
  asm volatile("{.reg .pred p; mbarrier.try_wait.parity.shared::cta.b64 p, [%1], 0; selp.u32 %0, 1, 0, p;}" : "=r"(done) : "r"(m) : "memory");
  return done;
}
__device__ __forceinline__ void mbar_wait(uint32_t m) {
  if (!mbar_try(m)) {
    int it = 0;
    while (!mbar_try(m) && ++it < (1 << 22)) {}
  }
}
__device__ __forceinline__ bool elect() {
  uint32_t e;
  asm volatile("{.reg .pred p; elect.sync _|p, 0xffffffff; selp.u32 %0, 1, 0, p;}" : "=r"(e));
  return e;
}
__device__ __forceinline__ void tma_load3(uint32_t dst, const CUtensorMap* tm, int c0, int c1, int c2, uint32_t mbar) {
  asm volatile("cp.async.bulk.tensor.3d.shared::cluster.global.mbarrier::complete_tx::bytes [%0], [%1, {%3, %4, %5}], [%2];"
               :: "r"(dst), "l"(tm), "r"(mbar), "r"(c0), "r"(c1), "r"(c2) : "memory");
}
__device__ __forceinline__ void mma1688(float (&c)[4], uint32_t a0, uint32_t a1, uint32_t b) {
  asm volatile("mma.sync.aligned.m16n8k8.row.col.f32.bf16.bf16.f32 {%0,%1,%2,%3}, {%4,%5}, {%6}, {%0,%1,%2,%3};"
               : "+f"(c[0]), "+f"(c[1]), "+f"(c[2]), "+f"(c[3]) : "r"(a0), "r"(a1), "r"(b));
}
__device__ __forceinline__ void wg_fence() { asm volatile("wgmma.fence.sync.aligned;" ::: "memory"); }
__device__ __forceinline__ void wg_commit() { asm volatile("wgmma.commit_group.sync.aligned;" ::: "memory"); }
template <int N> __device__ __forceinline__ void wg_wait() { asm volatile("wgmma.wait_group.sync.aligned %0;" :: "n"(N) : "memory"); }
template <int N> __device__ __forceinline__ void tie_all(uint32_t (&x)[N]) {
#pragma unroll
  for (int i = 0; i < N; i++) asm volatile("" : "+r"(x[i]) :: "memory");
}
template <int N> __device__ __forceinline__ void tie_all(float (&x)[N]) {
#pragma unroll
  for (int i = 0; i < N; i++) asm volatile("" : "+f"(x[i]) :: "memory");
}
#define R16(C, d) C(d[0]), C(d[1]), C(d[2]), C(d[3]), C(d[4]), C(d[5]), C(d[6]), C(d[7]), C(d[8]), C(d[9]), C(d[10]), C(d[11]), C(d[12]), C(d[13]), C(d[14]), C(d[15])
#define R32(C, d) R16(C, d), R16(C, (d + 16))
#define P16 "{%0,%1,%2,%3,%4,%5,%6,%7,%8,%9,%10,%11,%12,%13,%14,%15}"
#define P32 "{%0,%1,%2,%3,%4,%5,%6,%7,%8,%9,%10,%11,%12,%13,%14,%15,%16,%17,%18,%19,%20,%21,%22,%23,%24,%25,%26,%27,%28,%29,%30,%31}"
template <int SD, int OFF> __device__ __forceinline__ void rs64(float* d, const uint32_t* a, uint64_t db) {
  if (SD) asm volatile("{.reg .b64 db; add.s64 db, %36, %37; wgmma.mma_async.sync.aligned.m64n64k16.f32.bf16.bf16 " P32 ", {%32,%33,%34,%35}, db, 1, 1, 1, 1;}"
                       : R32("+f", d) : "r"(a[0]), "r"(a[1]), "r"(a[2]), "r"(a[3]), "l"(db), "n"(OFF));
  else asm volatile("{.reg .b64 db; add.s64 db, %36, %37; wgmma.mma_async.sync.aligned.m64n64k16.f32.bf16.bf16 " P32 ", {%32,%33,%34,%35}, db, 0, 1, 1, 1;}"
                    : R32("=f", d) : "r"(a[0]), "r"(a[1]), "r"(a[2]), "r"(a[3]), "l"(db), "n"(OFF));
}
#define R8(C, d) C(d[0]), C(d[1]), C(d[2]), C(d[3]), C(d[4]), C(d[5]), C(d[6]), C(d[7])
template <int SD, int TB, int OFF> __device__ __forceinline__ void rs32h(uint32_t* d, const uint32_t* a, uint64_t db) {
  if (SD) asm volatile("{.reg .b64 db; add.s64 db, %12, %13; wgmma.mma_async.sync.aligned.m64n32k16.f16.f16.f16 {%0,%1,%2,%3,%4,%5,%6,%7}, {%8,%9,%10,%11}, db, 1, 1, 1, %14;}"
                       : R8("+r", d) : "r"(a[0]), "r"(a[1]), "r"(a[2]), "r"(a[3]), "l"(db), "n"(OFF), "n"(TB));
  else asm volatile("{.reg .b64 db; add.s64 db, %12, %13; wgmma.mma_async.sync.aligned.m64n32k16.f16.f16.f16 {%0,%1,%2,%3,%4,%5,%6,%7}, {%8,%9,%10,%11}, db, 0, 1, 1, %14;}"
                    : R8("=r", d) : "r"(a[0]), "r"(a[1]), "r"(a[2]), "r"(a[3]), "l"(db), "n"(OFF), "n"(TB));
}
template <int SD, int OFFA, int OFFB> __device__ __forceinline__ void ss32(float* d, uint64_t da, uint64_t db) {
  if (SD) asm volatile("{.reg .b64 da, db; add.s64 da, %16, %18; add.s64 db, %17, %19; wgmma.mma_async.sync.aligned.m64n32k16.f32.f16.f16 " P16 ", da, db, 1, 1, 1, 1, 1;}"
                       : R16("+f", d) : "l"(da), "l"(db), "n"(OFFA), "n"(OFFB));
  else asm volatile("{.reg .b64 da, db; add.s64 da, %16, %18; add.s64 db, %17, %19; wgmma.mma_async.sync.aligned.m64n32k16.f32.f16.f16 " P16 ", da, db, 0, 1, 1, 1, 1;}"
                    : R16("=f", d) : "l"(da), "l"(db), "n"(OFFA), "n"(OFFB));
}
#define KGEN_ASM(SD) "{.reg .b64 da, db; add.s64 da, %32, %33; add.s64 db, %32, %34;\n" \
  "wgmma.mma_async.sync.aligned.m64n64k16.f32.f16.f16 " P32 ", da, db, " SD ", 1, 1, 1, 1;}"
template <int KS> __device__ __forceinline__ void kgen_mma(float (&c)[32], uint64_t da) {
  if (KS) asm volatile(KGEN_ASM("1") : R32("+f", c) : "l"(da), "n"(8 * KS), "n"(8 * KS + 512));
  else asm volatile(KGEN_ASM("0") : R32("=f", c) : "l"(da), "n"(8 * KS), "n"(8 * KS + 512));
  if constexpr (KS < 7) kgen_mma<KS + 1>(c, da);
}
template <int OFF, int KSTEP> __device__ __forceinline__ void stage1(float (&D)[32], const uint32_t (&A1)[8], uint64_t d) {
  rs64<0, OFF>(D, A1, d); rs64<1, OFF + KSTEP>(D, A1 + 4, d);
}
__device__ __forceinline__ constexpr int ix(int b, int c) { return 8 * (b >> 1) + 2 * c + (b & 1); }
template <int INV> __device__ __forceinline__ void stage2(uint32_t (&X)[16], const uint32_t (&F)[16], uint64_t dc) {
  constexpr int KS = INV ? 16 : 64, TB = INV ? 0 : 1;
  rs32h<0, TB, 0>(X, F, dc); rs32h<0, TB, 0>(X + 8, F + 8, dc); rs32h<1, TB, KS>(X, F + 4, dc); rs32h<1, TB, KS>(X + 8, F + 12, dc);
}
__device__ __forceinline__ void fwd_mid(uint32_t (&F)[16], const float (&D)[32], const uint32_t (&tc)[2], const uint32_t (&ts)[2]) {
#pragma unroll
  for (int b = 0; b < 4; b++)
#pragma unroll
    for (int c = 0; c < 2; c++) {
      const int i = 8 * b + 4 * c;
      const uint32_t ar = packh(D[i], D[i + 1]), ai = packh(D[i + 2], D[i + 3]);
      F[ix(b, c)] = ffma(ar, tc[c], fmul(ai, ts[c]));
      F[ix(b, c) + 4] = ffma(ai, tc[c], fneg(fmul(ar, ts[c])));
    }
}
__device__ __forceinline__ void put_exp(uint32_t a, uint32_t m, int lane) {
  m = __reduce_max_sync(0xffffffffu, max(m & 0x7f80u, (m >> 16) & 0x7f80u));
  if (lane == 0) sts32(a, m);
}
__device__ __forceinline__ uint32_t get_exp(uint32_t a) { const uint4 v = lds128(a); return max(max(v.x, v.y), max(v.z, v.w)) >> 7; }
__device__ __forceinline__ void scale_a1(uint32_t (&As)[8], const uint32_t (&A1)[8], uint32_t field) {
#pragma unroll
  for (int i = 0; i < 8; i++) As[i] = hmul2(A1[i], field * 0x00800080u);
}

struct cf { float x, y; };
__device__ __forceinline__ cf cmul(cf a, cf b) { cf r; r.x = fmaf(a.x, b.x, -a.y * b.y); r.y = fmaf(a.x, b.y, a.y * b.x); return r; }
__device__ __forceinline__ cf cexp_p(float lr2, float lt, float p) {
  float m;
  asm("ex2.approx.ftz.f32 %0, %1;" : "=f"(m) : "f"(lr2 * p));
  float t = lt * p;
  t = (t - rintf(t)) * 6.283185307179586f;
  cf r; r.x = m * __cosf(t); r.y = m * __sinf(t); return r;
}
__device__ __forceinline__ void store8(uint32_t a, uint32_t b, const cf (&v)[8]) {
  sts128(a, packh(v[0].x, v[1].x), packh(v[2].x, v[3].x), packh(v[4].x, v[5].x), packh(v[6].x, v[7].x));
  sts128(b, packh(v[0].y, v[1].y), packh(v[2].y, v[3].y), packh(v[4].y, v[5].y), packh(v[6].y, v[7].y));
}
__device__ __forceinline__ void mbar_arrive(uint32_t m) { asm volatile("mbarrier.arrive.shared::cta.b64 _, [%0];" :: "r"(m) : "memory"); }
__device__ __forceinline__ float sigmoidf_(float s) { return __fdividef(1.f, 1.f + __expf(fminf(-s, 80.f))); }

__global__ void __cluster_dims__(CS, 1, 1) __launch_bounds__(NTHREADS, 1) fused_kernel(const __grid_constant__ Params p) {
  extern __shared__ __align__(1024) uint8_t smem[];
  TL_INIT();
  TL(31);
  const int wid = __shfl_sync(0xffffffffu, threadIdx.x >> 5, 0);
  const uint32_t sb = (uint32_t)__cvta_generic_to_shared(smem);
  const uint32_t mb = sb + OFF_MB;
  const int u = wid >> 2, w = wid & 3;
  const int tid = threadIdx.x & 127, lane = tid & 31, g = lane >> 2, t = lane & 3;
  const int cl = blockIdx.x >> 3, rank = blockIdx.x & 7;
  const int ch0 = cl * CPC;
  const int nu = min(5, (DCH - ch0) >> 3);
  const int u4 = cl & 1;
  const int cg = u < 4 ? u + u4 : u4 ? 0 : 4;
  const bool act = cg < nu;

  uint32_t pla, pai, pcr, pci, pdt, tag = 0;
  uint2 pc4r, pc4i;
  auto load_params = [&]() {
    const int ch = act ? ch0 + 8 * cg + rank : 0, o = ch * NMODE + tid;
    pla = ldraw(p.logA + o); pdt = ldraw(p.logdt + ch); pai = ldraw(p.Aim + o); pcr = ldraw(p.Cre + o); pci = ldraw(p.Cim + o);
    asm volatile("ld.global.nc.v2.u32 {%0,%1}, [%2];" : "=r"(pc4r.x), "=r"(pc4r.y) : "l"(p.Cre + ch * NMODE + 4 * lane));
    asm volatile("ld.global.nc.v2.u32 {%0,%1}, [%2];" : "=r"(pc4i.x), "=r"(pc4i.y) : "l"(p.Cim + ch * NMODE + 4 * lane));
  };
  if (u == 4) {
    const bool e = elect();
    if (e) {
#pragma unroll
      for (int i = 0; i < 5; i++) mbar_init(mb + 40 * w + 8 * i, w == 2 ? (i < 2 ? 5 : 2) : 1);
      if (w == 3) { mbar_init(mb + 8 * MB_TH, 1); mbar_init(mb + 8 * MB_XQ, 1); mbar_init(mb + 8 * MB_KV, 1); }
      if (w == 2) mbar_init(mb + 8 * MB_G, 8);
      fence_mbinit();
      if ((sb & 0xffffffu) != SB0) __trap();
    }
    __syncwarp();
    load_params();
    if (w == 0 && lane < 2) asm volatile("atom.relaxed.gpu.global.add.u32 %0, [%1], %2;" : "=r"(tag) : "l"(&p.cnt[rank * 32 + lane]), "r"(cl == 0 ? 16 - (NCL - 1) : 1) : "memory");
    if (e) {
      if (w == 3) {
        mbar_expect(mb + 8 * MB_TH, 6144);
        bulk_load(sb + OFF_TV + KTAB, p.tab->thr[0], 4096, mb + 8 * MB_TH);
        bulk_load(sb + OFF_U + KTAB, p.tab->thr[2], 2048, mb + 8 * MB_TH);
        mbar_expect(mb + 8 * MB_XQ, 20480 + 6144 + 112 * nu);
        bulk_load(sb + OFF_SP, p.gate_w + ch0, 16 * nu, mb + 8 * MB_XQ);
        bulk_load(sb + OFF_SP + 80, p.Dskip + ch0, 16 * nu, mb + 8 * MB_XQ);
        bulk_load(sb + OFF_SP + 160, p.ssm_D + ch0, 16 * nu, mb + 8 * MB_XQ);
        bulk_load(sb + OFF_SP + 240, p.shift_k + 4 * ch0, 64 * nu, mb + 8 * MB_XQ);
        tma_load3(sb + OFF_TQ, &p.tq, ch0, 8 * rank, 0, mb + 8 * MB_XQ);
        bulk_load(sb + OFF_CF, p.tab->mat, 6144, mb + 8 * MB_XQ);
        TL(20);
        mbar_expect(mb + 8 * MB_KV, 2 * 20480 + 320);
        tma_load3(sb + OFF_TK, &p.tk, ch0, 8 * rank, 0, mb + 8 * MB_KV);
        tma_load3(sb + OFF_HALO, &p.tkh, ch0, 8 * rank - 1, 28, mb + 8 * MB_KV);
      }
#pragma unroll
      for (int i = 0; i < 5; i++) mbar_expect(mb + 40 * w + 8 * i, w == 3 ? 4096 : w == 2 ? (i < 2 ? 28 : 7) * 512 : 7 * YP);
    }
    __syncwarp();
  } else {
    load_params();
  }
  cluster_arrive();
  TL(0);

  const uint32_t tab = sb + OFF_T + u * KTAB;
  const uint32_t toff = (64 * w + lane) * 80 + 16 * cg;
  const int uown = u * USZ + (4 * (rank & 1) + (rank >> 1)) * UP;
  auto put = [&](int stage, const uint32_t (&a)[4], const uint32_t (&b)[4]) {
    const uint32_t o = sb + (g == rank ? OFF_U + uown : stage + (8 * u + g) * YP);
    const uint32_t od = o + UCS * (w & 1) + 16 * (w >> 1) + 64 * t, s0 = (t & 2) ? 0x7632 : 0x5410, s1 = s0 ^ 0x2222;
    sts128(od + 16 * (t & 2), prmt(a[0], a[1], s0), prmt(a[2], a[3], s0), prmt(b[0], b[1], s0), prmt(b[2], b[3], s0));
    sts128(od + 32 - 16 * (t & 2), prmt(a[0], a[1], s1), prmt(a[2], a[3], s1), prmt(b[0], b[1], s1), prmt(b[2], b[3], s1));
    const uint32_t m = amax2(amax2(amax2(a[0], a[1]), amax2(a[2], a[3])), amax2(amax2(b[0], b[1]), amax2(b[2], b[3])));
    asm volatile("st.shared.u8 [%0], %1;" :: "r"(o + 256 + 4 * w + t), "r"(amax2(m, m >> 16) >> 7) : "memory");
  };
  const int d0 = rank ^ (2 * w), d1 = d0 ^ 1;
  const uint32_t rb0 = mapa(sb, d0), rb1 = mapa(sb, d1);
  auto send = [&](int stage, int bytes, int dst, int mbar) {
    if (elect()) {
      if (w) bulk_dsmem(rb0 + dst, sb + stage + d0 * bytes, bytes, rb0 + mbar);
      bulk_dsmem(rb1 + dst, sb + stage + d1 * bytes, bytes, rb1 + mbar);
    }
    __syncwarp();
  };

  auto ysend = [&](int stage, int dst, int mbar) {
    fence_async();
    __syncwarp();
    if (elect()) {
      const uint32_t m = OFF_MB + 8 * (mbar + (u >> 2) * 2);
#pragma unroll
      for (int k = 0; k < 2; k++) {
        const int d = 2 * w + k;
        const uint32_t rb = mapa(sb, d);
        if (d != rank) bulk_dsmem(rb + dst + u * YU + rank * 512, tab + stage + d * 512, 512, rb + m); else mbar_arrive(sb + m);
      }
    }
    __syncwarp();
  };

  uint32_t A1[8], tc[2], ts[2];
  {
    const float dt = bf16r(expf(blo(pdt)));
    const float lr2 = (-bf16r(expf(blo(pla))) * dt) * 1.4426950408889634f;
    const float lt = (blo(pai) * dt) * 0.15915494309189535f;
    const uint32_t tim = sb + (u >= 2 ? OFF_IM + (u - 2) * KTAB : u ? OFF_TV : OFF_U);
    const uint32_t row = tab + tid * 16, rim = tim + tid * 16;
    const cf w1 = cexp_p(lr2, lt, 8.f);
    cf z1 = cexp_p(lr2, lt, 1.f), Z = cexp_p(lr2, lt, 256.f);
    uint32_t ec = amax2(amax2(pc4r.x, pc4r.y), amax2(pc4i.x, pc4i.y));
    ec = min(max(__reduce_max_sync(0xffffffffu, amax2(ec, ec >> 16) & 0x7f80u), 0x0100u), 0x7e00u) << 16;
    const float cs = __uint_as_float(0x7f000000u - ec), ks = 2.f * dt * __uint_as_float(ec);
    if (lr2 != 123.f) TL(16);
    auto setup = [&]() {
      cluster_wait();
      mbar_wait(mb + 8 * MB_TH);
      const uint4 x = lds128(sb + OFF_TV + KTAB + 16 * tid), y = lds128(sb + OFF_TV + KTAB + 2048 + 16 * tid);
      const uint4 a = lds128(sb + OFF_U + KTAB + 16 * tid);
      A1[0] = x.x; A1[1] = x.y; A1[2] = x.z; A1[3] = x.w; A1[4] = y.x; A1[5] = y.y; A1[6] = y.z; A1[7] = y.w;
      tc[0] = a.x; tc[1] = a.y; ts[0] = a.z; ts[1] = a.w;
    };
    if (u >= 2) {
      if (wid == 16 && lane == 0) sts32(mb + 8 * MB_TAG, tag);
      setup();
      if (u == 4) {
        float z[4] = {0.f, 0.f, 0.f, 0.f};
        mma1688(z, pla >> 16, pla >> 16, pla >> 16);
        pcr += __float_as_uint(z[0]);
      }
      bar_sync(NB_WG0 + u, 256);
      cluster_arrive();
    }
    TL(12);
    {
      cf v[8];
      v[0].x = 1.f; v[0].y = 0.f; v[1] = cmul(w1, w1); v[2] = cmul(v[1], v[1]); v[3] = cmul(v[2], v[1]);
      v[4] = cmul(v[2], v[2]); v[5] = cmul(v[1], v[4]); v[6] = cmul(v[2], v[4]); v[7] = cmul(v[3], v[4]);
      uint32_t re[4], im[4];
#pragma unroll
      for (int i = 0; i < 4; i++) { re[i] = packh(v[2 * i].x, v[2 * i + 1].x); im[i] = packh(v[2 * i].y, v[2 * i + 1].y); }
      sts128(row, re[0], re[1], re[2], re[3]);
      sts128(rim, im[0], im[1], im[2], im[3]);
      const cf w2 = cmul(v[4], v[4]), w3 = cmul(w2, w1);
#pragma unroll
      for (int k = 1; k < 4; k++) {
        const __half2 wk = H2(k == 1 ? packh(w1.x, w1.y) : k == 2 ? packh(w2.x, w2.y) : packh(w3.x, w3.y));
        const uint32_t wr = U2(__low2half2(wk)), wi = U2(__high2half2(wk));
        uint32_t a[4], b[4];
#pragma unroll
        for (int i = 0; i < 4; i++) { a[i] = ffma(re[i], wr, fneg(fmul(im[i], wi))); b[i] = ffma(re[i], wi, fmul(im[i], wr)); }
        sts128(row + 2048 * k, a[0], a[1], a[2], a[3]);
        sts128(rim + 2048 * k, b[0], b[1], b[2], b[3]);
      }
    }
    if (u < 3) bar_arrive(NB_WG0 + u + 2, 256);
    if (u < 2) setup();
    if (PREFETCH && wid == 8 && elect()) {
      const uint32_t o = blockIdx.x * 9856u, n = min(9856u, SEQ * DCH - o) * 2;
      asm volatile("cp.async.bulk.prefetch.L2.global [%0], %1;" :: "l"(p.v + o), "r"(n) : "memory");
      asm volatile("cp.async.bulk.prefetch.L2.global [%0], %1;" :: "l"(p.ssm_k + o), "r"(n) : "memory");
    }
    __syncwarp();
    {
      z1.y = -z1.y; Z.y = -Z.y;
      const cf z2 = cmul(z1, z1);
      cf h[8], v[8];
      h[0].x = blo(pcr) * cs; h[0].y = -blo(pci) * cs;
      h[1] = cmul(h[0], z1);
#pragma unroll
      for (int i = 2; i < 8; i++) h[i] = cmul(h[i - 2], z2);
      store8(row + 4 * 2048, rim + 4 * 2048, h);
      const cf h8 = cmul(h[6], z2);
      v[0] = cmul(h[0], Z); v[2] = cmul(h[2], Z); v[3] = cmul(h[4], Z); v[6] = cmul(h[6], Z); v[7] = cmul(h8, Z);
      v[1] = v[0]; v[4] = v[5] = v[3];
      store8(row + 5 * 2048, rim + 5 * 2048, v);
      h[0] = cmul(v[0], Z); h[1] = cmul(v[3], Z); h[3] = cmul(v[7], Z); h[4] = cmul(h[0], Z); h[5] = cmul(h[1], Z); h[7] = cmul(h[3], Z);
      h[2] = h[1]; h[6] = h[5];
      store8(row + 6 * 2048, rim + 6 * 2048, h);
      const cf Z2 = cmul(Z, Z);
      v[0] = cmul(h[0], Z2); v[1] = cmul(h[3], Z2); v[2] = cmul(h[4], Z2); v[3] = cmul(h[7], Z2);
#pragma unroll
      for (int i = 4; i < 8; i++) v[i] = cmul(v[i - 4], Z2);
      store8(row + 7 * 2048, rim + 7 * 2048, v);
    }
    TL(17);
    fence_async();
    if (u) bar_sync(NB_ORD + u - 1, 256); else bar_sync(NB_WG0, 128);
    if (u == 1) cluster_arrive();
    TL(13);
    float c[32];
    wg_fence();
    kgen_mma<0>(c, p.dk[u]);
    wg_commit();
    if (u < 4) bar_arrive(NB_ORD + u, 256);
    TL(14);
    mbar_wait(mb + 8 * MB_XQ);
    TL(18);
    uint32_t x0[4], x1[4];
    ldsm4t(x0, sb + OFF_TQ + toff);
    ldsm4t(x1, sb + OFF_TQ + toff + 2560);
    wg_wait<0>(); tie_all(c);
    TL(26);
    if (u == 0) cluster_arrive();
    bar_sync(u >= 3 ? NB_V + u - 2 : NB_WG0 + u, u >= 3 ? 256 : 128);
    if (u == 2) bar_arrive(NB_V, 384);
    if ((u & 6) == 2) bar_arrive(NB_V + u - 1, 256);
    cluster_wait();
    if (wid == 4 && elect()) tma_load3(sb + OFF_TV, &p.tv, ch0, 8 * rank, 0, mb + 8 * MB_KV);
    __syncwarp();
    const uint32_t k0 = pack((c[0] + c[6]) * ks, (c[1] + c[7]) * ks), k1 = pack((c[8] + c[14]) * ks, (c[9] + c[15]) * ks);
    const uint32_t k2 = pack((c[16] + c[22]) * ks, (c[17] + c[23]) * ks), k3 = pack((c[24] + c[30]) * ks, (c[25] + c[31]) * ks);
    const uint32_t ka = tab + UCS * (w & 1) + 128 * (w >> 1) + 16 * g;
    sts32(ka + 4 * t, k0);
    sts32(ka + 4 * UP + 4 * t, k1);
    sts64(ka + UP + 4 * UP * (t >> 1) + 8 * (t & 1), prmt(k2, 0, 0x1010), (t & 1) ? prmt(k2, 0, 0x3232) : k2);
    const uint32_t lo = prmt(k3, 0, 0x1010), hi = prmt(k3, 0, 0x3232);
    sts128(ka + (2 + 4 * (t & 1) + (t >> 1)) * UP, lo, lo, (w & 1) ? hi : k3, hi);
    put_exp(sb + OFF_MX + u * 32 + 4 * w, amax2(amax2(k0, k1), amax2(k2, k3)), lane);
    if (u < 2) bar_sync(NB_V, 384);
    put(OFF_YB, x0, x1);
    TL(15);
    fence_async();
    bar_sync(NB_WG0 + u, 128);
    TL(4);
    send(OFF_YB + 8 * u * YP, YP, OFF_U + uown, OFF_MB + 8 * (MB_UX + u));
  }
  float gs0, gs1;
  if (u == GPU_) {
    float ga[4][4];
#pragma unroll
    for (int i = 0; i < 4; i++) ga[i][0] = ga[i][1] = ga[i][2] = ga[i][3] = 0.f;
#pragma unroll
    for (int j = 0; j < 5; j++) {
      uint32_t a0[4], a1[4], b;
      ldsm4(a0, sb + OFF_TQ + toff + 16 * (j - cg));
      ldsm4(a1, sb + OFF_TQ + toff + 2560 + 16 * (j - cg));
      asm volatile("ld.shared.u32 %0, [%1];" : "=r"(b) : "r"(sb + OFF_SP + 16 * j + 4 * t) : "memory");
      if (j >= 2 && j >= nu) b = 0;
      mma1688(ga[0], hmul2(a0[0], b), hmul2(a0[1], b), 0x3f803f80u); mma1688(ga[1], hmul2(a0[2], b), hmul2(a0[3], b), 0x3f803f80u);
      mma1688(ga[2], hmul2(a1[0], b), hmul2(a1[1], b), 0x3f803f80u); mma1688(ga[3], hmul2(a1[2], b), hmul2(a1[3], b), 0x3f803f80u);
    }
    gs0 = t == 0 ? ga[0][0] : t == 1 ? ga[1][0] : t == 2 ? ga[2][0] : ga[3][0];
    gs1 = t == 0 ? ga[0][2] : t == 1 ? ga[1][2] : t == 2 ? ga[2][2] : ga[3][2];
  }
  if (u == GPU_) {
    tag = (lds64(mb + 8 * MB_TAG).x >> 4) + 1;
    uint2* gp = p.part + cl * SEQ + rank * 256 + 64 * w + 16 * t + g;
    asm volatile("st.relaxed.gpu.global.u64 [%0], %1;" :: "l"(gp), "l"(((uint64_t)tag << 32) | __float_as_uint(gs0)) : "memory");
    asm volatile("st.relaxed.gpu.global.u64 [%0], %1;" :: "l"(gp + 8), "l"(((uint64_t)tag << 32) | __float_as_uint(gs1)) : "memory");
  }

#pragma unroll
  for (int isA = 0; isA < 2; isA++) {
    {
      TL(1 + isA);
      const uint32_t mxa = sb + OFF_MX + u * 32 + 16 * isA;
      const uint32_t pd = lds16(sb + OFF_SP + 80 + 80 * isA + 16 * cg + 2 * rank);
      float D[32];
      uint32_t As[8], F[16], H[16], X[16];
      const uint32_t eh = min(max((int)get_exp(mxa), (int)((pd >> 7) & 0xff) - 5), 240);
      scale_a1(As, A1, 248 - eh);
      wg_fence();
      if (isA) stage1<0, 32>(D, As, p.dt[u]); else stage1<0, 4 * UP / 16>(D, As, p.db[u]);
      wg_commit();
      wg_wait<0>(); tie_all(D);
      fwd_mid(F, D, tc, ts);
      wg_fence();
      stage2<0>(H, F, p.dfwd);
      wg_commit();
      if (isA) ysend(T_YS, OFF_YB, MB_Y);
      mbar_wait(mb + 8 * ((isA ? MB_UKV : MB_UX) + u));
      TL(5 + isA);
      uint32_t eu;
      asm volatile("ld.shared.u32 %0, [%1];" : "=r"(eu) : "r"(sb + OFF_U + u * USZ + g * UP + 256 + 4 * t) : "memory");
      eu = __vmaxu2(eu & 0x00ff00ffu, (eu >> 8) & 0x00ff00ffu);
      eu = min(__reduce_max_sync(0xffffffffu, max(eu & 0xffffu, eu >> 16)), 240u);
      scale_a1(As, A1, 250 - eu);
      wg_wait<0>(); tie_all(H);
      wg_fence();
      stage1<0, 4 * UP / 16>(D, As, p.dx[u]);
      wg_commit();
      wg_wait<0>(); tie_all(D);
      cluster_arrive();
      fwd_mid(F, D, tc, ts);
      wg_fence();
      stage2<0>(X, F, p.dfwd);
      wg_commit();
      if (!isA) {
        if (w == 2 && elect()) bulk_load(tab + T_HA, p.ssm_k + (size_t)(act ? ch0 + 8 * cg + rank : 0) * SEQ, 4096, mb + 8 * (MB_HA + u));
        __syncwarp();
        TL(7);
      }
      {
        const float dsk = blo(pd) * __uint_as_float((248 - eh) << 23);
        const uint32_t d2 = packh(dsk, dsk);
        H[ix(0, 0)] = U2(__hadd2(H2(H[ix(0, 0)]), H2(d2))); H[ix(0, 1)] = U2(__hadd2(H2(H[ix(0, 1)]), H2(d2)));
      }
      wg_wait<0>(); tie_all(X);
#pragma unroll
      for (int c = 0; c < 2; c++) {
        uint32_t pr[4], pi[4];
#pragma unroll
        for (int b = 0; b < 4; b++) {
#pragma unroll
          for (int j = 0; j <= b; j++) {
            const uint32_t hr = H[ix(j, c)], hi = H[ix(j, c) + 4], xr = X[ix(b - j, c)], xi = X[ix(b - j, c) + 4];
            if (j == 0 && b < 3) { pr[b] = ffma(xr, hr, fneg(fmul(xi, hi))); pi[b] = ffma(xr, hi, fmul(xi, hr)); }
            else if (j == 0) { pr[b] = ffma(xr, hr, fneg(ffma(xi, hi, pi[2]))); pi[b] = ffma(xr, hi, ffma(xi, hr, pr[2])); }
            else { pr[b] = ffma(xr, hr, ffma(fneg(xi), hi, pr[b])); pi[b] = ffma(xr, hi, ffma(xi, hr, pi[b])); }
          }
          const bool add = b == 1 || b == 2;
          F[ix(b, c)] = add ? U2(__hsub2(H2(pr[b]), H2(pi[b - add]))) : pr[b];
          F[ix(b, c) + 4] = add ? U2(__hadd2(H2(pi[b]), H2(pr[b - add]))) : pi[b];
        }
      }
      wg_fence();
      stage2<1>(H, F, p.dinv);
      wg_commit();
      uint64_t ga[4];
      const int sl2 = min(18 * cl + min(8 * w + g, 17), 255), sl3 = tid + 128 * (u & 1);
      auto gload = [&]() {
        if (isA) {
          asm volatile("ld.relaxed.gpu.global.u64 %0, [%1];" : "=l"(ga[0]) : "l"(p.part + NCL * SEQ + rank * 256 + sl3) : "memory");
        } else {
#pragma unroll
          for (int k = 0; k < 4; k++)
            asm volatile("ld.relaxed.gpu.global.u64 %0, [%1];" : "=l"(ga[k]) : "l"(p.part + (t + (k == 3 && t == 3 ? 8 : 4 * k)) * SEQ + rank * 256 + sl2) : "memory");
        }
      };
      if (isA ? (u & 6) == 2 : u == GL2_) gload();
      if (isA) TL(23);
      wg_wait<0>(); tie_all(H);
      {
        const uint32_t va = tab + (16 * w + (lane & 15)) * 128;
        const int vx = (lane >> 4) ^ (lane & 7);
#pragma unroll
        for (int j = 0; j < 4; j++) {
          uint32_t V[4];
#pragma unroll
          for (int b = 0; b < 2; b++) {
            const uint32_t er = H[ix(j, b)], ei = H[ix(j, b) + 4];
            V[2 * b] = ffma(er, tc[b], fneg(fmul(ei, ts[b])));
            V[2 * b + 1] = ffma(ei, tc[b], fmul(er, ts[b]));
          }
          stsm4(va + ((vx ^ (2 * j)) << 4), V);
        }
      }
      if (!isA) {
        cluster_wait();
        mbar_wait(mb + 8 * MB_KV);
        TL(21);
        uint32_t K[3][4], V[2][4];
        const uint2 psw = lds64(sb + OFF_SP + 240 + 64 * cg + 8 * g);
        ldsm4t(K[0], w ? sb + OFF_TK + toff - 2560 : (lane & 7) ? sb + OFF_TK + toff + 223 * 80 : sb + OFF_HALO + 10 * lane + 16 * cg);
        ldsm4t(K[1], sb + OFF_TK + toff);
        ldsm4t(K[2], sb + OFF_TK + toff + 2560);
        ldsm4t(V[0], sb + OFF_TV + toff);
        ldsm4t(V[1], sb + OFF_TV + toff + 2560);
        mbar_wait(mb + 8 * (MB_HA + u));
        const uint4 hx = lds128(tab + T_HA + 16 * tid), hy = lds128(tab + T_HA + 2048 + 16 * tid);
        const uint32_t w0 = prmt(psw.x, 0, 0x1010), w1 = prmt(psw.x, 0, 0x3232), w2 = prmt(psw.y, 0, 0x1010), w3 = prmt(psw.y, 0, 0x3232);
#pragma unroll
        for (int m = 4; m < 12; m++)
          V[(m >> 2) - 1][m & 3] = hmul2(hadd2(hadd2(hadd2(hmul2(K[(m - 3) >> 2][(m - 3) & 3], w3), hmul2(K[(m - 2) >> 2][(m - 2) & 3], w2)),
                                                     hmul2(K[(m - 1) >> 2][(m - 1) & 3], w1)), hmul2(K[m >> 2][m & 3], w0)), V[(m >> 2) - 1][m & 3]);
        put(OFF_YA, V[0], V[1]);
        put_exp(mxa + 16 + 4 * w, amax2(amax2(amax2(hx.x, hx.y), amax2(hx.z, hx.w)), amax2(amax2(hy.x, hy.y), amax2(hy.z, hy.w))), lane);
        sts128(tab + T_HA + 16 * (tid ^ ((lane >> 3) & 1)), hx.x, hx.y, hx.z, hx.w);
        sts128(tab + T_HA + 2048 + 16 * (tid ^ ((lane >> 3) & 1)), hy.x, hy.y, hy.z, hy.w);
        TL(22);
      }
      fence_async();
      bar_sync(NB_WG0 + u, 128);
      float O[16];
      {
        const uint64_t dv = p.dv[u], dl = p.dlast;
        wg_fence();
        ss32<0, 0, 0>(O, dv, dl); ss32<1, 128, 64>(O, dv, dl); ss32<1, 256, 128>(O, dv, dl); ss32<1, 384, 192>(O, dv, dl);
        wg_commit();
      }
      if (!isA) send(OFF_YA + 8 * u * YP, YP, OFF_U + uown, OFF_MB + 8 * (MB_UKV + u));
      if (isA ? (u & 6) == 2 : u == GL2_) {
        tag = (lds64(mb + 8 * MB_TAG).x >> 4) + 1;
        bool ok;
#pragma unroll 1
        for (int it = 0;; it++) {
          ok = (uint32_t)(ga[0] >> 32) == tag;
          if (!isA) ok = ok && (uint32_t)(ga[1] >> 32) == tag && (uint32_t)(ga[2] >> 32) == tag && (uint32_t)(ga[3] >> 32) == tag;
          ok = __all_sync(0xffffffffu, ok);
          if (ok || it == (isA ? 8000 : 2000)) break;
          gload();
        }
        if (!isA) {
          float s = __uint_as_float((uint32_t)ga[0]) + __uint_as_float((uint32_t)ga[1]) + __uint_as_float((uint32_t)ga[2]);
          if (t < 3) s += __uint_as_float((uint32_t)ga[3]);
          s += __shfl_xor_sync(0xffffffffu, s, 1);
          s += __shfl_xor_sync(0xffffffffu, s, 2);
          const float g0 = bf16r(sigmoidf_(bf16r(s)));
          if (ok && t == 0)
            asm volatile("st.relaxed.gpu.global.u64 [%0], %1;" :: "l"(p.part + NCL * SEQ + rank * 256 + sl2), "l"(((uint64_t)tag << 32) | pack(g0, 1.f - g0)) : "memory");
        } else {
          uint32_t gv = (uint32_t)ga[0];
          if (!ok) {
            const uint32_t* xr = (const uint32_t*)(p.q + (size_t)(rank * 256 + 32 * (sl3 & 7) + (sl3 >> 3)) * DCH);
            const uint32_t* gr = (const uint32_t*)p.gate_w;
            float s = 0.f;
#pragma unroll 1
            for (int k = 0; k < DCH / 2; k++) { const uint32_t m = hmul2(__ldg(xr + k), __ldg(gr + k)); s += blo(m) + bhi(m); }
            const float g0 = bf16r(sigmoidf_(bf16r(s)));
            gv = pack(g0, 1.f - g0);
          }
          sts64(sb + OFF_GB + 8 * sl3, prmt(gv, 0, 0x1010), prmt(gv, 0, 0x3232));
          __syncwarp();
          if (lane == 0) mbar_arrive(mb + 8 * MB_G);
        }
      }
      if (isA) cluster_wait();
      if (isA) TL(28);
      wg_wait<0>(); tie_all(O);
      {
        const int dst = 2 * w + (t >> 1);
        const uint32_t ya = (dst == rank ? sb + (isA ? OFF_YA : OFF_YB) + u * YU : tab + (isA ? T_HA : T_YS)) + dst * 512 +
                            ((16 * (t & 1) + g) ^ (2 * t) ^ rank ^ (2 * (u & 3))) * 16;
        const uint32_t us = min(max((int)(eu + eh) - 126, 0), 254) * 0x00800080u;
        const uint32_t a0 = hmul2(pack(O[0], O[1]), us), a1 = hmul2(pack(O[4], O[5]), us), a2 = hmul2(pack(O[8], O[9]), us), a3 = hmul2(pack(O[12], O[13]), us);
        const uint32_t b0 = hmul2(pack(O[2], O[3]), us), b1 = hmul2(pack(O[6], O[7]), us), b2 = hmul2(pack(O[10], O[11]), us), b3 = hmul2(pack(O[14], O[15]), us);
        sts128(ya, a0, a1, a2, a3);
        sts128(ya + 128, b0, b1, b2, b3);
        if (isA) ysend(T_HA, OFF_YA, MB_Y + 1);
      }
      TL(9 + isA);
    }
  }

  {
    const int tu = u < 4 ? u4 + t : cg, tc0 = u < 4 ? 2 * wid : 8 * w + 2 * t;
    const int lt = (lane >> 1) & 3, lr = 2 * (lane >> 3) + (lane & 1);
    const int lu = u < 4 ? lt : 4, lc0 = u < 4 ? 2 * wid : 8 * w + 2 * lt;
    const uint32_t yo = sb + lu * YU + lr * 512 + ((lc0 ^ (4 * (rank & 1) + 2 * (lc0 >> 4)) ^ lr ^ (2 * (lu & 3))) << 4);
    __nv_bfloat16* op = p.out + (size_t)(256 * rank + 32 * g + tc0) * DCH + ch0 + 8 * tu;
    uint4 qv[2];
    uint2 gg[2];
    uint32_t ya[2][4], yb[2][4];
    mbar_wait(mb + 8 * (MB_Y + (u >> 2) * 2));
    mbar_wait(mb + 8 * MB_G);
#pragma unroll
    for (int k = 0; k < 2; k++) {
      qv[k] = lds128(sb + OFF_TQ + (8 * (tc0 + k) + g) * 80 + 16 * tu);
      gg[k] = lds64(sb + OFF_GB + 8 * (8 * (tc0 + k) + g));
      ldsm4t(yb[k], (yo ^ (16 * k)) + OFF_YB);
    }
#pragma unroll
    for (int k = 0; k < 2; k++)
#pragma unroll
      for (int i = 0; i < 4; i++) { yb[k][i] = hmul2(gg[k].y, yb[k][i]); asm volatile("" : "+r"(yb[k][i])); }
    TL(24);
    mbar_wait(mb + 8 * (MB_Y + 1 + (u >> 2) * 2));
    cluster_arrive();
#pragma unroll
    for (int k = 0; k < 2; k++) ldsm4t(ya[k], (yo ^ (16 * k)) + OFF_YA);
#pragma unroll
    for (int k = 0; k < 2; k++)
      if (tu < nu)
        asm volatile("st.global.cg.v4.u32 [%0], {%1,%2,%3,%4};" :: "l"(op + k * DCH),
                     "r"(hadd2(hmul2(gg[k].x, hmul2(qv[k].x, ya[k][0])), yb[k][0])), "r"(hadd2(hmul2(gg[k].x, hmul2(qv[k].y, ya[k][1])), yb[k][1])),
                     "r"(hadd2(hmul2(gg[k].x, hmul2(qv[k].z, ya[k][2])), yb[k][2])), "r"(hadd2(hmul2(gg[k].x, hmul2(qv[k].w, ya[k][3])), yb[k][3])) : "memory");
    TL(25);
  }
  cluster_wait();
  TL(27);
  TL_DUMP();
}

typedef CUresult (*EncodeFn)(CUtensorMap*, CUtensorMapDataType, cuuint32_t, void*, const cuuint64_t*, const cuuint64_t*,
                             const cuuint32_t*, const cuuint32_t*, CUtensorMapInterleave, CUtensorMapSwizzle,
                             CUtensorMapL2promotion, CUtensorMapFloatOOBfill);

void encode(EncodeFn fn, CUtensorMap* tm, const void* ptr, int nd, const cuuint64_t* dims, const cuuint64_t* strides,
            const cuuint32_t* box, CUtensorMapSwizzle swz) {
  cuuint32_t es[4] = {1, 1, 1, 1};
  fn(tm, CU_TENSOR_MAP_DATA_TYPE_BFLOAT16, nd, const_cast<void*>(ptr), dims, strides, box, es, CU_TENSOR_MAP_INTERLEAVE_NONE,
     swz, CU_TENSOR_MAP_L2_PROMOTION_L2_128B, CU_TENSOR_MAP_FLOAT_OOB_FILL_NONE);
}
void make_map(EncodeFn fn, CUtensorMap* tm, const void* ptr, int ne, int nr) {
  const cuuint64_t dims[3] = {DCH, SEQ / 32, 32}, strides[2] = {32 * DCH * 2, DCH * 2};
  const cuuint32_t box[3] = {CPC, (cuuint32_t)ne, (cuuint32_t)nr};
  encode(fn, tm, ptr, 3, dims, strides, box, CU_TENSOR_MAP_SWIZZLE_NONE);
}

}

extern "C" void kernel_launch(void* const* d_in, const int* in_sizes, int n_in, void* d_out, int out_size) {
  (void)in_sizes; (void)n_in; (void)out_size;
  static EncodeFn fn = nullptr;
  static void *tab = nullptr, *cnt = nullptr, *part = nullptr;
  if (!fn) {
    cudaGetSymbolAddress(&tab, d_tab);
    cudaGetSymbolAddress(&cnt, g_cnt);
    cudaGetSymbolAddress(&part, g_part);
    cudaDriverEntryPointQueryResult qr;
    cudaGetDriverEntryPoint("cuTensorMapEncodeTiled", (void**)&fn, cudaEnableDefault, &qr);
    cudaFuncSetAttribute(fused_kernel, cudaFuncAttributeMaxDynamicSharedMemorySize, SMEM_BYTES);
  }
  Params p;
  make_map(fn, &p.tq, d_in[0], 8, 32);
  make_map(fn, &p.tk, d_in[1], 8, 32);
  make_map(fn, &p.tv, d_in[2], 8, 32);
  make_map(fn, &p.tkh, d_in[1], 1, 4);
  p.out = (__nv_bfloat16*)d_out;
  p.dfwd = mkdesc(OFF_CF, 512, 128, 0);
  p.dinv = mkdesc(OFF_CF, 128, 512, 0);
  p.dlast = mkdesc(OFF_CL, 512, 128, 0);
  for (int u = 0; u < 5; u++) {
    p.dk[u] = mkdesc(OFF_T + u * KTAB, (u >= 2 ? OFF_IM + (u - 2) * KTAB : u ? OFF_TV : OFF_U) - (OFF_T + u * KTAB), 1024, 0);
    p.db[u] = mkdesc(OFF_T + u * KTAB, 128, UCS, 0);
    p.dt[u] = mkdesc(OFF_T + u * KTAB + T_HA, 1024, 256, 3);
    p.dx[u] = mkdesc(OFF_U + u * USZ, 128, UCS, 0);
    p.dv[u] = mkdesc(OFF_T + u * KTAB, 16, 1024, 1);
  }
  p.tab = (const Tables*)tab;
  p.cnt = (unsigned*)cnt;
  p.part = (uint2*)part;
  p.tl = nullptr;
  p.q = (const __nv_bfloat16*)d_in[0];
  p.v = (const __nv_bfloat16*)d_in[2];
  p.ssm_k = (const __nv_bfloat16*)d_in[4];
  p.shift_k = (const __nv_bfloat16*)d_in[3];
  p.ssm_D = (const __nv_bfloat16*)d_in[5];
  p.logA = (const __nv_bfloat16*)d_in[7];
  p.Aim = (const __nv_bfloat16*)d_in[8];
  p.Cre = (const __nv_bfloat16*)d_in[9];
  p.Cim = (const __nv_bfloat16*)d_in[10];
  p.logdt = (const __nv_bfloat16*)d_in[11];
  p.Dskip = (const __nv_bfloat16*)d_in[12];
  p.gate_w = (const __nv_bfloat16*)d_in[13];
  fused_kernel<<<NCL * CS, NTHREADS, SMEM_BYTES, cudaStreamPerThread>>>(p);
}
```
